```python
import torch

def _softmax(x, axis=-1):
    return torch.softmax(x, dim=axis)

def _gelu(x):
    return torch.nn.functional.gelu(x, approximate='tanh')

def _silu(x):
    return torch.nn.functional.silu(x)

def _sigmoid(x):
    return torch.sigmoid(x)

def _layernorm(x, axis=-1, eps=1e-05):
    m = x.mean(dim=axis, keepdim=True)
    v = x.var(dim=axis, keepdim=True, unbiased=False)
    return (x - m) / torch.sqrt(v + eps)

def _scatter_add(tgt, idx, src, axis=0):
    return tgt.clone().index_add_(axis, idx, src)

def _segment_sum(src, seg, n):
    out = torch.zeros((n,) + src.shape[1:], dtype=src.dtype)
    return out.index_add_(0, seg, src)

def _pad(x, pw):
    flat = tuple((v for pair in reversed(pw) for v in pair))
    return torch.nn.functional.pad(x, flat)
kernel_name = 'adaLN_cond__memory_aug_recurrent_mem_tr__mixer_s_mlp__prompt'

def setup_inputs():

    _w = lambda a: (lambda t: t.to(torch.bfloat16) if t.is_floating_point() else t)(torch.as_tensor(a))

    def _A_setup():
        B, S, Dm = (1, 2048, 1024)
        H, Dh = (32, 128)
        M, seg = (8, 32)
        seg = min(seg, S)
        S = S // seg * seg
        return {'x': _w((lambda *s: torch.randn(*s, dtype=torch.bfloat16) * 0.05)(B, S, Dm)), 'mem0': _w((lambda *s: torch.randn(*s, dtype=torch.bfloat16) * 0.4)(B, M, Dm)), 'Wq': _w((lambda *s: torch.randn(*s, dtype=torch.bfloat16) * 3.2)(Dm, H, Dh) * Dm ** (-0.5)), 'Wk': _w((lambda *s: torch.randn(*s, dtype=torch.bfloat16) * 3.2)(Dm, H, Dh) * Dm ** (-0.5)), 'Wv': _w((lambda *s: torch.randn(*s, dtype=torch.bfloat16) * 0.4)(Dm, H, Dh) * Dm ** (-0.5)), 'Wo': _w((lambda *s: torch.randn(*s, dtype=torch.bfloat16) * 0.4)(H, Dh, Dm) * (H * Dh) ** (-0.5)), 'seg_len': seg}
    _A_in = _A_setup()

    def _B_setup():
        B, S, D, F = (1, 2048, 1024, 3584)
        return {'x': _w((lambda *s: torch.randn(*s, dtype=torch.bfloat16) * 0.05)(B, S, D)), 'w1': _w((lambda *s: torch.randn(*s, dtype=torch.bfloat16) * 3.2)(D, D) * D ** (-0.5)), 'w2': _w((lambda *s: torch.randn(*s, dtype=torch.bfloat16) * 3.2)(D, D) * D ** (-0.5)), 'w3': _w((lambda *s: torch.randn(*s, dtype=torch.bfloat16) * 3.2)(D, F) * D ** (-0.5)), 'w4': _w((lambda *s: torch.randn(*s, dtype=torch.bfloat16) * 3.2)(F, D) * F ** (-0.5))}
    _B_in = _B_setup()
    return {'A_x': _A_in['x'], 'A_mem0': _A_in['mem0'], 'A_Wq': _A_in['Wq'], 'A_Wk': _A_in['Wk'], 'A_Wv': _A_in['Wv'], 'A_Wo': _A_in['Wo'], 'A_seg_len': _A_in['seg_len'], 'B_x': _B_in['x'], 'B_w1': _B_in['w1'], 'B_w2': _B_in['w2'], 'B_w3': _B_in['w3'], 'B_w4': _B_in['w4'], 'c': _w((lambda *s: torch.randn(*s, dtype=torch.bfloat16) * 0.1)(1, 1024) * 8.0), 'w_mod': _w((lambda *s: torch.randn(*s, dtype=torch.bfloat16) * 0.1)(1024, 6 * 1024) * 1024 ** (-0.5) * 8.0)}

def reference(A_x, A_mem0, A_Wq, A_Wk, A_Wv, A_Wo, A_seg_len, B_x, B_w1, B_w2, B_w3, B_w4, c, w_mod):

    def _A_ref(x, mem0, Wq, Wk, Wv, Wo, seg_len):
        B, S, Dm = x.shape
        H, Dh = (Wq.shape[1], Wq.shape[2])
        M = mem0.shape[1]
        scale = Dh ** (-0.5)
        n_seg = S // seg_len
        L = M + seg_len
        idx = torch.arange(L)
        mask = (idx[:, None] < M) | (idx[:, None] >= idx[None, :])
        mem = mem0
        outs = []
        for s in range(n_seg):
            xs = x[:, s * seg_len:(s + 1) * seg_len, :].clone()
            h = torch.concatenate([mem, xs], axis=1)
            q = torch.einsum('btd,dhe->bhte', h, Wq)
            k = torch.einsum('btd,dhe->bhte', h, Wk)
            v = torch.einsum('btd,dhe->bhte', h, Wv)
            scores = torch.einsum('bhqe,bhke->bhqk', q, k) * scale
            scores = torch.where(mask[None, None], scores, -1000000000.0)
            p = _softmax(scores, axis=-1)
            o = torch.einsum('bhqk,bhke->bhqe', p, v)
            o = torch.einsum('bhte,hed->btd', o, Wo)
            mem = o[:, :M, :].clone()
            outs.append(o[:, M:, :])
        return torch.concatenate(outs, axis=1)

    def _B_ref(x, w1, w2, w3, w4):
        B, S, D = x.shape
        h = _gelu(_layernorm(x, axis=-1) @ w1)
        c = D // 4
        g0 = _pad(h[:, :, 0 * c:1 * c], ((0, 0), (1, 0), (0, 0)))[:, :S, :]
        g1 = _pad(h[:, :, 1 * c:2 * c], ((0, 0), (0, 1), (0, 0)))[:, 1:, :]
        g2 = _pad(h[:, :, 2 * c:3 * c], ((0, 0), (2, 0), (0, 0)))[:, :S, :]
        g3 = _pad(h[:, :, 3 * c:], ((0, 0), (0, 2), (0, 0)))[:, 2:, :]
        hs = torch.concatenate([g0, g1, g2, g3], axis=-1) @ w2
        x1 = x + hs
        h2 = _gelu(_layernorm(x1, axis=-1) @ w3) @ w4
        return x1 + h2
    x = A_x
    mod = (_silu(c) @ w_mod).reshape(c.shape[0], 6, 1, -1)
    sa, ca, ga, sb, cb, gb = (mod[:, 0].clone(), mod[:, 1].clone(), mod[:, 2].clone(), mod[:, 3].clone(), mod[:, 4].clone(), mod[:, 5].clone())
    h = _layernorm(x, axis=-1) * (1 + ca) + sa
    x = x + ga * _A_ref(h, A_mem0, A_Wq, A_Wk, A_Wv, A_Wo, A_seg_len)
    h = _layernorm(x, axis=-1) * (1 + cb) + sb
    x = x + gb * _B_ref(h, B_w1, B_w2, B_w3, B_w4)
    return x
```

```cpp
#include <cuda_runtime.h>
#include <cuda.h>
#include <cuda_bf16.h>
#include <stdint.h>
#include <limits.h>

typedef __nv_bfloat16 bf16;

constexpr int S_ = 2048, DM = 1024, NH = 32, DH = 128, NSEG = 64, FF = 3584;
constexpr int SPIN_LIMIT = 1 << 22;
#define W_INFL 2
#define XP 0
#define H_PIECES 8
#define NPROBE 3

__device__ uint8_t g_arena[10 << 20];
__device__ uint32_t g_tick[64];
__device__ __align__(16) uint32_t g_modp[8 * 2 * DM];
__host__ __device__ constexpr uint32_t blk(uint32_t lb, uint32_t par) {
    return (lb << 13) | ((((lb) ^ (lb >> 3) ^ (lb >> 4) ^ (lb >> 6) ^ par) & 1) << 12);
}
__host__ __device__ constexpr uint32_t lb_x2(uint32_t h) { return (h & 1) | ((h >> 1) << 3); }
__host__ __device__ constexpr uint32_t acc_slot(uint32_t s) { return (1u << 20) + (s & 1) * 32768 + (s & 2) * 131072; }
#define CP2 0
constexpr uint32_t ACC_MT = CP2 ? 512 : 4096, ACC_X = CP2 ? 0x30000 : 512;
__host__ __device__ constexpr uint32_t acc_piece(uint32_t half, uint32_t u, uint32_t mt) { return (u & 3) * 1024 + mt * ACC_MT + half * 8192 + (u >> 2) * 16384; }
constexpr uint32_t LB_STAMP = 6;
__host__ __device__ constexpr uint32_t stamp_line(uint32_t w, uint32_t q) { return ((w & 1) * 2 + (q >> 1)) * 1024 + (q & 1) * 256; }
constexpr uint32_t ACC_ONE = 0x3c000000u, ACC_ALL = 0x50000000u;
constexpr uint32_t LB_PROBE = 6 | 64;
__host__ __device__ constexpr uint32_t lb_tok(uint32_t h) { return (h & 1) | ((h >> 1) << 3); }
__device__ float g_mod[6 * DM];
__device__ __align__(1024) bf16 g_himg[(S_ + 32) * DM];
__device__ __align__(1024) bf16 g_O[S_ * NH * DH];
__device__ __align__(1024) bf16 g_y[S_ * DM];
__device__ __align__(1024) bf16 g_g[S_ * DM];
__device__ __align__(1024) bf16 g_x1[S_ * DM];
__device__ __align__(16) float g_st[4 * S_ * 2];
__device__ float g_vec[3 * DM + FF];
__device__ float g_cst[8];
__device__ uint32_t g_pcnt[2 * 32 * 8], g_pflag[6 * 32 * 8];
__device__ __align__(1024) bf16 g_u[S_ * FF];

#define TL(i) {}
#define TLC(i) {}
__device__ __forceinline__ uint32_t smem_u32(const void* p) { return (uint32_t)__cvta_generic_to_shared(p); }
__device__ __forceinline__ void spin_guard(int it) {
    asm volatile("{.reg .pred p; setp.gt.s32 p, %0, %1; @p st.global.u32 [%2], %0;}" ::"r"(it), "n"(SPIN_LIMIT), "l"(1ull));
}
__device__ __forceinline__ void wg_fence() { asm volatile("wgmma.fence.sync.aligned;" ::: "memory"); }
__device__ __forceinline__ void wg_commit() { asm volatile("wgmma.commit_group.sync.aligned;" ::: "memory"); }
template <int N> __device__ __forceinline__ void wg_wait() { asm volatile("wgmma.wait_group.sync.aligned %0;" ::"n"(N) : "memory"); }
__host__ __device__ constexpr uint64_t mkdesc(uint32_t addr, uint32_t lbo, uint32_t sbo, uint32_t swz) {
    return (uint64_t)((addr & 0x3FFFF) >> 4) | ((uint64_t)(lbo >> 4) << 16) | ((uint64_t)(sbo >> 4) << 32) | ((uint64_t)swz << 62);
}
__device__ __forceinline__ uint64_t dadd(uint64_t d, uint32_t o) { return (d & 0xffffffff00000000ull) | (uint32_t)((uint32_t)d + o); }
__device__ __forceinline__ void mbar_init(uint32_t b, uint32_t c) { asm volatile("mbarrier.init.shared.b64 [%0], %1;" ::"r"(b), "r"(c) : "memory"); }
__device__ __forceinline__ void mbar_expect(uint32_t b, uint32_t tx) { asm volatile("mbarrier.arrive.expect_tx.shared.b64 _, [%0], %1;" ::"r"(b), "r"(tx) : "memory"); }
__device__ __forceinline__ void mbar_arrive(uint32_t b) { asm volatile("mbarrier.arrive.shared.b64 _, [%0];" ::"r"(b) : "memory"); }
__device__ __forceinline__ void mbar_arrive_cluster(uint32_t b, uint32_t cta) {
    asm volatile("{.reg .b32 r; mapa.shared::cluster.u32 r, %0, %1; mbarrier.arrive.shared::cluster.b64 _, [r];}" ::"r"(b), "r"(cta) : "memory");
}
__device__ __forceinline__ bool mbar_try(uint32_t b, uint32_t par) {
    uint32_t ok;
    asm volatile("{.reg .pred p; mbarrier.try_wait.parity.shared.b64 p, [%1], %2; selp.u32 %0, 1, 0, p;}" : "=r"(ok) : "r"(b), "r"(par) : "memory");
    return ok;
}
__device__ __forceinline__ void mbar_wait(uint32_t b, uint32_t par) {
    int it = 0;
#pragma unroll 1
    while (!mbar_try(b, par)) { spin_guard(++it); }
}
__device__ __forceinline__ void mbar_wait_w(uint32_t b, uint32_t par) {
    int it = 0;
    bool ok;
#pragma unroll 1
    do { ok = __all_sync(~0u, mbar_try(b, par)); spin_guard(++it); } while (!ok);
}
__device__ __forceinline__ void mbar_wait_cluster(uint32_t b, uint32_t par) {
    int it = 0;
    while (true) {
        uint32_t ok;
        asm volatile("{.reg .pred p; mbarrier.try_wait.parity.acquire.cluster.shared::cta.b64 p, [%1], %2; selp.u32 %0, 1, 0, p;}" : "=r"(ok) : "r"(b), "r"(par) : "memory");
        if (ok) break;
        spin_guard(++it);
    }
}
__device__ __forceinline__ void tma2d(uint32_t dst, const CUtensorMap* m, int c0, int c1, uint32_t bar) {
    asm volatile("cp.async.bulk.tensor.2d.shared::cluster.global.mbarrier::complete_tx::bytes [%0], [%1, {%3, %4}], [%2];" ::"r"(dst), "l"(m), "r"(bar), "r"(c0), "r"(c1) : "memory");
}
__device__ __forceinline__ void tma2d_mc(uint32_t dst, const CUtensorMap* m, int c0, int c1, uint32_t bar, uint16_t mask) {
    asm volatile("cp.async.bulk.tensor.2d.shared::cluster.global.mbarrier::complete_tx::bytes.multicast::cluster [%0], [%1, {%3, %4}], [%2], %5;" ::"r"(dst), "l"(m), "r"(bar), "r"(c0), "r"(c1), "h"(mask) : "memory");
}
__device__ __forceinline__ void bulk_g2s(uint32_t dst, const void* src, uint32_t bytes, uint32_t bar) {
    asm volatile("cp.async.bulk.shared::cluster.global.mbarrier::complete_tx::bytes [%0], [%1], %2, [%3];" ::"r"(dst), "l"(src), "r"(bytes), "r"(bar) : "memory");
}
__device__ __forceinline__ void bar_sync(int id, int n) { asm volatile("bar.sync %0, %1;" ::"r"(id), "r"(n) : "memory"); }
__device__ __forceinline__ void bar_arrive(int id, int n) { asm volatile("bar.arrive %0, %1;" ::"r"(id), "r"(n) : "memory"); }
__device__ __forceinline__ void cluster_sync_all() { asm volatile("barrier.cluster.arrive.aligned; barrier.cluster.wait.aligned;" ::: "memory"); }
__device__ __forceinline__ void fence_async_smem() { asm volatile("fence.proxy.async.shared::cta;" ::: "memory"); }
__device__ __forceinline__ void ldsm4t(uint32_t* r, uint32_t a) {
    asm volatile("ldmatrix.sync.aligned.m8n8.x4.trans.shared.b16 {%0,%1,%2,%3}, [%4];" : "=r"(r[0]), "=r"(r[1]), "=r"(r[2]), "=r"(r[3]) : "r"(a) : "memory");
}
__device__ __forceinline__ void ldsm4(uint32_t* r, uint32_t a) {
    asm volatile("ldmatrix.sync.aligned.m8n8.x4.shared.b16 {%0,%1,%2,%3}, [%4];" : "=r"(r[0]), "=r"(r[1]), "=r"(r[2]), "=r"(r[3]) : "r"(a) : "memory");
}
__device__ __forceinline__ uint32_t movm(uint32_t a) {
    uint32_t d; asm volatile("movmatrix.sync.aligned.m8n8.trans.b16 %0, %1;" : "=r"(d) : "r"(a)); return d;
}
__device__ __forceinline__ void mma16816(float* d, uint32_t a0, uint32_t a1, uint32_t a2, uint32_t a3, uint32_t b0, uint32_t b1) {
    asm volatile("mma.sync.aligned.m16n8k16.row.col.f32.bf16.bf16.f32 {%0,%1,%2,%3},{%4,%5,%6,%7},{%8,%9},{%0,%1,%2,%3};"
                 : "+f"(d[0]), "+f"(d[1]), "+f"(d[2]), "+f"(d[3]) : "r"(a0), "r"(a1), "r"(a2), "r"(a3), "r"(b0), "r"(b1));
}
__device__ __forceinline__ void mma16816z(float* d, const uint32_t* a, uint32_t b0, uint32_t b1) {
    asm volatile("mma.sync.aligned.m16n8k16.row.col.f32.bf16.bf16.f32 {%0,%1,%2,%3},{%4,%5,%6,%7},{%8,%9},{%10,%10,%10,%10};"
                 : "=f"(d[0]), "=f"(d[1]), "=f"(d[2]), "=f"(d[3]) : "r"(a[0]), "r"(a[1]), "r"(a[2]), "r"(a[3]), "r"(b0), "r"(b1), "f"(0.f));
}
__device__ __forceinline__ void mma1688(float* d, uint32_t a0, uint32_t a1, uint32_t b0) {
    asm volatile("mma.sync.aligned.m16n8k8.row.col.f32.bf16.bf16.f32 {%0,%1,%2,%3},{%4,%5},{%6},{%0,%1,%2,%3};"
                 : "+f"(d[0]), "+f"(d[1]), "+f"(d[2]), "+f"(d[3]) : "r"(a0), "r"(a1), "r"(b0));
}
__device__ __forceinline__ uint32_t pack2(float lo, float hi) {
    uint32_t r; asm("cvt.rn.bf16x2.f32 %0, %1, %2;" : "=r"(r) : "f"(hi), "f"(lo)); return r;
}
__device__ __forceinline__ uint32_t hadd2(uint32_t a, uint32_t b) {
    uint32_t r; asm("add.rn.bf16x2 %0, %1, %2;" : "=r"(r) : "r"(a), "r"(b)); return r;
}
__device__ __forceinline__ uint32_t hadd2v(uint32_t a, uint32_t b) {
    uint32_t r; asm volatile("add.rn.bf16x2 %0, %1, %2;" : "=r"(r) : "r"(a), "r"(b)); return r;
}
__device__ __forceinline__ float bflo(uint32_t u) { return __uint_as_float(u << 16); }
__device__ __forceinline__ float bfhi(uint32_t u) { return __uint_as_float(u & 0xffff0000u); }
__device__ __forceinline__ float ex2(float x) { float r; asm("ex2.approx.ftz.f32 %0, %1;" : "=f"(r) : "f"(x)); return r; }
__device__ __forceinline__ uint4 ldg_rlx4(const void* p) {
    uint4 v; asm volatile("ld.relaxed.gpu.global.v4.u32 {%0,%1,%2,%3}, [%4];" : "=r"(v.x), "=r"(v.y), "=r"(v.z), "=r"(v.w) : "l"(p) : "memory"); return v;
}
__device__ __forceinline__ uint2 ldg_rlx2(const void* p) {
    unsigned long long v; asm volatile("ld.relaxed.gpu.global.b64 %0, [%1];" : "=l"(v) : "l"(p) : "memory");
    return make_uint2((uint32_t)v, (uint32_t)(v >> 32));
}
__device__ __forceinline__ uint32_t ldg_rlx1(const void* p) {
    uint32_t v; asm volatile("ld.relaxed.gpu.global.u32 %0, [%1];" : "=r"(v) : "l"(p) : "memory"); return v;
}
__device__ __forceinline__ void stg_rlx1(void* p, uint32_t v) { asm volatile("st.relaxed.gpu.global.u32 [%0], %1;" ::"l"(p), "r"(v) : "memory"); }
__device__ __forceinline__ void stg_rlx2(void* p, uint32_t x, uint32_t y) {
    unsigned long long v = (unsigned long long)x | ((unsigned long long)y << 32);
    asm volatile("st.relaxed.gpu.global.b64 [%0], %1;" ::"l"(p), "l"(v) : "memory");
}
__device__ __forceinline__ void stg_rlx4(void* p, uint32_t x, uint32_t y, uint32_t z, uint32_t w) {
    asm volatile("st.relaxed.gpu.global.v4.u32 [%0], {%1,%2,%3,%4};" ::"l"(p), "r"(x), "r"(y), "r"(z), "r"(w) : "memory");
}
__device__ __forceinline__ void sts4(uint32_t a, uint32_t x, uint32_t y, uint32_t z, uint32_t w) {
    asm volatile("st.shared.v4.u32 [%0], {%1,%2,%3,%4};" ::"r"(a), "r"(x), "r"(y), "r"(z), "r"(w) : "memory");
}
__device__ __forceinline__ uint4 lds4(uint32_t a) {
    uint4 v; asm volatile("ld.shared.v4.u32 {%0,%1,%2,%3}, [%4];" : "=r"(v.x), "=r"(v.y), "=r"(v.z), "=r"(v.w) : "r"(a) : "memory"); return v;
}
__device__ __forceinline__ void st_async4(uint32_t a, float x, float y, float z, float w, uint32_t bar) {
    asm volatile("st.async.shared::cluster.mbarrier::complete_tx::bytes.v4.f32 [%0], {%1,%2,%3,%4}, [%5];" ::"r"(a), "f"(x), "f"(y), "f"(z), "f"(w), "r"(bar) : "memory");
}
#define F4(d, i) "+f"(d[i]), "+f"(d[i + 1]), "+f"(d[i + 2]), "+f"(d[i + 3])
template <bool V> __device__ __forceinline__ void wgmma_tok_rs(float* d, const uint32_t* a, uint64_t b, int sc) {
    if (V) asm volatile("{.reg .pred p; setp.ne.b32 p, %25, 0;\n wgmma.mma_async.sync.aligned.m64n40k16.f32.bf16.bf16 {%0,%1,%2,%3,%4,%5,%6,%7,%8,%9,%10,%11,%12,%13,%14,%15,%16,%17,%18,%19}, {%20,%21,%22,%23}, %24, p, 1, 1, 0;}"
                        : F4(d, 0), F4(d, 4), F4(d, 8), F4(d, 12), F4(d, 16) : "r"(a[0]), "r"(a[1]), "r"(a[2]), "r"(a[3]), "l"(b), "r"(sc));
    else asm volatile("{.reg .pred p; setp.ne.b32 p, %21, 0;\n wgmma.mma_async.sync.aligned.m64n32k16.f32.bf16.bf16 {%0,%1,%2,%3,%4,%5,%6,%7,%8,%9,%10,%11,%12,%13,%14,%15}, {%16,%17,%18,%19}, %20, p, 1, 1, 0;}"
                      : F4(d, 0), F4(d, 4), F4(d, 8), F4(d, 12) : "r"(a[0]), "r"(a[1]), "r"(a[2]), "r"(a[3]), "l"(b), "r"(sc));
}
template <bool V> __device__ __forceinline__ void wgmma_tok_ss(float* d, uint64_t a, uint64_t b) {
    if (V) asm volatile("wgmma.mma_async.sync.aligned.m64n40k16.f32.bf16.bf16 {%0,%1,%2,%3,%4,%5,%6,%7,%8,%9,%10,%11,%12,%13,%14,%15,%16,%17,%18,%19}, %20, %21, 1, 1, 1, 1, 0;"
                        : F4(d, 0), F4(d, 4), F4(d, 8), F4(d, 12), F4(d, 16) : "l"(a), "l"(b));
    else asm volatile("wgmma.mma_async.sync.aligned.m64n32k16.f32.bf16.bf16 {%0,%1,%2,%3,%4,%5,%6,%7,%8,%9,%10,%11,%12,%13,%14,%15}, %16, %17, 1, 1, 1, 1, 0;"
                      : F4(d, 0), F4(d, 4), F4(d, 8), F4(d, 12) : "l"(a), "l"(b));
}
#define F16(d, i) F4(d, i), F4(d, i + 4), F4(d, i + 8), F4(d, i + 12)
template <int TA>
__device__ __forceinline__ void wgmma_ss128(float* d, uint64_t a, uint64_t b, int sc) {
    asm volatile("{.reg .pred p; setp.ne.b32 p, %66, 0;\n wgmma.mma_async.sync.aligned.m64n128k16.f32.bf16.bf16 "
                 "{%0,%1,%2,%3,%4,%5,%6,%7,%8,%9,%10,%11,%12,%13,%14,%15,%16,%17,%18,%19,%20,%21,%22,%23,%24,%25,%26,%27,%28,%29,%30,%31,"
                 "%32,%33,%34,%35,%36,%37,%38,%39,%40,%41,%42,%43,%44,%45,%46,%47,%48,%49,%50,%51,%52,%53,%54,%55,%56,%57,%58,%59,%60,%61,%62,%63}, %64, %65, p, 1, 1, %67, 1;}"
                 : F16(d, 0), F16(d, 16), F16(d, 32), F16(d, 48) : "l"(a), "l"(b), "r"(sc), "n"(TA));
}

__device__ __forceinline__ float warp_sum(float v) {
#pragma unroll
    for (int o = 16; o; o >>= 1) v += __shfl_xor_sync(~0u, v, o);
    return v;
}
__device__ __forceinline__ float bfround(float x) { return __bfloat162float(__float2bfloat16(x)); }

__device__ __forceinline__ void wait_count1(const uint32_t* p, uint32_t target) {
    int it = 0;
#pragma unroll 1
    while (true) {
        uint32_t v;
        asm volatile("ld.acquire.gpu.global.u32 %0, [%1];" : "=r"(v) : "l"(p) : "memory");
        if (v >= target) break;
        spin_guard(++it);
    }
}
__device__ __forceinline__ void red2(float* p, float a, float b) {
    asm volatile("red.relaxed.gpu.global.add.v2.f32 [%0], {%1, %2};" ::"l"(p), "f"(a), "f"(b) : "memory");
}
__device__ __forceinline__ void l2_prefetch(const void* p, uint32_t bytes) {
    asm volatile("cp.async.bulk.prefetch.L2.global [%0], %1;" ::"l"(p), "r"(bytes) : "memory");
}
__device__ __forceinline__ void signal_count(uint32_t* p) { asm volatile("red.release.gpu.global.add.u32 [%0], 1;" ::"l"(p) : "memory"); }
__device__ __forceinline__ void e_expect(uint32_t b, uint32_t tx) {
    asm volatile("{.reg .pred p; elect.sync _|p, 0xffffffff; @p mbarrier.arrive.expect_tx.shared.b64 _, [%0], %1;}" ::"r"(b), "r"(tx) : "memory");
}
__device__ __forceinline__ void e_tma2d(uint32_t dst, const CUtensorMap* m, int c0, int c1, uint32_t bar) {
    asm volatile("{.reg .pred p; elect.sync _|p, 0xffffffff;\n @p cp.async.bulk.tensor.2d.shared::cluster.global.mbarrier::complete_tx::bytes [%0], [%1, {%3, %4}], [%2];}"
                 ::"r"(dst), "l"(m), "r"(bar), "r"(c0), "r"(c1) : "memory");
}
__device__ __forceinline__ void e_tma2d_mc(uint32_t dst, const CUtensorMap* m, int c0, int c1, uint32_t bar) {
    asm volatile("{.reg .pred p; elect.sync _|p, 0xffffffff;\n @p cp.async.bulk.tensor.2d.shared::cluster.global.mbarrier::complete_tx::bytes.multicast::cluster [%0], [%1, {%3, %4}], [%2], %5;}"
                 ::"r"(dst), "l"(m), "r"(bar), "r"(c0), "r"(c1), "h"((uint16_t)3) : "memory");
}
__device__ __forceinline__ void e_prefetch(const void* p, uint32_t bytes) {
    asm volatile("{.reg .pred p; elect.sync _|p, 0xffffffff; @p cp.async.bulk.prefetch.L2.global [%0], %1;}" ::"l"(p), "r"(bytes) : "memory");
}
__device__ __forceinline__ void wait_count_w(const uint32_t* p, uint32_t target) {
    int it = 0;
#pragma unroll 1
    while (true) {
        uint32_t v;
        asm volatile("ld.acquire.gpu.global.u32 %0, [%1];" : "=r"(v) : "l"(p) : "memory");
        if (__all_sync(~0u, v >= target)) break;
        spin_guard(++it);
    }
}

__device__ __forceinline__ void ln_row(float* x) {
    float s = 0;
#pragma unroll
    for (int i = 0; i < 32; i++) s += x[i];
    float m = warp_sum(s) * (1.0f / DM);
    float q = 0;
#pragma unroll
    for (int i = 0; i < 32; i++) { x[i] -= m; q += x[i] * x[i]; }
    float r = rsqrtf(warp_sum(q) * (1.0f / DM) + 1e-5f);
#pragma unroll
    for (int i = 0; i < 32; i++) x[i] *= r;
}
__device__ __forceinline__ uint4 pack8(const float* x) {
    return make_uint4(pack2(x[0], x[1]), pack2(x[2], x[3]), pack2(x[4], x[5]), pack2(x[6], x[7]));
}
#define NL 5
constexpr uint32_t HCH = 5120, HBUF = 8 * HCH;
constexpr uint32_t SM_SX = 0, SM_ST = 2560, SM_OX = 8192, SM_LX = 10240, SM_PX = 11392, SM_PA = 12288, SM_VF = 18432, SM_TAB = 26624, SM_TRC = 41984, SM_HB = 49152, SM_WO = 131072,
                   SM_WL = 196608, SM_PRE = SM_WL, SM_BAR = 227328, SM_REC_TOTAL = 227328 + 256;
constexpr uint32_t SB0 = 1024;
constexpr int B_WO = 0, B_HE = 1, B_ROLE = 2, B_HB = 3, B_W = 5;
constexpr int NB_MEM = 1, NB_QK = 2, NB_X1 = 3, NB_X2 = 4, NB_WIN = 5, NB_WG = 6, NB_KDONE = 7, NB_FIN0 = 8, NB_H = 11, NB_A = 12, NB_B = 13, NB_C = 14, NB_F = 15;
#define ST_GATE 1
#define SPF 33
#define SPF_NS 100
#define TPV_DLY 0
#define L_AT 1
#define D_X2 200
#define D_V 150
#define NPF1 6
#define NPF 12
#define ROTM 7
#define FARF 1
#define T_GO 31
#define STG_ORD 2
#define GATE_AT 26
#define H4 2
#define T_X2 2000
#define T_V 2800
#define LAST_WG 0
#define QK_EARLY 1
#define SMX16 1
#define NOB 1
#define VP_AT 0
#define KQ_AT 17
#define PD 4
#define PFENCE 1
#define NPF2 9
#define PF_DLY 0
#define H_AT 0
#define H_D 50
#define REQ_LATE 0
#define PIN_EPI 1

#define PROF_INIT
#define PROF(i)
#define PROFV(i, v)
#define PROF_OUT

__device__ __forceinline__ uint32_t clk32() { uint32_t t; asm volatile("mov.u32 %0, %%clock;" : "=r"(t) :: "memory"); return t; }
__device__ __forceinline__ uint32_t gtime32() { uint32_t t; asm volatile("mov.u32 %0, %%globaltimer_lo;" : "=r"(t) :: "memory"); return t; }
__device__ __forceinline__ void spin_until(uint32_t t0, uint32_t d) { while (clk32() - t0 < d) {} }
template <int N> __device__ __forceinline__ uint32_t delay(uint32_t zero) {
    float x = __uint_as_float(clk32());
#pragma unroll
    for (int i = 0; i < N; i++) asm volatile("ex2.approx.ftz.f32 %0, %0;" : "+f"(x));
    return __float_as_uint(x) & zero;
}
__device__ __forceinline__ uint32_t clk_after(uint32_t x, uint32_t zero) {
    unsigned long long c = 0;
    asm volatile("{.reg .pred p; setp.eq.u32 p, %1, 0; @p mov.u64 %0, %%clock64;}" : "+l"(c) : "r"(x & zero) : "memory");
    return (uint32_t)c;
}
__device__ __forceinline__ uint32_t later(uint32_t a, uint32_t b) { return a + max((int)(b - a), 0); }
__device__ __forceinline__ void wait_clk(uint32_t t) {
#pragma unroll 1
    while (true) {
        unsigned long long c;
        asm volatile("mov.u64 %0, %%clock64;" : "=l"(c) :: "memory");
        if ((int)((uint32_t)c - t) >= 0) break;
    }
}
__device__ __forceinline__ uint32_t opaque(uint32_t v) { return __shfl_sync(~0u, v, threadIdx.x & 31); }
__device__ __forceinline__ uint32_t xor_or(uint32_t a, uint32_t b, uint32_t t) {
    uint32_t r; asm volatile("lop3.b32 %0, %1, %2, %3, 0x7E;" : "=r"(r) : "r"(a), "r"(b), "r"(t)); return r;
}
__device__ __forceinline__ uint32_t or3(uint32_t a, uint32_t b, uint32_t c) {
    uint32_t r; asm volatile("lop3.b32 %0, %1, %2, %3, 0xFE;" : "=r"(r) : "r"(a), "r"(b), "r"(c)); return r;
}
__device__ __forceinline__ uint32_t settag(uint32_t v, uint32_t tag) {
    uint32_t r; asm("lop3.b32 %0, %1, 1, %2, 0xB8;" : "=r"(r) : "r"(v), "r"(tag)); return r;
}
__device__ __forceinline__ void ldg4_if(uint4& v, const void* p, bool c) {
    asm volatile("{.reg .pred p; setp.ne.u32 p, %5, 0; @p ld.relaxed.gpu.global.v4.u32 {%0,%1,%2,%3}, [%4];}"
                 : "+r"(v.x), "+r"(v.y), "+r"(v.z), "+r"(v.w) : "l"(p), "r"((uint32_t)c) : "memory");
}
__device__ __forceinline__ uint4 ldg_rlx2x2(const void* p) {
    unsigned long long a, b;
    asm volatile("ld.relaxed.gpu.global.v2.b64 {%0,%1}, [%2];" : "=l"(a), "=l"(b) : "l"(p) : "memory");
    return make_uint4((uint32_t)a, (uint32_t)(a >> 32), (uint32_t)b, (uint32_t)(b >> 32));
}
__device__ __forceinline__ void stg_rlx2x2(void* p, uint32_t x, uint32_t y, uint32_t z, uint32_t w) {
    asm volatile("{.reg .b64 a, b; mov.b64 a, {%1,%2}; mov.b64 b, {%3,%4}; st.relaxed.gpu.global.v2.b64 [%0], {a, b};}" ::"l"(p), "r"(x), "r"(y), "r"(z), "r"(w) : "memory");
}
__device__ __forceinline__ void ldg1_if(uint32_t& v, const void* p, bool c) {
    asm volatile("{.reg .pred p; setp.ne.u32 p, %2, 0; @p ld.relaxed.gpu.global.u32 %0, [%1];}" : "+r"(v) : "l"(p), "r"((uint32_t)c) : "memory");
}
__device__ __forceinline__ void sts2(uint32_t a, float x, float y) { asm volatile("st.shared.v2.f32 [%0], {%1,%2};" ::"r"(a), "f"(x), "f"(y) : "memory"); }
__device__ __forceinline__ void sts4f(uint32_t a, float x, float y, float z, float w) {
    asm volatile("st.shared.v4.f32 [%0], {%1,%2,%3,%4};" ::"r"(a), "f"(x), "f"(y), "f"(z), "f"(w) : "memory");
}
__device__ __forceinline__ void sts1(uint32_t a, uint32_t x) { asm volatile("st.shared.u32 [%0], %1;" ::"r"(a), "r"(x) : "memory"); }
__device__ __forceinline__ uint32_t lds1(uint32_t a) { uint32_t v; asm volatile("ld.shared.u32 %0, [%1];" : "=r"(v) : "r"(a) : "memory"); return v; }
__device__ __forceinline__ float4 lds4f(uint32_t a) {
    float4 v; asm volatile("ld.shared.v4.f32 {%0,%1,%2,%3}, [%4];" : "=f"(v.x), "=f"(v.y), "=f"(v.z), "=f"(v.w) : "r"(a) : "memory"); return v;
}
__device__ __forceinline__ float2 lds2f(uint32_t a) {
    float2 v; asm volatile("ld.shared.v2.f32 {%0,%1}, [%2];" : "=f"(v.x), "=f"(v.y) : "r"(a) : "memory"); return v;
}
__device__ __forceinline__ bool any_bit0(uint32_t x) {
    uint32_t r;
    asm volatile("{.reg .pred p, q; .reg .b32 t; and.b32 t, %1, 1; setp.ne.u32 p, t, 0; vote.sync.any.pred q, p, 0xffffffff; selp.u32 %0, 1, 0, q;}" : "=r"(r) : "r"(x));
    return r;
}
__device__ __forceinline__ float rcp_fast(float x) { float r; asm("rcp.approx.ftz.f32 %0, %1;" : "=f"(r) : "f"(x)); return r; }
__device__ __forceinline__ void stsm4(uint32_t a, uint32_t r0, uint32_t r1, uint32_t r2, uint32_t r3) {
    asm volatile("stmatrix.sync.aligned.m8n8.x4.shared.b16 [%0], {%1,%2,%3,%4};" ::"r"(a), "r"(r0), "r"(r1), "r"(r2), "r"(r3) : "memory");
}
__device__ __forceinline__ void stsm4t(uint32_t a, uint32_t r0, uint32_t r1, uint32_t r2, uint32_t r3) {
    asm volatile("stmatrix.sync.aligned.m8n8.x4.trans.shared.b16 [%0], {%1,%2,%3,%4};" ::"r"(a), "r"(r0), "r"(r1), "r"(r2), "r"(r3) : "memory");
}
__device__ __forceinline__ void stg_b64_if(bool c, void* p, uint32_t x, uint32_t y) {
    asm volatile("{.reg .pred p; .reg .b64 a; setp.ne.u32 p, %3, 0; mov.b64 a, {%1,%2}; @p st.relaxed.gpu.global.b64 [%0], a;}" ::"l"(p), "r"(x), "r"(y), "r"((uint32_t)c) : "memory");
}
__device__ __forceinline__ void cp_async16(uint32_t dst, const void* src) { asm volatile("cp.async.cg.shared.global [%0], [%1], 16;" ::"r"(dst), "l"(src) : "memory"); }
__device__ __forceinline__ uint32_t hadd2h(uint32_t a, uint32_t b) { uint32_t r; asm("add.rn.f16x2 %0, %1, %2;" : "=r"(r) : "r"(a), "r"(b)); return r; }
__device__ __forceinline__ uint32_t hmax2h(uint32_t a, uint32_t b) { uint32_t r; asm("max.f16x2 %0, %1, %2;" : "=r"(r) : "r"(a), "r"(b)); return r; }
__device__ __forceinline__ uint32_t max3u(uint32_t a, uint32_t b, uint32_t c) { return __vimax3_u32(a, b, c); }
__device__ __forceinline__ void fence_gpu() { asm volatile("fence.acq_rel.gpu;" ::: "memory"); }

__device__ __forceinline__ void h_load(uint32_t sb, const uint8_t* hsrc, int pass, uint32_t rank, uint32_t rot, uint32_t wq) {
    const uint32_t bar = sb + SM_BAR + 8 * (B_HB + (pass & 1)), c = (wq + rot) & 3, dst = sb + SM_HB + (pass & 1) * HBUF + (rank * 4 + c) * HCH;
    const uint8_t* src = hsrc + ((size_t)pass * 65536 + c * 4096);
    if (wq == 0) e_expect(bar, 32768);
#pragma unroll
    for (int i = 0; i < H4; i++) {
        const uint32_t o = ((i + (rot >> 2)) & (H4 - 1)) * (4096 / H4);
        asm volatile("{.reg .pred p; elect.sync _|p, 0xffffffff;\n"
                     " @p cp.async.bulk.shared::cluster.global.mbarrier::complete_tx::bytes.multicast::cluster [%0], [%1], %4, [%2], %3;}"
                     ::"r"(dst + o), "l"(src + o), "r"(bar), "h"((uint16_t)3), "n"(4096 / H4) : "memory");
    }
}
__device__ __forceinline__ uint4 ldg_b128(const void* p) {
    uint4 v;
    asm volatile("{.reg .b128 t; .reg .b64 a, b; ld.relaxed.gpu.global.b128 t, [%4]; mov.b128 {a, b}, t; mov.b64 {%0,%1}, a; mov.b64 {%2,%3}, b;}"
                 : "=r"(v.x), "=r"(v.y), "=r"(v.z), "=r"(v.w) : "l"(p) : "memory");
    return v;
}
__device__ __forceinline__ void stg_b128_if(bool c, void* p, uint32_t x, uint32_t y, uint32_t z, uint32_t w) {
    asm volatile("{.reg .pred p; .reg .b128 t; .reg .b64 a, b; setp.ne.u32 p, %5, 0; mov.b64 a, {%1,%2}; mov.b64 b, {%3,%4}; mov.b128 t, {a, b}; @p st.relaxed.gpu.global.b128 [%0], t;}"
                 ::"l"(p), "r"(x), "r"(y), "r"(z), "r"(w), "r"((uint32_t)c) : "memory");
}
__device__ __forceinline__ float pretag(float x, uint32_t add, uint32_t keep) { return __uint_as_float((__float_as_uint(x) + add) & keep); }

template <bool MASK, class F>
__device__ __forceinline__ void softmax_rows(uint32_t src, uint32_t dst, uint32_t g16, int row0, F mid) {
    const uint32_t u = (g16 >> 7) & 3, e = ((g16 >> 9) << 3) | ((g16 >> 4) & 7);
    const uint32_t se = src + e * 8, su = se + u * 1088;
    const float2 p0 = lds2f(su), p1 = lds2f(su + 256), p2 = lds2f(su + 512), p3 = lds2f(su + 768);
    const float2 m0 = lds2f(se + 4352), m1 = lds2f(se + 4352 + 256), m2 = lds2f(se + 4352 + 512), m3 = lds2f(se + 4352 + 768);
    float a0 = (p0.x + p1.x) + (p2.x + p3.x), a1 = (p0.y + p1.y) + (p2.y + p3.y);
    const float a2 = (m0.x + m1.x) + (m2.x + m3.x), a3 = (m0.y + m1.y) + (m2.y + m3.y);
    mid(__float_as_uint(a3));
    if (MASK) {
        const int vis = row0 + (e >> 2) - 2 * (e & 3) - 8 * u;
        if (vis < 0) a0 = -1e9f / 0.08838834764831845f;
        if (vis < 1) a1 = -1e9f / 0.08838834764831845f;
    }
    int k = __float_as_int(fmaxf(fmaxf(a0, a1), fmaxf(a2, a3)));
    k ^= (k >> 31) & 0x7fffffff;
    const bool hi = g16 & 64;
    const int k0 = __reduce_max_sync(~0u, hi ? INT_MIN : k), k1 = __reduce_max_sync(~0u, hi ? k : INT_MIN);
    k = hi ? k1 : k0;
    const float m = __int_as_float(k ^ ((k >> 31) & 0x7fffffff));
    const float sl2 = 0.08838834764831845f * 1.4426950408889634f, mb = -m * sl2;
    sts1(dst + e * 16 + u * 4, pack2(ex2(fmaf(a0, sl2, mb)), ex2(fmaf(a1, sl2, mb))));
    sts1(dst + 512 + e * 4, pack2(ex2(fmaf(a2, sl2, mb)), ex2(fmaf(a3, sl2, mb))));
}

__device__ __forceinline__ uint32_t pack_h2(float lo, float hi) {
    uint32_t r; asm("cvt.rn.satfinite.f16x2.f32 %0, %1, %2;" : "=r"(r) : "f"(hi), "f"(lo)); return r;
}
__device__ __forceinline__ float2 unpack_h2(uint32_t u) {
    float2 r; asm("{.reg .b16 l, h; mov.b32 {l, h}, %2; cvt.f32.f16 %0, l; cvt.f32.f16 %1, h;}" : "=f"(r.x), "=f"(r.y) : "r"(u)); return r;
}
__device__ __forceinline__ uint32_t h2bf(uint32_t u) { const float2 f = unpack_h2(u); return pack2(f.x, f.y); }
__device__ __forceinline__ void red_h8(void* p, uint32_t x, uint32_t y, uint32_t z, uint32_t w) {
    asm volatile("red.relaxed.gpu.global.add.noftz.v4.f16x2 [%0], {%1,%2,%3,%4};" ::"l"(p), "r"(x), "r"(y), "r"(z), "r"(w) : "memory");
}
__device__ __forceinline__ void red_h2_if(bool c, void* p, uint32_t x) {
    asm volatile("{.reg .pred p; setp.ne.u32 p, %2, 0; @p red.relaxed.gpu.global.add.noftz.f16x2 [%0], %1;}" ::"l"(p), "r"(x), "r"((uint32_t)c) : "memory");
}
__device__ __forceinline__ void red_h10(bool c, void* p, void* q, uint32_t x, uint32_t y, uint32_t z, uint32_t w, uint32_t e) {
    asm volatile("{.reg .pred p; setp.ne.u32 p, %7, 0; red.relaxed.gpu.global.add.noftz.v4.f16x2 [%0], {%2,%3,%4,%5};\n"
                 " @p red.relaxed.gpu.global.add.noftz.f16x2 [%1], %6;}" ::"l"(p), "l"(q), "r"(x), "r"(y), "r"(z), "r"(w), "r"(e), "r"((uint32_t)c) : "memory");
}
constexpr float SM_L2E = 0.08838834764831845f * 1.4426950408889634f;
template <int V> struct IC { static constexpr int value = V; };
typedef unsigned long long u64;
__device__ __forceinline__ uint32_t lo32(u64 v) { return (uint32_t)v; }
__device__ __forceinline__ uint32_t hi32(u64 v) { return (uint32_t)(v >> 32); }
__device__ __forceinline__ u64 ldg_u64(const void* p) { u64 v; asm volatile("ld.relaxed.gpu.global.b64 %0, [%1];" : "=l"(v) : "l"(p) : "memory"); return v; }
__device__ __forceinline__ void ldg_u64_if(u64& v, const void* p, bool c) {
    asm volatile("{.reg .pred p; setp.ne.u32 p, %2, 0; @p ld.relaxed.gpu.global.b64 %0, [%1];}" : "+l"(v) : "l"(p), "r"((uint32_t)c) : "memory");
}
struct RecTime { uint32_t go, x2, v, dx2, dv, h; };
__device__ __forceinline__ void rec_main(uint32_t sb, const CUtensorMap* tWo, uint8_t* arena, int role, int hinfo, int wg, uint32_t zero, const RecTime& tm) {
    const int hA = hinfo & 255;
    const int tid = threadIdx.x, t = tid & 127, lane = tid & 31, wi = t >> 5;
    const uint32_t bars = sb + SM_BAR;
    const int head = role >> 2, qd = role & 3, j = blockIdx.x & 1, kh = role & 1;
    const uint32_t mypar = head >= hA;
    const uint32_t wiu = __reduce_max_sync(~0u, wi);
    const bool warp0 = wiu == 0;
    const uint8_t* hsrc = (const uint8_t*)g_himg + kh * 32768 + j * 16384;
    auto tokbase = [&](int ty) { return ((ty + 1) << 21) + blk(lb_tok(head), mypar ^ ((hinfo >> (8 + ty)) & 1)); };
    const uint32_t tbw = tokbase(wg), tbq = tokbase(0) + (qd >> 1) * 2048 + (qd & 1) * 8;
#define KS(p) (4 * (((p) >> 1) & 7) + ((p) >> 4) + 2 * ((p) & 1))
    uint32_t w[32 - NL][4];
    const uint32_t frow = ((lane >> 4) * 8 + (lane & 7)) * 128, fx = ((lane >> 3) & 1) ^ (lane & 7);
    {
#pragma unroll 1
        for (int i = 0; i < 4; i++) mbar_wait_w(bars + 8 * (B_W + (wg == 2 ? 8 + i : 2 * i + wg)), 0);
        const uint32_t stg = sb + wg * 65536;
#pragma unroll
        for (int p = NL; p < 32; p++) ldsm4t(w[p - NL], stg + KS(p) * 2048 + frow + ((fx ^ (2 * wi)) << 4));
#pragma unroll
        for (int i = 0; i < NL; i++) {
            const uint4 v = lds4(stg + KS(i) * 2048 + t * 16);
            sts4(sb + SM_WL + (wg * NL + i) * 2048 + t * 16, v.x, v.y, v.z, v.w);
        }
        fence_async_smem();
        if (wg < 2) bar_sync(NB_WG, 256);
        if (wg > 0) wait_count_w(&g_tick[32 + (lane & 3) * 8], 1);
        if (wg == 1) {
            if (t == 0) mbar_arrive_cluster(bars + 8 * B_HE, j ^ 1);
            asm volatile("fence.proxy.async.global;" ::: "memory");
            mbar_wait_w(bars + 8 * B_HE, 0);
#pragma unroll 1
            for (int i = 0; i < 2; i++) h_load(sb, hsrc, i, j, head, wiu);
        }
        TL(3 + wg)
    }
    uint32_t g16 = opaque(t * 16);
    {
        const uint32_t c16 = kh * 2048 + ((2 * j + (wi >> 1)) * 32 + lane) * 16;
        const uint32_t xso = blk(lb_x2(head), mypar), wr = wi ^ (head & ROTM & 3), gr = (wg ^ ((head & ROTM) >> 2)) & 1, ff = kh ^ mypar ^ FARF;
        const uint32_t pc = wg < 2 ? acc_piece(wr >> 1, qd * 2 + (wr & 1), gr) + CP2 * ((wr >> 1) ^ mypar ^ 1) * 4096 : acc_piece(kh, wi, ff) + CP2 * (kh ^ mypar) * 4096;
        const uint32_t lm = sb + SM_HB + 4096 + (lane & 7) * 128 + ((fx ^ ((lane >> 4) * 4)) << 4);
        const uint32_t a0 = wg < 2 ? sb + SM_WL + wg * NL * 2048 + frow + ((fx ^ (2 * wi)) << 4) : blk(LB_STAMP + (wi >> 1), mypar) + stamp_line(wi, lane >> 3) + (lane & 7) * 16;
        const uint32_t a1 = pc + lane * 16;
        const uint32_t a2 = wg < 2 ? pc + ACC_X + (lane >> 3) * 4 : CP2 ? role * 256 + (lane < 16 ? 0 : ACC_X - 256) + lane * 16 : (role >> 2) * 1024 + (lane < 8 ? (role & 3) * 128 : 384) + lane * 16;
        const uint32_t a3 = wg < 2 ? sb + SM_WO + wr * 16384 + frow + ((fx ^ (2 * gr)) << 4) : qd * 65536 + head * 2048 + wi * 512 + lane * 4;
        const uint32_t a4 = wg < 2 ? lm : (lm ^ (ff * 32)) + wi * HCH;
        bar_sync(NB_X2, 384);
        if (wg == 0 && lane == 0) {
            mbar_expect(bars + 8 * B_WO, 16384);
            tma2d(sb + SM_WO + wi * 16384, tWo, (wi >> 1) * 512 + qd * 128 + (wi & 1) * 64, head * DH, bars + 8 * B_WO);
            tma2d(sb + SM_WO + wi * 16384 + 8192, tWo, (wi >> 1) * 512 + qd * 128 + (wi & 1) * 64, head * DH + 64, bars + 8 * B_WO);
        }
        __syncwarp();
        sts4(sb + SM_TAB + wg * 5120 + g16, a0, xso + wg * 16384 + (wi & 1) * 2048 + (c16 >> 1),
             wg ? xso + (wg == 2 ? 32768 : 0) + t * 8 : blk(LB_STAMP + ((lane >> 1) & 1), (lane >> 2) & 1) + stamp_line(lane, qd) + head * 4, tbw + (wi & 1) * 16384 + c16);
        sts4(sb + SM_TAB + wg * 5120 + 2048 + g16, a1, a2, a3, a4);
        sts2(sb + SM_TAB + wg * 5120 + 4096 + t * 8, __uint_as_float(tbw + t * 16), __uint_as_float((wg ? tbq : tokbase(1)) + t * 16));
    }
    const uint32_t po = (1 << 20) + j * 16384 + kh * 2048;
    const uint32_t ONES = 0x3f803f80u, tabw = sb + SM_TAB + wg * 5120;
#define LAST ((g16 & 0x70) == 0x70)
    PROF_INIT

    auto pa_ptr = [&](int p) { return arena + (((p & 1) ^ 1) * 32768 + po + lds1(tabw + 4096 + (g16 >> 1))); };
    auto pa_request = [&](int p) { cp_async16(sb + SM_PA + wg * 2048 + g16, pa_ptr(p)); };
    auto pa_get = [&](int p) {
        asm volatile("cp.async.wait_all;" ::: "memory");
        uint4 pa = lds4(sb + SM_PA + wg * 2048 + g16);
        int it = 0;
#pragma unroll 1
        while (any_bit0(pa.x ^ ((p - 1) >> 1) ^ 1) && p > 0 && p <= NSEG) { pa = ldg_b128(pa_ptr(p)); spin_guard(++it); }
        return pa;
    };
    auto token_pass = [&](auto vc, int s, uint4 pa, auto mid) {
        constexpr bool V = decltype(vc)::value;
        const int p = s + 2, b = p & 1;
        const uint32_t ftag = (((p - 1) >> 1) & 1) ^ 1, ptag = ((p >> 1) & 1) ^ 1;
#define HB(ks) dadd(mkdesc(SB0 + SM_HB + ((ks) >> 2) * HCH + ((ks) & 3) * 32, 16, 1024, 1), b * (HBUF / 16))
        float acc[V ? 20 : 16];
#pragma unroll
        for (int i = 0; i < 4; i++) { acc[2 * i] = bflo((&pa.x)[i]); acc[2 * i + 1] = bfhi((&pa.x)[i]); }
#pragma unroll
        for (int i = 8; i < (V ? 20 : 16); i++) acc[i] = 0.f;
        mid(-1, acc);
        wg_fence();
#pragma unroll
        for (int i = 0; i < 32; i++) {
            constexpr int GAP = 32 / NL;
            const int u = i / GAP, q = i - (u < NL ? u : NL);
            if (i % GAP == GAP - 1 && u < NL) wgmma_tok_ss<V>(acc, dadd(mkdesc(SB0 + SM_WL + u * 2048, 8192, 1024, 1), (V ? 2 : wg) * NL * 128), HB(KS(u)));
            else wgmma_tok_rs<V>(acc, w[q], HB(KS(NL + q)), 1);
            mid(i, acc);
        }
        wg_commit();
        const bool tg = V || !(g16 & 64);
        const uint32_t add = tg ? (ftag ^ 1) << 16 : 0u, keep = tg ? 0xfffe0000u : ~0u;
        const uint32_t add1 = V ? 0u : add, keep1 = V ? ~0u : keep;
        uint32_t add2 = !V && wg == 0 ? add : 0u, keep2 = !V && wg == 0 ? keep : ~0u;
        uint8_t* pdst = arena + (b * 32768 + (po ^ 2048) + lds1(tabw + 4096 + (g16 >> 1)));
        uint8_t* fdst = arena + ((b ^ 1) * 32768 + lds1(tabw + 12 + g16));
        mid(32, acc);
        if (PIN_EPI) asm volatile("" : "+l"(pdst), "+l"(fdst));
        wg_wait<0>();
        mid(33, acc);
        PROF(9)
        uint32_t r0 = pack2(pretag(acc[0], add, keep), pretag(acc[1], add1, keep1));
        uint32_t r1 = pack2(acc[2], acc[3]), r3 = pack2(acc[6], acc[7]);
        uint32_t r2 = pack2(pretag(acc[4], add2, keep2), pretag(acc[5], add2, keep2));
        if (!V) { r0 = movm(r0); r1 = movm(r1); r2 = movm(r2); r3 = movm(r3); }
        mid(34, acc);
        stg_b128_if(p < NSEG, pdst, settag(pack2(pretag(acc[8], (ptag ^ 1) << 16, 0xfffe0000u), acc[9]), ptag), pack2(acc[10], acc[11]), pack2(acc[12], acc[13]), pack2(acc[14], acc[15]));
        stg_b128_if(p > 0 && p <= NSEG, fdst, settag(r0, ftag), r1, !V && wg == 0 ? settag(r2, ftag) : r2, r3);
        PROF(10)
    };
    uint4 tf[2][2];
    auto load_tok = [&](int s, uint32_t o) {
        const uint8_t* ts = arena + ((s & 1) * 32768 + o);
#pragma unroll
        for (int a = 0; a < 2; a++)
#pragma unroll
            for (int b = 0; b < 2; b++) tf[a][b] = ldg_b128(ts + a * 16384 + b * 2048);
    };

    if (wg < 2) {
        mbar_wait_w(bars + 8 * B_HB, 0);
        token_pass(IC<0>(), -2, make_uint4(0, 0, 0, 0), [](int, float*) {});
        bar_sync(NB_MEM, 384);
        if (wg == 1) {
            if (g16 == 0) mbar_arrive_cluster(bars + 8 * B_HE, j ^ 1);
            mbar_wait_w(bars + 8 * B_HE, 1);
            h_load(sb, hsrc, 2, j, head, wiu);
        } else {
            bar_arrive(NB_WIN, 384);
        }
        pa_request(1);
        mbar_wait_w(bars + 8 * (B_HB + 1), 0);
        uint4 pa = pa_get(1);
#pragma unroll 1
        for (int s = 0; s < NSEG; s++) {
            uint32_t w0[NL][4], xo, lm;
            uint32_t kq;
            token_pass(IC<0>(), s - 1, pa, [&](int i, float*) {
                if (i == -1) {
                    if (wg == LAST_WG) bar_sync(NB_B, 256);
                    else bar_sync(NB_WIN, 384);
                }
                if (i == GATE_AT && wg != LAST_WG) bar_arrive(NB_B, 256);
                if (i == 34 && ST_GATE && wg != LAST_WG) bar_sync(NB_F, 256);
                if (i == 32) {
                    const float2 u = lds2f(tabw + g16);
                    xo = __float_as_uint(u.y);
                    lm = lds1(tabw + 2060 + g16) + (s & 1) * HBUF;
                    if (KQ_AT <= 16) kq = lds1(tabw + 4096 + (g16 >> 1) * wg);
#pragma unroll
                    for (int i = 0; i < NL; i++) ldsm4t(w0[i], __float_as_uint(u.x) + i * 2048);
                }
            });
            asm volatile("" : "+r"(lm));
            bar_sync(NB_MEM, 384);
            PROF(1)
            float c[4][4];
            uint32_t bq[PD][4], fz = 0;
#define MEMF(it) ((lm ^ (((it) >> 3) * 32)) + ((it) & 7) * HCH)
#pragma unroll
            for (int it = 0; it < PD; it++) ldsm4(bq[it], MEMF(it));
#pragma unroll
            for (int it = 0; it < 16; it++) {
                uint32_t* bfr = bq[it % PD];
                const uint32_t* wa = 2 * it < NL ? w0[2 * it < NL ? 2 * it : 0] : w[2 * it < NL ? 0 : 2 * it - NL];
                const uint32_t* wb = 2 * it + 1 < NL ? w0[2 * it + 1 < NL ? 2 * it + 1 : 0] : w[2 * it + 1 < NL ? 0 : 2 * it + 1 - NL];
                float *ca = c[(2 * it) & 3], *cb = c[(2 * it + 1) & 3];
                if (it < 2) { mma16816z(ca, wa, bfr[0], bfr[1]); mma16816z(cb, wb, bfr[2], bfr[3]); }
                else { mma16816(ca, wa[0], wa[1], wa[2], wa[3], bfr[0], bfr[1]); mma16816(cb, wb[0], wb[1], wb[2], wb[3], bfr[2], bfr[3]); }
                if (it + PD < 16) ldsm4(bfr, MEMF(it + PD));
                if (it == KQ_AT) {
                    if (PFENCE) fz = clk32();
                    load_tok(s, kq);
                }
            }
            if (QK_EARLY) bar_arrive(NB_QK + (__float_as_uint(c[0][0]) & zero), 384);
            const uint32_t r0 = pack2((c[0][0] + c[1][0]) + (c[2][0] + c[3][0]), (c[0][1] + c[1][1]) + (c[2][1] + c[3][1]));
            const uint32_t r1 = pack2((c[0][2] + c[1][2]) + (c[2][2] + c[3][2]), (c[0][3] + c[1][3]) + (c[2][3] + c[3][3]));
            if (!QK_EARLY) bar_arrive(NB_QK + (r0 & zero), 384);
            stg_rlx2(arena + xo, settag(movm(r0), (s & 1) ^ 1), movm(r1));
            const uint32_t tx = later(lds1(sb + SM_LX + 1040) + tm.x2, clk_after(r0, zero) + tm.dx2);
            g16 |= (fz | tx) & zero;
            PROF(2)
            {
                const uint32_t l16 = sb + (g16 & 0x1f0), g8 = g16 >> 1;
                const uint32_t tag = (s & 1) ^ 1, ttag = ((s >> 1) & 1) ^ 1;
                uint32_t wf[NPF][4], a3;
#define WF(f) ((a3 ^ (((f) & 1) * 64)) + ((f) >> 1) * 2048)
                if (wg == 1) {
                    float sc[5][4];
                    uint4 (&kf)[2][2] = tf;
                    uint32_t qa[2][4], km[4], fz;
                    int it = 0;
                    bool bad;
#pragma unroll 1
                    do {
                        u64 qf[2], x[8];
                        const float2 u = lds2f(tabw + 4096 + g8);
                        if (KQ_AT > 16) load_tok(s, __float_as_uint(u.x));
                        else {
#pragma unroll 1
                            for (int i = it; i > 0; i &= zero) load_tok(s, __float_as_uint(u.x));
                        }
                        const uint8_t *xp = arena + lds1(tabw + 8 + g16), *tq = arena + ((s & 1) * 32768 + __float_as_uint(u.y));
                        asm volatile("" : "+l"(xp));
#pragma unroll
                        for (int a = 0; a < 2; a++) qf[a] = ldg_u64(tq + a * 16384);
                        spin_guard(++it);
                        wait_clk(tx);
                        PROF(8)
#pragma unroll
                        for (int i = 0; i < 8; i++) x[i] = ldg_u64(xp + (i >> 2) * 16384 + (i & 3) * 1024);
                        fz = clk32();
                        const uint32_t bt = or3(xor_or(lo32(qf[0]), lo32(qf[1]), ttag), xor_or(kf[0][0].x, kf[0][1].x, ttag), xor_or(kf[1][0].x, kf[1][1].x, ttag));
#pragma unroll
                        for (int a = 0; a < 2; a++) { qa[a][1] = or3(lo32(qf[a]), zero, 0); qa[a][3] = or3(hi32(qf[a]), zero, 0); }
                        fz |= clk32();
#pragma unroll
                        for (int a = 0; a < 2; a++) { qa[a][0] = hadd2v(lo32(x[2 * a]), lo32(x[2 * a + 1])); qa[a][2] = hadd2v(hi32(x[2 * a]), hi32(x[2 * a + 1])); }
#pragma unroll
                        for (int a = 0; a < 2; a++) { km[2 * a] = hadd2v(lo32(x[4 + 2 * a]), lo32(x[5 + 2 * a])); km[2 * a + 1] = hadd2v(hi32(x[4 + 2 * a]), hi32(x[5 + 2 * a])); }
                        bad = any_bit0(or3(or3(bt, xor_or(lo32(x[0]), lo32(x[1]), tag), xor_or(lo32(x[2]), lo32(x[3]), tag)), xor_or(lo32(x[4]), lo32(x[5]), tag), xor_or(lo32(x[6]), lo32(x[7]), tag)));
                    } while (bad);
                    PROFV(13, it - 1)
                    PROF(7)
                    mma16816z(sc[0], qa[0], kf[0][0].x, kf[0][0].y);
                    mma16816z(sc[1], qa[0], kf[0][0].z, kf[0][0].w);
                    mma16816z(sc[2], qa[0], kf[0][1].x, kf[0][1].y);
                    mma16816z(sc[3], qa[0], kf[0][1].z, kf[0][1].w);
                    mma16816z(sc[4], qa[0], km[0], km[1]);
                    mma16816(sc[0], qa[1][0], qa[1][1], qa[1][2], qa[1][3], kf[1][0].x, kf[1][0].y);
                    mma16816(sc[1], qa[1][0], qa[1][1], qa[1][2], qa[1][3], kf[1][0].z, kf[1][0].w);
                    mma16816(sc[2], qa[1][0], qa[1][1], qa[1][2], qa[1][3], kf[1][1].x, kf[1][1].y);
                    mma16816(sc[3], qa[1][0], qa[1][1], qa[1][2], qa[1][3], kf[1][1].z, kf[1][1].w);
                    mma16816(sc[4], qa[1][0], qa[1][1], qa[1][2], qa[1][3], km[2], km[3]);
                    const uint32_t sx = sb + SM_SX + (g16 & 0x1f0) * 5;
                    sts4(sx + (g16 >> 5 & 0x30), pack_h2(sc[0][0] * SM_L2E, sc[0][1] * SM_L2E), pack_h2(sc[1][0] * SM_L2E, sc[1][1] * SM_L2E),
                         pack_h2(sc[2][0] * SM_L2E, sc[2][1] * SM_L2E), pack_h2(sc[3][0] * SM_L2E, sc[3][1] * SM_L2E));
                    sts1(sx + 64 + (g16 >> 7 & 0xc), pack_h2(sc[4][0] * SM_L2E, sc[4][1] * SM_L2E));
                    bar_arrive(NB_X1, 256);
                    const uint32_t now = gtime32();
#pragma unroll
                    for (int n = 0; n < 5; n++) sts2(sb + SM_ST + g8 + n * 1088, sc[n][2], sc[n][3]);
                    bar_arrive(NB_H, 256);
                    PROF(3)
                    a3 = lds1(tabw + 2056 + g16) | (fz & zero);
                    asm volatile("{.reg .pred p; setp.lt.u32 p, %2, 128; @p red.relaxed.gpu.global.max.u32 [%0], %1;}"
                                 ::"l"(arena + lds1(sb + SM_TAB + 8 + g16)), "r"(__funnelshift_r(now * 8, s + 1, 8)), "r"(g16) : "memory");
                    if (!H_AT) {
                        asm volatile("fence.proxy.async.global;" ::: "memory");
                        if (s + 3 <= NSEG) h_load(sb, hsrc, s + 3, j, head, wiu);
                    }
                    if (s == 0) mbar_wait_w(bars + 8 * B_WO, 0);
                    if (PF_DLY) a3 += delay<PF_DLY>(zero);
#pragma unroll
                    for (int f = 0; f < NPF; f++) ldsm4t(wf[f], WF(f));
                } else {
                    if (H_AT && g16 == 0) mbar_arrive_cluster(bars + 8 * B_HE, j ^ 1);
                    if (s == 0) { TL(9) mbar_wait_w(bars + 8 * B_WO, 0); TL(6) }
                    if (warp0 && !(s & 3)) wait_count_w(&g_tick[32 + ((g16 >> 4) & 3) * 8], min((s + 4) / 4 + 1, 16));
                    a3 = lds1(tabw + 2056 + g16);
#pragma unroll
                    for (int f = 0; f < NPF1; f++) ldsm4t(wf[f], WF(f));
                    const float2 u = lds2f(tabw + 4096 + g8);
                    const uint8_t *q0 = arena + (tag * 32768 + po + __float_as_uint(u.x)), *q1 = arena + (tag * 32768 + po + __float_as_uint(u.y));
                    if (H_AT) {
                        mbar_wait_w(bars + 8 * B_HE, s & 1);
                        asm volatile("fence.proxy.async.global;" ::: "memory");
                    }
                    wait_clk(tx + tm.h);
                    int it = 0;
                    bool bad;
#pragma unroll 1
                    do {
                        const uint4 p0 = ldg_b128(q0), p1 = ldg_b128(q1);
                        if (H_AT && !it && s + 3 <= NSEG) h_load(sb, hsrc, s + 3, j, head, wiu);
                        spin_guard(++it);
                        sts4(sb + SM_PA + g16, p0.x, p0.y, p0.z, p0.w);
                        sts4(sb + SM_PA + 2048 + g16, p1.x, p1.y, p1.z, p1.w);
                        bad = any_bit0(xor_or(p0.x, p1.x, ((s + 1) >> 1) ^ 1)) && s + 2 <= NSEG;
                    } while (bad);
                    bar_sync(NB_H, 256);
                    PROF(3)
                    softmax_rows<true>(sb + SM_ST, sb + SM_PX, g16, qd * 8, [&](uint32_t v) {
                        a3 += v & zero;
#pragma unroll
                        for (int f = NPF1; f < NPF2; f++) ldsm4t(wf[f], WF(f));
                    });
#pragma unroll
                    for (int f = NPF2; f < NPF; f++) ldsm4t(wf[f], WF(f));
                }
                PROF(5)
                float2 ls, a12;
                uint8_t *d0, *d1;
                bar_sync(NB_X2, 384);
                float c[4][4];
                uint32_t obs[4][4];
#pragma unroll
                for (int q = 0; q < NOB; q++) ldsm4t(obs[q], l16 + SM_OX + q * 512);
                if (NOB > 1) __syncwarp();
#pragma unroll
                for (int q = 0; q < 4; q++) {
                    const uint32_t* ob = obs[q];
                    if (q > 0 && q + NOB - 1 < 4) ldsm4t(obs[q + NOB - 1], l16 + SM_OX + (q + NOB - 1) * 512);
                    if (q == L_AT) ls = lds2f(sb + SM_LX + g8);
                    if (q == 2) { a12 = lds2f(tabw + 2048 + g16); d0 = arena + (acc_slot(s + 1) + __float_as_uint(a12.x)); d1 = arena + (acc_slot(s + 1) + __float_as_uint(a12.y)); }
#pragma unroll
                    for (int f = 4 * q; f < 4 * q + 4; f++) {
                        const uint32_t* a = wf[f % NPF];
                        if (f < 4) mma16816z(c[f], a, ob[f & 2], ob[(f & 2) + 1]);
                        else mma16816(c[f & 3], a[0], a[1], a[2], a[3], ob[f & 2], ob[(f & 2) + 1]);
                        if (f + NPF < 16) ldsm4t(wf[f % NPF], WF(f + NPF));
                    }
                }
                pa = lds4(sb + SM_PA + wg * 2048 + g16);
                if (wg == LAST_WG) bar_arrive(NB_WIN, 384);
                const float i0 = rcp_fast(ls.x), i1 = rcp_fast(ls.y);
                uint32_t v[4];
#pragma unroll
                for (int m = 0; m < 4; m++) v[m] = pack_h2((c[m >> 1][(m & 1) * 2] + c[(m >> 1) + 2][(m & 1) * 2]) * i0, (c[m >> 1][(m & 1) * 2 + 1] + c[(m >> 1) + 2][(m & 1) * 2 + 1]) * i1);
                red_h10(LAST, d0, d1, v[0], v[1], v[2], __byte_perm(v[3], ACC_ONE, LAST ? 0x7610 : 0x3210), __byte_perm(v[3], ACC_ONE, 0x7632));
                g16 |= v[0] & zero;
                if (CP2) {
                    red_h8((uint8_t*)((uintptr_t)d0 ^ 4096), v[0], v[1], v[2], __byte_perm(v[3], ACC_ONE, LAST ? 0x7610 : 0x3210));
                    red_h2_if(LAST, (uint8_t*)((uintptr_t)d1 ^ 4096), __byte_perm(v[3], ACC_ONE, 0x7632));
                }
                PROF(6)
            }
        }
        if (wg != LAST_WG) bar_sync(NB_WIN, 384);
    } else {
        uint32_t tgo = 0;
        TLC(0)
#pragma unroll 1
        for (int s = -2; s < NSEG; s++) {
            g16 |= s & zero;
            const uint32_t tag = (s & 1) ^ 1, ttag = ((s >> 1) & 1) ^ 1, l16 = sb + (g16 & 0x1f0), g8 = g16 >> 1;
            const int p = s + 2;
            auto request = [&](int s, uint32_t o) {
                cp_async16(sb + SM_PA + 4096 + g16, arena + (((s & 1) ^ 1) * 32768 + po + o));
                const uint8_t* ts = arena + ((s & 1) * 32768 + o);
#pragma unroll
                for (int i = 0; i < 4; i++) cp_async16(sb + SM_VF + i * 2048 + g16, ts + (i >> 1) * 16384 + (i & 1) * 2048);
            };
            if (s <= 0) request(s, lds1(tabw + 4096 + g8));
            if (s >= 0) {
                int it = 0;
                bool bad;
#pragma unroll 1
                do {
                    const uint4 t1 = lds4(tabw + 2048 + g16);
                    const uint32_t mo = acc_slot(s) + t1.x, eo = mo - (g16 & 0x1f0) + ACC_X + ((g16 >> 5) & 12);
                    const uint8_t *ms[2] = {arena + mo, arena + (mo ^ ACC_MT)}, *es[2] = {arena + eo, arena + (eo ^ ACC_MT)};
                    uint4 m[4];
                    uint32_t e[4] = {0, 0, 0, 0}, b = 0, sel = LAST ? 0x5410 : 0x3210, dst = t1.w + (s & 1) * HBUF;
                    asm volatile("" : "+l"(ms[0]), "+l"(ms[1]), "+l"(es[0]), "+l"(es[1]), "+r"(e[0]), "+r"(e[1]), "+r"(e[2]), "+r"(e[3]), "+r"(sel), "+r"(dst));
                    int late;
#pragma unroll 1
                    do { late = gtime32() * 8 - tgo; } while (late < 0 && s > 0);
                    __syncwarp();
                    if (it == 0) { PROF(11) PROFV(0, gtime32()) }
#pragma unroll
                    for (int i = 0; i < 4; i++) {
                        m[i] = ldg_rlx4(ms[i >> 1] + (i & 1) * 16384);
                        ldg1_if(e[i], es[i >> 1] + (i & 1) * 16384, LAST);
                    }
                    if (ST_GATE && it == 0) bar_arrive(NB_F, 256);
                    sts1(sb + SM_LX + 1040, clk32() - (it ? 0 : min((uint32_t)late >> 8, 8u) * 57));
                    spin_guard(++it);
#pragma unroll
                    for (int n = 0; n < 4; n++) {
                        const int i = n ^ STG_ORD;
                        b |= xor_or(m[i].w, e[i], ACC_ALL);
                        stsm4t((dst ^ ((i >> 1) * 32)) + (i & 1) * 4 * HCH, h2bf(m[i].x), h2bf(m[i].y), h2bf(m[i].z), h2bf(__byte_perm(m[i].w, e[i], sel)));
                    }
                    bad = __any_sync(~0u, LAST && b > 0xffffu);
                } while (bad);
                bar_arrive(NB_MEM, 384);
                PROFV(12, it - 1)
                PROF(1)
                if (s == 1) TL(7)
                if (s == 0) TL(13)
                if (s == 2) TL(14)
                fence_async_smem();
                stg_b128_if(g16 < (CP2 ? 288 : (role & 3) ? 128 : 160), arena + (acc_slot(s + 3) + lds1(tabw + 2052 + g16)), 0, 0, 0, 0);
            }
            const uint4 pa = pa_get(p);
            if (p <= NSEG) mbar_wait_w(bars + 8 * (B_HB + (p & 1)), (p >> 1) & 1);
            uint8_t* xd = arena + lds1(tabw + 4 + g16);
            uint32_t tx;
            token_pass(IC<1>(), s, pa, [&](int i, float* acc) {
                if (i == -1 && s >= 0) bar_sync(NB_QK, 384);
                if (i == 33) {
                    const uint32_t r0 = pack2(acc[16], acc[17]);
                    stg_b64_if(s >= 0, xd, settag(r0, tag), pack2(acc[18], acc[19]));
                    tx = clk_after(r0, zero) + tm.dv;
                    PROF(2)
                }
            });
            if (s < 0) {
                if (s == -2) { bar_sync(NB_MEM, 384); bar_arrive(NB_WIN, 384); }
                tgo = 0;
                continue;
            }
            uint4 (&vf)[2][2] = tf;
#pragma unroll
            for (int i = 0; i < 4; i++) vf[i >> 1][i & 1] = lds4(sb + SM_VF + i * 2048 + g16);
            uint32_t xv[4] = {0, 0, 0, 0};
            float oc[2][4], lc[4];
            auto pv = [&](uint32_t p0, uint32_t p1, uint32_t p2, uint32_t p3, uint32_t p4) {
                lc[0] = lc[1] = lc[2] = lc[3] = 0.f;
                mma16816z(oc[0], &vf[0][0].x, p0, p1);
                mma16816z(oc[1], &vf[1][0].x, p0, p1);
                mma16816(lc, ONES, ONES, ONES, ONES, p0, p1);
                mma16816(oc[0], vf[0][1].x, vf[0][1].y, vf[0][1].z, vf[0][1].w, p2, p3);
                mma16816(oc[1], vf[1][1].x, vf[1][1].y, vf[1][1].z, vf[1][1].w, p2, p3);
                mma16816(lc, ONES, ONES, ONES, ONES, p2, p3);
                mma1688(oc[0], xv[0], xv[1], p4);
                mma1688(oc[1], xv[2], xv[3], p4);
                mma1688(lc, ONES, ONES, p4);
            };
            int it = 0;
            bool bad;
#pragma unroll 1
            do {
#pragma unroll 1
                for (int i = it; i > 0; i &= zero) load_tok(s, lds1(tabw + 4096 + g8));
                u64 xr[4];
                const uint8_t* xp = arena + lds1(tabw + 8 + g16);
                asm volatile("" : "+l"(xp));
                auto load_v = [&](uint32_t z) {
#pragma unroll
                    for (int i = 0; i < 4; i++) xr[i] = ldg_u64(xp + z + i * 1024);
                };
                wait_clk(tx);
                PROF(3)
                if (it == 0) bar_sync(NB_X1, 256);
                if (VP_AT == 0) load_v(0);
                uint4 sx[5];
#pragma unroll
                for (int i = 0; i < 5; i++) sx[i] = lds4(sb + SM_SX + (g16 & 0x1f0) * 5 + i * 16);
                __syncwarp();
                if (VP_AT == 1) load_v(0);
                if (VP_AT == 2) load_v(sx[0].x & zero);
                if (VP_AT == 3) load_v(sx[4].x & zero);
                spin_guard(++it);
                uint32_t pm[5];
                uint32_t a[5];
#pragma unroll
                for (int n = 0; n < 5; n++) {
                    uint32_t u[4];
#pragma unroll
                    for (int w = 0; w < 4; w++) u[w] = n < 4 ? (&sx[w].x)[n] : (&sx[4].x)[w];
                    a[n] = hadd2h(hadd2h(u[0], u[1]), hadd2h(u[2], u[3]));
                }
                uint32_t m = hmax2h(hmax2h(hmax2h(a[0], a[1]), hmax2h(a[2], a[3])), a[4]);
                m = hmax2h(m, __byte_perm(m, 0, 0x1032));
                m = hmax2h(m, __shfl_xor_sync(~0u, m, 1));
                m = hmax2h(m, __shfl_xor_sync(~0u, m, 2));
                const float mf = unpack_h2(m).x;
#pragma unroll
                for (int n = 0; n < 5; n++) { const float2 u = unpack_h2(a[n]); pm[n] = pack2(ex2(u.x - mf), ex2(u.y - mf)); }
                PROF(4)
#pragma unroll
                for (int i = 0; i < 2; i++) { xv[2 * i] = hadd2(lo32(xr[2 * i]), lo32(xr[2 * i + 1])); xv[2 * i + 1] = hadd2(hi32(xr[2 * i]), hi32(xr[2 * i + 1])); }
                pv(pm[0], pm[1], pm[2], pm[3], pm[4]);
                bad = any_bit0(or3(or3(xor_or(vf[0][0].x, vf[0][1].x, ttag), xor_or(vf[1][0].x, vf[1][1].x, ttag), xor_or(lo32(xr[0]), lo32(xr[1]), tag)), xor_or(lo32(xr[2]), lo32(xr[3]), tag), 0));
                stsm4(sb + SM_OX + g16, pack2(oc[0][0], oc[0][1]), pack2(oc[0][2], oc[0][3]), pack2(oc[1][0], oc[1][1]), pack2(oc[1][2], oc[1][3]));
                sts2(sb + SM_LX + g8, lc[0], lc[1]);
            } while (bad);
            PROFV(14, it - 1)
            PROF(5)
            const uint32_t so = lds1(tabw + g16), oo = lds1(tabw + 2056 + g16), to = lds1(tabw + 4096 + g8);
            bar_sync(NB_X2, 384);
            const uint8_t* sp = arena + so;
            uint4 sv = ldg_rlx4(sp);
            if (!REQ_LATE) request(s + 1, to);
            const uint32_t dz = TPV_DLY ? delay<TPV_DLY>(zero) : 0;
            {
                const uint4 pp = lds4(l16 + SM_PX + dz);
                pv(pp.x, pp.y, pp.z, pp.w, lds1(sb + SM_PX + 512 + ((g16 >> 2) & 0x7c)));
            }
            const float i0 = rcp_fast(lc[0]), i1 = rcp_fast(lc[1]);
            bar_arrive(NB_WIN + (__float_as_uint(i0) & zero), 384);
            uint8_t* od = (uint8_t*)g_O + ((size_t)s * (32 * NH * DH * 2) + oo);
            const uint32_t ov[4] = {pack2(oc[0][0] * i0, oc[0][1] * i1), pack2(oc[0][2] * i0, oc[0][3] * i1), pack2(oc[1][0] * i0, oc[1][1] * i1), pack2(oc[1][2] * i0, oc[1][3] * i1)};
#pragma unroll
            for (int a = 0; a < 4; a++) stg_rlx1(od + a * 128, ov[a]);
            if (REQ_LATE) request(s + 1, to);
            PROF(6)
            it = 0;
#pragma unroll 1
            while (__any_sync(~0u, (int)(min(__vimin3_u32(sv.x, sv.y, sv.z), sv.w) >> 24) <= s)) { sv = ldg_rlx4(sp); spin_guard(++it); }
            PROFV(15, it)
            tgo = (__reduce_max_sync(~0u, max(max3u(sv.x, sv.y, sv.z), sv.w)) + tm.go + (g16 & zero)) << 8;
            PROF(7)
        }
        TL(8) TLC(1)
    }
    asm volatile("cp.async.wait_all;" ::: "memory");
    PROF_OUT
}

struct RecMaps { CUtensorMap wq, wk, wv, wo; };
struct RecPtrs { const bf16 *x, *mem0, *c, *wmod, *w1, *w3; uint8_t* arena; uint32_t zero; const bf16 *w2, *w4, *wo; RecTime tm; };

__device__ __forceinline__ float silu_bf(const bf16* c, int i) {
    const float v = __bfloat162float(c[i]);
    return bfround(__fdividef(v, 1.0f + __expf(-v)));
}
__device__ __noinline__ void rec_ln(float* coef, const RecPtrs& p, int id, int r0) {
    int r1 = 32;
    const int tid = threadIdx.x;
    const int lane = tid & 31, wid = tid >> 5;
    const uint32_t ring = smem_u32(coef) - SM_PRE + wid * 8192 + lane * 16;
    auto rowof = [&](int j) { return (j >> 1) * 64 + (id * 8 + wid) * 2 + (j & 1); };
    auto fetch = [&](int j) {
        if (j < 2 * r1) {
#pragma unroll
            for (int i = 0; i < 4; i++)
                asm volatile("cp.async.cg.shared.global [%0], [%1], 16;" ::"r"(ring + (j & 3) * 2048 + i * 512), "l"(p.x + (size_t)rowof(j) * DM + i * 256 + lane * 8) : "memory");
        }
        asm volatile("cp.async.commit_group;" ::: "memory");
    };
#pragma unroll 1
    for (int j = 2 * r0; j < 2 * r0 + 4; j++) fetch(j);
#pragma unroll 1
    for (int i = tid; i < 2 * DM / 4; i += 256) {
        uint4 v[8];
        int it = 0;
        uint32_t ok;
        do {
            ok = 1;
#pragma unroll
            for (int k = 0; k < 8; k++) v[k] = ldg_rlx4(g_modp + k * 2 * DM + i * 4);
#pragma unroll
            for (int k = 0; k < 8; k++) ok &= v[k].x & v[k].y & v[k].z & v[k].w;
            spin_guard(++it);
        } while (!ok);
        float t[4] = {0, 0, 0, 0};
#pragma unroll
        for (int k = 0; k < 8; k++) { t[0] += __uint_as_float(v[k].x); t[1] += __uint_as_float(v[k].y); t[2] += __uint_as_float(v[k].z); t[3] += __uint_as_float(v[k].w); }
#pragma unroll
        for (int j = 0; j < 4; j++) coef[i * 4 + j] = bfround(t[j]) + (i >= DM / 4 ? 1.0f : 0.0f);
    }
    bar_sync(NB_FIN0, 256);
    if (r0 == 0) {
        int v, it = 0;
#pragma unroll 1
        do { v = *(volatile int*)((uint8_t*)coef - SM_PRE + SM_BAR + 192); spin_guard(++it); } while (v == INT_MIN);
        if (v >= 0) r1 = 2;
    }
    if (tid == 0 && r0 == 0) TL(2)
#pragma unroll 1
    for (int j = 2 * r0; j < 2 * r1; j++) {
        float x[32];
        asm volatile("cp.async.wait_group 3;" ::: "memory");
#pragma unroll
        for (int i = 0; i < 4; i++) {
            const uint4 v = lds4(ring + (j & 3) * 2048 + i * 512);
            float* d = x + i * 8;
            d[0] = bflo(v.x); d[1] = bfhi(v.x); d[2] = bflo(v.y); d[3] = bfhi(v.y); d[4] = bflo(v.z); d[5] = bfhi(v.z); d[6] = bflo(v.w); d[7] = bfhi(v.w);
        }
        const int row = rowof(j), rr = row & 15;
        ln_row(x);
        fetch(j + 4);
#pragma unroll
        for (int i = 0; i < 4; i++) {
            float y[8];
            const float4* cf = (const float4*)(coef + i * 256 + lane * 8);
            const float4 s0 = cf[0], s1 = cf[1], c0 = cf[256], c1 = cf[257];
            const float sh[8] = {s0.x, s0.y, s0.z, s0.w, s1.x, s1.y, s1.z, s1.w}, sc[8] = {c0.x, c0.y, c0.z, c0.w, c1.x, c1.y, c1.z, c1.w};
#pragma unroll
            for (int e = 0; e < 8; e++) y[e] = fmaf(x[i * 8 + e], sc[e], sh[e]);
            const int own = ((row >> 4) & 1) == (i >> 1), c16 = i * 32 + lane;
            const uint32_t off = ((row >> 5) + own) * 65536 + (c16 >> 3) * 4096 + (rr + (own ? 0 : 16)) * 128 + (((c16 & 7) ^ (rr & 7)) << 4);
            *(uint4*)((uint8_t*)g_himg + off) = pack8(y);
        }
        if ((j & 3) != 3) continue;
        bar_sync(j == 3 ? NB_C : NB_FIN0, j == 3 ? 320 : 256);
        if (wid == 0) {
            if (j == 3) bar_arrive(NB_B, 64);
            if (lane == 0) { if (j == 7) wait_count1(&g_tick[32 + id * 8], 1); signal_count(&g_tick[32 + id * 8]); if (j < 8) TL(13) }
            __syncwarp();
        }
    }
}
template <int NQ, int CG>
__device__ __forceinline__ void side_gemv(const bf16* w, int ld, int ncol, const float* coef, float* red, float* out, int ostride, bool round) {
    constexpr int KG = 384 / CG, W = CG * 8;
    const int tid = threadIdx.x, cg = tid % CG, kg = tid / CG;
    float acc[NQ][8];
#pragma unroll
    for (int q = 0; q < NQ; q++)
#pragma unroll
        for (int j = 0; j < 8; j++) acc[q][j] = 0.f;
    if (cg * 8 < ncol) {
#pragma unroll 1
        for (int k0 = kg * 16; k0 < DM; k0 += KG * 16) {
            uint4 v[16];
#pragma unroll
            for (int i = 0; i < 16; i++) v[i] = __ldg((const uint4*)(w + (size_t)(k0 + i) * ld + cg * 8));
#pragma unroll
            for (int i = 0; i < 16; i++) {
                const float f[8] = {bflo(v[i].x), bfhi(v[i].x), bflo(v[i].y), bfhi(v[i].y), bflo(v[i].z), bfhi(v[i].z), bflo(v[i].w), bfhi(v[i].w)};
#pragma unroll
                for (int q = 0; q < NQ; q++) {
                    const float cf = coef[q * DM + k0 + i];
#pragma unroll
                    for (int j = 0; j < 8; j++) acc[q][j] = fmaf(cf, f[j], acc[q][j]);
                }
            }
        }
    }
    __syncthreads();
#pragma unroll
    for (int q = 0; q < NQ; q++)
#pragma unroll
        for (int j = 0; j < 8; j++) red[(kg * NQ + q) * W + cg * 8 + j] = acc[q][j];
    __syncthreads();
#pragma unroll 1
    for (int i = tid; i < NQ * W; i += 384) {
        const int q = i / W, cidx = i % W;
        float t = 0.f;
#pragma unroll
        for (int k = 0; k < KG; k++) t += red[k * NQ * W + i];
        if (cidx < ncol) out[q * ostride + cidx] = round ? bfround(t) : t;
    }
}
__device__ __noinline__ void rec_side(float* sm, const RecPtrs& p, int id) {
    const int tid = threadIdx.x;
    float *coef = sm, *red = sm + 3 * DM;
    if (tid < 256 && blockIdx.x < 128) rec_ln(sm + SM_PRE / 4, p, id, 2);
    __syncthreads();
    for (int i = tid; i < 2 * S_; i += 384) g_st[id * 2 * S_ + i] = 0.f;
    if (id == 0) for (int i = tid; i < 2 * 32; i += 384) g_pcnt[i * 8] = 0;
    if (id == 1) for (int i = tid; i < 5 * 256; i += 384) g_pflag[i] = 0;
    for (int i = tid; i < DM; i += 384) { coef[i] = silu_bf(p.c, i); coef[2 * DM + i] = 1.0f; }
    __syncthreads();
    side_gemv<1, 128>(p.wmod + (2 + id) * DM, 6 * DM, DM, coef, red, g_mod + (2 + id) * DM, 0, true);
    __syncthreads();
    if (tid == 0) signal_count(&g_tick[8]);
    side_gemv<1, 128>(p.w3 + id * (FF / 4), FF, FF / 4, coef + 2 * DM, red, g_vec + 3 * DM + id * (FF / 4), 0, false);
    if (tid == 0) wait_count1(&g_tick[8], 4);
    __syncthreads();
    for (int i = tid; i < DM; i += 384) { coef[i] = 1.0f + __ldcg(g_mod + 4 * DM + i); coef[DM + i] = __ldcg(g_mod + 3 * DM + i); }
    __syncthreads();
    if (id == 1 && tid < 32) {
        float t[5] = {0, 0, 0, 0, 0};
        for (int i = tid; i < DM; i += 32) {
            const float a = coef[i], b = coef[DM + i];
            t[0] += a; t[1] += a * a; t[2] += a * b; t[3] += b; t[4] += b * b;
        }
#pragma unroll
        for (int q = 0; q < 5; q++) { const float r = warp_sum(t[q]); if (tid == 0) g_cst[q] = r * (1.0f / DM); }
    }
    side_gemv<3, 32>(p.w1 + id * 256, DM, 256, coef, red, g_vec + id * 256, DM, false);
    if (tid == 0) TL(9)
#pragma unroll 1
    for (int m = 0; m < 6; m++) {
        if (!((SPF >> m) & 1)) continue;
        const uint8_t* w = (const uint8_t*)(m == 0 ? p.wo : m == 1 ? p.w1 : m == 2 ? p.w2 : m == 3 ? p.w3 : m == 4 ? p.w4 : p.x);
        const int n = (m == 0 ? 4096 : m < 3 ? 1024 : m == 5 ? 2048 : FF) * 2048 / 4;
#pragma unroll 1
        for (int o = tid * 128; o < n; o += 384 * 128) {
            asm volatile("prefetch.global.L2 [%0];" ::"l"(w + id * n + o));
            __nanosleep(SPF_NS);
        }
    }
}

__global__ void __cluster_dims__(2, 1, 1) __launch_bounds__(384, 1)
k_rec(const __grid_constant__ RecMaps mp, const __grid_constant__ RecPtrs p) {
    extern __shared__ uint8_t smraw[];
    const uint32_t sb = smem_u32(smraw);
    if ((sb & 0x3FFFF) != SB0) __trap();
    const uint32_t bars = sb + SM_BAR;
    const int tid = threadIdx.x, lane = tid & 31, b = blockIdx.x;
    const int wid = __reduce_max_sync(~0u, tid >> 5);
    const uint32_t rank = b & 1;
    uint8_t* arena = p.arena;
    volatile int* sinfo = (volatile int*)(smraw + SM_BAR + 192);
    if (tid == 0) TL(0)
    if (tid == 0) sinfo[0] = INT_MIN;
    if (tid == 352) {
        for (int i = 0; i < 17; i++) mbar_init(bars + 8 * i, i == B_WO ? 4 : 1);
        asm volatile("fence.mbarrier_init.release.cluster;" ::: "memory");
        mbar_expect(bars + 8 * B_ROLE, 8);

    }
    __syncwarp();
    asm volatile("barrier.cluster.arrive.relaxed.aligned;" ::: "memory");
    int pr = 0, hA = 0;
    if (wid < 8) {
        if (b < 128) {
            const int cb = (b & 15) * 128, k0 = (b >> 4) * 128 + (tid >> 4);
            uint4 v[8];
#pragma unroll
            for (int i = 0; i < 8; i++) v[i] = __ldg((const uint4*)(p.wmod + (size_t)(k0 + 16 * i) * (6 * DM) + cb + (tid & 15) * 8));
            float acc[8] = {0, 0, 0, 0, 0, 0, 0, 0};
#pragma unroll
            for (int i = 0; i < 8; i++) {
                const float sv = silu_bf(p.c, k0 + 16 * i);
                acc[0] += sv * bflo(v[i].x); acc[1] += sv * bfhi(v[i].x); acc[2] += sv * bflo(v[i].y); acc[3] += sv * bfhi(v[i].y);
                acc[4] += sv * bflo(v[i].z); acc[5] += sv * bfhi(v[i].z); acc[6] += sv * bflo(v[i].w); acc[7] += sv * bfhi(v[i].w);
            }
            float* red = (float*)(smraw + SM_PRE);
            *(float4*)(red + (tid >> 4) * 128 + (tid & 15) * 8) = make_float4(acc[0], acc[1], acc[2], acc[3]);
            *(float4*)(red + (tid >> 4) * 128 + (tid & 15) * 8 + 4) = make_float4(acc[4], acc[5], acc[6], acc[7]);
            bar_sync(NB_FIN0, 256);
            if (wid < 4) {
                float t = 0;
#pragma unroll
                for (int i = 0; i < 16; i++) t += red[i * 128 + tid];
                stg_rlx1(&g_modp[(b >> 4) * 2 * DM + cb + tid], __float_as_uint(t) | 1u);
            }
        } else {
            rec_ln((float*)(smraw + SM_PRE), p, b - 128, 0);
        }
    } else if (wid >= 10 && b >= 128) {
        {
            const int u = (b - 128) * 2 + wid - 10;
            const uint16_t* src = (const uint16_t*)p.mem0 + (lane & 3) * 2 * DM + u * 64 + (lane >> 2);
            uint32_t w[16];
#pragma unroll
            for (int r = 0; r < 16; r++) {
                const uint16_t* q = src + (r >> 3) * 512 + ((r >> 2) & 1) * 16 + (r & 2) * 16 + (r & 1) * 8;
                w[r] = pack_h2(bflo(q[0]), bflo(q[DM]));
            }
            stg_rlx4(arena + (LB_STAMP << 13) + u * 2048 + (lane >> 4) * 1024 + ((lane >> 3) & 1) * 256 + (lane & 7) * 16, 0, 0, 0, 0);
#pragma unroll 1
            for (int i = 0; i < (CP2 ? 6 : 3); i++) {
#pragma unroll
                for (int r = 0; r < 4; r++) {
                    uint8_t* d = arena + acc_slot(i % 3) + acc_piece(r >> 1, u, r & 1) + (i / 3) * 4096;
                    const uint32_t k = i % 3 ? 0u : ~0u, w3 = w[4 * r + 3];
                    stg_rlx4(d + lane * 16, w[4 * r] & k, w[4 * r + 1] & k, w[4 * r + 2] & k, __byte_perm(w3, ACC_ALL, (lane & 7) == 7 ? 0x7610 : 0x3210) & k);
                    const uint32_t x = __shfl_sync(~0u, __byte_perm(w3, ACC_ALL, 0x7632), lane * 8 + 7);
                    if (lane < 8) stg_rlx1(d + ACC_X + lane * 4, x & k);
                }
            }
            bar_arrive(NB_C, 320);
        }
    } else if (rank == 0) {
        uint32_t best = ~0u;
        const int pg = wid < 10 ? 0 : 1 + (b >> 1) % 3;
        uint32_t* q = (uint32_t*)(arena + (pg << 21) + (pg ? blk(b >> 1, wid & 1) : blk(LB_PROBE, wid & 1) + b * 16));
        if (lane < 8) stg_rlx1(q + lane, 0);
        uint2 tk2 = ldg_rlx2(&g_tick[0]);
        __syncwarp();
        if (lane == 0) {
            q += 3;
            uint32_t v = atomicAdd(q, 1u);
#pragma unroll 1
            for (int r = 0; r < NPROBE; r++) {
                const uint32_t t0 = clk32() + (v >> 8);
                v = atomicAdd(q + (v >> 8), 1u);
                uint32_t t1;
                asm volatile("{.reg .pred p; setp.eq.u32 p, %1, 0xffffffff; @p exit; mov.u32 %0, %%clock;}" : "=r"(t1) : "r"(v) : "memory");
                best = min(best, t1 - t0);
            }
            sinfo[wid - 6] = best;
        }
        bar_sync(NB_KDONE, b < 128 ? 128 : 64);
        if (wid == 8) {
            const int par = sinfo[2] <= sinfo[3] ? 0 : 1, ncl = gridDim.x >> 1;
            int tk = 0, it = 0;
            const uint32_t vote = b < 128 && (sinfo[4] <= sinfo[5] ? 0 : 1) != par ? 256u << (8 * ((b >> 1) % 3)) : 0u;
            if (b >= 128) {
#pragma unroll 1
                while (!__all_sync(~0u, (int)((tk2.x + tk2.y) & 255) >= ncl - 2)) { tk2 = ldg_rlx2(&g_tick[0]); spin_guard(++it); }
            }
            if (lane == 0) tk = atomicAdd(&g_tick[par], 1u + vote) & 255;
#pragma unroll 1
            while (!__all_sync(~0u, (int)((tk2.x + tk2.y) & 255) >= ncl)) { tk2 = ldg_rlx2(&g_tick[0]); spin_guard(++it); }
            tk = __shfl_sync(~0u, tk, 0);
            const int n0 = tk2.x & 255, n1 = tk2.y & 255;
            hA = min(n0 >> 1, NH);
            const int q0 = 2 * hA, q1 = 2 * NH - q0;
            const int over = tk - (par ? q1 : q0), lack = max(par ? q0 - n0 : q1 - n1, 0);
            if (over < 0) pr = par ? q0 + tk : tk;
            else if (over < lack) pr = (par ? n0 : q0 + n1) + over;
            else pr = -1 - (over - lack + (par ? max(n0 - q0, 0) : 0));
#pragma unroll
            for (int i = 0; i < 3; i++) hA |= (((tk2.x + tk2.y) >> (8 + 8 * i)) & 255) > 10 ? 256 << i : 0;
        }
    }
    asm volatile("barrier.cluster.wait.aligned;" ::: "memory");
    if (wid == 8) {
        if (rank == 0) {
            if (lane == 0) {
                uint32_t rsb;
                asm("mapa.shared::cluster.u32 %0, %1, 1;" : "=r"(rsb) : "r"(sb));
                asm volatile("st.async.shared::cluster.mbarrier::complete_tx::bytes.v2.u32 [%0], {%1, %2}, [%3];"
                             ::"r"(rsb + SM_BAR + 192), "r"(pr), "r"(hA), "r"(rsb + SM_BAR + 8 * B_ROLE) : "memory");
                sinfo[0] = pr; sinfo[1] = hA;
                if (b >= 128) atomicOr(&g_tick[4], (pr < 0 ? 4u : 1u) << ((b - 128) >> 1));
            }
        } else {
            mbar_wait_w(bars + 8 * B_ROLE, 0);
            pr = sinfo[0];
        }
        TL(1)
        __syncwarp();
        bar_arrive(NB_A, 384);
        if (b >= 128 && pr < 0) bar_sync(NB_B, 64);
        if (pr >= 0) {
            const int pu = __reduce_max_sync(~0u, pr), c0 = (pu >> 1) * 128 + rank * 64, r0 = (pu & 1) * 512;
            bool fast = false;
#pragma unroll 1
            for (int n = 0; n < 12; n++) {
                const int rot = b >= 128 ? 8 : 0, i = (n + rot) % 12;
                if (rot && n == 4) bar_sync(NB_B, 64);
                if (n >= W_INFL && !fast) {
                    const uint32_t v = ldg_rlx1(&g_tick[32 + (lane & 3) * 8]);
                    mbar_wait_w(bars + 8 * (B_W + (n - W_INFL + rot) % 12), 0);
                    fast = __all_sync(~0u, v != 0);
                }
                const int m = i < 8 ? i & 1 : 2, k = i < 8 ? i >> 1 : i - 8;
                const uint32_t dst = sb + m * 65536 + k * 16384, br = bars + 8 * (B_W + i);
                if (lane == 0) {
                    mbar_expect(br, 16384);
                    tma2d(dst, &mp.wq + m, c0, r0 + k * 128, br);
                    tma2d(dst + 8192, &mp.wq + m, c0, r0 + k * 128 + 64, br);
                }
                __syncwarp();
            }
        }
    } else {
        bar_sync(NB_A, 384);
    }
    const int prr = __reduce_max_sync(~0u, sinfo[0]);
    hA = __reduce_max_sync(~0u, sinfo[1]);
    if (prr < 0) {
        int j = (b - 128) >> 1;
        if (b < 128) {
            uint32_t v;
            int it = 0;
#pragma unroll 1
            do { v = __reduce_max_sync(~0u, ldg_rlx1(&g_tick[4])); spin_guard(++it); } while (__popc(v) < 2);
            j = v == 3 ? -1 - prr : (v & 1) ^ 1;
        }
        rec_side((float*)smraw, p, j * 2 + rank);
        return;
    }
    const int role = (prr >> 1) * 4 + rank * 2 + (prr & 1);
    rec_main(sb, &mp.wo, arena, role, hA, wid >> 2, p.zero, p.tm);
}

__device__ __forceinline__ void wgmma_ss192(float* d, uint64_t a, uint64_t b, int sc) {
    asm volatile("{.reg .pred p; setp.ne.b32 p, %98, 0;\n wgmma.mma_async.sync.aligned.m64n192k16.f32.bf16.bf16 "
                 "{%0,%1,%2,%3,%4,%5,%6,%7,%8,%9,%10,%11,%12,%13,%14,%15,%16,%17,%18,%19,%20,%21,%22,%23,%24,%25,%26,%27,%28,%29,%30,%31,%32,%33,%34,%35,%36,%37,%38,%39,%40,%41,%42,%43,%44,%45,%46,%47,%48,%49,%50,%51,%52,%53,%54,%55,%56,%57,%58,%59,%60,%61,%62,%63,%64,%65,%66,%67,%68,%69,%70,%71,%72,%73,%74,%75,%76,%77,%78,%79,%80,%81,%82,%83,%84,%85,%86,%87,%88,%89,%90,%91,%92,%93,%94,%95}, %96, %97, p, 1, 1, 0, 1;}"
                 : F16(d, 0), F16(d, 16), F16(d, 32), F16(d, 48), F16(d, 64), F16(d, 80) : "l"(a), "l"(b), "r"(sc));
}
__device__ __forceinline__ void wgmma_ss256(float* d, uint64_t a, uint64_t b, int sc) {
    asm volatile("{.reg .pred p; setp.ne.b32 p, %130, 0;\n wgmma.mma_async.sync.aligned.m64n256k16.f32.bf16.bf16 "
                 "{%0,%1,%2,%3,%4,%5,%6,%7,%8,%9,%10,%11,%12,%13,%14,%15,%16,%17,%18,%19,%20,%21,%22,%23,%24,%25,%26,%27,%28,%29,%30,%31,%32,%33,%34,%35,%36,%37,%38,%39,%40,%41,%42,%43,%44,%45,%46,%47,%48,%49,%50,%51,%52,%53,%54,%55,%56,%57,%58,%59,%60,%61,%62,%63,%64,%65,%66,%67,%68,%69,%70,%71,%72,%73,%74,%75,%76,%77,%78,%79,%80,%81,%82,%83,%84,%85,%86,%87,%88,%89,%90,%91,%92,%93,%94,%95,%96,%97,%98,%99,%100,%101,%102,%103,%104,%105,%106,%107,%108,%109,%110,%111,%112,%113,%114,%115,%116,%117,%118,%119,%120,%121,%122,%123,%124,%125,%126,%127}, %128, %129, p, 1, 1, 0, 1;}"
                 : F16(d, 0), F16(d, 16), F16(d, 32), F16(d, 48), F16(d, 64), F16(d, 80), F16(d, 96), F16(d, 112) : "l"(a), "l"(b), "r"(sc));
}

constexpr uint32_t P_VEC = 212992, P_ROW = P_VEC + 6144, P_BAR = P_ROW + 4096, P_SMEM = P_BAR + 256;
constexpr uint32_t P_OUT = 180224, P_OUT3 = 147456, P_OUT4 = 163840;
#define PPH 1
#define FLAG_ST "st.release.gpu.global.u32"
#define FLAG_LD "ld.acquire.gpu.global.u32"
#define BA3 2
#define BA 5
#define BA0 1
constexpr int P_SA = 5, P_SB = 3;
constexpr int PB_FA = 0, PB_EA = 5, PB_FB = 10, PB_EB = 13, PB_OUT = 16;
enum { C_Y = 0, C_G = 1, C_X1 = 2, C_U = 3, C_S1 = 8, C_S3 = 9 };
enum { V_GA = 0, V_A = 1, V_B = 2, V_GB = 3, V_VA = 4, V_VB = 5, V_VC = 6, V_C3 = 7 };
struct PostMaps { CUtensorMap o, wo, y, w1, g, w2, x1, w3, u, w4, out; };
struct PostPtrs { const bf16* x; };

struct GeluK { float k0, k1, kh; };
__device__ __forceinline__ GeluK gelu_k(float c) { return {0.7978845608028654f * c, 0.7978845608028654f * 0.044715f * c * c * c, 0.5f * c}; }
__device__ __forceinline__ float gelu_s(float t, const GeluK& k) {
    const float u = t * fmaf(t * t, k.k1, k.k0);
    float th; asm("tanh.approx.f32 %0, %1;" : "=f"(th) : "f"(u));
    const float hx = k.kh * t;
    return fmaf(hx, th, hx);
}
__device__ __forceinline__ float2 ldsv(uint32_t a) {
    float2 v; asm("ld.shared.v2.f32 {%0,%1}, [%2];" : "=f"(v.x), "=f"(v.y) : "r"(a)); return v;
}
__device__ __forceinline__ void wait_smem(uint32_t a, int target) {
    int it = 0;
#pragma unroll 1
    while (true) {
        int v;
        asm volatile("ld.acquire.cta.shared.u32 %0, [%1];" : "=r"(v) : "r"(a) : "memory");
        if (__all_sync(~0u, v >= target)) break;
        spin_guard(++it);
    }
}

#define PP(i)
#define PH_(c, w, i)
struct Pipe { int st, ph; };
template <int ST> __device__ __forceinline__ void adv(Pipe& p) { if (++p.st == ST) { p.st = 0; p.ph ^= 1; } }

__device__ __forceinline__ void post_produce(uint32_t sb, const PostMaps& mp, int mb, int nb, int rank) {
    const int rh = 2 * mb + rank, lane = threadIdx.x & 31;
    int st = 0, pp = 0, st2 = 0, pp2 = 0;
#pragma unroll 1
    for (int ph = 0; ph < 7; ph++) {
        const bool W = ph == 3 || ph == 4;
        if (ph == 3 || ph >= 5) {
            const int n = ph == 5 ? P_SB : P_SA;
            const uint32_t e = sb + P_BAR + 8 * (ph == 5 ? PB_EB : PB_EA);
#pragma unroll 1
            for (int i = 0; i < n; i++) mbar_wait_w(e + 8 * i, pp ^ (i >= st));
            if (ph == 6) break;
            if (ph == 5) wait_smem(sb + P_BAR + 8 * (PB_OUT + (lane & 1)), 4);
            int t = st; st = st2; st2 = t; t = pp; pp = pp2; pp2 = t;
        }
        const int ST = W ? P_SB : P_SA, NK = ph == 0 ? 64 : ph == 5 ? 56 : 16, NB = ph == 3 ? 4 : ph == 4 ? 3 : 2;
        const uint32_t SBYTES = W ? 49152 : 32768;
        const uint32_t full = sb + P_BAR + 8 * (W ? PB_FB : PB_FA), empty = sb + P_BAR + 8 * (W ? PB_EB : PB_EA);
        const CUtensorMap* ta = &mp.o + 2 * (ph > 3 ? ph - 1 : ph);
        const CUtensorMap* tb = ta + 1;
        const int n0 = ph == 3 ? nb * 256 : ph == 4 ? 2048 + nb * 192 : nb * 128;
        const int amul = ph == 0 ? 256 : 64, arow = ph == 0 ? rh * 8 : rh * 64;
        const uint32_t shifts = ph == 2 ? 0x04000301u : 0x02020202u;
        const uint32_t* fl = &g_pflag[(ph == 5 ? C_U + ((lane >> 3) & 1) : ph - 1) * 256 + (ph == 2 ? min(max(rh + min(lane >> 3, 2) - 1, 0), 31) : rh) * 8 + (lane & 7)];
        uint32_t have = ph == 0 || ph == 4 ? 9 : 0;
        auto order = [&](int i, int& need, int& grp) {
            need = 0; grp = i & 1;
            if (ph == 5) {
                const int q = i < 32 ? i >> 2 : ((i - 32) * 43) >> 7, src = (q + (nb & 6)) & 7;
                need = (i < 32 ? 1 : 256) << src; grp = i < 32 ? i & 3 : i - 32 - 3 * q;
                return i + (src - q) * (i < 32 ? 4 : 3);
            }
            if (ph == 0) return i;
            const int kb = (i + 2 * (nb & 6)) & 15;
            need = (ph == 2 ? 0x10101 : 1) << (kb >> 1);
            return kb;
        };
        PH_(ph == PPH, 0, 26) PH_(ph == PPH, 1, 26)
        int ib = 0, sB = st, pB = pp;
#pragma unroll 1
        for (int i = 0; i < NK; i++) {
            int need, grp;
#pragma unroll 1
            for (const int lim = i || ph > 3 ? i + 1 : ph == 3 ? BA3 : ph ? BA : BA0; ib < lim; ib++) {
                const int kb = order(ib, need, grp);
                const uint32_t a = sb + sB * SBYTES, f = full + 8 * sB;
                mbar_wait_w(empty + 8 * sB, pB ^ 1);
                e_expect(f, 16384 + NB * 8192);
                e_tma2d(a + 16384, tb, n0, kb * 64, f);
                e_tma2d(a + 24576, tb, n0 + 64, kb * 64, f);
                if (W) { e_tma2d(a + 32768, tb, n0 + 128, kb * 64, f); if (ph == 3) e_tma2d(a + 40960, tb, n0 + 192, kb * 64, f); }
                if (++sB == ST) { sB = 0; pB ^= 1; }
            }
            const int kb = order(i, need, grp);
            PH_(ph == PPH && i == 0, 0, 27) PH_(ph == PPH && i == 0, 1, 27)
            if (ph == 0 && i == 0) {
                asm volatile("barrier.cluster.wait.aligned;" ::: "memory");
                PH_(PPH == 0, 0, 25) PH_(PPH == 0, 1, 25)
            }
            if ((__ballot_sync(~0u, have > grp) & need) != need) {
                int it = 0;
#pragma unroll 1
                do {
                    asm volatile(FLAG_LD " %0, [%1];" : "=r"(have) : "l"(fl) : "memory");
                    spin_guard(++it);
                } while ((__ballot_sync(~0u, have > grp) & need) != need);
                PH_(ph == PPH && i == 0, 0, 23) PH_(ph == PPH, 0, 24) PH_(ph == PPH && i == 0, 1, 23) PH_(ph == PPH, 1, 24)
                asm volatile("fence.proxy.async.global;" ::: "memory");
                PH_(ph == PPH && i == 0, 0, 25) PH_(ph == PPH && i == 0, 1, 25)
            }
            e_tma2d_mc(sb + st * SBYTES + rank * 8192, ta, kb * amul, arow + (int)((shifts >> ((kb & 12) * 2)) & 7) - 2, full + 8 * st);
            if (++st == ST) { st = 0; pp ^= 1; }
        }
    }
}

template <int PH>
__device__ __forceinline__ void post_mma(uint32_t sb, float* acc, Pipe& p, int wg, bool lead, int pi) {
    constexpr bool W = PH == 3 || PH == 4;
    constexpr int ST = W ? P_SB : P_SA, SBYTES = W ? 49152 : 32768, NK = PH == 0 ? 64 : PH == 5 ? 56 : 16;
    const uint32_t full = sb + P_BAR + 8 * (W ? PB_FB : PB_FA), empty = sb + P_BAR + 8 * (W ? PB_EB : PB_EA);
    constexpr uint64_t DA = PH == 0 ? mkdesc(SB0, 128, 1024, 0) : mkdesc(SB0, 16, 1024, 1);
    constexpr uint64_t DB = mkdesc(SB0 + 16384, 8192, 1024, 1);
    auto release = [&](int st) { if (lead) { mbar_arrive_cluster(empty + 8 * st, 0); mbar_arrive_cluster(empty + 8 * st, 1); } };
    int prev = 0;
#pragma unroll 1
    for (int kb = 0; kb < NK; kb++) {
        mbar_wait_w(full + 8 * p.st, p.ph);
        const uint32_t so = p.st * (SBYTES >> 4);
        const uint32_t a = (uint32_t)DA + so + wg * 512, b = (uint32_t)DB + so;
        wg_fence();
#pragma unroll
        for (int k = 0; k < 4; k++) {
            const uint64_t da = (DA & 0xffffffff00000000ull) | (a + k * (PH == 0 ? 16 : 2)), db = (DB & 0xffffffff00000000ull) | (b + k * 128);
            if (PH == 3) wgmma_ss256(acc, da, db, (kb | k) != 0);
            else if (PH == 4) wgmma_ss192(acc, da, db, (kb | k) != 0);
            else wgmma_ss128<PH == 0>(acc, da, db, (kb | k) != 0);
        }
        wg_commit();
        if (kb == 0) { PP(pi) if (PH == 0 && wg == 0) TL(11) }
        wg_wait<1>();
        if (kb > 0) release(prev);
        prev = p.st;
        adv<ST>(p);
    }
    wg_wait<0>();
    release(prev);
    PP(pi + 1)
}

__global__ void __cluster_dims__(2, 1, 1) __launch_bounds__(384, 1)
k_post(const __grid_constant__ PostMaps mp, const __grid_constant__ PostPtrs pp) {
    extern __shared__ uint8_t smraw[];
    const uint32_t sb = smem_u32(smraw);
    if ((sb & 0x3FFFF) != SB0) __trap();
    const int tid = threadIdx.x, lane = tid & 31;
    const int mb = blockIdx.x >> 3, nb = blockIdx.x & 7, rank = blockIdx.x & 1;
    const uint32_t bars = sb + P_BAR;
    if (tid < PB_OUT) {
        mbar_init(bars + 8 * tid, (tid >= PB_EA && tid < PB_FB) || tid >= PB_EB ? 4 : 1);
        asm volatile("fence.mbarrier_init.release.cluster;" ::: "memory");
    }
    if (tid == 32) sts4(bars + 8 * PB_OUT, 0, 0, 0, 0);
    if (tid >= 256 && tid < 267) asm volatile("prefetch.tensormap [%0];" ::"l"(&mp.o + (tid - 256)) : "memory");
    __syncthreads();
    asm volatile("barrier.cluster.arrive.aligned;" ::: "memory");
    if (tid < 256 || tid >= 288) asm volatile("barrier.cluster.wait.aligned;" ::: "memory");
    if (tid >= 256) {
        asm volatile("setmaxnreg.dec.sync.aligned.u32 40;");
        const int w = __reduce_max_sync(~0u, (tid >> 5) - 8);
        if (w == 0) {
            post_produce(sb, mp, mb, nb, rank);
        } else if (w < 3) {
            const int wg = w - 1, rh = 2 * mb + wg;
            float* rowc = (float*)(smraw + P_ROW) + (wg * 64 + lane * 2) * 8;
            int nout = 0, sig = 0;
#pragma unroll 1
            for (int i = 0; i < 8; i++) {
                const int cnt = (0x54392180u >> (4 * i)) & 15;
                if (cnt < C_S1) {
                    const int ng = cnt == 3 ? 4 : cnt == 4 ? 3 : 2, c0 = cnt == 3 ? nb * 256 : cnt == 4 ? 2048 + nb * 192 : nb * 128;
                    const uint32_t src = sb + (cnt == 3 ? P_OUT3 : cnt == 4 ? P_OUT4 : P_OUT) + wg * ng * 8192;
                    uint32_t* fl = &g_pflag[cnt * 256 + rh * 8 + nb];
#pragma unroll 1
                    for (int j = 0; j < ng; j++) {
                        bar_sync(4 + 4 * wg + (sig++ & 3), 160);
                        if (lane == 0) {
                            PH_(cnt == PPH - 1, wg, 20)
                            asm volatile("cp.async.bulk.tensor.2d.global.shared::cta.bulk_group [%0, {%2, %3}], [%1]; cp.async.bulk.commit_group;"
                                         ::"l"(&mp.y + 2 * (cnt > 3 ? cnt - 1 : cnt)), "r"(src + j * 8192), "r"(c0 + j * 64), "r"(rh * 64) : "memory");
                        }
                        __syncwarp();
                    }
                    if (lane == 0) {
                        asm volatile("cp.async.bulk.wait_group 0; fence.proxy.async.global;" ::: "memory");
                        PH_(cnt == PPH - 1, wg, 21)
                        asm volatile(FLAG_ST " [%0], %1;" ::"l"(fl), "r"(ng) : "memory");
                        PH_(cnt == PPH - 1, wg, 22)
                        asm volatile("st.release.cta.shared.u32 [%0], %1;" ::"r"(bars + 8 * (PB_OUT + wg)), "r"(nout + 1) : "memory");
                    }
                    nout++;
                    __syncwarp();
                    continue;
                }
                bar_sync(4 + 4 * wg + (sig++ & 3), 160);
                uint32_t* c = &g_pcnt[(cnt - C_S1) * 256 + rh * 8];
                if (lane == 0) { signal_count(c); wait_count1(c, 8); }
                __syncwarp();
                const float4* sp = (const float4*)g_st + rh * 32 + lane;
                float4 u[3] = {__ldcg(sp + (cnt == C_S1 ? 0 : 3) * (S_ / 2)), __ldcg(sp + S_ / 2), __ldcg(sp + S_)};
#pragma unroll 1
                for (int h = 0; h < 2; h++) {
                    const float id = 1.0f / DM;
                    const float m = u[0].x * id, var = fmaxf(u[0].y * id - m * m, 0.f) + 1e-5f, r = rsqrtf(var);
                    float sc = r, m2 = 0.f;
                    if (cnt == C_S1) {
                        m2 = r * (u[1].x * id - m * g_cst[0]) + g_cst[3];
                        const float e2 = r * r * (u[2].x * id - 2.0f * m * u[1].y * id + m * m * g_cst[1]) + 2.0f * r * (u[2].y * id - m * g_cst[2]) + g_cst[4];
                        sc = r * rsqrtf(fmaxf(e2 - m2 * m2, 0.f) + 1e-5f);
                    }
                    const GeluK k = gelu_k(sc);
                    *(float4*)(rowc + h * 8) = make_float4(k.k0, k.k1, k.kh, -m);
                    *(float4*)(rowc + h * 8 + 4) = make_float4(var * r, -m2 * var * r, r, -m * r);
#pragma unroll
                    for (int q = 0; q < 3; q++) { u[q].x = u[q].z; u[q].y = u[q].w; }
                }
                bar_arrive(1 + wg, 160);
            }
        }
    } else {
        asm volatile("setmaxnreg.inc.sync.aligned.u32 232;");
        const bf16* xin = pp.x;
        const int wg = __reduce_max_sync(~0u, tid >> 7), wi = (tid >> 5) & 3, g = lane >> 2, tq = lane & 3;
        const int rh = 2 * mb + wg, row = rh * 64 + wi * 16 + g;
        const bool lead = (tid & 127) == 0;
        PP(0)
        if (tid == 0) TL(10)
        uint4 xg[8];
#pragma unroll
        for (int i = 0; i < 8; i++)
            xg[i] = __ldg((const uint4*)(xin + (size_t)(rh * 64 + wi * 16 + (i & 3) * 4 + (lane >> 3)) * DM + nb * 128 + (i >> 2) * 64 + (lane & 7) * 8));
        if (blockIdx.x < 64) g_modp[blockIdx.x * 256 + tid] = 0;
        if (blockIdx.x == 64 && tid < 64) g_tick[tid] = 0;
        {
            float* sv = (float*)(smraw + P_VEC);
            if (tid < 128) {
                const int c = nb * 128 + tid;
                sv[V_GA * 128 + tid] = __ldcg(&g_mod[2 * DM + c]); sv[V_A * 128 + tid] = 1.0f + __ldcg(&g_mod[4 * DM + c]);
                sv[V_B * 128 + tid] = __ldcg(&g_mod[3 * DM + c]); sv[V_GB * 128 + tid] = __ldcg(&g_mod[5 * DM + c]);
            } else {
                const int c = nb * 128 + tid - 128;
                sv[V_VA * 128 + tid - 128] = __ldcg(&g_vec[c]); sv[V_VB * 128 + tid - 128] = __ldcg(&g_vec[DM + c]); sv[V_VC * 128 + tid - 128] = __ldcg(&g_vec[2 * DM + c]);
            }
            sv[V_C3 * 128 + tid] = __ldcg(&g_vec[3 * DM + nb * 256 + tid]);
            if (tid < 192) sv[V_C3 * 128 + 256 + tid] = __ldcg(&g_vec[3 * DM + 2048 + nb * 192 + tid]);
            bar_sync(3, 256);
        }
        uint32_t vec = sb + P_VEC + tq * 8;
        asm volatile("" : "+r"(vec) :: "memory");
        const uint32_t stw = sb + (wi * 16 + ((lane >> 3) & 1) * 8 + (lane & 7)) * 128 + (((lane >> 4) ^ (lane & 7)) << 4);
        int sig = 0;
        auto signal = [&]() { bar_arrive(4 + 4 * wg + (sig++ & 3), 160); };
        auto put64 = [&](uint32_t o, const float* v) {
#pragma unroll
            for (int jj = 0; jj < 4; jj++, v += 8) stsm4((stw + o) ^ (jj << 5), pack2(v[0], v[1]), pack2(v[2], v[3]), pack2(v[4], v[5]), pack2(v[6], v[7]));
            fence_async_smem();
            signal();
        };
        auto out_free = [&](int n) { wait_smem(bars + 8 * (PB_OUT + (lane & 1)), n); };
        const uint32_t rowc = sb + P_ROW + (wg * 64 + wi * 16 + g) * 32, o128 = P_OUT + wg * 16384;
        Pipe pa = {0, 0}, pb = {0, 0};
        uint32_t keep[32];
#define KEEP(jn, e) (((e) & 1) ? bfhi(keep[2 * (jn) + ((e) >> 1)]) : bflo(keep[2 * (jn) + ((e) >> 1)]))
        float mu1[2], r1[2];
        {
            float acc[64];
            const uint32_t xo = sb + o128 + wi * 2048 + (lane >> 3) * 128;
#pragma unroll
            for (int i = 0; i < 8; i++) sts4(xo + (i >> 2) * 8192 + (i & 3) * 512 + (((lane & 7) ^ ((i & 1) * 4 + (lane >> 3))) << 4), xg[i].x, xg[i].y, xg[i].z, xg[i].w);
            __syncwarp();
#pragma unroll
            for (int jj = 0; jj < 8; jj++) ldsm4(keep + jj * 4, (stw + o128 + (jj >> 2) * 8192) ^ ((jj & 3) << 5));
            __syncwarp();
            post_mma<0>(sb, acc, pa, wg, lead, 1);
            float st[2][6];
#pragma unroll
            for (int q = 0; q < 6; q++) st[0][q] = st[1][q] = 0.f;
#pragma unroll
            for (int jn = 0; jn < 16; jn++) {
                const float2 ga = ldsv(vec + V_GA * 512 + jn * 32), a = ldsv(vec + V_A * 512 + jn * 32);
                float xa[4];
#pragma unroll
                for (int e = 0; e < 4; e++) {
                    xa[e] = fmaf((e & 1) ? ga.y : ga.x, acc[4 * jn + e], KEEP(jn, e));
                    st[e >> 1][0] += xa[e]; st[e >> 1][1] = fmaf(xa[e], xa[e], st[e >> 1][1]);
                    acc[4 * jn + e] = ((e & 1) ? a.y : a.x) * xa[e];
                }
                keep[2 * jn] = pack2(xa[0], xa[1]); keep[2 * jn + 1] = pack2(xa[2], xa[3]);
                if ((jn & 7) == 7) put64(o128 + (jn >> 3) * 8192, acc + 4 * jn - 28);
            }
            PP(3)
#pragma unroll
            for (int jn = 0; jn < 16; jn++) {
                const float2 a = ldsv(vec + V_A * 512 + jn * 32), b = ldsv(vec + V_B * 512 + jn * 32);
#pragma unroll
                for (int e = 0; e < 4; e++) {
                    const float y = acc[4 * jn + e], aa = (e & 1) ? a.y : a.x, bb = (e & 1) ? b.y : b.x;
                    float* s = st[e >> 1];
                    s[2] += y; s[3] = fmaf(aa, y, s[3]); s[4] = fmaf(y, y, s[4]); s[5] = fmaf(bb, y, s[5]);
                }
            }
#pragma unroll
            for (int h = 0; h < 2; h++)
#pragma unroll
                for (int q = 0; q < 6; q++) { st[h][q] += __shfl_xor_sync(~0u, st[h][q], 1); st[h][q] += __shfl_xor_sync(~0u, st[h][q], 2); }
            if (tq < 3) {
#pragma unroll
                for (int h = 0; h < 2; h++)
                    red2(g_st + (tq * S_ + row + h * 8) * 2, tq == 0 ? st[h][0] : tq == 1 ? st[h][2] : st[h][4], tq == 0 ? st[h][1] : tq == 1 ? st[h][3] : st[h][5]);
            }
            signal();
            PP(29)
        }
        {
            float acc[64];
            post_mma<1>(sb, acc, pa, wg, lead, 4);
            float c1[2], c2[2], c3[2];
            GeluK gk[2];
            bar_sync(1 + wg, 160);
#pragma unroll
            for (int h = 0; h < 2; h++) {
                const float4 a = lds4f(rowc + h * 256), b = lds4f(rowc + h * 256 + 16);
                gk[h] = {a.x, a.y, a.z}; c1[h] = a.w; c2[h] = b.x; c3[h] = b.y; mu1[h] = b.w; r1[h] = b.z;
            }
#pragma unroll
            for (int jn = 0; jn < 16; jn++) {
                const float2 va = ldsv(vec + V_VA * 512 + jn * 32), vb = ldsv(vec + V_VB * 512 + jn * 32), vc = ldsv(vec + V_VC * 512 + jn * 32);
#pragma unroll
                for (int e = 0; e < 4; e++) {
                    const int h = e >> 1;
                    const float t = fmaf(c1[h], (e & 1) ? va.y : va.x, fmaf(c2[h], (e & 1) ? vb.y : vb.x, fmaf(c3[h], (e & 1) ? vc.y : vc.x, acc[4 * jn + e])));
                    acc[4 * jn + e] = gelu_s(t, gk[h]);
                }
                if ((jn & 7) == 7) put64(o128 + (jn >> 3) * 8192, acc + 4 * jn - 28);
            }
            PP(6)
        }
        {
            float acc[64];
            post_mma<2>(sb, acc, pa, wg, lead, 7);
#pragma unroll
            for (int jn = 0; jn < 16; jn++) {
                const float2 a = ldsv(vec + V_A * 512 + jn * 32), b = ldsv(vec + V_B * 512 + jn * 32);
#pragma unroll
                for (int e = 0; e < 4; e++) {
                    const int h = e >> 1;
                    acc[4 * jn + e] += fmaf(fmaf(KEEP(jn, e), r1[h], mu1[h]), (e & 1) ? a.y : a.x, (e & 1) ? b.y : b.x);
                }
                if ((jn & 7) == 7) put64(o128 + (jn >> 3) * 8192, acc + 4 * jn - 28);
            }
            PP(9)
            float st[2][2] = {{0.f, 0.f}, {0.f, 0.f}};
#pragma unroll
            for (int jn = 0; jn < 16; jn++) {
                const float2 gb = ldsv(vec + V_GB * 512 + jn * 32);
                float z[4];
#pragma unroll
                for (int e = 0; e < 4; e++) {
                    const float x1 = acc[4 * jn + e];
                    st[e >> 1][0] += x1; st[e >> 1][1] = fmaf(x1, x1, st[e >> 1][1]);
                    z[e] = fmaf((e & 1) ? gb.y : gb.x, x1, KEEP(jn, e));
                }
                keep[2 * jn] = pack2(z[0], z[1]); keep[2 * jn + 1] = pack2(z[2], z[3]);
            }
#pragma unroll
            for (int h = 0; h < 2; h++)
#pragma unroll
                for (int q = 0; q < 2; q++) { st[h][q] += __shfl_xor_sync(~0u, st[h][q], 1); st[h][q] += __shfl_xor_sync(~0u, st[h][q], 2); }
            if (tq < 2) red2(g_st + (3 * S_ + row + tq * 8) * 2, tq ? st[1][0] : st[0][0], tq ? st[1][1] : st[0][1]);
            signal();
            PP(30)
        }
        {
            uint32_t v3 = vec + V_C3 * 512;
#pragma unroll 1
            for (int r = 0; r < 2; r++) {
                float acc[128];
#pragma unroll
                for (int i = 96; i < 128; i++) acc[i] = 0.f;
                if (r == 0) post_mma<3>(sb, acc, pb, wg, lead, 10);
                else post_mma<4>(sb, acc, pb, wg, lead, 13);
                float c1[2];
                GeluK gk[2];
                if (r == 0) bar_sync(1 + wg, 160);
                out_free(3 + r);
#pragma unroll
                for (int h = 0; h < 2; h++) { const float4 a = lds4f(rowc + h * 256); gk[h] = {a.x, a.y, a.z}; c1[h] = a.w; }
                uint32_t o = r ? P_OUT4 + wg * 24576 : P_OUT3 + wg * 32768;
#pragma unroll 1
                for (int left = 3 - r; left >= 0; left--) {
#pragma unroll
                    for (int jn = 0; jn < 8; jn++) {
                        const float2 vc = ldsv(v3 + jn * 32);
#pragma unroll
                        for (int e = 0; e < 4; e++) acc[4 * jn + e] = gelu_s(fmaf(c1[e >> 1], (e & 1) ? vc.y : vc.x, acc[4 * jn + e]), gk[e >> 1]);
                    }
                    put64(o, acc);
#pragma unroll
                    for (int i = 0; i < 32; i++) acc[i] = acc[32 + i];
                    if (left > 1) {
#pragma unroll
                        for (int i = 32; i < 64; i++) acc[i] = acc[32 + i];
                        if (left > 2) {
#pragma unroll
                            for (int i = 64; i < 96; i++) acc[i] = acc[32 + i];
                        }
                    }
                    o += 8192; v3 += 256;
                }
                PP(12 + 3 * r)
            }
        }
        {
            float acc[64];
            post_mma<5>(sb, acc, pa, wg, lead, 16);
#pragma unroll
            for (int jn = 0; jn < 16; jn++) {
                const float2 gb = ldsv(vec + V_GB * 512 + jn * 32);
#pragma unroll
                for (int e = 0; e < 4; e++) acc[4 * jn + e] = fmaf((e & 1) ? gb.y : gb.x, acc[4 * jn + e], KEEP(jn, e));
                if ((jn & 7) == 7) put64(o128 + (jn >> 3) * 8192, acc + 4 * jn - 28);
            }
            PP(18)
            if (tid == 0) TL(12)
        }
    }
}

typedef CUresult (*EncFn)(CUtensorMap*, CUtensorMapDataType, cuuint32_t, void*, const cuuint64_t*, const cuuint64_t*, const cuuint32_t*,
                          const cuuint32_t*, CUtensorMapInterleave, CUtensorMapSwizzle, CUtensorMapL2promotion, CUtensorMapFloatOOBfill);

static CUtensorMap make_map(EncFn enc, const void* p, uint64_t inner, uint64_t outer, uint32_t bi = 64) {
    CUtensorMap m;
    cuuint64_t dims[2] = {inner, outer};
    cuuint64_t str[1] = {inner * 2};
    cuuint32_t box[2] = {bi, 64};
    cuuint32_t es[2] = {1, 1};
    enc(&m, CU_TENSOR_MAP_DATA_TYPE_BFLOAT16, 2, (void*)p, dims, str, box, es, CU_TENSOR_MAP_INTERLEAVE_NONE,
        bi == 64 ? CU_TENSOR_MAP_SWIZZLE_128B : CU_TENSOR_MAP_SWIZZLE_64B, CU_TENSOR_MAP_L2_PROMOTION_L2_256B, CU_TENSOR_MAP_FLOAT_OOB_FILL_NONE);
    return m;
}
static CUtensorMap make_map_o(EncFn enc, const void* p) {
    CUtensorMap m;
    cuuint64_t dims[2] = {16384, 256};
    cuuint64_t str[1] = {65536};
    cuuint32_t box[2] = {256, 8};
    cuuint32_t es[2] = {1, 1};
    enc(&m, CU_TENSOR_MAP_DATA_TYPE_UINT32, 2, (void*)p, dims, str, box, es, CU_TENSOR_MAP_INTERLEAVE_NONE, CU_TENSOR_MAP_SWIZZLE_NONE,
        CU_TENSOR_MAP_L2_PROMOTION_L2_256B, CU_TENSOR_MAP_FLOAT_OOB_FILL_NONE);
    return m;
}
template <class T> static T* sym(T& s) { void* p = nullptr; cudaGetSymbolAddress(&p, s); return (T*)p; }

constexpr RecTime g_time = {T_GO, T_X2, T_V, D_X2, D_V, H_D};
extern "C" void kernel_launch(void* const* d_in, const int* in_sizes, int n_in, void* d_out, int out_size) {
    const bf16* x = (const bf16*)d_in[0];
    const bf16* mem0 = (const bf16*)d_in[1];
    const bf16 *Wq = (const bf16*)d_in[2], *Wk = (const bf16*)d_in[3], *Wv = (const bf16*)d_in[4], *Wo = (const bf16*)d_in[5];
    const bf16 *w1 = (const bf16*)d_in[8], *w2 = (const bf16*)d_in[9], *w3 = (const bf16*)d_in[10], *w4 = (const bf16*)d_in[11];
    const bf16 *c = (const bf16*)d_in[12], *wmod = (const bf16*)d_in[13];
    bf16* out = (bf16*)d_out;

    EncFn enc = nullptr;
    cudaDriverEntryPointQueryResult qr;
    cudaGetDriverEntryPoint("cuTensorMapEncodeTiled", (void**)&enc, cudaEnableDefault, &qr);
    CUtensorMap tWq = make_map(enc, Wq, NH * DH, DM), tWk = make_map(enc, Wk, NH * DH, DM), tWv = make_map(enc, Wv, NH * DH, DM);
    PostMaps mp;
    mp.o = make_map_o(enc, sym(g_O)); mp.wo = make_map(enc, Wo, DM, NH * DH);
    mp.y = make_map(enc, sym(g_y), DM, S_); mp.w1 = make_map(enc, w1, DM, DM);
    mp.g = make_map(enc, sym(g_g), DM, S_); mp.w2 = make_map(enc, w2, DM, DM);
    mp.x1 = make_map(enc, sym(g_x1), DM, S_); mp.w3 = make_map(enc, w3, FF, DM);
    mp.u = make_map(enc, sym(g_u), FF, S_); mp.w4 = make_map(enc, w4, DM, FF);
    mp.out = make_map(enc, out, DM, S_);
    cudaFuncSetAttribute(k_rec, cudaFuncAttributeMaxDynamicSharedMemorySize, SM_REC_TOTAL + 2048);
    cudaFuncSetAttribute(k_post, cudaFuncAttributeMaxDynamicSharedMemorySize, P_SMEM);

    uint8_t* arena = (uint8_t*)(((uintptr_t)sym(g_arena) + (2u << 20) - 1) & ~(uintptr_t)((2u << 20) - 1));
    const PostPtrs pp = {x};
    const RecPtrs rp = {x, mem0, c, wmod, w1, w3, arena, 0u, w2, w4, Wo, g_time};
    const RecMaps rm = {tWq, tWk, tWv, mp.wo};
    k_rec<<<132, 384, SM_REC_TOTAL + 2048>>>(rm, rp);
    k_post<<<128, 384, P_SMEM>>>(mp, pp);
}
```

```cpp
#include <cuda_runtime.h>
#include <cuda.h>
#include <cuda_bf16.h>
#include <stdint.h>
#include <limits.h>

typedef __nv_bfloat16 bf16;

constexpr int S_ = 2048, DM = 1024, NH = 32, DH = 128, NSEG = 64, FF = 3584;
constexpr int SPIN_LIMIT = 1 << 22;
#define W_INFL 2
#define XP 0
#define H_PIECES 8
#define NPROBE 3

__device__ uint8_t g_arena[10 << 20];
__device__ uint32_t g_tick[64];
__device__ __align__(16) uint32_t g_modp[8 * 2 * DM];
__host__ __device__ constexpr uint32_t blk(uint32_t lb, uint32_t par) {
    return (lb << 13) | ((((lb) ^ (lb >> 3) ^ (lb >> 4) ^ (lb >> 6) ^ par) & 1) << 12);
}
__host__ __device__ constexpr uint32_t lb_x2(uint32_t h) { return (h & 1) | ((h >> 1) << 3); }
__host__ __device__ constexpr uint32_t acc_slot(uint32_t s) { return (1u << 20) + (s & 1) * 32768 + (s & 2) * 131072; }
__host__ __device__ constexpr uint32_t acc_piece(uint32_t half, uint32_t qd, uint32_t mt) { return mt * 1024 + (qd & 1) * 4096 + half * 8192 + (qd >> 1) * 16384; }
constexpr uint32_t LB_STAMP = 6;
__host__ __device__ constexpr uint32_t stamp_line(uint32_t w, uint32_t q) { return ((w & 1) * 2 + (q >> 1)) * 1024 + (q & 1) * 256; }
constexpr uint32_t ACC_ONE = 0x3c000000u, ACC_ALL = 0x50000000u;
constexpr uint32_t LB_PROBE = 6 | 64;
__host__ __device__ constexpr uint32_t lb_tok(uint32_t h) { return (h & 1) | ((h >> 1) << 3); }
__device__ float g_mod[6 * DM];
__device__ __align__(1024) bf16 g_himg[(S_ + 32) * DM];
__device__ __align__(1024) bf16 g_O[S_ * NH * DH];
__device__ __align__(1024) bf16 g_y[S_ * DM];
__device__ __align__(1024) bf16 g_g[S_ * DM];
__device__ __align__(1024) bf16 g_x1[S_ * DM];
__device__ __align__(16) float g_st[4 * S_ * 2];
__device__ float g_vec[3 * DM + FF];
__device__ float g_cst[8];
__device__ uint32_t g_pcnt[2 * 32 * 8], g_pflag[6 * 32 * 8];
__device__ __align__(1024) bf16 g_u[S_ * FF];

#define TL(i) {}
#define TLC(i) {}
__device__ __forceinline__ uint32_t smem_u32(const void* p) { return (uint32_t)__cvta_generic_to_shared(p); }
__device__ __forceinline__ void spin_guard(int it) {
    asm volatile("{.reg .pred p; setp.gt.s32 p, %0, %1; @p st.global.u32 [%2], %0;}" ::"r"(it), "n"(SPIN_LIMIT), "l"(1ull));
}
__device__ __forceinline__ void wg_fence() { asm volatile("wgmma.fence.sync.aligned;" ::: "memory"); }
__device__ __forceinline__ void wg_commit() { asm volatile("wgmma.commit_group.sync.aligned;" ::: "memory"); }
template <int N> __device__ __forceinline__ void wg_wait() { asm volatile("wgmma.wait_group.sync.aligned %0;" ::"n"(N) : "memory"); }
__host__ __device__ constexpr uint64_t mkdesc(uint32_t addr, uint32_t lbo, uint32_t sbo, uint32_t swz) {
    return (uint64_t)((addr & 0x3FFFF) >> 4) | ((uint64_t)(lbo >> 4) << 16) | ((uint64_t)(sbo >> 4) << 32) | ((uint64_t)swz << 62);
}
__device__ __forceinline__ uint64_t dadd(uint64_t d, uint32_t o) { return (d & 0xffffffff00000000ull) | (uint32_t)((uint32_t)d + o); }
__device__ __forceinline__ void mbar_init(uint32_t b, uint32_t c) { asm volatile("mbarrier.init.shared.b64 [%0], %1;" ::"r"(b), "r"(c) : "memory"); }
__device__ __forceinline__ void mbar_expect(uint32_t b, uint32_t tx) { asm volatile("mbarrier.arrive.expect_tx.shared.b64 _, [%0], %1;" ::"r"(b), "r"(tx) : "memory"); }
__device__ __forceinline__ void mbar_arrive(uint32_t b) { asm volatile("mbarrier.arrive.shared.b64 _, [%0];" ::"r"(b) : "memory"); }
__device__ __forceinline__ void mbar_arrive_cluster(uint32_t b, uint32_t cta) {
    asm volatile("{.reg .b32 r; mapa.shared::cluster.u32 r, %0, %1; mbarrier.arrive.shared::cluster.b64 _, [r];}" ::"r"(b), "r"(cta) : "memory");
}
__device__ __forceinline__ bool mbar_try(uint32_t b, uint32_t par) {
    uint32_t ok;
    asm volatile("{.reg .pred p; mbarrier.try_wait.parity.shared.b64 p, [%1], %2; selp.u32 %0, 1, 0, p;}" : "=r"(ok) : "r"(b), "r"(par) : "memory");
    return ok;
}
__device__ __forceinline__ void mbar_wait(uint32_t b, uint32_t par) {
    int it = 0;
#pragma unroll 1
    while (!mbar_try(b, par)) { spin_guard(++it); }
}
__device__ __forceinline__ void mbar_wait_w(uint32_t b, uint32_t par) {
    int it = 0;
    bool ok;
#pragma unroll 1
    do { ok = __all_sync(~0u, mbar_try(b, par)); spin_guard(++it); } while (!ok);
}
__device__ __forceinline__ void mbar_wait_cluster(uint32_t b, uint32_t par) {
    int it = 0;
    while (true) {
        uint32_t ok;
        asm volatile("{.reg .pred p; mbarrier.try_wait.parity.acquire.cluster.shared::cta.b64 p, [%1], %2; selp.u32 %0, 1, 0, p;}" : "=r"(ok) : "r"(b), "r"(par) : "memory");
        if (ok) break;
        spin_guard(++it);
    }
}
__device__ __forceinline__ void tma2d(uint32_t dst, const CUtensorMap* m, int c0, int c1, uint32_t bar) {
    asm volatile("cp.async.bulk.tensor.2d.shared::cluster.global.mbarrier::complete_tx::bytes [%0], [%1, {%3, %4}], [%2];" ::"r"(dst), "l"(m), "r"(bar), "r"(c0), "r"(c1) : "memory");
}
__device__ __forceinline__ void tma2d_mc(uint32_t dst, const CUtensorMap* m, int c0, int c1, uint32_t bar, uint16_t mask) {
    asm volatile("cp.async.bulk.tensor.2d.shared::cluster.global.mbarrier::complete_tx::bytes.multicast::cluster [%0], [%1, {%3, %4}], [%2], %5;" ::"r"(dst), "l"(m), "r"(bar), "r"(c0), "r"(c1), "h"(mask) : "memory");
}
__device__ __forceinline__ void bulk_g2s(uint32_t dst, const void* src, uint32_t bytes, uint32_t bar) {
    asm volatile("cp.async.bulk.shared::cluster.global.mbarrier::complete_tx::bytes [%0], [%1], %2, [%3];" ::"r"(dst), "l"(src), "r"(bytes), "r"(bar) : "memory");
}
__device__ __forceinline__ void bar_sync(int id, int n) { asm volatile("bar.sync %0, %1;" ::"r"(id), "r"(n) : "memory"); }
__device__ __forceinline__ void bar_arrive(int id, int n) { asm volatile("bar.arrive %0, %1;" ::"r"(id), "r"(n) : "memory"); }
__device__ __forceinline__ void cluster_sync_all() { asm volatile("barrier.cluster.arrive.aligned; barrier.cluster.wait.aligned;" ::: "memory"); }
__device__ __forceinline__ void fence_async_smem() { asm volatile("fence.proxy.async.shared::cta;" ::: "memory"); }
__device__ __forceinline__ void ldsm4t(uint32_t* r, uint32_t a) {
    asm volatile("ldmatrix.sync.aligned.m8n8.x4.trans.shared.b16 {%0,%1,%2,%3}, [%4];" : "=r"(r[0]), "=r"(r[1]), "=r"(r[2]), "=r"(r[3]) : "r"(a) : "memory");
}
__device__ __forceinline__ void ldsm4(uint32_t* r, uint32_t a) {
    asm volatile("ldmatrix.sync.aligned.m8n8.x4.shared.b16 {%0,%1,%2,%3}, [%4];" : "=r"(r[0]), "=r"(r[1]), "=r"(r[2]), "=r"(r[3]) : "r"(a) : "memory");
}
__device__ __forceinline__ uint32_t movm(uint32_t a) {
    uint32_t d; asm volatile("movmatrix.sync.aligned.m8n8.trans.b16 %0, %1;" : "=r"(d) : "r"(a)); return d;
}
__device__ __forceinline__ void mma16816(float* d, uint32_t a0, uint32_t a1, uint32_t a2, uint32_t a3, uint32_t b0, uint32_t b1) {
    asm volatile("mma.sync.aligned.m16n8k16.row.col.f32.bf16.bf16.f32 {%0,%1,%2,%3},{%4,%5,%6,%7},{%8,%9},{%0,%1,%2,%3};"
                 : "+f"(d[0]), "+f"(d[1]), "+f"(d[2]), "+f"(d[3]) : "r"(a0), "r"(a1), "r"(a2), "r"(a3), "r"(b0), "r"(b1));
}
__device__ __forceinline__ void mma16816z(float* d, const uint32_t* a, uint32_t b0, uint32_t b1) {
    asm volatile("mma.sync.aligned.m16n8k16.row.col.f32.bf16.bf16.f32 {%0,%1,%2,%3},{%4,%5,%6,%7},{%8,%9},{%10,%10,%10,%10};"
                 : "=f"(d[0]), "=f"(d[1]), "=f"(d[2]), "=f"(d[3]) : "r"(a[0]), "r"(a[1]), "r"(a[2]), "r"(a[3]), "r"(b0), "r"(b1), "f"(0.f));
}
__device__ __forceinline__ void mma1688(float* d, uint32_t a0, uint32_t a1, uint32_t b0) {
    asm volatile("mma.sync.aligned.m16n8k8.row.col.f32.bf16.bf16.f32 {%0,%1,%2,%3},{%4,%5},{%6},{%0,%1,%2,%3};"
                 : "+f"(d[0]), "+f"(d[1]), "+f"(d[2]), "+f"(d[3]) : "r"(a0), "r"(a1), "r"(b0));
}
__device__ __forceinline__ uint32_t pack2(float lo, float hi) {
    uint32_t r; asm("cvt.rn.bf16x2.f32 %0, %1, %2;" : "=r"(r) : "f"(hi), "f"(lo)); return r;
}
__device__ __forceinline__ uint32_t hadd2(uint32_t a, uint32_t b) {
    uint32_t r; asm("add.rn.bf16x2 %0, %1, %2;" : "=r"(r) : "r"(a), "r"(b)); return r;
}
__device__ __forceinline__ uint32_t hadd2v(uint32_t a, uint32_t b) {
    uint32_t r; asm volatile("add.rn.bf16x2 %0, %1, %2;" : "=r"(r) : "r"(a), "r"(b)); return r;
}
__device__ __forceinline__ float bflo(uint32_t u) { return __uint_as_float(u << 16); }
__device__ __forceinline__ float bfhi(uint32_t u) { return __uint_as_float(u & 0xffff0000u); }
__device__ __forceinline__ float ex2(float x) { float r; asm("ex2.approx.ftz.f32 %0, %1;" : "=f"(r) : "f"(x)); return r; }
__device__ __forceinline__ uint4 ldg_rlx4(const void* p) {
    uint4 v; asm volatile("ld.relaxed.gpu.global.v4.u32 {%0,%1,%2,%3}, [%4];" : "=r"(v.x), "=r"(v.y), "=r"(v.z), "=r"(v.w) : "l"(p) : "memory"); return v;
}
__device__ __forceinline__ uint2 ldg_rlx2(const void* p) {
    unsigned long long v; asm volatile("ld.relaxed.gpu.global.b64 %0, [%1];" : "=l"(v) : "l"(p) : "memory");
    return make_uint2((uint32_t)v, (uint32_t)(v >> 32));
}
__device__ __forceinline__ uint32_t ldg_rlx1(const void* p) {
    uint32_t v; asm volatile("ld.relaxed.gpu.global.u32 %0, [%1];" : "=r"(v) : "l"(p) : "memory"); return v;
}
__device__ __forceinline__ void stg_rlx1(void* p, uint32_t v) { asm volatile("st.relaxed.gpu.global.u32 [%0], %1;" ::"l"(p), "r"(v) : "memory"); }
__device__ __forceinline__ void stg_rlx2(void* p, uint32_t x, uint32_t y) {
    unsigned long long v = (unsigned long long)x | ((unsigned long long)y << 32);
    asm volatile("st.relaxed.gpu.global.b64 [%0], %1;" ::"l"(p), "l"(v) : "memory");
}
__device__ __forceinline__ void stg_rlx4(void* p, uint32_t x, uint32_t y, uint32_t z, uint32_t w) {
    asm volatile("st.relaxed.gpu.global.v4.u32 [%0], {%1,%2,%3,%4};" ::"l"(p), "r"(x), "r"(y), "r"(z), "r"(w) : "memory");
}
__device__ __forceinline__ void sts4(uint32_t a, uint32_t x, uint32_t y, uint32_t z, uint32_t w) {
    asm volatile("st.shared.v4.u32 [%0], {%1,%2,%3,%4};" ::"r"(a), "r"(x), "r"(y), "r"(z), "r"(w) : "memory");
}
__device__ __forceinline__ uint4 lds4(uint32_t a) {
    uint4 v; asm volatile("ld.shared.v4.u32 {%0,%1,%2,%3}, [%4];" : "=r"(v.x), "=r"(v.y), "=r"(v.z), "=r"(v.w) : "r"(a) : "memory"); return v;
}
__device__ __forceinline__ void st_async4(uint32_t a, float x, float y, float z, float w, uint32_t bar) {
    asm volatile("st.async.shared::cluster.mbarrier::complete_tx::bytes.v4.f32 [%0], {%1,%2,%3,%4}, [%5];" ::"r"(a), "f"(x), "f"(y), "f"(z), "f"(w), "r"(bar) : "memory");
}
#define F4(d, i) "+f"(d[i]), "+f"(d[i + 1]), "+f"(d[i + 2]), "+f"(d[i + 3])
template <bool V> __device__ __forceinline__ void wgmma_tok_rs(float* d, const uint32_t* a, uint64_t b, int sc) {
    if (V) asm volatile("{.reg .pred p; setp.ne.b32 p, %25, 0;\n wgmma.mma_async.sync.aligned.m64n40k16.f32.bf16.bf16 {%0,%1,%2,%3,%4,%5,%6,%7,%8,%9,%10,%11,%12,%13,%14,%15,%16,%17,%18,%19}, {%20,%21,%22,%23}, %24, p, 1, 1, 0;}"
                        : F4(d, 0), F4(d, 4), F4(d, 8), F4(d, 12), F4(d, 16) : "r"(a[0]), "r"(a[1]), "r"(a[2]), "r"(a[3]), "l"(b), "r"(sc));
    else asm volatile("{.reg .pred p; setp.ne.b32 p, %21, 0;\n wgmma.mma_async.sync.aligned.m64n32k16.f32.bf16.bf16 {%0,%1,%2,%3,%4,%5,%6,%7,%8,%9,%10,%11,%12,%13,%14,%15}, {%16,%17,%18,%19}, %20, p, 1, 1, 0;}"
                      : F4(d, 0), F4(d, 4), F4(d, 8), F4(d, 12) : "r"(a[0]), "r"(a[1]), "r"(a[2]), "r"(a[3]), "l"(b), "r"(sc));
}
template <bool V> __device__ __forceinline__ void wgmma_tok_ss(float* d, uint64_t a, uint64_t b) {
    if (V) asm volatile("wgmma.mma_async.sync.aligned.m64n40k16.f32.bf16.bf16 {%0,%1,%2,%3,%4,%5,%6,%7,%8,%9,%10,%11,%12,%13,%14,%15,%16,%17,%18,%19}, %20, %21, 1, 1, 1, 1, 0;"
                        : F4(d, 0), F4(d, 4), F4(d, 8), F4(d, 12), F4(d, 16) : "l"(a), "l"(b));
    else asm volatile("wgmma.mma_async.sync.aligned.m64n32k16.f32.bf16.bf16 {%0,%1,%2,%3,%4,%5,%6,%7,%8,%9,%10,%11,%12,%13,%14,%15}, %16, %17, 1, 1, 1, 1, 0;"
                      : F4(d, 0), F4(d, 4), F4(d, 8), F4(d, 12) : "l"(a), "l"(b));
}
#define F16(d, i) F4(d, i), F4(d, i + 4), F4(d, i + 8), F4(d, i + 12)
template <int TA>
__device__ __forceinline__ void wgmma_ss128(float* d, uint64_t a, uint64_t b, int sc) {
    asm volatile("{.reg .pred p; setp.ne.b32 p, %66, 0;\n wgmma.mma_async.sync.aligned.m64n128k16.f32.bf16.bf16 "
                 "{%0,%1,%2,%3,%4,%5,%6,%7,%8,%9,%10,%11,%12,%13,%14,%15,%16,%17,%18,%19,%20,%21,%22,%23,%24,%25,%26,%27,%28,%29,%30,%31,"
                 "%32,%33,%34,%35,%36,%37,%38,%39,%40,%41,%42,%43,%44,%45,%46,%47,%48,%49,%50,%51,%52,%53,%54,%55,%56,%57,%58,%59,%60,%61,%62,%63}, %64, %65, p, 1, 1, %67, 1;}"
                 : F16(d, 0), F16(d, 16), F16(d, 32), F16(d, 48) : "l"(a), "l"(b), "r"(sc), "n"(TA));
}

__device__ __forceinline__ float warp_sum(float v) {
#pragma unroll
    for (int o = 16; o; o >>= 1) v += __shfl_xor_sync(~0u, v, o);
    return v;
}
__device__ __forceinline__ float bfround(float x) { return __bfloat162float(__float2bfloat16(x)); }

__device__ __forceinline__ void wait_count1(const uint32_t* p, uint32_t target) {
    int it = 0;
#pragma unroll 1
    while (true) {
        uint32_t v;
        asm volatile("ld.acquire.gpu.global.u32 %0, [%1];" : "=r"(v) : "l"(p) : "memory");
        if (v >= target) break;
        spin_guard(++it);
    }
}
__device__ __forceinline__ void red2(float* p, float a, float b) {
    asm volatile("red.relaxed.gpu.global.add.v2.f32 [%0], {%1, %2};" ::"l"(p), "f"(a), "f"(b) : "memory");
}
__device__ __forceinline__ void l2_prefetch(const void* p, uint32_t bytes) {
    asm volatile("cp.async.bulk.prefetch.L2.global [%0], %1;" ::"l"(p), "r"(bytes) : "memory");
}
__device__ __forceinline__ void signal_count(uint32_t* p) { asm volatile("red.release.gpu.global.add.u32 [%0], 1;" ::"l"(p) : "memory"); }
__device__ __forceinline__ void e_expect(uint32_t b, uint32_t tx) {
    asm volatile("{.reg .pred p; elect.sync _|p, 0xffffffff; @p mbarrier.arrive.expect_tx.shared.b64 _, [%0], %1;}" ::"r"(b), "r"(tx) : "memory");
}
__device__ __forceinline__ void e_tma2d(uint32_t dst, const CUtensorMap* m, int c0, int c1, uint32_t bar) {
    asm volatile("{.reg .pred p; elect.sync _|p, 0xffffffff;\n @p cp.async.bulk.tensor.2d.shared::cluster.global.mbarrier::complete_tx::bytes [%0], [%1, {%3, %4}], [%2];}"
                 ::"r"(dst), "l"(m), "r"(bar), "r"(c0), "r"(c1) : "memory");
}
__device__ __forceinline__ void e_tma2d_mc(uint32_t dst, const CUtensorMap* m, int c0, int c1, uint32_t bar) {
    asm volatile("{.reg .pred p; elect.sync _|p, 0xffffffff;\n @p cp.async.bulk.tensor.2d.shared::cluster.global.mbarrier::complete_tx::bytes.multicast::cluster [%0], [%1, {%3, %4}], [%2], %5;}"
                 ::"r"(dst), "l"(m), "r"(bar), "r"(c0), "r"(c1), "h"((uint16_t)3) : "memory");
}
__device__ __forceinline__ void e_prefetch(const void* p, uint32_t bytes) {
    asm volatile("{.reg .pred p; elect.sync _|p, 0xffffffff; @p cp.async.bulk.prefetch.L2.global [%0], %1;}" ::"l"(p), "r"(bytes) : "memory");
}
__device__ __forceinline__ void wait_count_w(const uint32_t* p, uint32_t target) {
    int it = 0;
#pragma unroll 1
    while (true) {
        uint32_t v;
        asm volatile("ld.acquire.gpu.global.u32 %0, [%1];" : "=r"(v) : "l"(p) : "memory");
        if (__all_sync(~0u, v >= target)) break;
        spin_guard(++it);
    }
}

__device__ __forceinline__ void ln_rows(float (&x)[2][32]) {
    float s[2] = {0, 0}, q[2] = {0, 0};
#pragma unroll
    for (int i = 0; i < 64; i++) s[i & 1] += x[i & 1][i >> 1];
#pragma unroll
    for (int o = 16; o; o >>= 1) { s[0] += __shfl_xor_sync(~0u, s[0], o); s[1] += __shfl_xor_sync(~0u, s[1], o); }
#pragma unroll
    for (int i = 0; i < 64; i++) { float& v = x[i & 1][i >> 1]; v -= s[i & 1] * (1.0f / DM); q[i & 1] += v * v; }
#pragma unroll
    for (int o = 16; o; o >>= 1) { q[0] += __shfl_xor_sync(~0u, q[0], o); q[1] += __shfl_xor_sync(~0u, q[1], o); }
    const float r[2] = {rsqrtf(q[0] * (1.0f / DM) + 1e-5f), rsqrtf(q[1] * (1.0f / DM) + 1e-5f)};
#pragma unroll
    for (int i = 0; i < 64; i++) x[i & 1][i >> 1] *= r[i & 1];
}
__device__ __forceinline__ uint4 pack8(const float* x) {
    return make_uint4(pack2(x[0], x[1]), pack2(x[2], x[3]), pack2(x[4], x[5]), pack2(x[6], x[7]));
}
#define NL 6
constexpr uint32_t HCH = 5120, HBUF = 8 * HCH;
constexpr uint32_t SM_SX = 0, SM_ST = 2560, SM_OX = 8192, SM_LX = 10240, SM_PX = 11392, SM_PA = 12288, SM_VF = 18432, SM_TAB = 26624, SM_WL2 = 41984, SM_HB = 49152, SM_WO = 131072,
                   SM_WL = 196608, SM_PRE = SM_WL, SM_BAR = 227328, SM_SV = SM_BAR + 256, SM_TRC = SM_SV + 2048, SM_REC_TOTAL = SM_TRC + 2688;
__host__ __device__ constexpr uint32_t sm_wl(int i) { return i < 5 ? SM_WL + i * 6144 : SM_WL2; }
constexpr uint32_t SB0 = 1024;
constexpr int B_WO = 0, B_HE = 1, B_ROLE = 2, B_HB = 3, B_W = 5;
constexpr int NB_MEM = 1, NB_QK = 2, NB_X1 = 3, NB_X2 = 4, NB_WIN = 5, NB_WG = 6, NB_KDONE = 7, NB_FIN0 = 8, NB_LN = 9, NB_MEM2 = 10, NB_H = 11, NB_A = 12, NB_B = 13, NB_C = 14, NB_F = 15;
#define ST_GATE 1
#define SPF 33
#define SPF_NS 100
#define TPV_DLY 3
#define L_AT 1
#define D_X2 300
#define D_V 150
#define NPF1 6
#define NPF 12
#define ROTM 7
#define FARF 1
#define T_GO 29
#define STG_ORD 2
#define GATE_AT 29
#define H4 1
#define T_X2 1900
#define T_V 400
#define LAST_WG 0
#define QK_EARLY 0
#define NOB 1
#define VP_AT 1
#define KQ_AT 17
#define PD 4
#define PFENCE 1
#define SH3 1
#define PV_FENCE 3
#define SGATE 0
#define SW_T 18
#define SW_N 1
#define SW_END 48
#define SV_AT 0
#define SSG 4
#define SSG_V 4
#define SS0_K 2
#define SS0_V 4
#define W0_AT 12
#define NPF0 4
#define SPLIT_MEM 1
#define STG_FENCE 5
#define O_LATE 0
#define PF_BAR 0
#define NPF2 11
#define PF_DLY 6
#define H_AT 3
#define H_D 200
#define REQ_LATE 2
#define PIN_EPI 1

#define PROF_INIT
#define PROF(i)
#define PROFV(i, v)
#define PROF_OUT

__device__ __forceinline__ uint32_t clk32() { uint32_t t; asm volatile("mov.u32 %0, %%clock;" : "=r"(t) :: "memory"); return t; }
__device__ __forceinline__ uint32_t gtime32() { uint32_t t; asm volatile("mov.u32 %0, %%globaltimer_lo;" : "=r"(t) :: "memory"); return t; }
__device__ __forceinline__ void spin_until(uint32_t t0, uint32_t d) { while (clk32() - t0 < d) {} }
template <int N> __device__ __forceinline__ uint32_t delay(uint32_t zero) {
    float x = __uint_as_float(clk32());
#pragma unroll
    for (int i = 0; i < N; i++) asm volatile("ex2.approx.ftz.f32 %0, %0;" : "+f"(x));
    return __float_as_uint(x) & zero;
}
__device__ __forceinline__ uint32_t clk_after(uint32_t x, uint32_t zero) {
    unsigned long long c = 0;
    asm volatile("{.reg .pred p; setp.eq.u32 p, %1, 0; @p mov.u64 %0, %%clock64;}" : "+l"(c) : "r"(x & zero) : "memory");
    return (uint32_t)c;
}
__device__ __forceinline__ uint32_t later(uint32_t a, uint32_t b) { return a + max((int)(b - a), 0); }
__device__ __forceinline__ void wait_clk(uint32_t t) {
#pragma unroll 1
    while (true) {
        unsigned long long c;
        asm volatile("mov.u64 %0, %%clock64;" : "=l"(c) :: "memory");
        if ((int)((uint32_t)c - t) >= 0) break;
    }
}
__device__ __forceinline__ uint32_t opaque(uint32_t v) { return __shfl_sync(~0u, v, threadIdx.x & 31); }
__device__ __forceinline__ uint32_t xor_or(uint32_t a, uint32_t b, uint32_t t) {
    uint32_t r; asm volatile("lop3.b32 %0, %1, %2, %3, 0x7E;" : "=r"(r) : "r"(a), "r"(b), "r"(t)); return r;
}
__device__ __forceinline__ uint32_t or3(uint32_t a, uint32_t b, uint32_t c) {
    uint32_t r; asm volatile("lop3.b32 %0, %1, %2, %3, 0xFE;" : "=r"(r) : "r"(a), "r"(b), "r"(c)); return r;
}
__device__ __forceinline__ uint32_t settag(uint32_t v, uint32_t tag) {
    uint32_t r; asm("lop3.b32 %0, %1, 1, %2, 0xB8;" : "=r"(r) : "r"(v), "r"(tag)); return r;
}
__device__ __forceinline__ void ldg4_if(uint4& v, const void* p, bool c) {
    asm volatile("{.reg .pred p; setp.ne.u32 p, %5, 0; @p ld.relaxed.gpu.global.v4.u32 {%0,%1,%2,%3}, [%4];}"
                 : "+r"(v.x), "+r"(v.y), "+r"(v.z), "+r"(v.w) : "l"(p), "r"((uint32_t)c) : "memory");
}
__device__ __forceinline__ uint4 ldg_rlx2x2(const void* p) {
    unsigned long long a, b;
    asm volatile("ld.relaxed.gpu.global.v2.b64 {%0,%1}, [%2];" : "=l"(a), "=l"(b) : "l"(p) : "memory");
    return make_uint4((uint32_t)a, (uint32_t)(a >> 32), (uint32_t)b, (uint32_t)(b >> 32));
}
__device__ __forceinline__ void stg_rlx2x2(void* p, uint32_t x, uint32_t y, uint32_t z, uint32_t w) {
    asm volatile("{.reg .b64 a, b; mov.b64 a, {%1,%2}; mov.b64 b, {%3,%4}; st.relaxed.gpu.global.v2.b64 [%0], {a, b};}" ::"l"(p), "r"(x), "r"(y), "r"(z), "r"(w) : "memory");
}
__device__ __forceinline__ void ldg1_if(uint32_t& v, const void* p, bool c) {
    asm volatile("{.reg .pred p; setp.ne.u32 p, %2, 0; @p ld.relaxed.gpu.global.u32 %0, [%1];}" : "+r"(v) : "l"(p), "r"((uint32_t)c) : "memory");
}
__device__ __forceinline__ void sts2(uint32_t a, float x, float y) { asm volatile("st.shared.v2.f32 [%0], {%1,%2};" ::"r"(a), "f"(x), "f"(y) : "memory"); }
__device__ __forceinline__ void sts4f(uint32_t a, float x, float y, float z, float w) {
    asm volatile("st.shared.v4.f32 [%0], {%1,%2,%3,%4};" ::"r"(a), "f"(x), "f"(y), "f"(z), "f"(w) : "memory");
}
__device__ __forceinline__ void sts1(uint32_t a, uint32_t x) { asm volatile("st.shared.u32 [%0], %1;" ::"r"(a), "r"(x) : "memory"); }
__device__ __forceinline__ uint32_t lds1(uint32_t a) { uint32_t v; asm volatile("ld.shared.u32 %0, [%1];" : "=r"(v) : "r"(a) : "memory"); return v; }
__device__ __forceinline__ float4 lds4f(uint32_t a) {
    float4 v; asm volatile("ld.shared.v4.f32 {%0,%1,%2,%3}, [%4];" : "=f"(v.x), "=f"(v.y), "=f"(v.z), "=f"(v.w) : "r"(a) : "memory"); return v;
}
__device__ __forceinline__ float2 lds2f(uint32_t a) {
    float2 v; asm volatile("ld.shared.v2.f32 {%0,%1}, [%2];" : "=f"(v.x), "=f"(v.y) : "r"(a) : "memory"); return v;
}
__device__ __forceinline__ bool any_bit0(uint32_t x) {
    uint32_t r;
    asm volatile("{.reg .pred p, q; .reg .b32 t; and.b32 t, %1, 1; setp.ne.u32 p, t, 0; vote.sync.any.pred q, p, 0xffffffff; selp.u32 %0, 1, 0, q;}" : "=r"(r) : "r"(x));
    return r;
}
__device__ __forceinline__ float rcp_fast(float x) { float r; asm("rcp.approx.ftz.f32 %0, %1;" : "=f"(r) : "f"(x)); return r; }
__device__ __forceinline__ void stsm4(uint32_t a, uint32_t r0, uint32_t r1, uint32_t r2, uint32_t r3) {
    asm volatile("stmatrix.sync.aligned.m8n8.x4.shared.b16 [%0], {%1,%2,%3,%4};" ::"r"(a), "r"(r0), "r"(r1), "r"(r2), "r"(r3) : "memory");
}
__device__ __forceinline__ void stsm4t(uint32_t a, uint32_t r0, uint32_t r1, uint32_t r2, uint32_t r3) {
    asm volatile("stmatrix.sync.aligned.m8n8.x4.trans.shared.b16 [%0], {%1,%2,%3,%4};" ::"r"(a), "r"(r0), "r"(r1), "r"(r2), "r"(r3) : "memory");
}
__device__ __forceinline__ void stg_b64_if(bool c, void* p, uint32_t x, uint32_t y) {
    asm volatile("{.reg .pred p; .reg .b64 a; setp.ne.u32 p, %3, 0; mov.b64 a, {%1,%2}; @p st.relaxed.gpu.global.b64 [%0], a;}" ::"l"(p), "r"(x), "r"(y), "r"((uint32_t)c) : "memory");
}
__device__ __forceinline__ void cp_async16(uint32_t dst, const void* src) { asm volatile("cp.async.cg.shared.global [%0], [%1], 16;" ::"r"(dst), "l"(src) : "memory"); }
__device__ __forceinline__ uint32_t hadd2h(uint32_t a, uint32_t b) { uint32_t r; asm("add.rn.f16x2 %0, %1, %2;" : "=r"(r) : "r"(a), "r"(b)); return r; }
__device__ __forceinline__ uint32_t hmax2h(uint32_t a, uint32_t b) { uint32_t r; asm("max.f16x2 %0, %1, %2;" : "=r"(r) : "r"(a), "r"(b)); return r; }
__device__ __forceinline__ uint32_t max3u(uint32_t a, uint32_t b, uint32_t c) { return __vimax3_u32(a, b, c); }
__device__ __forceinline__ void fence_gpu() { asm volatile("fence.acq_rel.gpu;" ::: "memory"); }

__device__ __forceinline__ void h_load(uint32_t sb, const uint8_t* hsrc, int pass, uint32_t rank, uint32_t rot, uint32_t wq) {
    const uint32_t bar = sb + SM_BAR + 8 * (B_HB + (pass & 1)), c = (wq + rot) & 3, dst = sb + SM_HB + (pass & 1) * HBUF + (rank * 4 + c) * HCH;
    const uint8_t* src = hsrc + ((size_t)pass * 65536 + c * 4096);
    if (wq == 0) e_expect(bar, 32768);
#pragma unroll
    for (int i = 0; i < H4; i++) {
        const uint32_t o = ((i + (rot >> 2)) & (H4 - 1)) * (4096 / H4);
        asm volatile("{.reg .pred p; elect.sync _|p, 0xffffffff;\n"
                     " @p cp.async.bulk.shared::cluster.global.mbarrier::complete_tx::bytes.multicast::cluster [%0], [%1], %4, [%2], %3;}"
                     ::"r"(dst + o), "l"(src + o), "r"(bar), "h"((uint16_t)3), "n"(4096 / H4) : "memory");
    }
}
__device__ __forceinline__ uint4 ldg_b128(const void* p) {
    uint4 v;
    asm volatile("{.reg .b128 t; .reg .b64 a, b; ld.relaxed.gpu.global.b128 t, [%4]; mov.b128 {a, b}, t; mov.b64 {%0,%1}, a; mov.b64 {%2,%3}, b;}"
                 : "=r"(v.x), "=r"(v.y), "=r"(v.z), "=r"(v.w) : "l"(p) : "memory");
    return v;
}
__device__ __forceinline__ void stg_b128_if(bool c, void* p, uint32_t x, uint32_t y, uint32_t z, uint32_t w) {
    asm volatile("{.reg .pred p; .reg .b128 t; .reg .b64 a, b; setp.ne.u32 p, %5, 0; mov.b64 a, {%1,%2}; mov.b64 b, {%3,%4}; mov.b128 t, {a, b}; @p st.relaxed.gpu.global.b128 [%0], t;}"
                 ::"l"(p), "r"(x), "r"(y), "r"(z), "r"(w), "r"((uint32_t)c) : "memory");
}
__device__ __forceinline__ float pretag(float x, uint32_t add, uint32_t keep) { return __uint_as_float((__float_as_uint(x) + add) & keep); }

template <bool MASK, class F>
__device__ __forceinline__ void softmax_rows(uint32_t src, uint32_t dst, uint32_t g16, int row0, F mid) {
    const uint32_t u = (g16 >> 7) & 3, e = ((g16 >> 9) << 3) | ((g16 >> 4) & 7);
    const uint32_t se = src + e * 8, su = se + u * 1088;
    const float2 p0 = lds2f(su), p1 = lds2f(su + 256), p2 = lds2f(su + 512), p3 = lds2f(su + 768);
    const float2 m0 = lds2f(se + 4352), m1 = lds2f(se + 4352 + 256), m2 = lds2f(se + 4352 + 512), m3 = lds2f(se + 4352 + 768);
    float a0 = (p0.x + p1.x) + (p2.x + p3.x), a1 = (p0.y + p1.y) + (p2.y + p3.y);
    const float a2 = (m0.x + m1.x) + (m2.x + m3.x), a3 = (m0.y + m1.y) + (m2.y + m3.y);
    mid(__float_as_uint(a3));
    if (MASK) {
        const int vis = row0 + (e >> 2) - 2 * (e & 3) - 8 * u;
        if (vis < 0) a0 = -1e9f / 0.08838834764831845f;
        if (vis < 1) a1 = -1e9f / 0.08838834764831845f;
    }
    int k = __float_as_int(fmaxf(fmaxf(a0, a1), fmaxf(a2, a3)));
    k ^= (k >> 31) & 0x7fffffff;
    const bool hi = g16 & 64;
    const int k0 = __reduce_max_sync(~0u, hi ? INT_MIN : k), k1 = __reduce_max_sync(~0u, hi ? k : INT_MIN);
    k = hi ? k1 : k0;
    const float m = __int_as_float(k ^ ((k >> 31) & 0x7fffffff));
    const float sl2 = 0.08838834764831845f * 1.4426950408889634f, mb = -m * sl2;
    sts1(dst + e * 16 + u * 4, pack2(ex2(fmaf(a0, sl2, mb)), ex2(fmaf(a1, sl2, mb))));
    sts1(dst + 512 + e * 4, pack2(ex2(fmaf(a2, sl2, mb)), ex2(fmaf(a3, sl2, mb))));
}

__device__ __forceinline__ uint32_t pack_h2(float lo, float hi) {
    uint32_t r; asm("cvt.rn.satfinite.f16x2.f32 %0, %1, %2;" : "=r"(r) : "f"(hi), "f"(lo)); return r;
}
__device__ __forceinline__ float2 unpack_h2(uint32_t u) {
    float2 r; asm("{.reg .b16 l, h; mov.b32 {l, h}, %2; cvt.f32.f16 %0, l; cvt.f32.f16 %1, h;}" : "=f"(r.x), "=f"(r.y) : "r"(u)); return r;
}
__device__ __forceinline__ uint32_t h2bf(uint32_t u) {
    uint32_t r;
    asm volatile("{.reg .b16 l, h; .reg .f32 a, b; mov.b32 {l, h}, %1; cvt.f32.f16 a, l; cvt.f32.f16 b, h; cvt.rn.bf16x2.f32 %0, b, a;}" : "=r"(r) : "r"(u));
    return r;
}
__device__ __forceinline__ void red_h8(void* p, uint32_t x, uint32_t y, uint32_t z, uint32_t w) {
    asm volatile("red.relaxed.gpu.global.add.noftz.v4.f16x2 [%0], {%1,%2,%3,%4};" ::"l"(p), "r"(x), "r"(y), "r"(z), "r"(w) : "memory");
}
__device__ __forceinline__ void red_h2_if(bool c, void* p, uint32_t x) {
    asm volatile("{.reg .pred p; setp.ne.u32 p, %2, 0; @p red.relaxed.gpu.global.add.noftz.f16x2 [%0], %1;}" ::"l"(p), "r"(x), "r"((uint32_t)c) : "memory");
}
__device__ __forceinline__ void red_h10(bool c, void* p, void* q, uint32_t x, uint32_t y, uint32_t z, uint32_t w, uint32_t e) {
    asm volatile("{.reg .pred p; setp.ne.u32 p, %7, 0; red.relaxed.gpu.global.add.noftz.v4.f16x2 [%0], {%2,%3,%4,%5};\n"
                 " @p red.relaxed.gpu.global.add.noftz.f16x2 [%1], %6;}" ::"l"(p), "l"(q), "r"(x), "r"(y), "r"(z), "r"(w), "r"(e), "r"((uint32_t)c) : "memory");
}
constexpr float SM_L2E = 0.08838834764831845f * 1.4426950408889634f;
template <int V> struct IC { static constexpr int value = V; };
typedef unsigned long long u64;
__device__ __forceinline__ uint32_t lo32(u64 v) { return (uint32_t)v; }
__device__ __forceinline__ uint32_t hi32(u64 v) { return (uint32_t)(v >> 32); }
__device__ __forceinline__ u64 ldg_u64(const void* p) { u64 v; asm volatile("ld.relaxed.gpu.global.b64 %0, [%1];" : "=l"(v) : "l"(p) : "memory"); return v; }
__device__ __forceinline__ void ldg_u64_if(u64& v, const void* p, bool c) {
    asm volatile("{.reg .pred p; setp.ne.u32 p, %2, 0; @p ld.relaxed.gpu.global.b64 %0, [%1];}" : "+l"(v) : "l"(p), "r"((uint32_t)c) : "memory");
}
struct RecTime { uint32_t go, x2, v, dx2, dv, h; };
__device__ __forceinline__ void rec_main(uint32_t sb, const CUtensorMap* tWo, uint8_t* arena, int role, int hinfo, int wg, uint32_t zero, const RecTime& tm) {
    const int hA = hinfo & 255;
    const int tid = threadIdx.x, t = tid & 127, lane = tid & 31, wi = t >> 5;
    const uint32_t bars = sb + SM_BAR;
    const int head = role >> 2, qd = role & 3, j = blockIdx.x & 1, kh = role & 1;
    const uint32_t mypar = head >= hA;
    const uint32_t ff = kh ^ mypar ^ FARF;
    const uint32_t wiu = __reduce_max_sync(~0u, wi);
    const bool warp0 = wiu == 0;
    const uint8_t* hsrc = (const uint8_t*)g_himg + kh * 32768 + j * 16384;
    auto tokbase = [&](int ty) { return ((ty + 1) << 21) + blk(lb_tok(head), mypar ^ ((hinfo >> (8 + ty)) & 1)); };
    const uint32_t tbw = tokbase(wg), tbq = tokbase(0) + (qd >> 1) * 2048 + (qd & 1) * 8;
#define KS(p) (4 * (((p) >> 1) & 7) + ((p) >> 4) + 2 * ((p) & 1))
    uint32_t w[32 - NL][4];
    uint4 wl5;
    const uint32_t frow = ((lane >> 4) * 8 + (lane & 7)) * 128, fx = ((lane >> 3) & 1) ^ (lane & 7);
    {
#pragma unroll 1
        for (int i = 0; i < 4; i++) mbar_wait_w(bars + 8 * (B_W + (wg == 2 ? 8 + i : 2 * i + wg)), 0);
        const uint32_t stg = sb + wg * 65536;
#pragma unroll
        for (int p = NL; p < 32; p++) ldsm4t(w[p - NL], stg + KS(p) * 2048 + frow + ((fx ^ (2 * wi)) << 4));
#pragma unroll
        for (int i = 0; i < NL; i++) {
            wl5 = lds4(stg + KS(i) * 2048 + t * 16);
            if (i < 5) sts4(sb + sm_wl(i) + tid * 16, wl5.x, wl5.y, wl5.z, wl5.w);
        }
        fence_async_smem();
        if (wg < 2) bar_sync(NB_WG, 256);
        if (wg > 0) wait_count_w(&g_tick[32 + (lane & 3) * 8], 1);
        if (wg == 1) {
            if (t == 0) mbar_arrive_cluster(bars + 8 * B_HE, j ^ 1);
            asm volatile("fence.proxy.async.global;" ::: "memory");
            mbar_wait_w(bars + 8 * B_HE, 0);
#pragma unroll 1
            for (int i = 0; i < 2; i++) h_load(sb, hsrc, i, j, head, wiu);
        }
        TL(3 + wg)
    }
    uint32_t g16 = opaque(t * 16);
    {
        const uint32_t c16 = kh * 2048 + ((2 * j + (wi >> 1)) * 32 + lane) * 16;
        const uint32_t xso = blk(lb_x2(head), mypar), wr = ((wg * 4 + wi) ^ (head & ROTM)) & 7;
        const uint32_t pc = wg < 2 ? acc_piece(wr >> 2, qd, wr & 3) : acc_piece(kh, ff, wi);
        const uint32_t lm = sb + SM_HB + 4096 + (lane & 7) * 128;
        const uint32_t a0 = wg < 2 ? sb + SM_WL + wg * 2048 + frow + ((fx ^ (2 * wi)) << 4) : blk(LB_STAMP + (wi >> 1), mypar) + stamp_line(wi, lane >> 3) + (lane & 7) * 16;
        const uint32_t a1 = pc + lane * 16;
        const uint32_t a2 = wg < 2 ? pc + 512 + (lane >> 3) * 4 : (role >> 2) * 1024 + (lane < 8 ? (role & 3) * 128 : 384) + lane * 16;
        const uint32_t a3 = wg < 2 ? sb + SM_WO + (wr >> 2) * 32768 + frow + ((fx ^ (2 * (wr & 3))) << 4) : qd * 65536 + head * 2048 + wi * 512 + lane * 4;
        const uint32_t a4 = wg < 2 ? lm + ((fx ^ ((lane >> 4) * 4)) << 4) : lm + ((fx ^ (2 * wi)) << 4) + ((lane >> 4) + 2 * ff) * HCH;
        bar_sync(NB_X2, 384);
        if (wg == 0 && lane == 0) {
            mbar_expect(bars + 8 * B_WO, 16384);
            tma2d(sb + SM_WO + wi * 16384, tWo, (wi >> 1) * 512 + qd * 128 + (wi & 1) * 64, head * DH, bars + 8 * B_WO);
            tma2d(sb + SM_WO + wi * 16384 + 8192, tWo, (wi >> 1) * 512 + qd * 128 + (wi & 1) * 64, head * DH + 64, bars + 8 * B_WO);
        }
        __syncwarp();
        if (NL > 5) {
            sts4(sb + SM_WL2 + tid * 16, wl5.x, wl5.y, wl5.z, wl5.w);
            fence_async_smem();
            bar_sync(NB_WG + wg, 128);
        }
        sts4(sb + SM_TAB + wg * 5120 + g16, a0, xso + wg * 16384 + (wi & 1) * 2048 + (c16 >> 1),
             wg ? xso + (wg == 2 ? 32768 : 0) + t * 8 : blk(LB_STAMP + ((lane >> 1) & 1), (lane >> 2) & 1) + stamp_line(lane, qd) + head * 4, tbw + (wi & 1) * 16384 + c16);
        sts4(sb + SM_TAB + wg * 5120 + 2048 + g16, a1, a2, a3, a4);
        sts2(sb + SM_TAB + wg * 5120 + 4096 + t * 8, __uint_as_float(tbw + t * 16), __uint_as_float((wg ? tbq : tokbase(1)) + t * 16));
    }
    const uint32_t po = (1 << 20) + j * 16384 + kh * 2048;
    const uint32_t ONES = 0x3f803f80u, tabw = sb + SM_TAB + wg * 5120;
#define LAST ((g16 & 0x70) == 0x70)
    PROF_INIT

    auto pa_ptr = [&](int p) { return arena + (((p & 1) ^ 1) * 32768 + po + lds1(tabw + 4096 + (g16 >> 1))); };
    auto pa_request = [&](int p) { cp_async16(sb + SM_PA + wg * 2048 + g16, pa_ptr(p)); };
    auto pa_get = [&](int p) {
        asm volatile("cp.async.wait_all;" ::: "memory");
        uint4 pa = lds4(sb + SM_PA + wg * 2048 + g16);
        int it = 0;
#pragma unroll 1
        while (any_bit0(pa.x ^ ((p - 1) >> 1) ^ 1) && p > 0 && p <= NSEG) { pa = ldg_b128(pa_ptr(p)); spin_guard(++it); }
        return pa;
    };
    auto token_pass = [&](auto vc, int s, uint4 pa, auto mid) {
        constexpr bool V = decltype(vc)::value;
        const int p = s + 2, b = p & 1;
        const uint32_t ftag = (((p - 1) >> 1) & 1) ^ 1, ptag = ((p >> 1) & 1) ^ 1;
#define HB(ks) dadd(mkdesc(SB0 + SM_HB + ((ks) >> 2) * HCH + ((ks) & 3) * 32, 16, 1024, 1), b * (HBUF / 16))
        float acc[V ? 20 : 16];
#pragma unroll
        for (int i = 0; i < 4; i++) { acc[2 * i] = bflo((&pa.x)[i]); acc[2 * i + 1] = bfhi((&pa.x)[i]); }
#pragma unroll
        for (int i = 8; i < (V ? 20 : 16); i++) acc[i] = 0.f;
        mid(-1, acc);
        wg_fence();
#pragma unroll
        for (int i = 0; i < 32; i++) {
            constexpr int GAP = V ? SSG_V : SSG, SS0 = V ? SS0_V : SS0_K;
            const int u = i < SS0 ? 0 : (i - SS0 + GAP - 1) / GAP, q = i - (u < NL ? u : NL);
            if (i >= SS0 && (i - SS0) % GAP == 0 && u < NL) wgmma_tok_ss<V>(acc, dadd(mkdesc(SB0 + sm_wl(u), 8192, 1024, 1), (V ? 2 : wg) * 128), HB(KS(u)));
            else wgmma_tok_rs<V>(acc, w[q], HB(KS(NL + q)), 1);
            mid(i, acc);
        }
        wg_commit();
        const bool tg = V || !(g16 & 64);
        const uint32_t add = tg ? (ftag ^ 1) << 16 : 0u, keep = tg ? 0xfffe0000u : ~0u;
        const uint32_t add1 = V ? 0u : add, keep1 = V ? ~0u : keep;
        uint32_t add2 = !V && wg == 0 ? add : 0u, keep2 = !V && wg == 0 ? keep : ~0u;
        uint8_t* pdst = arena + (b * 32768 + (po ^ 2048) + lds1(tabw + 4096 + (g16 >> 1)));
        uint8_t* fdst = arena + ((b ^ 1) * 32768 + lds1(tabw + 12 + g16));
        mid(32, acc);
        if (PIN_EPI) asm volatile("" : "+l"(pdst), "+l"(fdst));
        wg_wait<0>();
        mid(33, acc);
        PROF(9)
        uint32_t r0 = pack2(pretag(acc[0], add, keep), pretag(acc[1], add1, keep1));
        uint32_t r1 = pack2(acc[2], acc[3]), r3 = pack2(acc[6], acc[7]);
        uint32_t r2 = pack2(pretag(acc[4], add2, keep2), pretag(acc[5], add2, keep2));
        if (!V) { r0 = movm(r0); r1 = movm(r1); r2 = movm(r2); r3 = movm(r3); }
        mid(34, acc);
        stg_b128_if(p < NSEG, pdst, settag(pack2(pretag(acc[8], (ptag ^ 1) << 16, 0xfffe0000u), acc[9]), ptag), pack2(acc[10], acc[11]), pack2(acc[12], acc[13]), pack2(acc[14], acc[15]));
        stg_b128_if(p > 0 && p <= NSEG, fdst, settag(r0, ftag), r1, !V && wg == 0 ? settag(r2, ftag) : r2, r3);
        PROF(10)
    };
    uint4 tf[2][2];
    auto load_tok = [&](int s, uint32_t o) {
        const uint8_t* ts = arena + ((s & 1) * 32768 + o);
#pragma unroll
        for (int a = 0; a < 2; a++)
#pragma unroll
            for (int b = 0; b < 2; b++) tf[a][b] = ldg_b128(ts + a * 16384 + b * 2048);
    };

    if (wg < 2) {
        mbar_wait_w(bars + 8 * B_HB, 0);
        token_pass(IC<0>(), -2, make_uint4(0, 0, 0, 0), [](int, float*) {});
        bar_sync(NB_MEM, 384);
        if (wg == 1) {
            if (g16 == 0) mbar_arrive_cluster(bars + 8 * B_HE, j ^ 1);
            mbar_wait_w(bars + 8 * B_HE, 1);
            h_load(sb, hsrc, 2, j, head, wiu);
        } else {
            bar_arrive(NB_WIN, 384);
        }
        pa_request(1);
        mbar_wait_w(bars + 8 * (B_HB + 1), 0);
        uint4 pa = pa_get(1);
#pragma unroll 1
        for (int s = 0; s < NSEG; s++) {
            uint32_t w0[NL][4], xo, lm, fz = 0;
            const uint32_t wl = lds1(tabw + g16);
            uint32_t kq;
            token_pass(IC<0>(), s - 1, pa, [&](int i, float*) {
                if (i == W0_AT) {
#pragma unroll
                    for (int i = 0; i < NL; i++) ldsm4t(w0[i], wl + (sm_wl(i) - SM_WL));
                    if (W0_AT < 32) fz = clk32();
                }
                if (i == -1) {
                    if (wg == LAST_WG) bar_sync(NB_B, 256);
                    else bar_sync(NB_WIN, 384);
                }
                if (i == GATE_AT && wg != LAST_WG) bar_arrive(NB_B, 256);
                if (i == 33 && SPLIT_MEM) {
                    if (wg == LAST_WG) bar_arrive(NB_MEM, 384);
                    fz |= clk32();
                }
                if (i == 34 && ST_GATE && wg != LAST_WG) bar_sync(NB_F, 256);
                if (i == 32) {
                    xo = lds1(tabw + 4 + g16);
                    lm = lds1(tabw + 2060 + g16) + (s & 1) * HBUF;
                    if (KQ_AT <= 16) kq = lds1(tabw + 4096 + (g16 >> 1) * wg);
                }
            });
            asm volatile("" : "+r"(lm));
            if (SPLIT_MEM && wg == LAST_WG) bar_sync(NB_MEM2, 256);
            else bar_sync(NB_MEM, 384);
            PROF(1)
            float c[4][4];
            uint32_t bq[PD][4];
#define MEMF(it) ((lm ^ (((it) >> 3) * 32)) + ((it) & 7) * HCH)
#pragma unroll
            for (int it = 0; it < PD; it++) ldsm4(bq[it], MEMF(it));
#pragma unroll
            for (int it = 0; it < 16; it++) {
                uint32_t* bfr = bq[it % PD];
                const uint32_t* wa = 2 * it < NL ? w0[2 * it < NL ? 2 * it : 0] : w[2 * it < NL ? 0 : 2 * it - NL];
                const uint32_t* wb = 2 * it + 1 < NL ? w0[2 * it + 1 < NL ? 2 * it + 1 : 0] : w[2 * it + 1 < NL ? 0 : 2 * it + 1 - NL];
                float *ca = c[(2 * it) & 3], *cb = c[(2 * it + 1) & 3];
                if (it < 2) { mma16816z(ca, wa, bfr[0], bfr[1]); mma16816z(cb, wb, bfr[2], bfr[3]); }
                else { mma16816(ca, wa[0], wa[1], wa[2], wa[3], bfr[0], bfr[1]); mma16816(cb, wb[0], wb[1], wb[2], wb[3], bfr[2], bfr[3]); }
                if (it + PD < 16) ldsm4(bfr, MEMF(it + PD));
                if (it == KQ_AT) {
                    if (PFENCE) fz |= clk32();
                    load_tok(s, kq);
                }
            }
            if (QK_EARLY) bar_arrive(NB_QK + (__float_as_uint(c[0][0]) & zero), 384);
            const uint32_t r0 = pack2((c[0][0] + c[1][0]) + (c[2][0] + c[3][0]), (c[0][1] + c[1][1]) + (c[2][1] + c[3][1]));
            const uint32_t r1 = pack2((c[0][2] + c[1][2]) + (c[2][2] + c[3][2]), (c[0][3] + c[1][3]) + (c[2][3] + c[3][3]));
            if (!QK_EARLY) bar_arrive(NB_QK + (r0 & zero), 384);
            stg_rlx2(arena + xo, settag(movm(r0), (s & 1) ^ 1), movm(r1));
            const uint32_t tx = later(lds1(sb + SM_LX + 1040) + tm.x2, clk_after(r0, zero) + tm.dx2);
            g16 |= (fz | tx) & zero;
            PROF(2)
            {
                const uint32_t l16 = sb + (g16 & 0x1f0), g8 = g16 >> 1;
                const uint32_t tag = (s & 1) ^ 1, ttag = ((s >> 1) & 1) ^ 1;
                uint32_t wf[NPF][4], a3;
#define WF(f) (a3 + ((f) & 1) * 16384 + ((f) >> 1) * 2048)
                if (wg == 1) {
                    float sc[5][4];
                    uint4 (&kf)[2][2] = tf;
                    uint32_t qa[2][4], km[4], fz;
                    int it = 0;
                    bool bad;
#pragma unroll 1
                    do {
                        u64 qf[2], x[8];
                        const float2 u = lds2f(tabw + 4096 + g8);
                        if (KQ_AT > 16) load_tok(s, __float_as_uint(u.x));
                        else {
#pragma unroll 1
                            for (int i = it; i > 0; i &= zero) load_tok(s, __float_as_uint(u.x));
                        }
                        const uint8_t *xp = arena + lds1(tabw + 8 + g16), *tq = arena + ((s & 1) * 32768 + __float_as_uint(u.y));
                        asm volatile("" : "+l"(xp));
#pragma unroll
                        for (int a = 0; a < 2; a++) qf[a] = ldg_u64(tq + a * 16384);
                        spin_guard(++it);
                        wait_clk(tx);
                        PROF(8)
#pragma unroll
                        for (int i = 0; i < 8; i++) x[i] = ldg_u64(xp + (i >> 2) * 16384 + (i & 3) * 1024);
                        fz = clk32();
                        const uint32_t bt = or3(xor_or(lo32(qf[0]), lo32(qf[1]), ttag), xor_or(kf[0][0].x, kf[0][1].x, ttag), xor_or(kf[1][0].x, kf[1][1].x, ttag));
#pragma unroll
                        for (int a = 0; a < 2; a++) { qa[a][1] = or3(lo32(qf[a]), zero, 0); qa[a][3] = or3(hi32(qf[a]), zero, 0); }
                        fz |= clk32();
#pragma unroll
                        for (int a = 0; a < 2; a++) { qa[a][0] = hadd2v(lo32(x[2 * a]), lo32(x[2 * a + 1])); qa[a][2] = hadd2v(hi32(x[2 * a]), hi32(x[2 * a + 1])); }
#pragma unroll
                        for (int a = 0; a < 2; a++) { km[2 * a] = hadd2v(lo32(x[4 + 2 * a]), lo32(x[5 + 2 * a])); km[2 * a + 1] = hadd2v(hi32(x[4 + 2 * a]), hi32(x[5 + 2 * a])); }
                        bad = any_bit0(or3(or3(bt, xor_or(lo32(x[0]), lo32(x[1]), tag), xor_or(lo32(x[2]), lo32(x[3]), tag)), xor_or(lo32(x[4]), lo32(x[5]), tag), xor_or(lo32(x[6]), lo32(x[7]), tag)));
                    } while (bad);
                    PROFV(13, it - 1)
                    PROF(7)
                    mma16816z(sc[0], qa[0], kf[0][0].x, kf[0][0].y);
                    mma16816z(sc[1], qa[0], kf[0][0].z, kf[0][0].w);
                    mma16816z(sc[2], qa[0], kf[0][1].x, kf[0][1].y);
                    mma16816z(sc[3], qa[0], kf[0][1].z, kf[0][1].w);
                    mma16816z(sc[4], qa[0], km[0], km[1]);
                    mma16816(sc[0], qa[1][0], qa[1][1], qa[1][2], qa[1][3], kf[1][0].x, kf[1][0].y);
                    mma16816(sc[1], qa[1][0], qa[1][1], qa[1][2], qa[1][3], kf[1][0].z, kf[1][0].w);
                    mma16816(sc[2], qa[1][0], qa[1][1], qa[1][2], qa[1][3], kf[1][1].x, kf[1][1].y);
                    mma16816(sc[3], qa[1][0], qa[1][1], qa[1][2], qa[1][3], kf[1][1].z, kf[1][1].w);
                    mma16816(sc[4], qa[1][0], qa[1][1], qa[1][2], qa[1][3], km[2], km[3]);
                    const uint32_t sx = sb + SM_SX + (g16 & 0x1f0) * 5;
                    sts4(sx + (g16 >> 5 & 0x30), pack_h2(sc[0][0], sc[0][1]), pack_h2(sc[1][0], sc[1][1]),
                         pack_h2(sc[2][0], sc[2][1]), pack_h2(sc[3][0], sc[3][1]));
                    sts1(sx + 64 + (g16 >> 7 & 0xc), pack_h2(sc[4][0], sc[4][1]));
                    bar_arrive(NB_X1, 256);
                    const uint32_t now = gtime32();
#pragma unroll
                    for (int n = 0; n < 5; n++) sts2(sb + SM_ST + g8 + n * 1088, sc[n][2], sc[n][3]);
                    bar_arrive(NB_H, 256);
                    PROF(3)
                    a3 = lds1(tabw + 2056 + g16) | (fz & zero);
                    asm volatile("{.reg .pred p; setp.lt.u32 p, %2, 128; @p red.relaxed.gpu.global.max.u32 [%0], %1;}"
                                 ::"l"(arena + lds1(sb + SM_TAB + 8 + g16)), "r"(__funnelshift_r(now * 8, s + 1, 8)), "r"(g16) : "memory");
                    auto h_next = [&]() {
                        asm volatile("fence.proxy.async.global;" ::: "memory");
                        if (s + 3 <= NSEG) h_load(sb, hsrc, s + 3, j, head, wiu);
                    };
                    if (H_AT == 0) h_next();
                    if (s == 0) mbar_wait_w(bars + 8 * B_WO, 0);
                    const uint32_t th = clk32() + tm.v;
                    if (PF_DLY) a3 += delay<PF_DLY>(zero);
                    if (PF_BAR) bar_sync(NB_C, 256);
#pragma unroll
                    for (int f = 0; f < NPF; f++) ldsm4t(wf[f], WF(f));
                    if (H_AT == 2) {
#pragma unroll 1
                        while ((int)(clk32() - th) < 0) {}
                        h_next();
                    }
                } else {
                    if (H_AT == 1 && g16 == 0) mbar_arrive_cluster(bars + 8 * B_HE, j ^ 1);
                    if (s == 0) { TL(9) mbar_wait_w(bars + 8 * B_WO, 0); TL(6) }
                    if (warp0 && !(s & 3)) wait_count_w(&g_tick[32 + ((g16 >> 4) & 3) * 8], min((s + 4) / 4 + 1, 16));
                    a3 = lds1(tabw + 2056 + g16);
#pragma unroll
                    for (int f = 0; f < NPF0; f++) ldsm4t(wf[f], WF(f));
                    const float2 u = lds2f(tabw + 4096 + g8);
                    const uint8_t *q0 = arena + (tag * 32768 + po + __float_as_uint(u.x)), *q1 = arena + (tag * 32768 + po + __float_as_uint(u.y));
                    if (H_AT == 1) {
                        mbar_wait_w(bars + 8 * B_HE, s & 1);
                        asm volatile("fence.proxy.async.global;" ::: "memory");
                    }
                    wait_clk(tx + tm.h);
                    int it = 0;
                    bool bad;
#pragma unroll 1
                    do {
                        const uint4 p0 = ldg_b128(q0), p1 = ldg_b128(q1);
                        if (H_AT == 1 && !it && s + 3 <= NSEG) h_load(sb, hsrc, s + 3, j, head, wiu);
                        spin_guard(++it);
                        if (NPF0 < NPF1) wait_clk(tx + tm.v);
#pragma unroll
                        for (int f = NPF0; f < NPF1; f++) ldsm4t(wf[f], WF(f));
                        sts4(sb + SM_PA + g16, p0.x, p0.y, p0.z, p0.w);
                        sts4(sb + SM_PA + 2048 + g16, p1.x, p1.y, p1.z, p1.w);
                        bad = any_bit0(xor_or(p0.x, p1.x, ((s + 1) >> 1) ^ 1)) && s + 2 <= NSEG;
                    } while (bad);
                    bar_sync(NB_H, 256);
                    PROF(3)
                    softmax_rows<true>(sb + SM_ST, sb + SM_PX, g16, qd * 8, [&](uint32_t v) {
                        a3 += v & zero;
#pragma unroll
                        for (int f = NPF1; f < NPF2; f++) ldsm4t(wf[f], WF(f));
                    });
#pragma unroll
                    for (int f = NPF2; f < NPF; f++) ldsm4t(wf[f], WF(f));
                }
                PROF(5)
                float2 ls, a12;
                uint8_t *d0, *d1;
                bar_sync(NB_X2, 384);
                float c[4][4];
                uint32_t obs[4][4];
#pragma unroll
                for (int q = 0; q < NOB; q++) ldsm4t(obs[q], l16 + SM_OX + q * 512);
                if (NOB > 1) __syncwarp();
#pragma unroll
                for (int q = 0; q < 4; q++) {
                    const uint32_t* ob = obs[q];
                    if (q > 0 && q + NOB - 1 < 4) ldsm4t(obs[q + NOB - 1], l16 + SM_OX + (q + NOB - 1) * 512);
                    if (q == L_AT) ls = lds2f(sb + SM_LX + g8);
                    if (q == 2) { a12 = lds2f(tabw + 2048 + g16); d0 = arena + (acc_slot(s + 1) + __float_as_uint(a12.x)); d1 = arena + (acc_slot(s + 1) + __float_as_uint(a12.y)); }
#pragma unroll
                    for (int f = 4 * q; f < 4 * q + 4; f++) {
                        const uint32_t* a = wf[f % NPF];
                        if (f < 4) mma16816z(c[f], a, ob[f & 2], ob[(f & 2) + 1]);
                        else mma16816(c[f & 3], a[0], a[1], a[2], a[3], ob[f & 2], ob[(f & 2) + 1]);
                        if (f + NPF < 16) ldsm4t(wf[f % NPF], WF(f + NPF));
                    }
                }
                pa = lds4(sb + SM_PA + wg * 2048 + g16);
                if (wg == LAST_WG) bar_arrive(NB_WIN, 384);
                const float i0 = rcp_fast(ls.x), i1 = rcp_fast(ls.y);
                uint32_t v[4];
#pragma unroll
                for (int m = 0; m < 4; m++) v[m] = pack_h2((c[m >> 1][(m & 1) * 2] + c[(m >> 1) + 2][(m & 1) * 2]) * i0, (c[m >> 1][(m & 1) * 2 + 1] + c[(m >> 1) + 2][(m & 1) * 2 + 1]) * i1);
                red_h10(LAST, d0, d1, v[0], v[1], v[2], __byte_perm(v[3], ACC_ONE, LAST ? 0x7610 : 0x3210), __byte_perm(v[3], ACC_ONE, 0x7632));
                g16 |= v[0] & zero;
                PROF(6)
            }
        }
        if (wg != LAST_WG) bar_sync(NB_WIN, 384);
    } else {
        TLC(0)
        auto request = [&](int s, uint32_t o) {
            cp_async16(sb + SM_PA + 4096 + g16, arena + (((s & 1) ^ 1) * 32768 + po + o));
            const uint8_t* ts = arena + ((s & 1) * 32768 + o);
#pragma unroll
            for (int i = 0; i < 4; i++) cp_async16(sb + SM_VF + i * 2048 + g16, ts + (i >> 1) * 16384 + (i & 1) * 2048);
        };
#pragma unroll 1
        for (int p = 0; p < 2; p++) {
            pa_request(p);
            mbar_wait_w(bars + 8 * (B_HB + p), 0);
            token_pass(IC<1>(), p - 2, pa_get(p), [](int, float*) {});
            if (p == 0) { bar_sync(NB_MEM, 384); bar_arrive(NB_WIN, 384); }
        }
        request(0, lds1(tabw + 4096 + (g16 >> 1)));
        auto fetch = [&](int s, auto wait, auto after) {
            const uint4 t1 = lds4(tabw + 2048 + g16);
            const uint32_t mo = acc_slot(s) + t1.x, eo = mo - (g16 & 0x1f0) + 512 + ((g16 >> 5) & 12);
            const uint8_t *ms[2] = {arena + mo, arena + (mo ^ 4096)}, *es[2] = {arena + eo, arena + (eo ^ 4096)};
            uint32_t e[4] = {0, 0, 0, 0}, sel = LAST ? 0x5410 : 0x3210, dst = t1.w + (s & 1) * HBUF;
            asm volatile("" : "+l"(ms[0]), "+l"(ms[1]), "+l"(es[0]), "+l"(es[1]), "+r"(e[0]), "+r"(e[1]), "+r"(e[2]), "+r"(e[3]), "+r"(sel), "+r"(dst));
            uint32_t late = wait(), fz;
            PROF(11) PROFV(0, gtime32())
            int it = 0;
            bool bad;
#pragma unroll 1
            do {
                uint4 m[4];
                uint32_t b = 0;
#pragma unroll
                for (int i = 0; i < 4; i++) {
                    m[i] = ldg_rlx4(ms[i >> 1] + (i & 1) * 16384);
                    ldg1_if(e[i], es[i >> 1] + (i & 1) * 16384, LAST);
                }
                if (ST_GATE && it == 0) bar_arrive(NB_F, 256);
                const uint32_t now = clk32();
                fz = now;
                after(now & zero);
                sts1(sb + SM_LX + 1040, now - min(late >> 8, 8u) * 57);
                late = 0;
                spin_guard(++it);
#pragma unroll
                for (int n = 0; n < 4; n++) {
                    const int i = n ^ STG_ORD;
                    if (STG_FENCE >> n & 1) fz |= clk32();
                    b |= xor_or(m[i].w, e[i], ACC_ALL);
                    stsm4t(dst + (i >> 1) * (2 - 4 * ff) * HCH + (i & 1) * 4 * HCH, h2bf(m[i].x), h2bf(m[i].y), h2bf(m[i].z), h2bf(__byte_perm(m[i].w, e[i], sel)));
                }
                bad = __any_sync(~0u, LAST && b > 0xffffu);
            } while (bad);
            bar_arrive(NB_MEM, 384);
            if (SPLIT_MEM) bar_arrive(NB_MEM2, 256);
            g16 |= fz & zero;
            PROFV(12, it - 1) PROF(1)
        };
        fetch(0, []() { return 0u; }, [](uint32_t) {});
#pragma unroll 1
        for (int s = 0;; s++) {
            const uint32_t tag = (s & 1) ^ 1, ttag = ((s >> 1) & 1) ^ 1, l16 = sb + (g16 & 0x1f0), g8 = g16 >> 1;
            const int p = s + 2;
            if (s == 1) TL(7)
            if (s == 0) TL(13)
            if (s == 2) TL(14)
            fence_async_smem();
            stg_b128_if(g16 < ((role & 3) ? 128 : 160), arena + (acc_slot(s + 3) + lds1(tabw + 2052 + g16)), 0, 0, 0, 0);
            const uint4 pa = pa_get(p);
            if (p <= NSEG) mbar_wait_w(bars + 8 * (B_HB + (p & 1)), (p >> 1) & 1);
            uint8_t* xd = arena + lds1(tabw + 4 + g16);
            uint32_t tx;
            token_pass(IC<1>(), s, pa, [&](int i, float* acc) {
                if (i == -1) bar_sync(NB_QK, 384);
                if (i == 33) {
                    const uint32_t r0 = pack2(acc[16], acc[17]);
                    stg_rlx2(xd, settag(r0, tag), pack2(acc[18], acc[19]));
                    tx = clk_after(r0, zero) + tm.dv;
                    PROF(2)
                }
            });
            uint4 (&vf)[2][2] = tf;
#pragma unroll
            for (int i = 0; i < 4; i++) vf[i >> 1][i & 1] = lds4(sb + SM_VF + i * 2048 + g16);
            uint32_t xv[4] = {0, 0, 0, 0};
            float oc[2][4], lc[4];
            auto pv = [&](uint32_t p0, uint32_t p1, uint32_t p2, uint32_t p3, uint32_t p4, auto mid) {
                lc[0] = lc[1] = lc[2] = lc[3] = 0.f;
                mma16816z(oc[0], &vf[0][0].x, p0, p1);
                mma16816z(oc[1], &vf[1][0].x, p0, p1);
                mma16816(lc, ONES, ONES, ONES, ONES, p0, p1);
                mma16816(oc[0], vf[0][1].x, vf[0][1].y, vf[0][1].z, vf[0][1].w, p2, p3);
                mma16816(oc[1], vf[1][1].x, vf[1][1].y, vf[1][1].z, vf[1][1].w, p2, p3);
                mma16816(lc, ONES, ONES, ONES, ONES, p2, p3);
                mid();
                mma1688(oc[0], xv[0], xv[1], p4);
                mma1688(oc[1], xv[2], xv[3], p4);
                mma1688(lc, ONES, ONES, p4);
            };
            uint32_t so, oo, to, fz = 0;
            int it = 0;
            bool bad;
#pragma unroll 1
            do {
#pragma unroll 1
                for (int i = it; i > 0; i &= zero) load_tok(s, lds1(tabw + 4096 + g8));
                u64 xr[4];
                const uint8_t* xp = arena + lds1(tabw + 8 + g16);
                asm volatile("" : "+l"(xp));
                auto load_v = [&](uint32_t z) {
#pragma unroll
                    for (int i = 0; i < 4; i++) xr[i] = ldg_u64(xp + z + i * 1024);
                };
                const uint32_t bt = or3(xor_or(vf[0][0].x, vf[0][1].x, ttag), xor_or(vf[1][0].x, vf[1][1].x, ttag), 0);
                uint32_t sa = sb + SM_SX + (g16 & 0x1f0) * 5;
                asm volatile("" : "+r"(sa));
                spin_guard(it);
                wait_clk(tx);
                PROF(3)
                if (it++ == 0) bar_sync(NB_X1, 256);
                if (VP_AT == 0) load_v(0);
                uint4 sx[5];
#pragma unroll
                for (int i = 0; i < 5; i++) sx[i] = lds4(sa + i * 16);
                __syncwarp();
                if (VP_AT == 1) load_v(0);
                if (VP_AT == 2) load_v(sx[0].x & zero);
                if (VP_AT == 3) load_v(sx[4].x & zero);
                uint32_t pm[5];
                uint32_t a[5];
#pragma unroll
                for (int n = 0; n < 5; n++) {
                    uint32_t u[4];
#pragma unroll
                    for (int w = 0; w < 4; w++) u[w] = n < 4 ? (&sx[w].x)[n] : (&sx[4].x)[w];
                    a[n] = hadd2h(hadd2h(u[0], u[1]), hadd2h(u[2], u[3]));
                }
                uint32_t m = hmax2h(hmax2h(hmax2h(a[0], a[1]), hmax2h(a[2], a[3])), a[4]);
                if (PF_BAR == 1 && it == 1) bar_arrive(NB_C + (a[3] & zero), 256);
                if (SH3) {
                    const uint32_t m1 = __shfl_xor_sync(~0u, m, 1), m2 = __shfl_xor_sync(~0u, m, 2), m3 = __shfl_xor_sync(~0u, m, 3);
                    if (PF_BAR == 2 && it == 1) bar_arrive(NB_C, 256);
                    m = hmax2h(hmax2h(m, m1), hmax2h(m2, m3));
                } else {
                    m = hmax2h(m, __shfl_xor_sync(~0u, m, 1));
                    m = hmax2h(m, __shfl_xor_sync(~0u, m, 2));
                }
                if (VP_AT == 4) load_v(m & zero);
                so = lds1(tabw + g16); oo = lds1(tabw + 2056 + g16); to = lds1(tabw + 4096 + g8);
                const float2 mm = unpack_h2(m);
                const float mf = -SM_L2E * fmaxf(mm.x, mm.y);
#pragma unroll
                for (int n = 0; n < 5; n++) { const float2 u = unpack_h2(a[n]); pm[n] = pack2(ex2(fmaf(u.x, SM_L2E, mf)), ex2(fmaf(u.y, SM_L2E, mf))); }
                PROF(4)
                pv(pm[0], pm[1], pm[2], pm[3], pm[4], [&]() {
                    if (PV_FENCE & 1) fz = clk32();
#pragma unroll
                    for (int i = 0; i < 2; i++) { xv[2 * i] = hadd2v(lo32(xr[2 * i]), lo32(xr[2 * i + 1])); xv[2 * i + 1] = hadd2v(hi32(xr[2 * i]), hi32(xr[2 * i + 1])); }
                });
                bad = any_bit0(or3(bt, xor_or(lo32(xr[0]), lo32(xr[1]), tag), xor_or(lo32(xr[2]), lo32(xr[3]), tag)));
                if (PV_FENCE & 2) fz |= clk32();
                stsm4(sb + SM_OX + g16, pack2(oc[0][0], oc[0][1]), pack2(oc[0][2], oc[0][3]), pack2(oc[1][0], oc[1][1]), pack2(oc[1][2], oc[1][3]));
                sts2(sb + SM_LX + g8, lc[0], lc[1]);
            } while (bad);
            PROFV(14, it - 1)
            PROF(5)
            bar_sync(NB_X2, 384);
            const uint8_t* sp = arena + so;
            uint4 sv;
            if (SV_AT != 1) sv = ldg_rlx4(sp);
            auto h_next = [&]() {
                asm volatile("fence.proxy.async.global;" ::: "memory");
                if (s + 3 <= NSEG) h_load(sb, hsrc, s + 3, j, head, wiu);
            };
            if (H_AT == 3) h_next();
            if (!REQ_LATE) request(s + 1, to);
            const uint32_t dz = TPV_DLY ? delay<TPV_DLY>(zero) : 0;
            {
                const uint4 pp = lds4(l16 + SM_PX + dz);
                pv(pp.x, pp.y, pp.z, pp.w, lds1(sb + SM_PX + 512 + ((g16 >> 2) & 0x7c)), [&]() {
                    if (SV_AT) fz |= clk32();
                    if (SV_AT == 1) sv = ldg_rlx4(sp);
                    if (SV_AT == 2) cp_async16(sb + SM_SV + g16, sp);
                });
            }
            const float i0 = rcp_fast(lc[0]), i1 = rcp_fast(lc[1]);
            bar_arrive(NB_WIN + ((__float_as_uint(i0) | fz) & zero), 384);
            if (H_AT == 4) h_next();
            uint8_t* od = (uint8_t*)g_O + ((size_t)s * (32 * NH * DH * 2) + oo);
            const uint32_t ov[4] = {pack2(oc[0][0] * i0, oc[0][1] * i1), pack2(oc[0][2] * i0, oc[0][3] * i1), pack2(oc[1][0] * i0, oc[1][1] * i1), pack2(oc[1][2] * i0, oc[1][3] * i1)};
#pragma unroll
            for (int a = 0; a < 4; a++) if (!O_LATE || s + 1 == NSEG) stg_rlx1(od + a * 128, ov[a]);
            if (REQ_LATE == 1) request(s + 1, to);
            PROF(6)
            if (s + 1 == NSEG) break;
            fetch(s + 1, [&]() {
                int it = 0;
#pragma unroll 1
                while (__any_sync(~0u, (int)(min(__vimin3_u32(sv.x, sv.y, sv.z), sv.w) >> 24) <= s)) {
                    if (SV_AT == 2 && it == 0) { asm volatile("cp.async.wait_all;" ::: "memory"); sv = lds4(sb + SM_SV + g16); }
                    else sv = ldg_rlx4(sp);
                    spin_guard(++it);
                }
                PROFV(15, it)
                const uint32_t tgo = (__reduce_max_sync(~0u, max(max3u(sv.x, sv.y, sv.z), sv.w)) + tm.go + (sv.x & zero)) << 8;
                PROF(7)
                int late;
#pragma unroll 1
                do { late = gtime32() * 8 - tgo; } while (late < 0);
                __syncwarp();
                return (uint32_t)late;
            }, [&](uint32_t z) {
#pragma unroll
                for (int a = 0; a < 4; a++) if (O_LATE) stg_rlx1(od + a * 128, ov[a]);
                if (REQ_LATE == 2) request(s + 1, to + z);
            });
            if (REQ_LATE == 3) request(s + 1, to);
        }
        TL(8) TLC(1)
    }
    asm volatile("cp.async.wait_all;" ::: "memory");
    PROF_OUT
}

struct RecMaps { CUtensorMap wq, wk, wv, wo; };
struct RecPtrs { const bf16 *x, *mem0, *c, *wmod, *w1, *w3; uint8_t* arena; uint32_t zero; const bf16 *w2, *w4, *wo; RecTime tm; };

__device__ __forceinline__ float silu_bf(const bf16* c, int i) {
    const float v = __bfloat162float(c[i]);
    return bfround(__fdividef(v, 1.0f + __expf(-v)));
}
__device__ __noinline__ void rec_ln(float* coef, const RecPtrs& p, int id, int r0) {
    int r1 = 32;
    const int tid = threadIdx.x;
    const int lane = tid & 31, wid = tid >> 5;
    const uint32_t ring = smem_u32(coef) - SM_PRE + wid * 8192 + lane * 16;
    auto rowof = [&](int j) { return (j >> 1) * 64 + (id * 8 + wid) * 2 + (j & 1); };
    auto fetch = [&](int j) {
        if (j < 2 * r1) {
#pragma unroll
            for (int i = 0; i < 4; i++)
                asm volatile("cp.async.cg.shared.global [%0], [%1], 16;" ::"r"(ring + (j & 3) * 2048 + i * 512), "l"(p.x + (size_t)rowof(j) * DM + i * 256 + lane * 8) : "memory");
        }
        asm volatile("cp.async.commit_group;" ::: "memory");
    };
#pragma unroll 1
    for (int j = 2 * r0; j < 2 * r0 + 4; j++) fetch(j);
#pragma unroll 1
    for (int i = tid; i < 2 * DM / 4; i += 256) {
        uint4 v[8];
        int it = 0;
        uint32_t ok;
        do {
            ok = 1;
#pragma unroll
            for (int k = 0; k < 8; k++) v[k] = ldg_rlx4(g_modp + k * 2 * DM + i * 4);
#pragma unroll
            for (int k = 0; k < 8; k++) ok &= v[k].x & v[k].y & v[k].z & v[k].w;
            spin_guard(++it);
        } while (!ok);
        float t[4] = {0, 0, 0, 0};
#pragma unroll
        for (int k = 0; k < 8; k++) { t[0] += __uint_as_float(v[k].x); t[1] += __uint_as_float(v[k].y); t[2] += __uint_as_float(v[k].z); t[3] += __uint_as_float(v[k].w); }
#pragma unroll
        for (int j = 0; j < 4; j++) coef[i * 4 + j] = bfround(t[j]) + (i >= DM / 4 ? 1.0f : 0.0f);
    }
    bar_sync(NB_FIN0, 256);
    if (r0 == 0) {
        int v, it = 0;
#pragma unroll 1
        do { v = *(volatile int*)((uint8_t*)coef - SM_PRE + SM_BAR + 192); spin_guard(++it); } while (v == INT_MIN);
        if (v >= 0) r1 = 2;
    }
    if (tid == 0 && r0 == 0) TL(2)
#pragma unroll 1
    for (int j = 2 * r0 + 1; j < 2 * r1; j += 2) {
        float x[2][32];
        asm volatile("cp.async.wait_group 2;" ::: "memory");
#pragma unroll
        for (int i = 0; i < 8; i++) {
            const uint4 v = lds4(ring + (j & 2) * 2048 + i * 512);
            float* d = x[i >> 2] + (i & 3) * 8;
            d[0] = bflo(v.x); d[1] = bfhi(v.x); d[2] = bflo(v.y); d[3] = bfhi(v.y); d[4] = bflo(v.z); d[5] = bfhi(v.z); d[6] = bflo(v.w); d[7] = bfhi(v.w);
        }
        const int row = rowof(j - 1);
        ln_rows(x);
        fetch(j + 3);
        fetch(j + 4);
#pragma unroll
        for (int i = 0; i < 4; i++) {
            const float4* cf = (const float4*)(coef + i * 256 + lane * 8);
            const float4 s0 = cf[0], s1 = cf[1], c0 = cf[256], c1 = cf[257];
            const float sh[8] = {s0.x, s0.y, s0.z, s0.w, s1.x, s1.y, s1.z, s1.w}, sc[8] = {c0.x, c0.y, c0.z, c0.w, c1.x, c1.y, c1.z, c1.w};
            const int own = ((row >> 4) & 1) == (i >> 1), c16 = i * 32 + lane;
#pragma unroll
            for (int h = 0; h < 2; h++) {
                float y[8];
#pragma unroll
                for (int e = 0; e < 8; e++) y[e] = fmaf(x[h][i * 8 + e], sc[e], sh[e]);
                const int rr = (row & 15) + h;
                const uint32_t off = ((row >> 5) + own) * 65536 + (c16 >> 3) * 4096 + (rr + (own ? 0 : 16)) * 128 + (((c16 & 7) ^ (rr & 7)) << 4);
                *(uint4*)((uint8_t*)g_himg + off) = pack8(y);
            }
        }
        if ((j & 3) != 3) continue;
        bar_sync(j == 3 ? NB_C : NB_LN, j == 3 ? 320 : 288);
        if (wid == 0 && j == 3) {
            bar_arrive(NB_B, 64);
            if (lane == 0) { signal_count(&g_tick[32 + id * 8]); TL(13) }
            __syncwarp();
        }
    }
}
template <int NQ, int CG>
__device__ __forceinline__ void side_gemv(const bf16* w, int ld, int ncol, const float* coef, float* red, float* out, int ostride, bool round) {
    constexpr int KG = 384 / CG, W = CG * 8;
    const int tid = threadIdx.x, cg = tid % CG, kg = tid / CG;
    float acc[NQ][8];
#pragma unroll
    for (int q = 0; q < NQ; q++)
#pragma unroll
        for (int j = 0; j < 8; j++) acc[q][j] = 0.f;
    if (cg * 8 < ncol) {
        const bf16* src = w + cg * 8;
        const uint32_t ring = smem_u32(red) + 36864 + tid * 16;
        auto fetch = [&](int k0, int slot) {
#pragma unroll
            for (int i = 0; i < 4; i++)
                if (k0 + i * KG < DM) cp_async16(ring + (slot * 4 + i) * 6144, src + (size_t)(k0 + i * KG) * ld);
            asm volatile("cp.async.commit_group;" ::: "memory");
        };
#pragma unroll 1
        for (int g = 0; g < 5; g++) fetch(kg + g * 4 * KG, g);
#pragma unroll 1
        for (int k0 = kg, slot = 0; k0 < DM; k0 += 4 * KG) {
            fetch(k0 + 20 * KG, slot ? slot - 1 : 5);
            asm volatile("cp.async.wait_group 5;" ::: "memory");
#pragma unroll
            for (int i = 0; i < 4; i++) {
                const int k = k0 + i * KG;
                if (k < DM) {
                    const uint4 v = lds4(ring + (slot * 4 + i) * 6144);
                    const float f[8] = {bflo(v.x), bfhi(v.x), bflo(v.y), bfhi(v.y), bflo(v.z), bfhi(v.z), bflo(v.w), bfhi(v.w)};
#pragma unroll
                    for (int q = 0; q < NQ; q++) {
                        const float cf = coef[q * DM + k];
#pragma unroll
                        for (int j = 0; j < 8; j++) acc[q][j] = fmaf(cf, f[j], acc[q][j]);
                    }
                }
            }
            slot = slot == 5 ? 0 : slot + 1;
        }
    }
    __syncthreads();
#pragma unroll
    for (int q = 0; q < NQ; q++)
#pragma unroll
        for (int j = 0; j < 8; j++) red[(kg * NQ + q) * W + cg * 8 + j] = acc[q][j];
    __syncthreads();
#pragma unroll 1
    for (int i = tid; i < NQ * W; i += 384) {
        const int q = i / W, cidx = i % W;
        float t = 0.f;
#pragma unroll
        for (int k = 0; k < KG; k++) t += red[k * NQ * W + i];
        if (cidx < ncol) out[q * ostride + cidx] = round ? bfround(t) : t;
    }
}
__device__ __forceinline__ void side_window(const RecPtrs& p, int& step) {
    uint32_t v;
    int it = 0;
#pragma unroll 1
    do { v = ldg_rlx1(p.arena + blk(LB_STAMP, 0)); spin_guard(++it); } while ((int)(v >> 24) <= step && step < NSEG);
    step = v >> 24;
#pragma unroll 1
    while ((int)(gtime32() * 8 - ((v + p.tm.go + SW_T) << 8)) < 0) {}
    __syncwarp();
}
__device__ __noinline__ void side_prefetch(const RecPtrs& p, int& step, const void* base, uint32_t ld, uint32_t bytes, int rows, int per) {
#pragma unroll 1
    for (int r = threadIdx.x & 127, n = 0; r < rows; r += 128, n++) {
        if (n % per == 0) side_window(p, step);
        l2_prefetch((const uint8_t*)base + (size_t)r * ld, bytes);
    }
}
__device__ __noinline__ void rec_side(float* sm, const RecPtrs& p, int id) {
    const int tid = threadIdx.x;
    float *coef = sm, *red = sm + 3 * DM;
    if (tid < 256 && blockIdx.x < 128) rec_ln(sm + SM_PRE / 4, p, id, 2);
    if (tid >> 5 == 8) {
#pragma unroll 1
        for (int n = 1; n < 16; n++) {
            bar_sync(NB_LN, 288);
            if (tid == 256) { if (n == 1) wait_count1(&g_tick[32 + id * 8], 1); signal_count(&g_tick[32 + id * 8]); }
            __syncwarp();
        }
    }
    int step = 0;
    if (SGATE && tid >= 256) {
        wait_count_w(&g_tick[32 + (tid & 3) * 8], 1);
        side_prefetch(p, step, p.x + id * 256, DM * 2, 512, S_, 8 * SW_N);
        side_prefetch(p, step, p.wmod + (2 + id) * DM, 6 * DM * 2, 2048, DM, SW_N);
        side_prefetch(p, step, p.w3 + id * (FF / 4), FF * 2, FF / 2, DM, SW_N);
        side_prefetch(p, step, p.w1 + id * 256, DM * 2, 512, DM, 4 * SW_N);
    }
    __syncthreads();
    for (int i = tid; i < 2 * S_; i += 384) g_st[id * 2 * S_ + i] = 0.f;
    if (id == 0) for (int i = tid; i < 2 * 32; i += 384) g_pcnt[i * 8] = 0;
    if (id == 1) for (int i = tid; i < 5 * 256; i += 384) g_pflag[i] = 0;
    for (int i = tid; i < DM; i += 384) { coef[i] = silu_bf(p.c, i); coef[2 * DM + i] = 1.0f; }
    __syncthreads();
    if (tid == 0) TL(3)
    side_gemv<1, 128>(p.wmod + (2 + id) * DM, 6 * DM, DM, coef, red, g_mod + (2 + id) * DM, 0, true);
    __syncthreads();
    if (tid == 0) signal_count(&g_tick[8]);
    if (tid == 0) TL(4)
    side_gemv<1, 128>(p.w3 + id * (FF / 4), FF, FF / 4, coef + 2 * DM, red, g_vec + 3 * DM + id * (FF / 4), 0, false);
    if (tid == 0) wait_count1(&g_tick[8], 4);
    __syncthreads();
    for (int i = tid; i < DM; i += 384) { coef[i] = 1.0f + __ldcg(g_mod + 4 * DM + i); coef[DM + i] = __ldcg(g_mod + 3 * DM + i); }
    __syncthreads();
    if (id == 1 && tid < 32) {
        float t[5] = {0, 0, 0, 0, 0};
        for (int i = tid; i < DM; i += 32) {
            const float a = coef[i], b = coef[DM + i];
            t[0] += a; t[1] += a * a; t[2] += a * b; t[3] += b; t[4] += b * b;
        }
#pragma unroll
        for (int q = 0; q < 5; q++) { const float r = warp_sum(t[q]); if (tid == 0) g_cst[q] = r * (1.0f / DM); }
    }
    side_gemv<3, 32>(p.w1 + id * 256, DM, 256, coef, red, g_vec + id * 256, DM, false);
    if (tid == 0) TL(9)
    if (SGATE) {
        if (tid < 256) return;
        step = max(step, SW_END);
        if (SPF & 32) side_prefetch(p, step, p.x + id * 512 * DM, 2048, 2048, 512, SW_N);
        if (SPF & 2) side_prefetch(p, step, p.w1 + id * 256 * DM, 2048, 2048, 256, SW_N);
        if (SPF & 4) side_prefetch(p, step, p.w2 + id * 256 * DM, 2048, 2048, 256, SW_N);
        if (SPF & 1) side_prefetch(p, step, p.wo + id * 1024 * DM, 2048, 2048, 1024, SW_N);
        return;
    }
#pragma unroll 1
    for (int m = 0; m < 6; m++) {
        if (!((SPF >> m) & 1)) continue;
        const uint8_t* w = (const uint8_t*)(m == 0 ? p.wo : m == 1 ? p.w1 : m == 2 ? p.w2 : m == 3 ? p.w3 : m == 4 ? p.w4 : p.x);
        const int n = (m == 0 ? 4096 : m < 3 ? 1024 : m == 5 ? 2048 : FF) * 2048 / 4;
#pragma unroll 1
        for (int o = tid * 128; o < n; o += 384 * 128) {
            asm volatile("prefetch.global.L2 [%0];" ::"l"(w + id * n + o));
            __nanosleep(SPF_NS);
        }
    }
    if (tid == 0) TL(5)
}

__global__ void __cluster_dims__(2, 1, 1) __launch_bounds__(384, 1)
k_rec(const __grid_constant__ RecMaps mp, const __grid_constant__ RecPtrs p) {
    extern __shared__ uint8_t smraw[];
    const uint32_t sb = smem_u32(smraw);
    if ((sb & 0x3FFFF) != SB0) __trap();
    const uint32_t bars = sb + SM_BAR;
    const int tid = threadIdx.x, lane = tid & 31, b = blockIdx.x;
    const int wid = __reduce_max_sync(~0u, tid >> 5);
    const uint32_t rank = b & 1;
    uint8_t* arena = p.arena;
    volatile int* sinfo = (volatile int*)(smraw + SM_BAR + 192);
    if (tid == 0) TL(0)
    if (tid == 0) sinfo[0] = INT_MIN;
    if (tid == 352) {
        for (int i = 0; i < 17; i++) mbar_init(bars + 8 * i, i == B_WO ? 4 : 1);
        asm volatile("fence.mbarrier_init.release.cluster;" ::: "memory");
        mbar_expect(bars + 8 * B_ROLE, 8);

    }
    __syncwarp();
    asm volatile("barrier.cluster.arrive.relaxed.aligned;" ::: "memory");
    int pr = 0, hA = 0;
    if (wid < 8) {
        if (b < 128) {
            const int cb = (b & 15) * 128, k0 = (b >> 4) * 128 + (tid >> 4);
            uint4 v[8];
#pragma unroll
            for (int i = 0; i < 8; i++) v[i] = __ldg((const uint4*)(p.wmod + (size_t)(k0 + 16 * i) * (6 * DM) + cb + (tid & 15) * 8));
            float acc[8] = {0, 0, 0, 0, 0, 0, 0, 0};
#pragma unroll
            for (int i = 0; i < 8; i++) {
                const float sv = silu_bf(p.c, k0 + 16 * i);
                acc[0] += sv * bflo(v[i].x); acc[1] += sv * bfhi(v[i].x); acc[2] += sv * bflo(v[i].y); acc[3] += sv * bfhi(v[i].y);
                acc[4] += sv * bflo(v[i].z); acc[5] += sv * bfhi(v[i].z); acc[6] += sv * bflo(v[i].w); acc[7] += sv * bfhi(v[i].w);
            }
            float* red = (float*)(smraw + SM_PRE);
            *(float4*)(red + (tid >> 4) * 128 + (tid & 15) * 8) = make_float4(acc[0], acc[1], acc[2], acc[3]);
            *(float4*)(red + (tid >> 4) * 128 + (tid & 15) * 8 + 4) = make_float4(acc[4], acc[5], acc[6], acc[7]);
            bar_sync(NB_FIN0, 256);
            if (wid < 4) {
                float t = 0;
#pragma unroll
                for (int i = 0; i < 16; i++) t += red[i * 128 + tid];
                stg_rlx1(&g_modp[(b >> 4) * 2 * DM + cb + tid], __float_as_uint(t) | 1u);
            }
        } else {
            rec_ln((float*)(smraw + SM_PRE), p, b - 128, 0);
        }
    } else if (wid >= 10 && b >= 128) {
        {
            const int u = (b - 128) * 2 + wid - 10;
            const uint16_t* src = (const uint16_t*)p.mem0 + (lane & 3) * 2 * DM + (u >> 1) * 128 + (u & 1) * 32 + (lane >> 2);
            uint32_t w[16];
#pragma unroll
            for (int r = 0; r < 16; r++) {
                const uint16_t* q = src + (r >> 3) * 512 + ((r >> 2) & 1) * 16 + (r & 2) * 32 + (r & 1) * 8;
                w[r] = pack_h2(bflo(q[0]), bflo(q[DM]));
            }
            stg_rlx4(arena + (LB_STAMP << 13) + u * 2048 + (lane >> 4) * 1024 + ((lane >> 3) & 1) * 256 + (lane & 7) * 16, 0, 0, 0, 0);
#pragma unroll 1
            for (int i = 0; i < 3; i++) {
#pragma unroll
                for (int r = 0; r < 4; r++) {
                    uint8_t* d = arena + acc_slot(i) + acc_piece(r >> 1, u >> 1, (u & 1) * 2 + (r & 1));
                    const uint32_t k = i ? 0u : ~0u, w3 = w[4 * r + 3];
                    stg_rlx4(d + lane * 16, w[4 * r] & k, w[4 * r + 1] & k, w[4 * r + 2] & k, __byte_perm(w3, ACC_ALL, (lane & 7) == 7 ? 0x7610 : 0x3210) & k);
                    const uint32_t x = __shfl_sync(~0u, __byte_perm(w3, ACC_ALL, 0x7632), lane * 8 + 7);
                    if (lane < 8) stg_rlx1(d + 512 + lane * 4, x & k);
                }
            }
            bar_arrive(NB_C, 320);
        }
    } else if (rank == 0) {
        uint32_t best = ~0u;
        const int pg = wid < 10 ? 0 : 1 + (b >> 1) % 3;
        uint32_t* q = (uint32_t*)(arena + (pg << 21) + (pg ? blk(b >> 1, wid & 1) : blk(LB_PROBE, wid & 1) + b * 16));
        if (lane < 8) stg_rlx1(q + lane, 0);
        uint2 tk2 = ldg_rlx2(&g_tick[0]);
        __syncwarp();
        if (lane == 0) {
            q += 3;
            uint32_t v = atomicAdd(q, 1u);
#pragma unroll 1
            for (int r = 0; r < NPROBE; r++) {
                const uint32_t t0 = clk32() + (v >> 8);
                v = atomicAdd(q + (v >> 8), 1u);
                uint32_t t1;
                asm volatile("{.reg .pred p; setp.eq.u32 p, %1, 0xffffffff; @p exit; mov.u32 %0, %%clock;}" : "=r"(t1) : "r"(v) : "memory");
                best = min(best, t1 - t0);
            }
            sinfo[wid - 6] = best;
        }
        bar_sync(NB_KDONE, b < 128 ? 128 : 64);
        if (wid == 8) {
            const int par = sinfo[2] <= sinfo[3] ? 0 : 1, ncl = gridDim.x >> 1;
            int tk = 0, it = 0;
            const uint32_t vote = b < 128 && (sinfo[4] <= sinfo[5] ? 0 : 1) != par ? 256u << (8 * ((b >> 1) % 3)) : 0u;
            if (b >= 128) {
#pragma unroll 1
                while (!__all_sync(~0u, (int)((tk2.x + tk2.y) & 255) >= ncl - 2)) { tk2 = ldg_rlx2(&g_tick[0]); spin_guard(++it); }
            }
            if (lane == 0) tk = atomicAdd(&g_tick[par], 1u + vote) & 255;
#pragma unroll 1
            while (!__all_sync(~0u, (int)((tk2.x + tk2.y) & 255) >= ncl)) { tk2 = ldg_rlx2(&g_tick[0]); spin_guard(++it); }
            tk = __shfl_sync(~0u, tk, 0);
            const int n0 = tk2.x & 255, n1 = tk2.y & 255;
            hA = min(n0 >> 1, NH);
            const int q0 = 2 * hA, q1 = 2 * NH - q0;
            const int over = tk - (par ? q1 : q0), lack = max(par ? q0 - n0 : q1 - n1, 0);
            if (over < 0) pr = par ? q0 + tk : tk;
            else if (over < lack) pr = (par ? n0 : q0 + n1) + over;
            else pr = -1 - (over - lack + (par ? max(n0 - q0, 0) : 0));
#pragma unroll
            for (int i = 0; i < 3; i++) hA |= (((tk2.x + tk2.y) >> (8 + 8 * i)) & 255) > 10 ? 256 << i : 0;
        }
    }
    asm volatile("barrier.cluster.wait.aligned;" ::: "memory");
    if (wid == 8) {
        if (rank == 0) {
            if (lane == 0) {
                uint32_t rsb;
                asm("mapa.shared::cluster.u32 %0, %1, 1;" : "=r"(rsb) : "r"(sb));
                asm volatile("st.async.shared::cluster.mbarrier::complete_tx::bytes.v2.u32 [%0], {%1, %2}, [%3];"
                             ::"r"(rsb + SM_BAR + 192), "r"(pr), "r"(hA), "r"(rsb + SM_BAR + 8 * B_ROLE) : "memory");
                sinfo[0] = pr; sinfo[1] = hA;
                if (b >= 128) atomicOr(&g_tick[4], (pr < 0 ? 4u : 1u) << ((b - 128) >> 1));
            }
        } else {
            mbar_wait_w(bars + 8 * B_ROLE, 0);
            pr = sinfo[0];
        }
        TL(1)
        __syncwarp();
        bar_arrive(NB_A, 384);
        if (b >= 128 && pr < 0) bar_sync(NB_B, 64);
        if (pr >= 0) {
            const int pu = __reduce_max_sync(~0u, pr), c0 = (pu >> 1) * 128 + rank * 64, r0 = (pu & 1) * 512;
            bool fast = false;
#pragma unroll 1
            for (int n = 0; n < 12; n++) {
                const int rot = b >= 128 ? 8 : 0, i = (n + rot) % 12;
                if (rot && n == 4) bar_sync(NB_B, 64);
                if (n >= W_INFL && !fast) {
                    const uint32_t v = ldg_rlx1(&g_tick[32 + (lane & 3) * 8]);
                    mbar_wait_w(bars + 8 * (B_W + (n - W_INFL + rot) % 12), 0);
                    fast = __all_sync(~0u, v != 0);
                }
                const int m = i < 8 ? i & 1 : 2, k = i < 8 ? i >> 1 : i - 8;
                const uint32_t dst = sb + m * 65536 + k * 16384, br = bars + 8 * (B_W + i);
                if (lane == 0) {
                    mbar_expect(br, 16384);
                    tma2d(dst, &mp.wq + m, c0, r0 + k * 128, br);
                    tma2d(dst + 8192, &mp.wq + m, c0, r0 + k * 128 + 64, br);
                }
                __syncwarp();
            }
        }
    } else {
        bar_sync(NB_A, 384);
    }
    const int prr = __reduce_max_sync(~0u, sinfo[0]);
    hA = __reduce_max_sync(~0u, sinfo[1]);
    if (prr < 0) {
        int j = (b - 128) >> 1;
        if (b < 128) {
            uint32_t v;
            int it = 0;
#pragma unroll 1
            do { v = __reduce_max_sync(~0u, ldg_rlx1(&g_tick[4])); spin_guard(++it); } while (__popc(v) < 2);
            j = v == 3 ? -1 - prr : (v & 1) ^ 1;
        }
        rec_side((float*)smraw, p, j * 2 + rank);
        return;
    }
    const int role = (prr >> 1) * 4 + rank * 2 + (prr & 1);
    rec_main(sb, &mp.wo, arena, role, hA, wid >> 2, p.zero, p.tm);
}

__device__ __forceinline__ void wgmma_ss192(float* d, uint64_t a, uint64_t b, int sc) {
    asm volatile("{.reg .pred p; setp.ne.b32 p, %98, 0;\n wgmma.mma_async.sync.aligned.m64n192k16.f32.bf16.bf16 "
                 "{%0,%1,%2,%3,%4,%5,%6,%7,%8,%9,%10,%11,%12,%13,%14,%15,%16,%17,%18,%19,%20,%21,%22,%23,%24,%25,%26,%27,%28,%29,%30,%31,%32,%33,%34,%35,%36,%37,%38,%39,%40,%41,%42,%43,%44,%45,%46,%47,%48,%49,%50,%51,%52,%53,%54,%55,%56,%57,%58,%59,%60,%61,%62,%63,%64,%65,%66,%67,%68,%69,%70,%71,%72,%73,%74,%75,%76,%77,%78,%79,%80,%81,%82,%83,%84,%85,%86,%87,%88,%89,%90,%91,%92,%93,%94,%95}, %96, %97, p, 1, 1, 0, 1;}"
                 : F16(d, 0), F16(d, 16), F16(d, 32), F16(d, 48), F16(d, 64), F16(d, 80) : "l"(a), "l"(b), "r"(sc));
}
__device__ __forceinline__ void wgmma_ss256(float* d, uint64_t a, uint64_t b, int sc) {
    asm volatile("{.reg .pred p; setp.ne.b32 p, %130, 0;\n wgmma.mma_async.sync.aligned.m64n256k16.f32.bf16.bf16 "
                 "{%0,%1,%2,%3,%4,%5,%6,%7,%8,%9,%10,%11,%12,%13,%14,%15,%16,%17,%18,%19,%20,%21,%22,%23,%24,%25,%26,%27,%28,%29,%30,%31,%32,%33,%34,%35,%36,%37,%38,%39,%40,%41,%42,%43,%44,%45,%46,%47,%48,%49,%50,%51,%52,%53,%54,%55,%56,%57,%58,%59,%60,%61,%62,%63,%64,%65,%66,%67,%68,%69,%70,%71,%72,%73,%74,%75,%76,%77,%78,%79,%80,%81,%82,%83,%84,%85,%86,%87,%88,%89,%90,%91,%92,%93,%94,%95,%96,%97,%98,%99,%100,%101,%102,%103,%104,%105,%106,%107,%108,%109,%110,%111,%112,%113,%114,%115,%116,%117,%118,%119,%120,%121,%122,%123,%124,%125,%126,%127}, %128, %129, p, 1, 1, 0, 1;}"
                 : F16(d, 0), F16(d, 16), F16(d, 32), F16(d, 48), F16(d, 64), F16(d, 80), F16(d, 96), F16(d, 112) : "l"(a), "l"(b), "r"(sc));
}

constexpr uint32_t P_VEC = 212992, P_ROW = P_VEC + 6144, P_BAR = P_ROW + 4096, P_SMEM = P_BAR + 256;
constexpr uint32_t P_OUT = 180224, P_OUT3 = 147456, P_OUT4 = 163840;
#define PPH 1
#define FLAG_ST "st.release.gpu.global.u32"
#define FLAG_LD "ld.acquire.gpu.global.u32"
#define BA3 2
#define BA 5
#define BA0 1
constexpr int P_SA = 5, P_SB = 3;
constexpr int PB_FA = 0, PB_EA = 5, PB_FB = 10, PB_EB = 13, PB_OUT = 16;
enum { C_Y = 0, C_G = 1, C_X1 = 2, C_U = 3, C_S1 = 8, C_S3 = 9 };
enum { V_GA = 0, V_A = 1, V_B = 2, V_GB = 3, V_VA = 4, V_VB = 5, V_VC = 6, V_C3 = 7 };
struct PostMaps { CUtensorMap o, wo, y, w1, g, w2, x1, w3, u, w4, out; };
struct PostPtrs { const bf16* x; };

struct GeluK { float k0, k1, kh; };
__device__ __forceinline__ GeluK gelu_k(float c) { return {0.7978845608028654f * c, 0.7978845608028654f * 0.044715f * c * c * c, 0.5f * c}; }
__device__ __forceinline__ float gelu_s(float t, const GeluK& k) {
    const float u = t * fmaf(t * t, k.k1, k.k0);
    float th; asm("tanh.approx.f32 %0, %1;" : "=f"(th) : "f"(u));
    const float hx = k.kh * t;
    return fmaf(hx, th, hx);
}
__device__ __forceinline__ float2 ldsv(uint32_t a) {
    float2 v; asm("ld.shared.v2.f32 {%0,%1}, [%2];" : "=f"(v.x), "=f"(v.y) : "r"(a)); return v;
}
__device__ __forceinline__ void wait_smem(uint32_t a, int target) {
    int it = 0;
#pragma unroll 1
    while (true) {
        int v;
        asm volatile("ld.acquire.cta.shared.u32 %0, [%1];" : "=r"(v) : "r"(a) : "memory");
        if (__all_sync(~0u, v >= target)) break;
        spin_guard(++it);
    }
}

#define PP(i)
#define PH_(c, w, i)
struct Pipe { int st, ph; };
template <int ST> __device__ __forceinline__ void adv(Pipe& p) { if (++p.st == ST) { p.st = 0; p.ph ^= 1; } }

__device__ __forceinline__ void post_produce(uint32_t sb, const PostMaps& mp, int mb, int nb, int rank) {
    const int rh = 2 * mb + rank, lane = threadIdx.x & 31;
    int st = 0, pp = 0, st2 = 0, pp2 = 0;
#pragma unroll 1
    for (int ph = 0; ph < 7; ph++) {
        const bool W = ph == 3 || ph == 4;
        if (ph == 3 || ph >= 5) {
            const int n = ph == 5 ? P_SB : P_SA;
            const uint32_t e = sb + P_BAR + 8 * (ph == 5 ? PB_EB : PB_EA);
#pragma unroll 1
            for (int i = 0; i < n; i++) mbar_wait_w(e + 8 * i, pp ^ (i >= st));
            if (ph == 6) break;
            if (ph == 5) wait_smem(sb + P_BAR + 8 * (PB_OUT + (lane & 1)), 4);
            int t = st; st = st2; st2 = t; t = pp; pp = pp2; pp2 = t;
        }
        const int ST = W ? P_SB : P_SA, NK = ph == 0 ? 64 : ph == 5 ? 56 : 16, NB = ph == 3 ? 4 : ph == 4 ? 3 : 2;
        const uint32_t SBYTES = W ? 49152 : 32768;
        const uint32_t full = sb + P_BAR + 8 * (W ? PB_FB : PB_FA), empty = sb + P_BAR + 8 * (W ? PB_EB : PB_EA);
        const CUtensorMap* ta = &mp.o + 2 * (ph > 3 ? ph - 1 : ph);
        const CUtensorMap* tb = ta + 1;
        const int n0 = ph == 3 ? nb * 256 : ph == 4 ? 2048 + nb * 192 : nb * 128;
        const int amul = ph == 0 ? 256 : 64, arow = ph == 0 ? rh * 8 : rh * 64;
        const uint32_t shifts = ph == 2 ? 0x04000301u : 0x02020202u;
        const uint32_t* fl = &g_pflag[(ph == 5 ? C_U + ((lane >> 3) & 1) : ph - 1) * 256 + (ph == 2 ? min(max(rh + min(lane >> 3, 2) - 1, 0), 31) : rh) * 8 + (lane & 7)];
        uint32_t have = ph == 0 || ph == 4 ? 9 : 0;
        auto order = [&](int i, int& need, int& grp) {
            need = 0; grp = i & 1;
            if (ph == 5) {
                const int q = i < 32 ? i >> 2 : ((i - 32) * 43) >> 7, src = (q + (nb & 6)) & 7;
                need = (i < 32 ? 1 : 256) << src; grp = i < 32 ? i & 3 : i - 32 - 3 * q;
                return i + (src - q) * (i < 32 ? 4 : 3);
            }
            if (ph == 0) return i;
            const int kb = (i + 2 * (nb & 6)) & 15;
            need = (ph == 2 ? 0x10101 : 1) << (kb >> 1);
            return kb;
        };
        PH_(ph == PPH, 0, 26) PH_(ph == PPH, 1, 26)
        int ib = 0, sB = st, pB = pp;
#pragma unroll 1
        for (int i = 0; i < NK; i++) {
            int need, grp;
#pragma unroll 1
            for (const int lim = i || ph > 3 ? i + 1 : ph == 3 ? BA3 : ph ? BA : BA0; ib < lim; ib++) {
                const int kb = order(ib, need, grp);
                const uint32_t a = sb + sB * SBYTES, f = full + 8 * sB;
                mbar_wait_w(empty + 8 * sB, pB ^ 1);
                e_expect(f, 16384 + NB * 8192);
                e_tma2d(a + 16384, tb, n0, kb * 64, f);
                e_tma2d(a + 24576, tb, n0 + 64, kb * 64, f);
                if (W) { e_tma2d(a + 32768, tb, n0 + 128, kb * 64, f); if (ph == 3) e_tma2d(a + 40960, tb, n0 + 192, kb * 64, f); }
                if (++sB == ST) { sB = 0; pB ^= 1; }
            }
            const int kb = order(i, need, grp);
            PH_(ph == PPH && i == 0, 0, 27) PH_(ph == PPH && i == 0, 1, 27)
            if (ph == 0 && i == 0) {
                asm volatile("barrier.cluster.wait.aligned;" ::: "memory");
                PH_(PPH == 0, 0, 25) PH_(PPH == 0, 1, 25)
            }
            if ((__ballot_sync(~0u, have > grp) & need) != need) {
                int it = 0;
#pragma unroll 1
                do {
                    asm volatile(FLAG_LD " %0, [%1];" : "=r"(have) : "l"(fl) : "memory");
                    spin_guard(++it);
                } while ((__ballot_sync(~0u, have > grp) & need) != need);
                PH_(ph == PPH && i == 0, 0, 23) PH_(ph == PPH, 0, 24) PH_(ph == PPH && i == 0, 1, 23) PH_(ph == PPH, 1, 24)
                asm volatile("fence.proxy.async.global;" ::: "memory");
                PH_(ph == PPH && i == 0, 0, 25) PH_(ph == PPH && i == 0, 1, 25)
            }
            e_tma2d_mc(sb + st * SBYTES + rank * 8192, ta, kb * amul, arow + (int)((shifts >> ((kb & 12) * 2)) & 7) - 2, full + 8 * st);
            if (++st == ST) { st = 0; pp ^= 1; }
        }
    }
}

template <int PH>
__device__ __forceinline__ void post_mma(uint32_t sb, float* acc, Pipe& p, int wg, bool lead, int pi) {
    constexpr bool W = PH == 3 || PH == 4;
    constexpr int ST = W ? P_SB : P_SA, SBYTES = W ? 49152 : 32768, NK = PH == 0 ? 64 : PH == 5 ? 56 : 16;
    const uint32_t full = sb + P_BAR + 8 * (W ? PB_FB : PB_FA), empty = sb + P_BAR + 8 * (W ? PB_EB : PB_EA);
    constexpr uint64_t DA = PH == 0 ? mkdesc(SB0, 128, 1024, 0) : mkdesc(SB0, 16, 1024, 1);
    constexpr uint64_t DB = mkdesc(SB0 + 16384, 8192, 1024, 1);
    auto release = [&](int st) { if (lead) { mbar_arrive_cluster(empty + 8 * st, 0); mbar_arrive_cluster(empty + 8 * st, 1); } };
    int prev = 0;
#pragma unroll 1
    for (int kb = 0; kb < NK; kb++) {
        mbar_wait_w(full + 8 * p.st, p.ph);
        const uint32_t so = p.st * (SBYTES >> 4);
        const uint32_t a = (uint32_t)DA + so + wg * 512, b = (uint32_t)DB + so;
        wg_fence();
#pragma unroll
        for (int k = 0; k < 4; k++) {
            const uint64_t da = (DA & 0xffffffff00000000ull) | (a + k * (PH == 0 ? 16 : 2)), db = (DB & 0xffffffff00000000ull) | (b + k * 128);
            if (PH == 3) wgmma_ss256(acc, da, db, (kb | k) != 0);
            else if (PH == 4) wgmma_ss192(acc, da, db, (kb | k) != 0);
            else wgmma_ss128<PH == 0>(acc, da, db, (kb | k) != 0);
        }
        wg_commit();
        if (kb == 0) { PP(pi) if (PH == 0 && wg == 0) TL(11) }
        wg_wait<1>();
        if (kb > 0) release(prev);
        prev = p.st;
        adv<ST>(p);
    }
    wg_wait<0>();
    release(prev);
    PP(pi + 1)
}

__global__ void __cluster_dims__(2, 1, 1) __launch_bounds__(384, 1)
k_post(const __grid_constant__ PostMaps mp, const __grid_constant__ PostPtrs pp) {
    extern __shared__ uint8_t smraw[];
    const uint32_t sb = smem_u32(smraw);
    if ((sb & 0x3FFFF) != SB0) __trap();
    const int tid = threadIdx.x, lane = tid & 31;
    const int mb = blockIdx.x >> 3, nb = blockIdx.x & 7, rank = blockIdx.x & 1;
    const uint32_t bars = sb + P_BAR;
    if (tid < PB_OUT) {
        mbar_init(bars + 8 * tid, (tid >= PB_EA && tid < PB_FB) || tid >= PB_EB ? 4 : 1);
        asm volatile("fence.mbarrier_init.release.cluster;" ::: "memory");
    }
    if (tid == 32) sts4(bars + 8 * PB_OUT, 0, 0, 0, 0);
    if (tid >= 256 && tid < 267) asm volatile("prefetch.tensormap [%0];" ::"l"(&mp.o + (tid - 256)) : "memory");
    __syncthreads();
    asm volatile("barrier.cluster.arrive.aligned;" ::: "memory");
    if (tid < 256 || tid >= 288) asm volatile("barrier.cluster.wait.aligned;" ::: "memory");
    if (tid >= 256) {
        asm volatile("setmaxnreg.dec.sync.aligned.u32 40;");
        const int w = __reduce_max_sync(~0u, (tid >> 5) - 8);
        if (w == 0) {
            post_produce(sb, mp, mb, nb, rank);
        } else if (w < 3) {
            const int wg = w - 1, rh = 2 * mb + wg;
            float* rowc = (float*)(smraw + P_ROW) + (wg * 64 + lane * 2) * 8;
            int nout = 0, sig = 0;
#pragma unroll 1
            for (int i = 0; i < 8; i++) {
                const int cnt = (0x54392180u >> (4 * i)) & 15;
                if (cnt < C_S1) {
                    const int ng = cnt == 3 ? 4 : cnt == 4 ? 3 : 2, c0 = cnt == 3 ? nb * 256 : cnt == 4 ? 2048 + nb * 192 : nb * 128;
                    const uint32_t src = sb + (cnt == 3 ? P_OUT3 : cnt == 4 ? P_OUT4 : P_OUT) + wg * ng * 8192;
                    uint32_t* fl = &g_pflag[cnt * 256 + rh * 8 + nb];
#pragma unroll 1
                    for (int j = 0; j < ng; j++) {
                        bar_sync(4 + 4 * wg + (sig++ & 3), 160);
                        if (lane == 0) {
                            PH_(cnt == PPH - 1, wg, 20)
                            asm volatile("cp.async.bulk.tensor.2d.global.shared::cta.bulk_group [%0, {%2, %3}], [%1]; cp.async.bulk.commit_group;"
                                         ::"l"(&mp.y + 2 * (cnt > 3 ? cnt - 1 : cnt)), "r"(src + j * 8192), "r"(c0 + j * 64), "r"(rh * 64) : "memory");
                        }
                        __syncwarp();
                    }
                    if (lane == 0) {
                        asm volatile("cp.async.bulk.wait_group 0; fence.proxy.async.global;" ::: "memory");
                        PH_(cnt == PPH - 1, wg, 21)
                        asm volatile(FLAG_ST " [%0], %1;" ::"l"(fl), "r"(ng) : "memory");
                        PH_(cnt == PPH - 1, wg, 22)
                        asm volatile("st.release.cta.shared.u32 [%0], %1;" ::"r"(bars + 8 * (PB_OUT + wg)), "r"(nout + 1) : "memory");
                    }
                    nout++;
                    __syncwarp();
                    continue;
                }
                bar_sync(4 + 4 * wg + (sig++ & 3), 160);
                uint32_t* c = &g_pcnt[(cnt - C_S1) * 256 + rh * 8];
                if (lane == 0) { signal_count(c); wait_count1(c, 8); }
                __syncwarp();
                const float4* sp = (const float4*)g_st + rh * 32 + lane;
                float4 u[3] = {__ldcg(sp + (cnt == C_S1 ? 0 : 3) * (S_ / 2)), __ldcg(sp + S_ / 2), __ldcg(sp + S_)};
#pragma unroll 1
                for (int h = 0; h < 2; h++) {
                    const float id = 1.0f / DM;
                    const float m = u[0].x * id, var = fmaxf(u[0].y * id - m * m, 0.f) + 1e-5f, r = rsqrtf(var);
                    float sc = r, m2 = 0.f;
                    if (cnt == C_S1) {
                        m2 = r * (u[1].x * id - m * g_cst[0]) + g_cst[3];
                        const float e2 = r * r * (u[2].x * id - 2.0f * m * u[1].y * id + m * m * g_cst[1]) + 2.0f * r * (u[2].y * id - m * g_cst[2]) + g_cst[4];
                        sc = r * rsqrtf(fmaxf(e2 - m2 * m2, 0.f) + 1e-5f);
                    }
                    const GeluK k = gelu_k(sc);
                    *(float4*)(rowc + h * 8) = make_float4(k.k0, k.k1, k.kh, -m);
                    *(float4*)(rowc + h * 8 + 4) = make_float4(var * r, -m2 * var * r, r, -m * r);
#pragma unroll
                    for (int q = 0; q < 3; q++) { u[q].x = u[q].z; u[q].y = u[q].w; }
                }
                bar_arrive(1 + wg, 160);
            }
        }
    } else {
        asm volatile("setmaxnreg.inc.sync.aligned.u32 232;");
        const bf16* xin = pp.x;
        const int wg = __reduce_max_sync(~0u, tid >> 7), wi = (tid >> 5) & 3, g = lane >> 2, tq = lane & 3;
        const int rh = 2 * mb + wg, row = rh * 64 + wi * 16 + g;
        const bool lead = (tid & 127) == 0;
        PP(0)
        if (tid == 0) TL(10)
        uint4 xg[8];
#pragma unroll
        for (int i = 0; i < 8; i++)
            xg[i] = __ldg((const uint4*)(xin + (size_t)(rh * 64 + wi * 16 + (i & 3) * 4 + (lane >> 3)) * DM + nb * 128 + (i >> 2) * 64 + (lane & 7) * 8));
        if (blockIdx.x < 64) g_modp[blockIdx.x * 256 + tid] = 0;
        if (blockIdx.x == 64 && tid < 64) g_tick[tid] = 0;
        {
            float* sv = (float*)(smraw + P_VEC);
            if (tid < 128) {
                const int c = nb * 128 + tid;
                sv[V_GA * 128 + tid] = __ldcg(&g_mod[2 * DM + c]); sv[V_A * 128 + tid] = 1.0f + __ldcg(&g_mod[4 * DM + c]);
                sv[V_B * 128 + tid] = __ldcg(&g_mod[3 * DM + c]); sv[V_GB * 128 + tid] = __ldcg(&g_mod[5 * DM + c]);
            } else {
                const int c = nb * 128 + tid - 128;
                sv[V_VA * 128 + tid - 128] = __ldcg(&g_vec[c]); sv[V_VB * 128 + tid - 128] = __ldcg(&g_vec[DM + c]); sv[V_VC * 128 + tid - 128] = __ldcg(&g_vec[2 * DM + c]);
            }
            sv[V_C3 * 128 + tid] = __ldcg(&g_vec[3 * DM + nb * 256 + tid]);
            if (tid < 192) sv[V_C3 * 128 + 256 + tid] = __ldcg(&g_vec[3 * DM + 2048 + nb * 192 + tid]);
            bar_sync(3, 256);
        }
        uint32_t vec = sb + P_VEC + tq * 8;
        asm volatile("" : "+r"(vec) :: "memory");
        const uint32_t stw = sb + (wi * 16 + ((lane >> 3) & 1) * 8 + (lane & 7)) * 128 + (((lane >> 4) ^ (lane & 7)) << 4);
        int sig = 0;
        auto signal = [&]() { bar_arrive(4 + 4 * wg + (sig++ & 3), 160); };
        auto put64 = [&](uint32_t o, const float* v) {
#pragma unroll
            for (int jj = 0; jj < 4; jj++, v += 8) stsm4((stw + o) ^ (jj << 5), pack2(v[0], v[1]), pack2(v[2], v[3]), pack2(v[4], v[5]), pack2(v[6], v[7]));
            fence_async_smem();
            signal();
        };
        auto out_free = [&](int n) { wait_smem(bars + 8 * (PB_OUT + (lane & 1)), n); };
        const uint32_t rowc = sb + P_ROW + (wg * 64 + wi * 16 + g) * 32, o128 = P_OUT + wg * 16384;
        Pipe pa = {0, 0}, pb = {0, 0};
        uint32_t keep[32];
#define KEEP(jn, e) (((e) & 1) ? bfhi(keep[2 * (jn) + ((e) >> 1)]) : bflo(keep[2 * (jn) + ((e) >> 1)]))
        float mu1[2], r1[2];
        {
            float acc[64];
            const uint32_t xo = sb + o128 + wi * 2048 + (lane >> 3) * 128;
#pragma unroll
            for (int i = 0; i < 8; i++) sts4(xo + (i >> 2) * 8192 + (i & 3) * 512 + (((lane & 7) ^ ((i & 1) * 4 + (lane >> 3))) << 4), xg[i].x, xg[i].y, xg[i].z, xg[i].w);
            __syncwarp();
#pragma unroll
            for (int jj = 0; jj < 8; jj++) ldsm4(keep + jj * 4, (stw + o128 + (jj >> 2) * 8192) ^ ((jj & 3) << 5));
            __syncwarp();
            post_mma<0>(sb, acc, pa, wg, lead, 1);
            float st[2][6];
#pragma unroll
            for (int q = 0; q < 6; q++) st[0][q] = st[1][q] = 0.f;
#pragma unroll
            for (int jn = 0; jn < 16; jn++) {
                const float2 ga = ldsv(vec + V_GA * 512 + jn * 32), a = ldsv(vec + V_A * 512 + jn * 32);
                float xa[4];
#pragma unroll
                for (int e = 0; e < 4; e++) {
                    xa[e] = fmaf((e & 1) ? ga.y : ga.x, acc[4 * jn + e], KEEP(jn, e));
                    st[e >> 1][0] += xa[e]; st[e >> 1][1] = fmaf(xa[e], xa[e], st[e >> 1][1]);
                    acc[4 * jn + e] = ((e & 1) ? a.y : a.x) * xa[e];
                }
                keep[2 * jn] = pack2(xa[0], xa[1]); keep[2 * jn + 1] = pack2(xa[2], xa[3]);
                if ((jn & 7) == 7) put64(o128 + (jn >> 3) * 8192, acc + 4 * jn - 28);
            }
            PP(3)
#pragma unroll
            for (int jn = 0; jn < 16; jn++) {
                const float2 a = ldsv(vec + V_A * 512 + jn * 32), b = ldsv(vec + V_B * 512 + jn * 32);
#pragma unroll
                for (int e = 0; e < 4; e++) {
                    const float y = acc[4 * jn + e], aa = (e & 1) ? a.y : a.x, bb = (e & 1) ? b.y : b.x;
                    float* s = st[e >> 1];
                    s[2] += y; s[3] = fmaf(aa, y, s[3]); s[4] = fmaf(y, y, s[4]); s[5] = fmaf(bb, y, s[5]);
                }
            }
#pragma unroll
            for (int h = 0; h < 2; h++)
#pragma unroll
                for (int q = 0; q < 6; q++) { st[h][q] += __shfl_xor_sync(~0u, st[h][q], 1); st[h][q] += __shfl_xor_sync(~0u, st[h][q], 2); }
            if (tq < 3) {
#pragma unroll
                for (int h = 0; h < 2; h++)
                    red2(g_st + (tq * S_ + row + h * 8) * 2, tq == 0 ? st[h][0] : tq == 1 ? st[h][2] : st[h][4], tq == 0 ? st[h][1] : tq == 1 ? st[h][3] : st[h][5]);
            }
            signal();
            PP(29)
        }
        {
            float acc[64];
            post_mma<1>(sb, acc, pa, wg, lead, 4);
            float c1[2], c2[2], c3[2];
            GeluK gk[2];
            bar_sync(1 + wg, 160);
#pragma unroll
            for (int h = 0; h < 2; h++) {
                const float4 a = lds4f(rowc + h * 256), b = lds4f(rowc + h * 256 + 16);
                gk[h] = {a.x, a.y, a.z}; c1[h] = a.w; c2[h] = b.x; c3[h] = b.y; mu1[h] = b.w; r1[h] = b.z;
            }
#pragma unroll
            for (int jn = 0; jn < 16; jn++) {
                const float2 va = ldsv(vec + V_VA * 512 + jn * 32), vb = ldsv(vec + V_VB * 512 + jn * 32), vc = ldsv(vec + V_VC * 512 + jn * 32);
#pragma unroll
                for (int e = 0; e < 4; e++) {
                    const int h = e >> 1;
                    const float t = fmaf(c1[h], (e & 1) ? va.y : va.x, fmaf(c2[h], (e & 1) ? vb.y : vb.x, fmaf(c3[h], (e & 1) ? vc.y : vc.x, acc[4 * jn + e])));
                    acc[4 * jn + e] = gelu_s(t, gk[h]);
                }
                if ((jn & 7) == 7) put64(o128 + (jn >> 3) * 8192, acc + 4 * jn - 28);
            }
            PP(6)
        }
        {
            float acc[64];
            post_mma<2>(sb, acc, pa, wg, lead, 7);
#pragma unroll
            for (int jn = 0; jn < 16; jn++) {
                const float2 a = ldsv(vec + V_A * 512 + jn * 32), b = ldsv(vec + V_B * 512 + jn * 32);
#pragma unroll
                for (int e = 0; e < 4; e++) {
                    const int h = e >> 1;
                    acc[4 * jn + e] += fmaf(fmaf(KEEP(jn, e), r1[h], mu1[h]), (e & 1) ? a.y : a.x, (e & 1) ? b.y : b.x);
                }
                if ((jn & 7) == 7) put64(o128 + (jn >> 3) * 8192, acc + 4 * jn - 28);
            }
            PP(9)
            float st[2][2] = {{0.f, 0.f}, {0.f, 0.f}};
#pragma unroll
            for (int jn = 0; jn < 16; jn++) {
                const float2 gb = ldsv(vec + V_GB * 512 + jn * 32);
                float z[4];
#pragma unroll
                for (int e = 0; e < 4; e++) {
                    const float x1 = acc[4 * jn + e];
                    st[e >> 1][0] += x1; st[e >> 1][1] = fmaf(x1, x1, st[e >> 1][1]);
                    z[e] = fmaf((e & 1) ? gb.y : gb.x, x1, KEEP(jn, e));
                }
                keep[2 * jn] = pack2(z[0], z[1]); keep[2 * jn + 1] = pack2(z[2], z[3]);
            }
#pragma unroll
            for (int h = 0; h < 2; h++)
#pragma unroll
                for (int q = 0; q < 2; q++) { st[h][q] += __shfl_xor_sync(~0u, st[h][q], 1); st[h][q] += __shfl_xor_sync(~0u, st[h][q], 2); }
            if (tq < 2) red2(g_st + (3 * S_ + row + tq * 8) * 2, tq ? st[1][0] : st[0][0], tq ? st[1][1] : st[0][1]);
            signal();
            PP(30)
        }
        {
            uint32_t v3 = vec + V_C3 * 512;
#pragma unroll 1
            for (int r = 0; r < 2; r++) {
                float acc[128];
#pragma unroll
                for (int i = 96; i < 128; i++) acc[i] = 0.f;
                if (r == 0) post_mma<3>(sb, acc, pb, wg, lead, 10);
                else post_mma<4>(sb, acc, pb, wg, lead, 13);
                float c1[2];
                GeluK gk[2];
                if (r == 0) bar_sync(1 + wg, 160);
                out_free(3 + r);
#pragma unroll
                for (int h = 0; h < 2; h++) { const float4 a = lds4f(rowc + h * 256); gk[h] = {a.x, a.y, a.z}; c1[h] = a.w; }
                uint32_t o = r ? P_OUT4 + wg * 24576 : P_OUT3 + wg * 32768;
#pragma unroll 1
                for (int left = 3 - r; left >= 0; left--) {
#pragma unroll
                    for (int jn = 0; jn < 8; jn++) {
                        const float2 vc = ldsv(v3 + jn * 32);
#pragma unroll
                        for (int e = 0; e < 4; e++) acc[4 * jn + e] = gelu_s(fmaf(c1[e >> 1], (e & 1) ? vc.y : vc.x, acc[4 * jn + e]), gk[e >> 1]);
                    }
                    put64(o, acc);
#pragma unroll
                    for (int i = 0; i < 32; i++) acc[i] = acc[32 + i];
                    if (left > 1) {
#pragma unroll
                        for (int i = 32; i < 64; i++) acc[i] = acc[32 + i];
                        if (left > 2) {
#pragma unroll
                            for (int i = 64; i < 96; i++) acc[i] = acc[32 + i];
                        }
                    }
                    o += 8192; v3 += 256;
                }
                PP(12 + 3 * r)
            }
        }
        {
            float acc[64];
            post_mma<5>(sb, acc, pa, wg, lead, 16);
#pragma unroll
            for (int jn = 0; jn < 16; jn++) {
                const float2 gb = ldsv(vec + V_GB * 512 + jn * 32);
#pragma unroll
                for (int e = 0; e < 4; e++) acc[4 * jn + e] = fmaf((e & 1) ? gb.y : gb.x, acc[4 * jn + e], KEEP(jn, e));
                if ((jn & 7) == 7) put64(o128 + (jn >> 3) * 8192, acc + 4 * jn - 28);
            }
            PP(18)
            if (tid == 0) TL(12)
        }
    }
}

typedef CUresult (*EncFn)(CUtensorMap*, CUtensorMapDataType, cuuint32_t, void*, const cuuint64_t*, const cuuint64_t*, const cuuint32_t*,
                          const cuuint32_t*, CUtensorMapInterleave, CUtensorMapSwizzle, CUtensorMapL2promotion, CUtensorMapFloatOOBfill);

static CUtensorMap make_map(EncFn enc, const void* p, uint64_t inner, uint64_t outer, uint32_t bi = 64) {
    CUtensorMap m;
    cuuint64_t dims[2] = {inner, outer};
    cuuint64_t str[1] = {inner * 2};
    cuuint32_t box[2] = {bi, 64};
    cuuint32_t es[2] = {1, 1};
    enc(&m, CU_TENSOR_MAP_DATA_TYPE_BFLOAT16, 2, (void*)p, dims, str, box, es, CU_TENSOR_MAP_INTERLEAVE_NONE,
        bi == 64 ? CU_TENSOR_MAP_SWIZZLE_128B : CU_TENSOR_MAP_SWIZZLE_64B, CU_TENSOR_MAP_L2_PROMOTION_L2_256B, CU_TENSOR_MAP_FLOAT_OOB_FILL_NONE);
    return m;
}
static CUtensorMap make_map_o(EncFn enc, const void* p) {
    CUtensorMap m;
    cuuint64_t dims[2] = {16384, 256};
    cuuint64_t str[1] = {65536};
    cuuint32_t box[2] = {256, 8};
    cuuint32_t es[2] = {1, 1};
    enc(&m, CU_TENSOR_MAP_DATA_TYPE_UINT32, 2, (void*)p, dims, str, box, es, CU_TENSOR_MAP_INTERLEAVE_NONE, CU_TENSOR_MAP_SWIZZLE_NONE,
        CU_TENSOR_MAP_L2_PROMOTION_L2_256B, CU_TENSOR_MAP_FLOAT_OOB_FILL_NONE);
    return m;
}
template <class T> static T* sym(T& s) { void* p = nullptr; cudaGetSymbolAddress(&p, s); return (T*)p; }

constexpr RecTime g_time = {T_GO, T_X2, T_V, D_X2, D_V, H_D};
extern "C" void kernel_launch(void* const* d_in, const int* in_sizes, int n_in, void* d_out, int out_size) {
    const bf16* x = (const bf16*)d_in[0];
    const bf16* mem0 = (const bf16*)d_in[1];
    const bf16 *Wq = (const bf16*)d_in[2], *Wk = (const bf16*)d_in[3], *Wv = (const bf16*)d_in[4], *Wo = (const bf16*)d_in[5];
    const bf16 *w1 = (const bf16*)d_in[8], *w2 = (const bf16*)d_in[9], *w3 = (const bf16*)d_in[10], *w4 = (const bf16*)d_in[11];
    const bf16 *c = (const bf16*)d_in[12], *wmod = (const bf16*)d_in[13];
    bf16* out = (bf16*)d_out;

    EncFn enc = nullptr;
    cudaDriverEntryPointQueryResult qr;
    cudaGetDriverEntryPoint("cuTensorMapEncodeTiled", (void**)&enc, cudaEnableDefault, &qr);
    CUtensorMap tWq = make_map(enc, Wq, NH * DH, DM), tWk = make_map(enc, Wk, NH * DH, DM), tWv = make_map(enc, Wv, NH * DH, DM);
    PostMaps mp;
    mp.o = make_map_o(enc, sym(g_O)); mp.wo = make_map(enc, Wo, DM, NH * DH);
    mp.y = make_map(enc, sym(g_y), DM, S_); mp.w1 = make_map(enc, w1, DM, DM);
    mp.g = make_map(enc, sym(g_g), DM, S_); mp.w2 = make_map(enc, w2, DM, DM);
    mp.x1 = make_map(enc, sym(g_x1), DM, S_); mp.w3 = make_map(enc, w3, FF, DM);
    mp.u = make_map(enc, sym(g_u), FF, S_); mp.w4 = make_map(enc, w4, DM, FF);
    mp.out = make_map(enc, out, DM, S_);
    cudaFuncSetAttribute(k_rec, cudaFuncAttributeMaxDynamicSharedMemorySize, SM_REC_TOTAL);
    cudaFuncSetAttribute(k_post, cudaFuncAttributeMaxDynamicSharedMemorySize, P_SMEM);

    uint8_t* arena = (uint8_t*)(((uintptr_t)sym(g_arena) + (2u << 20) - 1) & ~(uintptr_t)((2u << 20) - 1));
    const PostPtrs pp = {x};
    const RecPtrs rp = {x, mem0, c, wmod, w1, w3, arena, 0u, w2, w4, Wo, g_time};
    const RecMaps rm = {tWq, tWk, tWv, mp.wo};
    k_rec<<<132, 384, SM_REC_TOTAL>>>(rm, rp);
    k_post<<<128, 384, P_SMEM>>>(mp, pp);
}
```

```cpp
#include <cuda_runtime.h>
#include <cuda.h>
#include <cuda_bf16.h>
#include <stdint.h>
#include <limits.h>

typedef __nv_bfloat16 bf16;

constexpr int S_ = 2048, DM = 1024, NH = 32, DH = 128, NSEG = 64, FF = 3584;
constexpr int SPIN_LIMIT = 1 << 22;
#define W_INFL 3
#define XP 0
#define H_PIECES 8
#define NPROBE 3

__device__ uint8_t g_arena[10 << 20];
__device__ __align__(16) uint32_t g_tick[64];
__device__ __align__(16) uint32_t g_modp[8 * 2 * DM];
__host__ __device__ constexpr uint32_t blk(uint32_t lb, uint32_t par) {
    return (lb << 13) | ((((lb) ^ (lb >> 3) ^ (lb >> 4) ^ (lb >> 6) ^ par) & 1) << 12);
}
__host__ __device__ constexpr uint32_t lb_x2(uint32_t h) { return (h & 1) | ((h >> 1) << 3); }
__host__ __device__ constexpr uint32_t acc_slot(uint32_t s) { return (1u << 20) + (s & 1) * 32768 + (s & 2) * 131072; }
__host__ __device__ constexpr uint32_t acc_piece(uint32_t half, uint32_t qd, uint32_t mt) { return mt * 1024 + (qd & 1) * 4096 + half * 8192 + (qd >> 1) * 16384; }
constexpr uint32_t LB_STAMP = 6;
__host__ __device__ constexpr uint32_t stamp_line(uint32_t w, uint32_t q) { return ((w & 1) * 2 + (q >> 1)) * 1024 + (q & 1) * 256; }
constexpr uint32_t ACC_ONE = 0x3c000000u, ACC_ALL = 0x50000000u;
constexpr uint32_t LB_PROBE = 6 | 64;
__host__ __device__ constexpr uint32_t lb_tok(uint32_t h) { return (h & 1) | ((h >> 1) << 3); }
__device__ __align__(16) float g_mod[6 * DM];
__device__ __align__(1024) bf16 g_himg[(S_ + 32) * DM];
__device__ __align__(1024) bf16 g_O[S_ * NH * DH];
__device__ __align__(1024) bf16 g_y[S_ * DM];
__device__ __align__(1024) bf16 g_g[S_ * DM];
__device__ __align__(1024) bf16 g_x1[S_ * DM];
__device__ __align__(16) float g_st[4 * S_ * 2];
__device__ __align__(16) float g_vec[3 * DM + FF];
__device__ float g_cst[8];
__device__ uint32_t g_pcnt[2 * 32 * 8], g_pflag[6 * 32 * 8];
__device__ __align__(1024) bf16 g_u[S_ * FF];

#define TL(i) {}
#define TX(i) {}
#define TLC(i) {}
__device__ __forceinline__ uint32_t smem_u32(const void* p) { return (uint32_t)__cvta_generic_to_shared(p); }
__device__ __forceinline__ void spin_guard(int it) {
    asm volatile("{.reg .pred p; setp.gt.s32 p, %0, %1; @p st.global.u32 [%2], %0;}" ::"r"(it), "n"(SPIN_LIMIT), "l"(1ull));
}
__device__ __forceinline__ void wg_fence() { asm volatile("wgmma.fence.sync.aligned;" ::: "memory"); }
__device__ __forceinline__ void wg_commit() { asm volatile("wgmma.commit_group.sync.aligned;" ::: "memory"); }
template <int N> __device__ __forceinline__ void wg_wait() { asm volatile("wgmma.wait_group.sync.aligned %0;" ::"n"(N) : "memory"); }
__host__ __device__ constexpr uint64_t mkdesc(uint32_t addr, uint32_t lbo, uint32_t sbo, uint32_t swz) {
    return (uint64_t)((addr & 0x3FFFF) >> 4) | ((uint64_t)(lbo >> 4) << 16) | ((uint64_t)(sbo >> 4) << 32) | ((uint64_t)swz << 62);
}
__device__ __forceinline__ uint64_t dadd(uint64_t d, uint32_t o) { return (d & 0xffffffff00000000ull) | (uint32_t)((uint32_t)d + o); }
__device__ __forceinline__ void mbar_init(uint32_t b, uint32_t c) { asm volatile("mbarrier.init.shared.b64 [%0], %1;" ::"r"(b), "r"(c) : "memory"); }
__device__ __forceinline__ void mbar_expect(uint32_t b, uint32_t tx) { asm volatile("mbarrier.arrive.expect_tx.shared.b64 _, [%0], %1;" ::"r"(b), "r"(tx) : "memory"); }
__device__ __forceinline__ void mbar_arrive(uint32_t b) { asm volatile("mbarrier.arrive.shared.b64 _, [%0];" ::"r"(b) : "memory"); }
__device__ __forceinline__ void mbar_arrive_cluster(uint32_t b, uint32_t cta) {
    asm volatile("{.reg .b32 r; mapa.shared::cluster.u32 r, %0, %1; mbarrier.arrive.shared::cluster.b64 _, [r];}" ::"r"(b), "r"(cta) : "memory");
}
__device__ __forceinline__ bool mbar_try(uint32_t b, uint32_t par) {
    uint32_t ok;
    asm volatile("{.reg .pred p; mbarrier.try_wait.parity.shared.b64 p, [%1], %2; selp.u32 %0, 1, 0, p;}" : "=r"(ok) : "r"(b), "r"(par) : "memory");
    return ok;
}
__device__ __forceinline__ void mbar_wait(uint32_t b, uint32_t par) {
    int it = 0;
#pragma unroll 1
    while (!mbar_try(b, par)) { spin_guard(++it); }
}
__device__ __forceinline__ void mbar_wait_w(uint32_t b, uint32_t par) {
    int it = 0;
    bool ok;
#pragma unroll 1
    do { ok = __all_sync(~0u, mbar_try(b, par)); spin_guard(++it); } while (!ok);
}
__device__ __forceinline__ void mbar_wait_cluster(uint32_t b, uint32_t par) {
    int it = 0;
    while (true) {
        uint32_t ok;
        asm volatile("{.reg .pred p; mbarrier.try_wait.parity.acquire.cluster.shared::cta.b64 p, [%1], %2; selp.u32 %0, 1, 0, p;}" : "=r"(ok) : "r"(b), "r"(par) : "memory");
        if (ok) break;
        spin_guard(++it);
    }
}
__device__ __forceinline__ void tma2d(uint32_t dst, const CUtensorMap* m, int c0, int c1, uint32_t bar) {
    asm volatile("cp.async.bulk.tensor.2d.shared::cluster.global.mbarrier::complete_tx::bytes [%0], [%1, {%3, %4}], [%2];" ::"r"(dst), "l"(m), "r"(bar), "r"(c0), "r"(c1) : "memory");
}
__device__ __forceinline__ void tma2d_mc(uint32_t dst, const CUtensorMap* m, int c0, int c1, uint32_t bar, uint16_t mask) {
    asm volatile("cp.async.bulk.tensor.2d.shared::cluster.global.mbarrier::complete_tx::bytes.multicast::cluster [%0], [%1, {%3, %4}], [%2], %5;" ::"r"(dst), "l"(m), "r"(bar), "r"(c0), "r"(c1), "h"(mask) : "memory");
}
__device__ __forceinline__ void bulk_g2s(uint32_t dst, const void* src, uint32_t bytes, uint32_t bar) {
    asm volatile("cp.async.bulk.shared::cluster.global.mbarrier::complete_tx::bytes [%0], [%1], %2, [%3];" ::"r"(dst), "l"(src), "r"(bytes), "r"(bar) : "memory");
}
__device__ __forceinline__ void bar_sync(int id, int n) { asm volatile("bar.sync %0, %1;" ::"r"(id), "r"(n) : "memory"); }
__device__ __forceinline__ void bar_arrive(int id, int n) { asm volatile("bar.arrive %0, %1;" ::"r"(id), "r"(n) : "memory"); }
__device__ __forceinline__ void cluster_sync_all() { asm volatile("barrier.cluster.arrive.aligned; barrier.cluster.wait.aligned;" ::: "memory"); }
__device__ __forceinline__ void fence_async_smem() { asm volatile("fence.proxy.async.shared::cta;" ::: "memory"); }
__device__ __forceinline__ void ldsm4t(uint32_t* r, uint32_t a) {
    asm volatile("ldmatrix.sync.aligned.m8n8.x4.trans.shared.b16 {%0,%1,%2,%3}, [%4];" : "=r"(r[0]), "=r"(r[1]), "=r"(r[2]), "=r"(r[3]) : "r"(a) : "memory");
}
__device__ __forceinline__ void ldsm4(uint32_t* r, uint32_t a) {
    asm volatile("ldmatrix.sync.aligned.m8n8.x4.shared.b16 {%0,%1,%2,%3}, [%4];" : "=r"(r[0]), "=r"(r[1]), "=r"(r[2]), "=r"(r[3]) : "r"(a) : "memory");
}
__device__ __forceinline__ uint32_t movm(uint32_t a) {
    uint32_t d; asm volatile("movmatrix.sync.aligned.m8n8.trans.b16 %0, %1;" : "=r"(d) : "r"(a)); return d;
}
__device__ __forceinline__ void mma16816(float* d, uint32_t a0, uint32_t a1, uint32_t a2, uint32_t a3, uint32_t b0, uint32_t b1) {
    asm volatile("mma.sync.aligned.m16n8k16.row.col.f32.bf16.bf16.f32 {%0,%1,%2,%3},{%4,%5,%6,%7},{%8,%9},{%0,%1,%2,%3};"
                 : "+f"(d[0]), "+f"(d[1]), "+f"(d[2]), "+f"(d[3]) : "r"(a0), "r"(a1), "r"(a2), "r"(a3), "r"(b0), "r"(b1));
}
__device__ __forceinline__ void mma16816z(float* d, const uint32_t* a, uint32_t b0, uint32_t b1) {
    asm volatile("mma.sync.aligned.m16n8k16.row.col.f32.bf16.bf16.f32 {%0,%1,%2,%3},{%4,%5,%6,%7},{%8,%9},{%10,%10,%10,%10};"
                 : "=f"(d[0]), "=f"(d[1]), "=f"(d[2]), "=f"(d[3]) : "r"(a[0]), "r"(a[1]), "r"(a[2]), "r"(a[3]), "r"(b0), "r"(b1), "f"(0.f));
}
__device__ __forceinline__ void mma1688(float* d, uint32_t a0, uint32_t a1, uint32_t b0) {
    asm volatile("mma.sync.aligned.m16n8k8.row.col.f32.bf16.bf16.f32 {%0,%1,%2,%3},{%4,%5},{%6},{%0,%1,%2,%3};"
                 : "+f"(d[0]), "+f"(d[1]), "+f"(d[2]), "+f"(d[3]) : "r"(a0), "r"(a1), "r"(b0));
}
__device__ __forceinline__ uint32_t pack2(float lo, float hi) {
    uint32_t r; asm("cvt.rn.bf16x2.f32 %0, %1, %2;" : "=r"(r) : "f"(hi), "f"(lo)); return r;
}
__device__ __forceinline__ uint32_t hadd2(uint32_t a, uint32_t b) {
    uint32_t r; asm("add.rn.bf16x2 %0, %1, %2;" : "=r"(r) : "r"(a), "r"(b)); return r;
}
__device__ __forceinline__ uint32_t hadd2v(uint32_t a, uint32_t b) {
    uint32_t r; asm volatile("add.rn.bf16x2 %0, %1, %2;" : "=r"(r) : "r"(a), "r"(b)); return r;
}
__device__ __forceinline__ float bflo(uint32_t u) { return __uint_as_float(u << 16); }
__device__ __forceinline__ float bfhi(uint32_t u) { return __uint_as_float(u & 0xffff0000u); }
__device__ __forceinline__ float ex2(float x) { float r; asm("ex2.approx.ftz.f32 %0, %1;" : "=f"(r) : "f"(x)); return r; }
__device__ __forceinline__ uint4 ldg_rlx4(const void* p) {
    uint4 v; asm volatile("ld.relaxed.gpu.global.v4.u32 {%0,%1,%2,%3}, [%4];" : "=r"(v.x), "=r"(v.y), "=r"(v.z), "=r"(v.w) : "l"(p) : "memory"); return v;
}
__device__ __forceinline__ uint2 ldg_rlx2(const void* p) {
    unsigned long long v; asm volatile("ld.relaxed.gpu.global.b64 %0, [%1];" : "=l"(v) : "l"(p) : "memory");
    return make_uint2((uint32_t)v, (uint32_t)(v >> 32));
}
__device__ __forceinline__ uint32_t ldg_rlx1(const void* p) {
    uint32_t v; asm volatile("ld.relaxed.gpu.global.u32 %0, [%1];" : "=r"(v) : "l"(p) : "memory"); return v;
}
__device__ __forceinline__ void stg_rlx1(void* p, uint32_t v) { asm volatile("st.relaxed.gpu.global.u32 [%0], %1;" ::"l"(p), "r"(v) : "memory"); }
__device__ __forceinline__ void stg_rlx2(void* p, uint32_t x, uint32_t y) {
    unsigned long long v = (unsigned long long)x | ((unsigned long long)y << 32);
    asm volatile("st.relaxed.gpu.global.b64 [%0], %1;" ::"l"(p), "l"(v) : "memory");
}
__device__ __forceinline__ void stg_rlx4(void* p, uint32_t x, uint32_t y, uint32_t z, uint32_t w) {
    asm volatile("st.relaxed.gpu.global.v4.u32 [%0], {%1,%2,%3,%4};" ::"l"(p), "r"(x), "r"(y), "r"(z), "r"(w) : "memory");
}
__device__ __forceinline__ void sts4(uint32_t a, uint32_t x, uint32_t y, uint32_t z, uint32_t w) {
    asm volatile("st.shared.v4.u32 [%0], {%1,%2,%3,%4};" ::"r"(a), "r"(x), "r"(y), "r"(z), "r"(w) : "memory");
}
__device__ __forceinline__ uint4 lds4(uint32_t a) {
    uint4 v; asm volatile("ld.shared.v4.u32 {%0,%1,%2,%3}, [%4];" : "=r"(v.x), "=r"(v.y), "=r"(v.z), "=r"(v.w) : "r"(a) : "memory"); return v;
}
__device__ __forceinline__ void st_async4(uint32_t a, float x, float y, float z, float w, uint32_t bar) {
    asm volatile("st.async.shared::cluster.mbarrier::complete_tx::bytes.v4.f32 [%0], {%1,%2,%3,%4}, [%5];" ::"r"(a), "f"(x), "f"(y), "f"(z), "f"(w), "r"(bar) : "memory");
}
#define F4(d, i) "+f"(d[i]), "+f"(d[i + 1]), "+f"(d[i + 2]), "+f"(d[i + 3])
template <bool V> __device__ __forceinline__ void wgmma_tok_rs(float* d, const uint32_t* a, uint64_t b, int sc) {
    if (V) asm volatile("{.reg .pred p; setp.ne.b32 p, %25, 0;\n wgmma.mma_async.sync.aligned.m64n40k16.f32.bf16.bf16 {%0,%1,%2,%3,%4,%5,%6,%7,%8,%9,%10,%11,%12,%13,%14,%15,%16,%17,%18,%19}, {%20,%21,%22,%23}, %24, p, 1, 1, 0;}"
                        : F4(d, 0), F4(d, 4), F4(d, 8), F4(d, 12), F4(d, 16) : "r"(a[0]), "r"(a[1]), "r"(a[2]), "r"(a[3]), "l"(b), "r"(sc));
    else asm volatile("{.reg .pred p; setp.ne.b32 p, %21, 0;\n wgmma.mma_async.sync.aligned.m64n32k16.f32.bf16.bf16 {%0,%1,%2,%3,%4,%5,%6,%7,%8,%9,%10,%11,%12,%13,%14,%15}, {%16,%17,%18,%19}, %20, p, 1, 1, 0;}"
                      : F4(d, 0), F4(d, 4), F4(d, 8), F4(d, 12) : "r"(a[0]), "r"(a[1]), "r"(a[2]), "r"(a[3]), "l"(b), "r"(sc));
}
template <bool V> __device__ __forceinline__ void wgmma_tok_ss(float* d, uint64_t a, uint64_t b) {
    if (V) asm volatile("wgmma.mma_async.sync.aligned.m64n40k16.f32.bf16.bf16 {%0,%1,%2,%3,%4,%5,%6,%7,%8,%9,%10,%11,%12,%13,%14,%15,%16,%17,%18,%19}, %20, %21, 1, 1, 1, 1, 0;"
                        : F4(d, 0), F4(d, 4), F4(d, 8), F4(d, 12), F4(d, 16) : "l"(a), "l"(b));
    else asm volatile("wgmma.mma_async.sync.aligned.m64n32k16.f32.bf16.bf16 {%0,%1,%2,%3,%4,%5,%6,%7,%8,%9,%10,%11,%12,%13,%14,%15}, %16, %17, 1, 1, 1, 1, 0;"
                      : F4(d, 0), F4(d, 4), F4(d, 8), F4(d, 12) : "l"(a), "l"(b));
}
#define F16(d, i) F4(d, i), F4(d, i + 4), F4(d, i + 8), F4(d, i + 12)
template <int TA>
__device__ __forceinline__ void wgmma_ss128(float* d, uint64_t a, uint64_t b, int sc) {
    asm volatile("{.reg .pred p; setp.ne.b32 p, %66, 0;\n wgmma.mma_async.sync.aligned.m64n128k16.f32.bf16.bf16 "
                 "{%0,%1,%2,%3,%4,%5,%6,%7,%8,%9,%10,%11,%12,%13,%14,%15,%16,%17,%18,%19,%20,%21,%22,%23,%24,%25,%26,%27,%28,%29,%30,%31,"
                 "%32,%33,%34,%35,%36,%37,%38,%39,%40,%41,%42,%43,%44,%45,%46,%47,%48,%49,%50,%51,%52,%53,%54,%55,%56,%57,%58,%59,%60,%61,%62,%63}, %64, %65, p, 1, 1, %67, 1;}"
                 : F16(d, 0), F16(d, 16), F16(d, 32), F16(d, 48) : "l"(a), "l"(b), "r"(sc), "n"(TA));
}

__device__ __forceinline__ float warp_sum(float v) {
#pragma unroll
    for (int o = 16; o; o >>= 1) v += __shfl_xor_sync(~0u, v, o);
    return v;
}
__device__ __forceinline__ float bfround(float x) { return __bfloat162float(__float2bfloat16(x)); }

__device__ __forceinline__ void wait_count1(const uint32_t* p, uint32_t target) {
    int it = 0;
#pragma unroll 1
    while (true) {
        uint32_t v;
        asm volatile("ld.acquire.gpu.global.u32 %0, [%1];" : "=r"(v) : "l"(p) : "memory");
        if (v >= target) break;
        spin_guard(++it);
    }
}
__device__ __forceinline__ void red2(float* p, float a, float b) {
    asm volatile("red.relaxed.gpu.global.add.v2.f32 [%0], {%1, %2};" ::"l"(p), "f"(a), "f"(b) : "memory");
}
__device__ __forceinline__ void l2_prefetch(const void* p, uint32_t bytes) {
    asm volatile("cp.async.bulk.prefetch.L2.global [%0], %1;" ::"l"(p), "r"(bytes) : "memory");
}
__device__ __forceinline__ void signal_count(uint32_t* p) { asm volatile("red.release.gpu.global.add.u32 [%0], 1;" ::"l"(p) : "memory"); }
__device__ __forceinline__ void e_expect(uint32_t b, uint32_t tx) {
    asm volatile("{.reg .pred p; elect.sync _|p, 0xffffffff; @p mbarrier.arrive.expect_tx.shared.b64 _, [%0], %1;}" ::"r"(b), "r"(tx) : "memory");
}
__device__ __forceinline__ uint64_t evict_first() { uint64_t p; asm("createpolicy.fractional.L2::evict_first.b64 %0, 1.0;" : "=l"(p)); return p; }
__device__ __forceinline__ uint64_t evict_normal() { uint64_t p; asm("createpolicy.fractional.L2::evict_unchanged.b64 %0, 1.0;" : "=l"(p)); return p; }
__device__ __forceinline__ void e_tma2d(uint32_t dst, const CUtensorMap* m, int c0, int c1, uint32_t bar, uint64_t pol) {
    asm volatile("{.reg .pred p; elect.sync _|p, 0xffffffff;\n @p cp.async.bulk.tensor.2d.shared::cluster.global.mbarrier::complete_tx::bytes.L2::cache_hint [%0], [%1, {%3, %4}], [%2], %5;}"
                 ::"r"(dst), "l"(m), "r"(bar), "r"(c0), "r"(c1), "l"(pol) : "memory");
}
__device__ __forceinline__ void e_tma2d_mc(uint32_t dst, const CUtensorMap* m, int c0, int c1, uint32_t bar, uint64_t pol) {
    asm volatile("{.reg .pred p; elect.sync _|p, 0xffffffff;\n @p cp.async.bulk.tensor.2d.shared::cluster.global.mbarrier::complete_tx::bytes.multicast::cluster.L2::cache_hint [%0], [%1, {%3, %4}], [%2], %5, %6;}"
                 ::"r"(dst), "l"(m), "r"(bar), "r"(c0), "r"(c1), "h"((uint16_t)3), "l"(pol) : "memory");
}
__device__ __forceinline__ void e_prefetch(const void* p, uint32_t bytes) {
    asm volatile("{.reg .pred p; elect.sync _|p, 0xffffffff; @p cp.async.bulk.prefetch.L2.global [%0], %1;}" ::"l"(p), "r"(bytes) : "memory");
}
__device__ __forceinline__ void wait_count_w(const uint32_t* p, uint32_t target) {
    int it = 0;
#pragma unroll 1
    while (true) {
        uint32_t v;
        asm volatile("ld.acquire.gpu.global.u32 %0, [%1];" : "=r"(v) : "l"(p) : "memory");
        if (__all_sync(~0u, v >= target)) break;
        spin_guard(++it);
    }
}

__device__ __forceinline__ uint4 pack8(const float* x) {
    return make_uint4(pack2(x[0], x[1]), pack2(x[2], x[3]), pack2(x[4], x[5]), pack2(x[6], x[7]));
}
#define NL 6
constexpr uint32_t HCH = 5120, HBUF = 8 * HCH;
constexpr uint32_t SM_SX = 0, SM_ST = 2560, SM_OX = 8192, SM_LX = 10240, SM_PX = 11392, SM_PA = 12288, SM_VF = 18432, SM_TAB = 26624, SM_WL2 = 41984, SM_HB = 49152, SM_WO = 131072,
                   SM_WL = 196608, SM_PRE = SM_WL, SM_BAR = 227328, SM_SV = SM_BAR + 256, SM_TRC = SM_SV + 2048, SM_REC_TOTAL = SM_TRC + 2688;
__host__ __device__ constexpr uint32_t sm_wl(int i) { return i < 5 ? SM_WL + i * 6144 : SM_WL2; }
constexpr uint32_t SB0 = 1024;
constexpr int B_WO = 0, B_HE = 1, B_ROLE = 2, B_HB = 3, B_W = 5;
constexpr int NB_MEM = 1, NB_QK = 2, NB_X1 = 3, NB_X2 = 4, NB_WIN = 5, NB_WG = 6, NB_KDONE = 7, NB_FIN0 = 8, NB_LN = 9, NB_MEM2 = 10, NB_H = 11, NB_A = 12, NB_B = 13, NB_C = 14, NB_F = 15;
#define ST_GATE 1
#define SPF 33
#define SPF_NS 100
#define TPV_DLY 3
#define L_AT 1
#define D_X2 300
#define D_V 150
#define NPF1 6
#define NPF 12
#define ROTM 7
#define FARF 1
#define T_GO 30
#define STG_ORD 2
#define GATE_AT 29
#define H4 1
#define T_X2 1900
#define T_V 400
#define LAST_WG 0
#define QK_EARLY 0
#define NOB 1
#define VP_AT 1
#define KQ_AT 17
#define PD 4
#define PFENCE 1
#define SH3 1
#define PV_FENCE 3
#define SGATE 0
#define SW_T 18
#define SW_N 1
#define SW_END 48
#define SV_AT 0
#define SSG 4
#define SSG_V 4
#define SS0_K 2
#define SS0_V 4
#define W0_AT 12
#define NPF0 4
#define SPLIT_MEM 1
#define STG_FENCE 5
#define O_LATE 0
#define F0_EARLY 0
#define WO_AT 0
#define W_PF 4
#define EF 13
#define NPF2 11
#define PF_DLY 6
#define H_AT 3
#define H_D 200
#define REQ_LATE 2
#define PIN_EPI 1

#define PROF_INIT
#define PROF(i)
#define PROFV(i, v)
#define PROF_OUT

__device__ __forceinline__ uint32_t clk32() { uint32_t t; asm volatile("mov.u32 %0, %%clock;" : "=r"(t) :: "memory"); return t; }
__device__ __forceinline__ uint32_t gtime32() { uint32_t t; asm volatile("mov.u32 %0, %%globaltimer_lo;" : "=r"(t) :: "memory"); return t; }
__device__ __forceinline__ void spin_until(uint32_t t0, uint32_t d) { while (clk32() - t0 < d) {} }
template <int N> __device__ __forceinline__ uint32_t delay(uint32_t zero) {
    float x = __uint_as_float(clk32());
#pragma unroll
    for (int i = 0; i < N; i++) asm volatile("ex2.approx.ftz.f32 %0, %0;" : "+f"(x));
    return __float_as_uint(x) & zero;
}
__device__ __forceinline__ uint32_t clk_after(uint32_t x, uint32_t zero) {
    unsigned long long c = 0;
    asm volatile("{.reg .pred p; setp.eq.u32 p, %1, 0; @p mov.u64 %0, %%clock64;}" : "+l"(c) : "r"(x & zero) : "memory");
    return (uint32_t)c;
}
__device__ __forceinline__ uint32_t later(uint32_t a, uint32_t b) { return a + max((int)(b - a), 0); }
__device__ __forceinline__ void wait_clk(uint32_t t) {
#pragma unroll 1
    while (true) {
        unsigned long long c;
        asm volatile("mov.u64 %0, %%clock64;" : "=l"(c) :: "memory");
        if ((int)((uint32_t)c - t) >= 0) break;
    }
}
__device__ __forceinline__ uint32_t opaque(uint32_t v) { return __shfl_sync(~0u, v, threadIdx.x & 31); }
__device__ __forceinline__ uint32_t xor_or(uint32_t a, uint32_t b, uint32_t t) {
    uint32_t r; asm volatile("lop3.b32 %0, %1, %2, %3, 0x7E;" : "=r"(r) : "r"(a), "r"(b), "r"(t)); return r;
}
__device__ __forceinline__ uint32_t or3(uint32_t a, uint32_t b, uint32_t c) {
    uint32_t r; asm volatile("lop3.b32 %0, %1, %2, %3, 0xFE;" : "=r"(r) : "r"(a), "r"(b), "r"(c)); return r;
}
__device__ __forceinline__ uint32_t settag(uint32_t v, uint32_t tag) {
    uint32_t r; asm("lop3.b32 %0, %1, 1, %2, 0xB8;" : "=r"(r) : "r"(v), "r"(tag)); return r;
}
__device__ __forceinline__ void ldg4_if(uint4& v, const void* p, bool c) {
    asm volatile("{.reg .pred p; setp.ne.u32 p, %5, 0; @p ld.relaxed.gpu.global.v4.u32 {%0,%1,%2,%3}, [%4];}"
                 : "+r"(v.x), "+r"(v.y), "+r"(v.z), "+r"(v.w) : "l"(p), "r"((uint32_t)c) : "memory");
}
__device__ __forceinline__ uint4 ldg_rlx2x2(const void* p) {
    unsigned long long a, b;
    asm volatile("ld.relaxed.gpu.global.v2.b64 {%0,%1}, [%2];" : "=l"(a), "=l"(b) : "l"(p) : "memory");
    return make_uint4((uint32_t)a, (uint32_t)(a >> 32), (uint32_t)b, (uint32_t)(b >> 32));
}
__device__ __forceinline__ void stg_rlx2x2(void* p, uint32_t x, uint32_t y, uint32_t z, uint32_t w) {
    asm volatile("{.reg .b64 a, b; mov.b64 a, {%1,%2}; mov.b64 b, {%3,%4}; st.relaxed.gpu.global.v2.b64 [%0], {a, b};}" ::"l"(p), "r"(x), "r"(y), "r"(z), "r"(w) : "memory");
}
__device__ __forceinline__ void ldg1_if(uint32_t& v, const void* p, bool c) {
    asm volatile("{.reg .pred p; setp.ne.u32 p, %2, 0; @p ld.relaxed.gpu.global.u32 %0, [%1];}" : "+r"(v) : "l"(p), "r"((uint32_t)c) : "memory");
}
__device__ __forceinline__ void sts2(uint32_t a, float x, float y) { asm volatile("st.shared.v2.f32 [%0], {%1,%2};" ::"r"(a), "f"(x), "f"(y) : "memory"); }
__device__ __forceinline__ void sts4f(uint32_t a, float x, float y, float z, float w) {
    asm volatile("st.shared.v4.f32 [%0], {%1,%2,%3,%4};" ::"r"(a), "f"(x), "f"(y), "f"(z), "f"(w) : "memory");
}
__device__ __forceinline__ void sts1(uint32_t a, uint32_t x) { asm volatile("st.shared.u32 [%0], %1;" ::"r"(a), "r"(x) : "memory"); }
__device__ __forceinline__ uint32_t lds1(uint32_t a) { uint32_t v; asm volatile("ld.shared.u32 %0, [%1];" : "=r"(v) : "r"(a) : "memory"); return v; }
__device__ __forceinline__ float4 lds4f(uint32_t a) {
    float4 v; asm volatile("ld.shared.v4.f32 {%0,%1,%2,%3}, [%4];" : "=f"(v.x), "=f"(v.y), "=f"(v.z), "=f"(v.w) : "r"(a) : "memory"); return v;
}
__device__ __forceinline__ float2 lds2f(uint32_t a) {
    float2 v; asm volatile("ld.shared.v2.f32 {%0,%1}, [%2];" : "=f"(v.x), "=f"(v.y) : "r"(a) : "memory"); return v;
}
__device__ __forceinline__ bool any_bit0(uint32_t x) {
    uint32_t r;
    asm volatile("{.reg .pred p, q; .reg .b32 t; and.b32 t, %1, 1; setp.ne.u32 p, t, 0; vote.sync.any.pred q, p, 0xffffffff; selp.u32 %0, 1, 0, q;}" : "=r"(r) : "r"(x));
    return r;
}
__device__ __forceinline__ float rcp_fast(float x) { float r; asm("rcp.approx.ftz.f32 %0, %1;" : "=f"(r) : "f"(x)); return r; }
__device__ __forceinline__ void stsm4(uint32_t a, uint32_t r0, uint32_t r1, uint32_t r2, uint32_t r3) {
    asm volatile("stmatrix.sync.aligned.m8n8.x4.shared.b16 [%0], {%1,%2,%3,%4};" ::"r"(a), "r"(r0), "r"(r1), "r"(r2), "r"(r3) : "memory");
}
__device__ __forceinline__ void stsm4t(uint32_t a, uint32_t r0, uint32_t r1, uint32_t r2, uint32_t r3) {
    asm volatile("stmatrix.sync.aligned.m8n8.x4.trans.shared.b16 [%0], {%1,%2,%3,%4};" ::"r"(a), "r"(r0), "r"(r1), "r"(r2), "r"(r3) : "memory");
}
__device__ __forceinline__ void stg_b64_if(bool c, void* p, uint32_t x, uint32_t y) {
    asm volatile("{.reg .pred p; .reg .b64 a; setp.ne.u32 p, %3, 0; mov.b64 a, {%1,%2}; @p st.relaxed.gpu.global.b64 [%0], a;}" ::"l"(p), "r"(x), "r"(y), "r"((uint32_t)c) : "memory");
}
__device__ __forceinline__ void cp_async16(uint32_t dst, const void* src) { asm volatile("cp.async.cg.shared.global [%0], [%1], 16;" ::"r"(dst), "l"(src) : "memory"); }
__device__ __forceinline__ void cp_async16_ef(uint32_t dst, const void* src) {
    asm volatile("cp.async.cg.shared.global.L2::cache_hint [%0], [%1], 16, %2;" ::"r"(dst), "l"(src), "l"(evict_first()) : "memory");
}
__device__ __forceinline__ uint32_t hadd2h(uint32_t a, uint32_t b) { uint32_t r; asm("add.rn.f16x2 %0, %1, %2;" : "=r"(r) : "r"(a), "r"(b)); return r; }
__device__ __forceinline__ uint32_t hmax2h(uint32_t a, uint32_t b) { uint32_t r; asm("max.f16x2 %0, %1, %2;" : "=r"(r) : "r"(a), "r"(b)); return r; }
__device__ __forceinline__ uint32_t max3u(uint32_t a, uint32_t b, uint32_t c) { return __vimax3_u32(a, b, c); }
__device__ __forceinline__ void fence_gpu() { asm volatile("fence.acq_rel.gpu;" ::: "memory"); }

__device__ __forceinline__ void h_load(uint32_t sb, const uint8_t* hsrc, int pass, uint32_t rank, uint32_t rot, uint32_t wq) {
    const uint32_t bar = sb + SM_BAR + 8 * (B_HB + (pass & 1)), c = (wq + rot) & 3, dst = sb + SM_HB + (pass & 1) * HBUF + (rank * 4 + c) * HCH;
    const uint8_t* src = hsrc + ((size_t)pass * 65536 + c * 4096);
    if (wq == 0) e_expect(bar, 32768);
#pragma unroll
    for (int i = 0; i < H4; i++) {
        const uint32_t o = ((i + (rot >> 2)) & (H4 - 1)) * (4096 / H4);
        if (EF & 4) asm volatile("{.reg .pred p; elect.sync _|p, 0xffffffff;\n"
                     " @p cp.async.bulk.shared::cluster.global.mbarrier::complete_tx::bytes.multicast::cluster.L2::cache_hint [%0], [%1], %4, [%2], %3, %5;}"
                     ::"r"(dst + o), "l"(src + o), "r"(bar), "h"((uint16_t)3), "n"(4096 / H4), "l"(evict_first()) : "memory");
        else asm volatile("{.reg .pred p; elect.sync _|p, 0xffffffff;\n"
                     " @p cp.async.bulk.shared::cluster.global.mbarrier::complete_tx::bytes.multicast::cluster [%0], [%1], %4, [%2], %3;}"
                     ::"r"(dst + o), "l"(src + o), "r"(bar), "h"((uint16_t)3), "n"(4096 / H4) : "memory");
    }
}
__device__ __forceinline__ uint4 ldg_b128(const void* p) {
    uint4 v;
    asm volatile("{.reg .b128 t; .reg .b64 a, b; ld.relaxed.gpu.global.b128 t, [%4]; mov.b128 {a, b}, t; mov.b64 {%0,%1}, a; mov.b64 {%2,%3}, b;}"
                 : "=r"(v.x), "=r"(v.y), "=r"(v.z), "=r"(v.w) : "l"(p) : "memory");
    return v;
}
__device__ __forceinline__ void stg_b128_if(bool c, void* p, uint32_t x, uint32_t y, uint32_t z, uint32_t w) {
    asm volatile("{.reg .pred p; .reg .b128 t; .reg .b64 a, b; setp.ne.u32 p, %5, 0; mov.b64 a, {%1,%2}; mov.b64 b, {%3,%4}; mov.b128 t, {a, b}; @p st.relaxed.gpu.global.b128 [%0], t;}"
                 ::"l"(p), "r"(x), "r"(y), "r"(z), "r"(w), "r"((uint32_t)c) : "memory");
}
__device__ __forceinline__ float pretag(float x, uint32_t add, uint32_t keep) { return __uint_as_float((__float_as_uint(x) + add) & keep); }

template <bool MASK, class F>
__device__ __forceinline__ void softmax_rows(uint32_t src, uint32_t dst, uint32_t g16, int row0, F mid) {
    const uint32_t u = (g16 >> 7) & 3, e = ((g16 >> 9) << 3) | ((g16 >> 4) & 7);
    const uint32_t se = src + e * 8, su = se + u * 1088;
    const float2 p0 = lds2f(su), p1 = lds2f(su + 256), p2 = lds2f(su + 512), p3 = lds2f(su + 768);
    const float2 m0 = lds2f(se + 4352), m1 = lds2f(se + 4352 + 256), m2 = lds2f(se + 4352 + 512), m3 = lds2f(se + 4352 + 768);
    float a0 = (p0.x + p1.x) + (p2.x + p3.x), a1 = (p0.y + p1.y) + (p2.y + p3.y);
    const float a2 = (m0.x + m1.x) + (m2.x + m3.x), a3 = (m0.y + m1.y) + (m2.y + m3.y);
    mid(__float_as_uint(a3));
    if (MASK) {
        const int vis = row0 + (e >> 2) - 2 * (e & 3) - 8 * u;
        if (vis < 0) a0 = -1e9f / 0.08838834764831845f;
        if (vis < 1) a1 = -1e9f / 0.08838834764831845f;
    }
    int k = __float_as_int(fmaxf(fmaxf(a0, a1), fmaxf(a2, a3)));
    k ^= (k >> 31) & 0x7fffffff;
    const bool hi = g16 & 64;
    const int k0 = __reduce_max_sync(~0u, hi ? INT_MIN : k), k1 = __reduce_max_sync(~0u, hi ? k : INT_MIN);
    k = hi ? k1 : k0;
    const float m = __int_as_float(k ^ ((k >> 31) & 0x7fffffff));
    const float sl2 = 0.08838834764831845f * 1.4426950408889634f, mb = -m * sl2;
    sts1(dst + e * 16 + u * 4, pack2(ex2(fmaf(a0, sl2, mb)), ex2(fmaf(a1, sl2, mb))));
    sts1(dst + 512 + e * 4, pack2(ex2(fmaf(a2, sl2, mb)), ex2(fmaf(a3, sl2, mb))));
}

__device__ __forceinline__ uint32_t pack_h2(float lo, float hi) {
    uint32_t r; asm("cvt.rn.satfinite.f16x2.f32 %0, %1, %2;" : "=r"(r) : "f"(hi), "f"(lo)); return r;
}
__device__ __forceinline__ float2 unpack_h2(uint32_t u) {
    float2 r; asm("{.reg .b16 l, h; mov.b32 {l, h}, %2; cvt.f32.f16 %0, l; cvt.f32.f16 %1, h;}" : "=f"(r.x), "=f"(r.y) : "r"(u)); return r;
}
__device__ __forceinline__ uint32_t h2bf(uint32_t u) {
    uint32_t r;
    asm volatile("{.reg .b16 l, h; .reg .f32 a, b; mov.b32 {l, h}, %1; cvt.f32.f16 a, l; cvt.f32.f16 b, h; cvt.rn.bf16x2.f32 %0, b, a;}" : "=r"(r) : "r"(u));
    return r;
}
__device__ __forceinline__ void red_h8(void* p, uint32_t x, uint32_t y, uint32_t z, uint32_t w) {
    asm volatile("red.relaxed.gpu.global.add.noftz.v4.f16x2 [%0], {%1,%2,%3,%4};" ::"l"(p), "r"(x), "r"(y), "r"(z), "r"(w) : "memory");
}
__device__ __forceinline__ void red_h2_if(bool c, void* p, uint32_t x) {
    asm volatile("{.reg .pred p; setp.ne.u32 p, %2, 0; @p red.relaxed.gpu.global.add.noftz.f16x2 [%0], %1;}" ::"l"(p), "r"(x), "r"((uint32_t)c) : "memory");
}
__device__ __forceinline__ void red_h10(bool c, void* p, void* q, uint32_t x, uint32_t y, uint32_t z, uint32_t w, uint32_t e) {
    asm volatile("{.reg .pred p; setp.ne.u32 p, %7, 0; red.relaxed.gpu.global.add.noftz.v4.f16x2 [%0], {%2,%3,%4,%5};\n"
                 " @p red.relaxed.gpu.global.add.noftz.f16x2 [%1], %6;}" ::"l"(p), "l"(q), "r"(x), "r"(y), "r"(z), "r"(w), "r"(e), "r"((uint32_t)c) : "memory");
}
constexpr float SM_L2E = 0.08838834764831845f * 1.4426950408889634f;
template <int V> struct IC { static constexpr int value = V; };
typedef unsigned long long u64;
__device__ __forceinline__ uint32_t lo32(u64 v) { return (uint32_t)v; }
__device__ __forceinline__ uint32_t hi32(u64 v) { return (uint32_t)(v >> 32); }
__device__ __forceinline__ u64 ldg_u64(const void* p) { u64 v; asm volatile("ld.relaxed.gpu.global.b64 %0, [%1];" : "=l"(v) : "l"(p) : "memory"); return v; }
__device__ __forceinline__ void ldg_u64_if(u64& v, const void* p, bool c) {
    asm volatile("{.reg .pred p; setp.ne.u32 p, %2, 0; @p ld.relaxed.gpu.global.b64 %0, [%1];}" : "+l"(v) : "l"(p), "r"((uint32_t)c) : "memory");
}
struct RecTime { uint32_t go, x2, v, dx2, dv, h; };
__device__ __forceinline__ void rec_main(uint32_t sb, const CUtensorMap* tWo, uint8_t* arena, int role, int hinfo, int wg, uint32_t zero, const RecTime& tm) {
    const int hA = hinfo & 255;
    const int tid = threadIdx.x, t = tid & 127, lane = tid & 31, wi = t >> 5;
    const uint32_t bars = sb + SM_BAR;
    const int head = role >> 2, qd = role & 3, j = blockIdx.x & 1, kh = role & 1;
    const uint32_t mypar = head >= hA;
    const uint32_t ff = kh ^ mypar ^ FARF;
    const uint32_t wiu = __reduce_max_sync(~0u, wi);
    const bool warp0 = wiu == 0;
    const uint8_t* hsrc = (const uint8_t*)g_himg + kh * 32768 + j * 16384;
    auto tokbase = [&](int ty) { return ((ty + 1) << 21) + blk(lb_tok(head), mypar ^ ((hinfo >> (8 + ty)) & 1)); };
    const uint32_t tbw = tokbase(wg), tbq = tokbase(0) + (qd >> 1) * 2048 + (qd & 1) * 8;
#define KS(p) (4 * (((p) >> 1) & 7) + ((p) >> 4) + 2 * ((p) & 1))
    uint32_t w[32 - NL][4];
    uint4 wl5;
    if (wg == 2) bar_arrive(NB_WIN, 384);
    const uint32_t frow = ((lane >> 4) * 8 + (lane & 7)) * 128, fx = ((lane >> 3) & 1) ^ (lane & 7);
    {
#pragma unroll 1
        for (int i = 0; i < 4; i++) mbar_wait_w(bars + 8 * (B_W + (wg == 2 ? 8 + i : 2 * i + wg)), 0);
        const uint32_t stg = sb + wg * 65536;
#pragma unroll
        for (int p = NL; p < 32; p++) ldsm4t(w[p - NL], stg + KS(p) * 2048 + frow + ((fx ^ (2 * wi)) << 4));
#pragma unroll
        for (int i = 0; i < NL; i++) {
            wl5 = lds4(stg + KS(i) * 2048 + t * 16);
            if (i < 5) sts4(sb + sm_wl(i) + tid * 16, wl5.x, wl5.y, wl5.z, wl5.w);
        }
        fence_async_smem();
        if (wg < 2) bar_sync(NB_WG, 256);
        if (wg > 0) wait_count_w(&g_tick[32 + (lane & 3) * 8], 1);
        if (wg == 1) {
            if (t == 0) mbar_arrive_cluster(bars + 8 * B_HE, j ^ 1);
            asm volatile("fence.proxy.async.global;" ::: "memory");
            mbar_wait_w(bars + 8 * B_HE, 0);
#pragma unroll 1
            for (int i = 0; i < 2; i++) h_load(sb, hsrc, i, j, head, wiu);
        }
        TL(3 + wg)
    }
    uint32_t g16 = opaque(t * 16);
    {
        const uint32_t c16 = kh * 2048 + ((2 * j + (wi >> 1)) * 32 + lane) * 16;
        const uint32_t xso = blk(lb_x2(head), mypar), wr = ((wg * 4 + wi) ^ (head & ROTM)) & 7;
        const uint32_t pc = wg < 2 ? acc_piece(wr >> 2, qd, wr & 3) : acc_piece(kh, ff, wi);
        const uint32_t lm = sb + SM_HB + 4096 + (lane & 7) * 128;
        const uint32_t a0 = wg < 2 ? sb + SM_WL + wg * 2048 + frow + ((fx ^ (2 * wi)) << 4) : blk(LB_STAMP + (wi >> 1), mypar) + stamp_line(wi, lane >> 3) + (lane & 7) * 16;
        const uint32_t a1 = pc + lane * 16;
        const uint32_t a2 = wg < 2 ? pc + 512 + (lane >> 3) * 4 : (role >> 2) * 1024 + (lane < 8 ? (role & 3) * 128 : 384) + lane * 16;
        const uint32_t a3 = wg < 2 ? sb + SM_WO + (wr >> 2) * 32768 + frow + ((fx ^ (2 * (wr & 3))) << 4) : qd * 65536 + head * 2048 + wi * 512 + lane * 4;
        const uint32_t a4 = wg < 2 ? lm + ((fx ^ ((lane >> 4) * 4)) << 4) : lm + ((fx ^ (2 * wi)) << 4) + ((lane >> 4) + 2 * ff) * HCH;
        if (wg < 2) bar_arrive(NB_X2, 384);
        else bar_sync(NB_X2, 384);
        if (NL > 5) {
            sts4(sb + SM_WL2 + tid * 16, wl5.x, wl5.y, wl5.z, wl5.w);
            fence_async_smem();
            bar_sync(NB_WG + 1 + wg, 128);
        }
        sts4(sb + SM_TAB + wg * 5120 + g16, a0, xso + wg * 16384 + (wi & 1) * 2048 + (c16 >> 1),
             wg ? xso + (wg == 2 ? 32768 : 0) + t * 8 : blk(LB_STAMP + ((lane >> 1) & 1), (lane >> 2) & 1) + stamp_line(lane, qd) + head * 4, tbw + (wi & 1) * 16384 + c16);
        sts4(sb + SM_TAB + wg * 5120 + 2048 + g16, a1, a2, a3, a4);
        sts2(sb + SM_TAB + wg * 5120 + 4096 + t * 8, __uint_as_float(tbw + t * 16), __uint_as_float((wg ? tbq : tokbase(1)) + t * 16));
    }
    const uint32_t po = (1 << 20) + j * 16384 + kh * 2048;
    const uint32_t ONES = 0x3f803f80u, tabw = sb + SM_TAB + wg * 5120;
#define LAST ((g16 & 0x70) == 0x70)
    PROF_INIT

    auto pa_ptr = [&](int p) { return arena + (((p & 1) ^ 1) * 32768 + po + lds1(tabw + 4096 + (g16 >> 1))); };
    auto pa_request = [&](int p) { cp_async16(sb + SM_PA + wg * 2048 + g16, pa_ptr(p)); };
    auto pa_get = [&](int p) {
        asm volatile("cp.async.wait_all;" ::: "memory");
        uint4 pa = lds4(sb + SM_PA + wg * 2048 + g16);
        int it = 0;
#pragma unroll 1
        while (any_bit0(pa.x ^ ((p - 1) >> 1) ^ 1) && p > 0 && p <= NSEG) { pa = ldg_b128(pa_ptr(p)); spin_guard(++it); }
        return pa;
    };
    auto token_pass = [&](auto vc, int s, uint4 pa, auto mid) {
        constexpr bool V = decltype(vc)::value;
        const int p = s + 2, b = p & 1;
        const uint32_t ftag = (((p - 1) >> 1) & 1) ^ 1, ptag = ((p >> 1) & 1) ^ 1;
#define HB(ks) dadd(mkdesc(SB0 + SM_HB + ((ks) >> 2) * HCH + ((ks) & 3) * 32, 16, 1024, 1), b * (HBUF / 16))
        float acc[V ? 20 : 16];
#pragma unroll
        for (int i = 0; i < 4; i++) { acc[2 * i] = bflo((&pa.x)[i]); acc[2 * i + 1] = bfhi((&pa.x)[i]); }
#pragma unroll
        for (int i = 8; i < (V ? 20 : 16); i++) acc[i] = 0.f;
        mid(-1, acc);
        wg_fence();
#pragma unroll
        for (int i = 0; i < 32; i++) {
            constexpr int GAP = V ? SSG_V : SSG, SS0 = V ? SS0_V : SS0_K;
            const int u = i < SS0 ? 0 : (i - SS0 + GAP - 1) / GAP, q = i - (u < NL ? u : NL);
            if (i >= SS0 && (i - SS0) % GAP == 0 && u < NL) wgmma_tok_ss<V>(acc, dadd(mkdesc(SB0 + sm_wl(u), 8192, 1024, 1), (V ? 2 : wg) * 128), HB(KS(u)));
            else wgmma_tok_rs<V>(acc, w[q], HB(KS(NL + q)), 1);
            mid(i, acc);
        }
        wg_commit();
        const bool tg = V || !(g16 & 64);
        const uint32_t add = tg ? (ftag ^ 1) << 16 : 0u, keep = tg ? 0xfffe0000u : ~0u;
        const uint32_t add1 = V ? 0u : add, keep1 = V ? ~0u : keep;
        uint32_t add2 = !V && wg == 0 ? add : 0u, keep2 = !V && wg == 0 ? keep : ~0u;
        uint8_t* pdst = arena + (b * 32768 + (po ^ 2048) + lds1(tabw + 4096 + (g16 >> 1)));
        uint8_t* fdst = arena + ((b ^ 1) * 32768 + lds1(tabw + 12 + g16));
        mid(32, acc);
        if (PIN_EPI) asm volatile("" : "+l"(pdst), "+l"(fdst));
        wg_wait<0>();
        mid(33, acc);
        PROF(9)
        uint32_t r0 = pack2(pretag(acc[0], add, keep), pretag(acc[1], add1, keep1));
        uint32_t r1 = pack2(acc[2], acc[3]), r3 = pack2(acc[6], acc[7]);
        uint32_t r2 = pack2(pretag(acc[4], add2, keep2), pretag(acc[5], add2, keep2));
        if (!V) { r0 = movm(r0); r1 = movm(r1); r2 = movm(r2); r3 = movm(r3); }
        mid(34, acc);
        stg_b128_if(p < NSEG, pdst, settag(pack2(pretag(acc[8], (ptag ^ 1) << 16, 0xfffe0000u), acc[9]), ptag), pack2(acc[10], acc[11]), pack2(acc[12], acc[13]), pack2(acc[14], acc[15]));
        stg_b128_if(p > 0 && p <= NSEG, fdst, settag(r0, ftag), r1, !V && wg == 0 ? settag(r2, ftag) : r2, r3);
        PROF(10)
    };
    uint4 tf[2][2];
    auto load_tok = [&](int s, uint32_t o) {
        const uint8_t* ts = arena + ((s & 1) * 32768 + o);
#pragma unroll
        for (int a = 0; a < 2; a++)
#pragma unroll
            for (int b = 0; b < 2; b++) tf[a][b] = ldg_b128(ts + a * 16384 + b * 2048);
    };

    if (wg < 2) {
        mbar_wait_w(bars + 8 * B_HB, 0);
        token_pass(IC<0>(), -2, make_uint4(0, 0, 0, 0), [](int, float*) {});
        bar_arrive(NB_C, 384);
        if (wg == LAST_WG) bar_arrive(NB_WIN, 384);
        pa_request(1);
        mbar_wait_w(bars + 8 * (B_HB + 1), 0);
        uint4 pa = pa_get(1);
#pragma unroll 1
        for (int s = 0; s < NSEG; s++) {
            uint32_t w0[NL][4], xo, lm, fz = 0;
            const uint32_t wl = lds1(tabw + g16);
            uint32_t kq;
            token_pass(IC<0>(), s - 1, pa, [&](int i, float*) {
                if (i == W0_AT) {
#pragma unroll
                    for (int i = 0; i < NL; i++) ldsm4t(w0[i], wl + (sm_wl(i) - SM_WL));
                    if (W0_AT < 32) fz = clk32();
                }
                if (i == -1) {
                    if (wg == LAST_WG) bar_sync(NB_B, 256);
                    else bar_sync(NB_WIN, 384);
                }
                if (i == GATE_AT && wg != LAST_WG) bar_arrive(NB_B, 256);
                if (i == 33 && SPLIT_MEM) {
                    if (wg == LAST_WG) bar_arrive(NB_MEM, 384);
                    fz |= clk32();
                }
                if (i == 34 && ST_GATE && wg != LAST_WG) bar_sync(NB_F, 256);
                if (i == 32) {
                    xo = lds1(tabw + 4 + g16);
                    lm = lds1(tabw + 2060 + g16) + (s & 1) * HBUF;
                    if (KQ_AT <= 16) kq = lds1(tabw + 4096 + (g16 >> 1) * wg);
                }
            });
            asm volatile("" : "+r"(lm));
            if (SPLIT_MEM && wg == LAST_WG) bar_sync(NB_MEM2, 256);
            else bar_sync(NB_MEM, 384);
            PROF(1)
            float c[4][4];
            uint32_t bq[PD][4];
#define MEMF(it) ((lm ^ (((it) >> 3) * 32)) + ((it) & 7) * HCH)
#pragma unroll
            for (int it = 0; it < PD; it++) ldsm4(bq[it], MEMF(it));
#pragma unroll
            for (int it = 0; it < 16; it++) {
                uint32_t* bfr = bq[it % PD];
                const uint32_t* wa = 2 * it < NL ? w0[2 * it < NL ? 2 * it : 0] : w[2 * it < NL ? 0 : 2 * it - NL];
                const uint32_t* wb = 2 * it + 1 < NL ? w0[2 * it + 1 < NL ? 2 * it + 1 : 0] : w[2 * it + 1 < NL ? 0 : 2 * it + 1 - NL];
                float *ca = c[(2 * it) & 3], *cb = c[(2 * it + 1) & 3];
                if (it < 2) { mma16816z(ca, wa, bfr[0], bfr[1]); mma16816z(cb, wb, bfr[2], bfr[3]); }
                else { mma16816(ca, wa[0], wa[1], wa[2], wa[3], bfr[0], bfr[1]); mma16816(cb, wb[0], wb[1], wb[2], wb[3], bfr[2], bfr[3]); }
                if (it + PD < 16) ldsm4(bfr, MEMF(it + PD));
                if (it == KQ_AT) {
                    if (PFENCE) fz |= clk32();
                    load_tok(s, kq);
                }
            }
            if (QK_EARLY) bar_arrive(NB_QK + (__float_as_uint(c[0][0]) & zero), 384);
            const uint32_t r0 = pack2((c[0][0] + c[1][0]) + (c[2][0] + c[3][0]), (c[0][1] + c[1][1]) + (c[2][1] + c[3][1]));
            const uint32_t r1 = pack2((c[0][2] + c[1][2]) + (c[2][2] + c[3][2]), (c[0][3] + c[1][3]) + (c[2][3] + c[3][3]));
            if (!QK_EARLY) bar_arrive(NB_QK + (r0 & zero), 384);
            stg_rlx2(arena + xo, settag(movm(r0), (s & 1) ^ 1), movm(r1));
            const uint32_t tx = later(lds1(sb + SM_LX + 1040) + tm.x2, clk_after(r0, zero) + tm.dx2);
            g16 |= (fz | tx) & zero;
            PROF(2)
            {
                const uint32_t l16 = sb + (g16 & 0x1f0), g8 = g16 >> 1;
                const uint32_t tag = (s & 1) ^ 1, ttag = ((s >> 1) & 1) ^ 1;
                uint32_t wf[NPF][4], a3;
#define WF(f) (a3 + ((f) & 1) * 16384 + ((f) >> 1) * 2048)
                if (wg == 1) {
                    float sc[5][4];
                    uint4 (&kf)[2][2] = tf;
                    uint32_t qa[2][4], km[4], fz;
                    int it = 0;
                    bool bad;
#pragma unroll 1
                    do {
                        u64 qf[2], x[8];
                        const float2 u = lds2f(tabw + 4096 + g8);
                        if (KQ_AT > 16) load_tok(s, __float_as_uint(u.x));
                        else {
#pragma unroll 1
                            for (int i = it; i > 0; i &= zero) load_tok(s, __float_as_uint(u.x));
                        }
                        const uint8_t *xp = arena + lds1(tabw + 8 + g16), *tq = arena + ((s & 1) * 32768 + __float_as_uint(u.y));
                        asm volatile("" : "+l"(xp));
#pragma unroll
                        for (int a = 0; a < 2; a++) qf[a] = ldg_u64(tq + a * 16384);
                        spin_guard(++it);
                        wait_clk(tx);
                        PROF(8)
#pragma unroll
                        for (int i = 0; i < 8; i++) x[i] = ldg_u64(xp + (i >> 2) * 16384 + (i & 3) * 1024);
                        fz = clk32();
                        const uint32_t bt = or3(xor_or(lo32(qf[0]), lo32(qf[1]), ttag), xor_or(kf[0][0].x, kf[0][1].x, ttag), xor_or(kf[1][0].x, kf[1][1].x, ttag));
#pragma unroll
                        for (int a = 0; a < 2; a++) { qa[a][1] = or3(lo32(qf[a]), zero, 0); qa[a][3] = or3(hi32(qf[a]), zero, 0); }
                        fz |= clk32();
#pragma unroll
                        for (int a = 0; a < 2; a++) { qa[a][0] = hadd2v(lo32(x[2 * a]), lo32(x[2 * a + 1])); qa[a][2] = hadd2v(hi32(x[2 * a]), hi32(x[2 * a + 1])); }
#pragma unroll
                        for (int a = 0; a < 2; a++) { km[2 * a] = hadd2v(lo32(x[4 + 2 * a]), lo32(x[5 + 2 * a])); km[2 * a + 1] = hadd2v(hi32(x[4 + 2 * a]), hi32(x[5 + 2 * a])); }
                        bad = any_bit0(or3(or3(bt, xor_or(lo32(x[0]), lo32(x[1]), tag), xor_or(lo32(x[2]), lo32(x[3]), tag)), xor_or(lo32(x[4]), lo32(x[5]), tag), xor_or(lo32(x[6]), lo32(x[7]), tag)));
                    } while (bad);
                    PROFV(13, it - 1)
                    PROF(7)
                    mma16816z(sc[0], qa[0], kf[0][0].x, kf[0][0].y);
                    mma16816z(sc[1], qa[0], kf[0][0].z, kf[0][0].w);
                    mma16816z(sc[2], qa[0], kf[0][1].x, kf[0][1].y);
                    mma16816z(sc[3], qa[0], kf[0][1].z, kf[0][1].w);
                    mma16816z(sc[4], qa[0], km[0], km[1]);
                    mma16816(sc[0], qa[1][0], qa[1][1], qa[1][2], qa[1][3], kf[1][0].x, kf[1][0].y);
                    mma16816(sc[1], qa[1][0], qa[1][1], qa[1][2], qa[1][3], kf[1][0].z, kf[1][0].w);
                    mma16816(sc[2], qa[1][0], qa[1][1], qa[1][2], qa[1][3], kf[1][1].x, kf[1][1].y);
                    mma16816(sc[3], qa[1][0], qa[1][1], qa[1][2], qa[1][3], kf[1][1].z, kf[1][1].w);
                    mma16816(sc[4], qa[1][0], qa[1][1], qa[1][2], qa[1][3], km[2], km[3]);
                    const uint32_t sx = sb + SM_SX + (g16 & 0x1f0) * 5;
                    sts4(sx + (g16 >> 5 & 0x30), pack_h2(sc[0][0], sc[0][1]), pack_h2(sc[1][0], sc[1][1]),
                         pack_h2(sc[2][0], sc[2][1]), pack_h2(sc[3][0], sc[3][1]));
                    sts1(sx + 64 + (g16 >> 7 & 0xc), pack_h2(sc[4][0], sc[4][1]));
                    bar_arrive(NB_X1, 256);
                    if (s == 0) TX(15)
                    const uint32_t now = gtime32();
#pragma unroll
                    for (int n = 0; n < 5; n++) sts2(sb + SM_ST + g8 + n * 1088, sc[n][2], sc[n][3]);
                    bar_arrive(NB_H, 256);
                    PROF(3)
                    a3 = lds1(tabw + 2056 + g16) | (fz & zero);
                    asm volatile("{.reg .pred p; setp.lt.u32 p, %2, 128; @p red.relaxed.gpu.global.max.u32 [%0], %1;}"
                                 ::"l"(arena + lds1(sb + SM_TAB + 8 + g16)), "r"(__funnelshift_r(now * 8, s + 1, 8)), "r"(g16) : "memory");
                    auto h_next = [&]() {
                        asm volatile("fence.proxy.async.global;" ::: "memory");
                        if (s + 3 <= NSEG) h_load(sb, hsrc, s + 3, j, head, wiu);
                    };
                    if (H_AT == 0) h_next();
                    if (s == 0) mbar_wait_w(bars + 8 * B_WO, 0);
                    const uint32_t th = clk32() + tm.v;
                    if (PF_DLY) a3 += delay<PF_DLY>(zero);
#pragma unroll
                    for (int f = 0; f < NPF; f++) ldsm4t(wf[f], WF(f));
                    if (H_AT == 2) {
#pragma unroll 1
                        while ((int)(clk32() - th) < 0) {}
                        h_next();
                    }
                } else {
                    if (H_AT == 1 && g16 == 0) mbar_arrive_cluster(bars + 8 * B_HE, j ^ 1);
                    if (s == 0) { TL(9) mbar_wait_w(bars + 8 * B_WO, 0); TL(6) }
                    if (warp0 && !(s & 3)) wait_count_w(&g_tick[32 + ((g16 >> 4) & 3) * 8], min((s + 4) / 4 + 2, 17));
                    a3 = lds1(tabw + 2056 + g16);
#pragma unroll
                    for (int f = 0; f < NPF0; f++) ldsm4t(wf[f], WF(f));
                    const float2 u = lds2f(tabw + 4096 + g8);
                    const uint8_t *q0 = arena + (tag * 32768 + po + __float_as_uint(u.x)), *q1 = arena + (tag * 32768 + po + __float_as_uint(u.y));
                    if (H_AT == 1) {
                        mbar_wait_w(bars + 8 * B_HE, s & 1);
                        asm volatile("fence.proxy.async.global;" ::: "memory");
                    }
                    wait_clk(tx + tm.h);
                    int it = 0;
                    bool bad;
#pragma unroll 1
                    do {
                        const uint4 p0 = ldg_b128(q0), p1 = ldg_b128(q1);
                        if (H_AT == 1 && !it && s + 3 <= NSEG) h_load(sb, hsrc, s + 3, j, head, wiu);
                        spin_guard(++it);
                        if (NPF0 < NPF1) wait_clk(tx + tm.v);
#pragma unroll
                        for (int f = NPF0; f < NPF1; f++) ldsm4t(wf[f], WF(f));
                        sts4(sb + SM_PA + g16, p0.x, p0.y, p0.z, p0.w);
                        sts4(sb + SM_PA + 2048 + g16, p1.x, p1.y, p1.z, p1.w);
                        bad = any_bit0(xor_or(p0.x, p1.x, ((s + 1) >> 1) ^ 1)) && s + 2 <= NSEG;
                    } while (bad);
                    bar_sync(NB_H, 256);
                    PROF(3)
                    softmax_rows<true>(sb + SM_ST, sb + SM_PX, g16, qd * 8, [&](uint32_t v) {
                        a3 += v & zero;
#pragma unroll
                        for (int f = NPF1; f < NPF2; f++) ldsm4t(wf[f], WF(f));
                    });
#pragma unroll
                    for (int f = NPF2; f < NPF; f++) ldsm4t(wf[f], WF(f));
                }
                PROF(5)
                float2 ls, a12;
                uint8_t *d0, *d1;
                bar_sync(NB_X2, 384);
                float c[4][4];
                uint32_t obs[4][4];
#pragma unroll
                for (int q = 0; q < NOB; q++) ldsm4t(obs[q], l16 + SM_OX + q * 512);
                if (NOB > 1) __syncwarp();
#pragma unroll
                for (int q = 0; q < 4; q++) {
                    const uint32_t* ob = obs[q];
                    if (q > 0 && q + NOB - 1 < 4) ldsm4t(obs[q + NOB - 1], l16 + SM_OX + (q + NOB - 1) * 512);
                    if (q == L_AT) ls = lds2f(sb + SM_LX + g8);
                    if (q == 2) { a12 = lds2f(tabw + 2048 + g16); d0 = arena + (acc_slot(s + 1) + __float_as_uint(a12.x)); d1 = arena + (acc_slot(s + 1) + __float_as_uint(a12.y)); }
#pragma unroll
                    for (int f = 4 * q; f < 4 * q + 4; f++) {
                        const uint32_t* a = wf[f % NPF];
                        if (f < 4) mma16816z(c[f], a, ob[f & 2], ob[(f & 2) + 1]);
                        else mma16816(c[f & 3], a[0], a[1], a[2], a[3], ob[f & 2], ob[(f & 2) + 1]);
                        if (f + NPF < 16) ldsm4t(wf[f % NPF], WF(f + NPF));
                    }
                }
                pa = lds4(sb + SM_PA + wg * 2048 + g16);
                if (wg == LAST_WG) bar_arrive(NB_WIN, 384);
                const float i0 = rcp_fast(ls.x), i1 = rcp_fast(ls.y);
                uint32_t v[4];
#pragma unroll
                for (int m = 0; m < 4; m++) v[m] = pack_h2((c[m >> 1][(m & 1) * 2] + c[(m >> 1) + 2][(m & 1) * 2]) * i0, (c[m >> 1][(m & 1) * 2 + 1] + c[(m >> 1) + 2][(m & 1) * 2 + 1]) * i1);
                red_h10(LAST, d0, d1, v[0], v[1], v[2], __byte_perm(v[3], ACC_ONE, LAST ? 0x7610 : 0x3210), __byte_perm(v[3], ACC_ONE, 0x7632));
                g16 |= v[0] & zero;
                PROF(6)
            }
        }
        if (wg != LAST_WG) bar_sync(NB_WIN, 384);
    } else {
        TLC(0)
        auto request = [&](int s, uint32_t o) {
            cp_async16(sb + SM_PA + 4096 + g16, arena + (((s & 1) ^ 1) * 32768 + po + o));
            const uint8_t* ts = arena + ((s & 1) * 32768 + o);
#pragma unroll
            for (int i = 0; i < 4; i++) cp_async16(sb + SM_VF + i * 2048 + g16, ts + (i >> 1) * 16384 + (i & 1) * 2048);
        };
        auto fetch = [&](int s, auto wait, auto after) {
            const uint4 t1 = lds4(tabw + 2048 + g16);
            const uint32_t mo = acc_slot(s) + t1.x, eo = mo - (g16 & 0x1f0) + 512 + ((g16 >> 5) & 12);
            const uint8_t *ms[2] = {arena + mo, arena + (mo ^ 4096)}, *es[2] = {arena + eo, arena + (eo ^ 4096)};
            uint32_t e[4] = {0, 0, 0, 0}, sel = LAST ? 0x5410 : 0x3210, dst = t1.w + (s & 1) * HBUF;
            asm volatile("" : "+l"(ms[0]), "+l"(ms[1]), "+l"(es[0]), "+l"(es[1]), "+r"(e[0]), "+r"(e[1]), "+r"(e[2]), "+r"(e[3]), "+r"(sel), "+r"(dst));
            uint32_t late = wait(), fz;
            PROF(11) PROFV(0, gtime32())
            int it = 0;
            bool bad;
#pragma unroll 1
            do {
                uint4 m[4];
                uint32_t b = 0;
#pragma unroll
                for (int i = 0; i < 4; i++) {
                    m[i] = ldg_rlx4(ms[i >> 1] + (i & 1) * 16384);
                    ldg1_if(e[i], es[i >> 1] + (i & 1) * 16384, LAST);
                }
                if (ST_GATE && it == 0) bar_arrive(NB_F, 256);
                const uint32_t now = clk32();
                fz = now;
                after(now & zero);
                sts1(sb + SM_LX + 1040, now - min(late >> 8, 8u) * 57);
                late = 0;
                spin_guard(++it);
#pragma unroll
                for (int n = 0; n < 4; n++) {
                    const int i = n ^ STG_ORD;
                    if (STG_FENCE >> n & 1) fz |= clk32();
                    b |= xor_or(m[i].w, e[i], ACC_ALL);
                    stsm4t(dst + (i >> 1) * (2 - 4 * ff) * HCH + (i & 1) * 4 * HCH, h2bf(m[i].x), h2bf(m[i].y), h2bf(m[i].z), h2bf(__byte_perm(m[i].w, e[i], sel)));
                }
                bad = __any_sync(~0u, LAST && b > 0xffffu);
            } while (bad);
            bar_arrive(NB_MEM, 384);
            if (SPLIT_MEM) bar_arrive(NB_MEM2, 256);
            g16 |= fz & zero;
            PROFV(12, it - 1) PROF(1)
        };
        TX(0)
        if (F0_EARLY) fetch(0, []() { return 0u; }, [](uint32_t) {});
        TX(1)
#pragma unroll 1
        for (int p = 0; p < 2; p++) {
            if (p) pa_request(p);
            mbar_wait_w(bars + 8 * (B_HB + p), 0);
            TX(2 + 5 * p)
            token_pass(IC<1>(), p - 2, pa_get(p), [&](int i, float*) { if (i == -1) TX(3 + 5 * p) if (i == 33) TX(4 + 5 * p) });
            if (p == WO_AT && !(g16 & 0x1f0)) {
                const int c0 = (wiu >> 1) * 512 + qd * 128 + (wiu & 1) * 64;
                mbar_expect(bars + 8 * B_WO, 16384);
                tma2d(sb + SM_WO + wiu * 16384, tWo, c0, head * DH, bars + 8 * B_WO);
                tma2d(sb + SM_WO + wiu * 16384 + 8192, tWo, c0, head * DH + 64, bars + 8 * B_WO);
            }
            __syncwarp();
            if (p == 0) {
                bar_sync(NB_C, 384);
                TX(5)
                if (g16 == 0) mbar_arrive_cluster(bars + 8 * B_HE, j ^ 1);
                wait_count_w(&g_tick[32 + ((g16 >> 4) & 3) * 8], 2);
                asm volatile("fence.proxy.async.global;" ::: "memory");
                mbar_wait_w(bars + 8 * B_HE, 1);
                TX(6)
                h_load(sb, hsrc, 2, j, head, wiu);
            }
        }
        request(0, lds1(tabw + 4096 + (g16 >> 1)));
        if (!F0_EARLY) fetch(0, []() { return 0u; }, [](uint32_t) {});
#pragma unroll 1
        for (int s = 0;; s++) {
            const uint32_t tag = (s & 1) ^ 1, ttag = ((s >> 1) & 1) ^ 1, l16 = sb + (g16 & 0x1f0), g8 = g16 >> 1;
            const int p = s + 2;
            if (s == 1) TL(7)
            if (s == 0) TL(13)
            fence_async_smem();
            stg_b128_if(g16 < ((role & 3) ? 128 : 160), arena + (acc_slot(s + 3) + lds1(tabw + 2052 + g16)), 0, 0, 0, 0);
            const uint4 pa = pa_get(p);
            if (p <= NSEG) mbar_wait_w(bars + 8 * (B_HB + (p & 1)), (p >> 1) & 1);
            uint8_t* xd = arena + lds1(tabw + 4 + g16);
            uint32_t tx;
            token_pass(IC<1>(), s, pa, [&](int i, float* acc) {
                if (i == -1) { if (s == 0) TX(10) bar_sync(NB_QK, 384); }
                if (i == 33) {
                    const uint32_t r0 = pack2(acc[16], acc[17]);
                    stg_rlx2(xd, settag(r0, tag), pack2(acc[18], acc[19]));
                    tx = clk_after(r0, zero) + tm.dv;
                    PROF(2)
                }
            });
            uint4 (&vf)[2][2] = tf;
#pragma unroll
            for (int i = 0; i < 4; i++) vf[i >> 1][i & 1] = lds4(sb + SM_VF + i * 2048 + g16);
            uint32_t xv[4] = {0, 0, 0, 0};
            float oc[2][4], lc[4];
            auto pv = [&](uint32_t p0, uint32_t p1, uint32_t p2, uint32_t p3, uint32_t p4, auto mid) {
                lc[0] = lc[1] = lc[2] = lc[3] = 0.f;
                mma16816z(oc[0], &vf[0][0].x, p0, p1);
                mma16816z(oc[1], &vf[1][0].x, p0, p1);
                mma16816(lc, ONES, ONES, ONES, ONES, p0, p1);
                mma16816(oc[0], vf[0][1].x, vf[0][1].y, vf[0][1].z, vf[0][1].w, p2, p3);
                mma16816(oc[1], vf[1][1].x, vf[1][1].y, vf[1][1].z, vf[1][1].w, p2, p3);
                mma16816(lc, ONES, ONES, ONES, ONES, p2, p3);
                mid();
                mma1688(oc[0], xv[0], xv[1], p4);
                mma1688(oc[1], xv[2], xv[3], p4);
                mma1688(lc, ONES, ONES, p4);
            };
            uint32_t so, oo, to, fz = 0;
            int it = 0;
            bool bad;
#pragma unroll 1
            do {
#pragma unroll 1
                for (int i = it; i > 0; i &= zero) load_tok(s, lds1(tabw + 4096 + g8));
                u64 xr[4];
                const uint8_t* xp = arena + lds1(tabw + 8 + g16);
                asm volatile("" : "+l"(xp));
                auto load_v = [&](uint32_t z) {
#pragma unroll
                    for (int i = 0; i < 4; i++) xr[i] = ldg_u64(xp + z + i * 1024);
                };
                const uint32_t bt = or3(xor_or(vf[0][0].x, vf[0][1].x, ttag), xor_or(vf[1][0].x, vf[1][1].x, ttag), 0);
                uint32_t sa = sb + SM_SX + (g16 & 0x1f0) * 5;
                asm volatile("" : "+r"(sa));
                spin_guard(it);
                wait_clk(tx);
                PROF(3)
                if (s == 0 && it == 0) TX(11)
                if (it++ == 0) bar_sync(NB_X1, 256);
                if (VP_AT == 0) load_v(0);
                uint4 sx[5];
#pragma unroll
                for (int i = 0; i < 5; i++) sx[i] = lds4(sa + i * 16);
                __syncwarp();
                if (VP_AT == 1) load_v(0);
                if (VP_AT == 2) load_v(sx[0].x & zero);
                if (VP_AT == 3) load_v(sx[4].x & zero);
                uint32_t pm[5];
                uint32_t a[5];
#pragma unroll
                for (int n = 0; n < 5; n++) {
                    uint32_t u[4];
#pragma unroll
                    for (int w = 0; w < 4; w++) u[w] = n < 4 ? (&sx[w].x)[n] : (&sx[4].x)[w];
                    a[n] = hadd2h(hadd2h(u[0], u[1]), hadd2h(u[2], u[3]));
                }
                uint32_t m = hmax2h(hmax2h(hmax2h(a[0], a[1]), hmax2h(a[2], a[3])), a[4]);
                if (SH3) {
                    const uint32_t m1 = __shfl_xor_sync(~0u, m, 1), m2 = __shfl_xor_sync(~0u, m, 2), m3 = __shfl_xor_sync(~0u, m, 3);
                    m = hmax2h(hmax2h(m, m1), hmax2h(m2, m3));
                } else {
                    m = hmax2h(m, __shfl_xor_sync(~0u, m, 1));
                    m = hmax2h(m, __shfl_xor_sync(~0u, m, 2));
                }
                if (VP_AT == 4) load_v(m & zero);
                so = lds1(tabw + g16); oo = lds1(tabw + 2056 + g16); to = lds1(tabw + 4096 + g8);
                const float2 mm = unpack_h2(m);
                const float mf = -SM_L2E * fmaxf(mm.x, mm.y);
#pragma unroll
                for (int n = 0; n < 5; n++) { const float2 u = unpack_h2(a[n]); pm[n] = pack2(ex2(fmaf(u.x, SM_L2E, mf)), ex2(fmaf(u.y, SM_L2E, mf))); }
                PROF(4)
                pv(pm[0], pm[1], pm[2], pm[3], pm[4], [&]() {
                    if (PV_FENCE & 1) fz = clk32();
#pragma unroll
                    for (int i = 0; i < 2; i++) { xv[2 * i] = hadd2v(lo32(xr[2 * i]), lo32(xr[2 * i + 1])); xv[2 * i + 1] = hadd2v(hi32(xr[2 * i]), hi32(xr[2 * i + 1])); }
                });
                bad = any_bit0(or3(bt, xor_or(lo32(xr[0]), lo32(xr[1]), tag), xor_or(lo32(xr[2]), lo32(xr[3]), tag)));
                if (PV_FENCE & 2) fz |= clk32();
                stsm4(sb + SM_OX + g16, pack2(oc[0][0], oc[0][1]), pack2(oc[0][2], oc[0][3]), pack2(oc[1][0], oc[1][1]), pack2(oc[1][2], oc[1][3]));
                sts2(sb + SM_LX + g8, lc[0], lc[1]);
            } while (bad);
            if (s == 0) TX(12)
            PROFV(14, it - 1)
            PROF(5)
            bar_sync(NB_X2, 384);
            const uint8_t* sp = arena + so;
            uint4 sv;
            if (SV_AT != 1) sv = ldg_rlx4(sp);
            if (s == 0) TX(13)
            auto h_next = [&]() {
                asm volatile("fence.proxy.async.global;" ::: "memory");
                if (s + 3 <= NSEG) h_load(sb, hsrc, s + 3, j, head, wiu);
            };
            if (H_AT == 3) h_next();
            if (!REQ_LATE) request(s + 1, to);
            const uint32_t dz = TPV_DLY ? delay<TPV_DLY>(zero) : 0;
            {
                const uint4 pp = lds4(l16 + SM_PX + dz);
                pv(pp.x, pp.y, pp.z, pp.w, lds1(sb + SM_PX + 512 + ((g16 >> 2) & 0x7c)), [&]() {
                    if (SV_AT) fz |= clk32();
                    if (SV_AT == 1) sv = ldg_rlx4(sp);
                    if (SV_AT == 2) cp_async16(sb + SM_SV + g16, sp);
                });
            }
            const float i0 = rcp_fast(lc[0]), i1 = rcp_fast(lc[1]);
            bar_arrive(NB_WIN + ((__float_as_uint(i0) | fz) & zero), 384);
            if (H_AT == 4) h_next();
            uint8_t* od = (uint8_t*)g_O + ((size_t)s * (32 * NH * DH * 2) + oo);
            const uint32_t ov[4] = {pack2(oc[0][0] * i0, oc[0][1] * i1), pack2(oc[0][2] * i0, oc[0][3] * i1), pack2(oc[1][0] * i0, oc[1][1] * i1), pack2(oc[1][2] * i0, oc[1][3] * i1)};
#pragma unroll
            for (int a = 0; a < 4; a++) if (!O_LATE || s + 1 == NSEG) stg_rlx1(od + a * 128, ov[a]);
            if (REQ_LATE == 1) request(s + 1, to);
            PROF(6)
            if (s + 1 == NSEG) break;
            fetch(s + 1, [&]() {
                int it = 0;
#pragma unroll 1
                while (__any_sync(~0u, (int)(min(__vimin3_u32(sv.x, sv.y, sv.z), sv.w) >> 24) <= s)) {
                    if (SV_AT == 2 && it == 0) { asm volatile("cp.async.wait_all;" ::: "memory"); sv = lds4(sb + SM_SV + g16); }
                    else sv = ldg_rlx4(sp);
                    spin_guard(++it);
                }
                if (s == 0) TX(14)
                PROFV(15, it)
                const uint32_t tgo = (__reduce_max_sync(~0u, max(max3u(sv.x, sv.y, sv.z), sv.w)) + tm.go + (sv.x & zero)) << 8;
                PROF(7)
                int late;
#pragma unroll 1
                do { late = gtime32() * 8 - tgo; } while (late < 0);
                __syncwarp();
                return (uint32_t)late;
            }, [&](uint32_t z) {
#pragma unroll
                for (int a = 0; a < 4; a++) if (O_LATE) stg_rlx1(od + a * 128, ov[a]);
                if (REQ_LATE == 2) request(s + 1, to + z);
            });
            if (REQ_LATE == 3) request(s + 1, to);
        }
        TL(8) TLC(1)
    }
    asm volatile("cp.async.wait_all;" ::: "memory");
    PROF_OUT
}

struct RecMaps { CUtensorMap wq, wk, wv, wo; };
struct RecPtrs { const bf16 *x, *mem0, *c, *wmod, *w1, *w3; uint8_t* arena; uint32_t zero; const bf16 *w2, *w4, *wo; RecTime tm; const bf16 *wq, *wk; };

__device__ __forceinline__ float silu_bf(const bf16* c, int i) {
    const float v = __bfloat162float(c[i]);
    return bfround(__fdividef(v, 1.0f + __expf(-v)));
}
__device__ __noinline__ void rec_ln(float* coef, const RecPtrs& p, int id, int r0) {
    int r1 = 32;
    const int tid = threadIdx.x;
    const int lane = tid & 31, wid = tid >> 5;
    const uint32_t ring = smem_u32(coef) - SM_PRE + wid * 8192 + lane * 16;
    auto fetch = [&](int r) {
        if (r < r1) {
            const bf16* src = p.x + (size_t)(r * 64 + (id * 8 + wid) * 2) * DM + lane * 8;
#pragma unroll
            for (int i = 0; i < 8; i++) {
                if (EF & 2) cp_async16_ef(ring + (r & 1) * 4096 + i * 512, src + i * 256);
                else cp_async16(ring + (r & 1) * 4096 + i * 512, src + i * 256);
            }
        }
        asm volatile("cp.async.commit_group;" ::: "memory");
    };
    auto row8 = [&](uint32_t a, float* f) {
        const uint4 v = lds4(a);
        f[0] = bflo(v.x); f[1] = bfhi(v.x); f[2] = bflo(v.y); f[3] = bfhi(v.y); f[4] = bflo(v.z); f[5] = bfhi(v.z); f[6] = bflo(v.w); f[7] = bfhi(v.w);
    };
#pragma unroll 1
    for (int r = r0 - 2; r < r1; r++) {
        if (r >= r0) {
            asm volatile("cp.async.wait_group 1;" ::: "memory");
            const uint32_t a = ring + (r & 1) * 4096;
            float m[2] = {0.f, 0.f}, t[2];
#pragma unroll 1
            for (int ps = 0; ps < 2; ps++) {
                t[0] = t[1] = 0.f;
#pragma unroll 1
                for (int i = 0; i < 4; i++)
#pragma unroll
                    for (int h = 0; h < 2; h++) {
                        float f[8];
                        row8(a + h * 2048 + i * 512, f);
#pragma unroll
                        for (int e = 0; e < 8; e++) { const float d = f[e] - m[h]; t[h] = fmaf(d, ps ? d : 1.0f, t[h]); }
                    }
#pragma unroll
                for (int o = 16; o; o >>= 1) { t[0] += __shfl_xor_sync(~0u, t[0], o); t[1] += __shfl_xor_sync(~0u, t[1], o); }
                if (ps == 0) { m[0] = t[0] * (1.0f / DM); m[1] = t[1] * (1.0f / DM); }
            }
            t[0] = rsqrtf(t[0] * (1.0f / DM) + 1e-5f); t[1] = rsqrtf(t[1] * (1.0f / DM) + 1e-5f);
            if (r == r0) {
#pragma unroll 1
                for (int i = tid; i < 2 * DM / 4; i += 256) {
                    float4 u;
                    int it = 0;
                    uint32_t ok;
#pragma unroll 1
                    do {
                        uint4 v[8];
#pragma unroll
                        for (int k = 0; k < 8; k++) v[k] = ldg_rlx4(g_modp + k * 2 * DM + i * 4);
                        ok = 1;
                        u = make_float4(0.f, 0.f, 0.f, 0.f);
#pragma unroll
                        for (int k = 0; k < 8; k++) {
                            ok &= v[k].x & v[k].y & v[k].z & v[k].w;
                            u.x += __uint_as_float(v[k].x); u.y += __uint_as_float(v[k].y); u.z += __uint_as_float(v[k].z); u.w += __uint_as_float(v[k].w);
                        }
                        spin_guard(++it);
                    } while (!ok);
                    const uint32_t lo = pack2(u.x, u.y), hi = pack2(u.z, u.w);
                    const float one = i >= DM / 4 ? 1.0f : 0.0f;
                    *(float4*)(coef + i * 4) = make_float4(bflo(lo) + one, bfhi(lo) + one, bflo(hi) + one, bfhi(hi) + one);
                }
                bar_sync(NB_FIN0, 256);
                if (tid == 0 && r0 == 0) TL(2)
            }
            const int row = r * 64 + (id * 8 + wid) * 2;
#pragma unroll 1
            for (int i = 0; i < 4; i++) {
                const float4* cf = (const float4*)(coef + i * 256 + lane * 8);
                const float4 s0 = cf[0], s1 = cf[1], c0 = cf[256], c1 = cf[257];
                const float sh[8] = {s0.x, s0.y, s0.z, s0.w, s1.x, s1.y, s1.z, s1.w}, sc[8] = {c0.x, c0.y, c0.z, c0.w, c1.x, c1.y, c1.z, c1.w};
                const int own = ((row >> 4) & 1) == (i >> 1), rr = row & 15;
                const uint32_t off = ((row >> 5) + own) * 65536 + (i * 4 + (lane >> 3)) * 4096 + (rr + (own ? 0 : 16)) * 128 + (((lane & 7) ^ (rr & 7)) << 4);
#pragma unroll
                for (int h = 0; h < 2; h++) {
                    float y[8];
                    row8(a + h * 2048 + i * 512, y);
#pragma unroll
                    for (int e = 0; e < 8; e++) y[e] = fmaf((y[e] - m[h]) * t[h], sc[e], sh[e]);
                    *(uint4*)((uint8_t*)g_himg + (off ^ (h * 144))) = pack8(y);
                }
            }
            if (r == 0) {
                int v, it = 0;
#pragma unroll 1
                do { v = *(volatile int*)((uint8_t*)coef - SM_PRE + SM_BAR + 192); spin_guard(++it); } while (v == INT_MIN);
                if (v >= 0) r1 = 2;
            }
        }
        fetch(r + 2);
        if (r < r0 || (r > 0 && !(r & 1))) continue;
        bar_sync(r == 0 ? NB_C : r == 1 ? NB_FIN0 : NB_LN, r == 0 ? 320 : r == 1 ? 256 : 288);
        if (r < 2 && wid == r) {
            if (r == 1) bar_arrive(NB_B, 64);
            if (lane == 0) { signal_count(&g_tick[32 + id * 8]); TL(13) }
            __syncwarp();
        }
    }
}
template <int NQ, int CG>
__device__ __forceinline__ void side_gemv(const bf16* w, int ld, int ncol, const float* coef, float* red, float* out, int ostride, bool round) {
    constexpr int KG = 384 / CG, W = CG * 8;
    const int tid = threadIdx.x, cg = tid % CG, kg = tid / CG;
    float acc[NQ][8];
#pragma unroll
    for (int q = 0; q < NQ; q++)
#pragma unroll
        for (int j = 0; j < 8; j++) acc[q][j] = 0.f;
    if (cg * 8 < ncol) {
        const bf16* src = w + cg * 8;
        const uint32_t ring = smem_u32(red) + 36864 + tid * 16;
        auto fetch = [&](int k0, int slot) {
#pragma unroll
            for (int i = 0; i < 4; i++)
                if (k0 + i * KG < DM) {
                    if (EF & 1) cp_async16_ef(ring + (slot * 4 + i) * 6144, src + (size_t)(k0 + i * KG) * ld);
                    else cp_async16(ring + (slot * 4 + i) * 6144, src + (size_t)(k0 + i * KG) * ld);
                }
            asm volatile("cp.async.commit_group;" ::: "memory");
        };
#pragma unroll 1
        for (int g = 0; g < 5; g++) fetch(kg + g * 4 * KG, g);
#pragma unroll 1
        for (int k0 = kg, slot = 0; k0 < DM; k0 += 4 * KG) {
            fetch(k0 + 20 * KG, slot ? slot - 1 : 5);
            asm volatile("cp.async.wait_group 5;" ::: "memory");
#pragma unroll
            for (int i = 0; i < 4; i++) {
                const int k = k0 + i * KG;
                if (k < DM) {
                    const uint4 v = lds4(ring + (slot * 4 + i) * 6144);
                    const float f[8] = {bflo(v.x), bfhi(v.x), bflo(v.y), bfhi(v.y), bflo(v.z), bfhi(v.z), bflo(v.w), bfhi(v.w)};
#pragma unroll
                    for (int q = 0; q < NQ; q++) {
                        const float cf = coef[q * DM + k];
#pragma unroll
                        for (int j = 0; j < 8; j++) acc[q][j] = fmaf(cf, f[j], acc[q][j]);
                    }
                }
            }
            slot = slot == 5 ? 0 : slot + 1;
        }
    }
    __syncthreads();
#pragma unroll
    for (int q = 0; q < NQ; q++)
#pragma unroll
        for (int j = 0; j < 8; j++) red[(kg * NQ + q) * W + cg * 8 + j] = acc[q][j];
    __syncthreads();
#pragma unroll 1
    for (int i = tid; i < NQ * W; i += 384) {
        const int q = i / W, cidx = i % W;
        float t = 0.f;
#pragma unroll
        for (int k = 0; k < KG; k++) t += red[k * NQ * W + i];
        if (cidx < ncol) out[q * ostride + cidx] = round ? bfround(t) : t;
    }
}
__device__ __forceinline__ void side_window(const RecPtrs& p, int& step) {
    uint32_t v;
    int it = 0;
#pragma unroll 1
    do { v = ldg_rlx1(p.arena + blk(LB_STAMP, 0)); spin_guard(++it); } while ((int)(v >> 24) <= step && step < NSEG);
    step = v >> 24;
#pragma unroll 1
    while ((int)(gtime32() * 8 - ((v + p.tm.go + SW_T) << 8)) < 0) {}
    __syncwarp();
}
__device__ __noinline__ void side_prefetch(const RecPtrs& p, int& step, const void* base, uint32_t ld, uint32_t bytes, int rows, int per) {
#pragma unroll 1
    for (int r = threadIdx.x & 127, n = 0; r < rows; r += 128, n++) {
        if (n % per == 0) side_window(p, step);
        l2_prefetch((const uint8_t*)base + (size_t)r * ld, bytes);
    }
}
__device__ __noinline__ void rec_side(float* sm, const RecPtrs& p, int id) {
    const int tid = threadIdx.x;
    float *coef = sm, *red = sm + 3 * DM;
    if (tid < 256 && blockIdx.x < 128) rec_ln(sm + SM_PRE / 4, p, id, 2);
    if (tid >> 5 == 8) {
#pragma unroll 1
        for (int n = 1; n < 16; n++) {
            bar_sync(NB_LN, 288);
            if (tid == 256) { if (n == 1) wait_count1(&g_tick[32 + id * 8], 2); signal_count(&g_tick[32 + id * 8]); }
            __syncwarp();
        }
    }
    int step = 0;
    if (SGATE && tid >= 256) {
        wait_count_w(&g_tick[32 + (tid & 3) * 8], 1);
        side_prefetch(p, step, p.x + id * 256, DM * 2, 512, S_, 8 * SW_N);
        side_prefetch(p, step, p.wmod + (2 + id) * DM, 6 * DM * 2, 2048, DM, SW_N);
        side_prefetch(p, step, p.w3 + id * (FF / 4), FF * 2, FF / 2, DM, SW_N);
        side_prefetch(p, step, p.w1 + id * 256, DM * 2, 512, DM, 4 * SW_N);
    }
    __syncthreads();
    for (int i = tid; i < 2 * S_; i += 384) g_st[id * 2 * S_ + i] = 0.f;
    if (id == 0) for (int i = tid; i < 2 * 32; i += 384) g_pcnt[i * 8] = 0;
    if (id == 1) for (int i = tid; i < 6 * 256; i += 384) g_pflag[i] = 0;
    for (int i = tid; i < DM; i += 384) { coef[i] = silu_bf(p.c, i); coef[2 * DM + i] = 1.0f; }
    __syncthreads();
    if (tid == 0) TL(3)
    side_gemv<1, 128>(p.wmod + (2 + id) * DM, 6 * DM, DM, coef, red, g_mod + (2 + id) * DM, 0, true);
    __syncthreads();
    if (tid == 0) signal_count(&g_tick[8]);
    if (tid == 0) TL(4)
    side_gemv<1, 128>(p.w3 + id * (FF / 4), FF, FF / 4, coef + 2 * DM, red, g_vec + 3 * DM + id * (FF / 4), 0, false);
    if (tid == 0) wait_count1(&g_tick[8], 4);
    __syncthreads();
    for (int i = tid; i < DM; i += 384) { coef[i] = 1.0f + __ldcg(g_mod + 4 * DM + i); coef[DM + i] = __ldcg(g_mod + 3 * DM + i); }
    __syncthreads();
    if (id == 1 && tid < 32) {
        float t[5] = {0, 0, 0, 0, 0};
        for (int i = tid; i < DM; i += 32) {
            const float a = coef[i], b = coef[DM + i];
            t[0] += a; t[1] += a * a; t[2] += a * b; t[3] += b; t[4] += b * b;
        }
#pragma unroll
        for (int q = 0; q < 5; q++) { const float r = warp_sum(t[q]); if (tid == 0) g_cst[q] = r * (1.0f / DM); }
    }
    side_gemv<3, 32>(p.w1 + id * 256, DM, 256, coef, red, g_vec + id * 256, DM, false);
    if (tid == 0) TL(9)
    if (SGATE) {
        if (tid < 256) return;
        step = max(step, SW_END);
        if (SPF & 32) side_prefetch(p, step, p.x + id * 512 * DM, 2048, 2048, 512, SW_N);
        if (SPF & 2) side_prefetch(p, step, p.w1 + id * 256 * DM, 2048, 2048, 256, SW_N);
        if (SPF & 4) side_prefetch(p, step, p.w2 + id * 256 * DM, 2048, 2048, 256, SW_N);
        if (SPF & 1) side_prefetch(p, step, p.wo + id * 1024 * DM, 2048, 2048, 1024, SW_N);
        return;
    }
#pragma unroll 1
    for (int m = 0; m < 6; m++) {
        if (!((SPF >> m) & 1)) continue;
        const uint8_t* w = (const uint8_t*)(m == 0 ? p.wo : m == 1 ? p.w1 : m == 2 ? p.w2 : m == 3 ? p.w3 : m == 4 ? p.w4 : p.x);
        const int n = (m == 0 ? 4096 : m < 3 ? 1024 : m == 5 ? 2048 : FF) * 2048 / 4;
#pragma unroll 1
        for (int o = tid * 128; o < n; o += 384 * 128) {
            asm volatile("prefetch.global.L2 [%0];" ::"l"(w + id * n + o));
            __nanosleep(SPF_NS);
        }
    }
    if (tid == 0) TL(5)
}

__global__ void __cluster_dims__(2, 1, 1) __launch_bounds__(384, 1)
k_rec(const __grid_constant__ RecMaps mp, const __grid_constant__ RecPtrs p) {
    extern __shared__ uint8_t smraw[];
    const uint32_t sb = smem_u32(smraw);
    if ((sb & 0x3FFFF) != SB0) __trap();
    const uint32_t bars = sb + SM_BAR;
    const int tid = threadIdx.x, lane = tid & 31, b = blockIdx.x;
    const int wid = __reduce_max_sync(~0u, tid >> 5);
    const uint32_t rank = b & 1;
    uint8_t* arena = p.arena;
    volatile int* sinfo = (volatile int*)(smraw + SM_BAR + 192);
    if (tid == 0) TL(0)
    if (tid == 0) sinfo[0] = INT_MIN;
    if (tid == 352) {
        for (int i = 0; i < 17; i++) mbar_init(bars + 8 * i, i == B_WO ? 4 : 1);
        asm volatile("fence.mbarrier_init.release.cluster;" ::: "memory");
        mbar_expect(bars + 8 * B_ROLE, 8);

    }
    __syncwarp();
    asm volatile("barrier.cluster.arrive.relaxed.aligned;" ::: "memory");
    int pr = 0, hA = 0;
    if (wid < 8) {
        if (b < 128) {
            const int cb = (b & 15) * 128, k0 = (b >> 4) * 128 + (tid >> 4);
            uint4 v[8];
#pragma unroll
            for (int i = 0; i < 8; i++) v[i] = __ldg((const uint4*)(p.wmod + (size_t)(k0 + 16 * i) * (6 * DM) + cb + (tid & 15) * 8));
            float acc[8] = {0, 0, 0, 0, 0, 0, 0, 0};
            const float sl = silu_bf(p.c, k0 + 16 * (lane & 7));
#pragma unroll
            for (int i = 0; i < 8; i++) {
                const float sv = __shfl_sync(~0u, sl, i, 16);
                acc[0] += sv * bflo(v[i].x); acc[1] += sv * bfhi(v[i].x); acc[2] += sv * bflo(v[i].y); acc[3] += sv * bfhi(v[i].y);
                acc[4] += sv * bflo(v[i].z); acc[5] += sv * bfhi(v[i].z); acc[6] += sv * bflo(v[i].w); acc[7] += sv * bfhi(v[i].w);
            }
            float* red = (float*)(smraw + SM_PRE);
            *(float4*)(red + (tid >> 4) * 128 + (tid & 15) * 8) = make_float4(acc[0], acc[1], acc[2], acc[3]);
            *(float4*)(red + (tid >> 4) * 128 + (tid & 15) * 8 + 4) = make_float4(acc[4], acc[5], acc[6], acc[7]);
            bar_sync(NB_FIN0, 256);
            if (wid < 4) {
                float t = 0;
#pragma unroll
                for (int i = 0; i < 16; i++) t += red[i * 128 + tid];
                stg_rlx1(&g_modp[(b >> 4) * 2 * DM + cb + tid], __float_as_uint(t) | 1u);
                if (rank) TL(2)
            }
        } else {
            rec_ln((float*)(smraw + SM_PRE), p, b - 128, 0);
        }
    } else if (wid >= 10 && b >= 128) {
        {
            const int u = (b - 128) * 2 + wid - 10;
            const uint16_t* src = (const uint16_t*)p.mem0 + (lane & 3) * 2 * DM + (u >> 1) * 128 + (u & 1) * 32 + (lane >> 2);
            stg_rlx4(arena + (LB_STAMP << 13) + u * 2048 + (lane >> 4) * 1024 + ((lane >> 3) & 1) * 256 + (lane & 7) * 16, 0, 0, 0, 0);
#pragma unroll 1
            for (int r = 0; r < 4; r++) {
                uint32_t w[5];
#pragma unroll
                for (int e = 0; e < 4; e++) {
                    const uint16_t* q = src + (r >> 1) * 512 + (r & 1) * 16 + (e & 2) * 32 + (e & 1) * 8;
                    w[e] = pack_h2(bflo(q[0]), bflo(q[DM]));
                }
                w[4] = __shfl_sync(~0u, __byte_perm(w[3], ACC_ALL, 0x7632), lane * 8 + 7);
                w[3] = __byte_perm(w[3], ACC_ALL, (lane & 7) == 7 ? 0x7610 : 0x3210);
#pragma unroll 1
                for (int i = 0; i < 3; i++) {
                    uint8_t* d = arena + acc_slot(i) + acc_piece(r >> 1, u >> 1, (u & 1) * 2 + (r & 1));
                    stg_rlx4(d + lane * 16, w[0], w[1], w[2], w[3]);
                    if (lane < 8) stg_rlx1(d + 512 + lane * 4, w[4]);
                    w[0] = w[1] = w[2] = w[3] = w[4] = 0;
                }
            }
            bar_arrive(NB_C, 320);
        }
    } else if (rank == 0) {
        uint32_t best = ~0u;
        const int pg = wid < 10 ? 0 : 1 + (b >> 1) % 3;
        uint32_t* q = (uint32_t*)(arena + (pg << 21) + (pg ? blk(b >> 1, wid & 1) : blk(LB_PROBE, wid & 1) + b * 16));
        if (lane < 8) stg_rlx1(q + lane, 0);
        uint2 tk2 = ldg_rlx2(&g_tick[0]);
        __syncwarp();
        if (lane == 0) {
            q += 3;
            uint32_t v = atomicAdd(q, 1u);
#pragma unroll 1
            for (int r = 0; r < NPROBE; r++) {
                const uint32_t t0 = clk32() + (v >> 8);
                v = atomicAdd(q + (v >> 8), 1u);
                uint32_t t1;
                asm volatile("{.reg .pred p; setp.eq.u32 p, %1, 0xffffffff; @p exit; mov.u32 %0, %%clock;}" : "=r"(t1) : "r"(v) : "memory");
                best = min(best, t1 - t0);
            }
            sinfo[wid - 6] = best;
        }
        bar_sync(NB_KDONE, b < 128 ? 128 : 64);
        if (W_PF && wid == 9 && b < 128) {
#pragma unroll 1
            for (int i = lane; i < W_PF * 16; i += 32) {
                const int r = (b >> 1) + 64 * (i >> 4);
                l2_prefetch((i & 8 ? p.wk : p.wq) + (size_t)((r >> 1) + (r & 1) * 512) * (NH * DH) + (i & 7) * 512, 1024);
            }
        }
        if (wid == 8) {
            if (b < 128) TL(2)
            const int par = sinfo[2] <= sinfo[3] ? 0 : 1, ncl = gridDim.x >> 1;
            int tk = 0, it = 0;
            const uint32_t vote = b < 128 && (sinfo[4] <= sinfo[5] ? 0 : 1) != par ? 256u << (8 * ((b >> 1) % 3)) : 0u;
            if (b >= 128) {
#pragma unroll 1
                while (!__all_sync(~0u, (int)((tk2.x + tk2.y) & 255) >= ncl - 2)) { tk2 = ldg_rlx2(&g_tick[0]); spin_guard(++it); }
            }
            if (lane == 0) tk = atomicAdd(&g_tick[par], 1u + vote) & 255;
#pragma unroll 1
            while (!__all_sync(~0u, (int)((tk2.x + tk2.y) & 255) >= ncl)) { tk2 = ldg_rlx2(&g_tick[0]); spin_guard(++it); }
            tk = __shfl_sync(~0u, tk, 0);
            const int n0 = tk2.x & 255, n1 = tk2.y & 255;
            hA = min(n0 >> 1, NH);
            const int q0 = 2 * hA, q1 = 2 * NH - q0;
            const int over = tk - (par ? q1 : q0), lack = max(par ? q0 - n0 : q1 - n1, 0);
            if (over < 0) pr = par ? q0 + tk : tk;
            else if (over < lack) pr = (par ? n0 : q0 + n1) + over;
            else pr = -1 - (over - lack + (par ? max(n0 - q0, 0) : 0));
#pragma unroll
            for (int i = 0; i < 3; i++) hA |= (((tk2.x + tk2.y) >> (8 + 8 * i)) & 255) > 10 ? 256 << i : 0;
        }
    }
    asm volatile("barrier.cluster.wait.aligned;" ::: "memory");
    if (wid == 8) {
        if (rank == 0) {
            if (lane == 0) {
                uint32_t rsb;
                asm("mapa.shared::cluster.u32 %0, %1, 1;" : "=r"(rsb) : "r"(sb));
                asm volatile("st.async.shared::cluster.mbarrier::complete_tx::bytes.v2.u32 [%0], {%1, %2}, [%3];"
                             ::"r"(rsb + SM_BAR + 192), "r"(pr), "r"(hA), "r"(rsb + SM_BAR + 8 * B_ROLE) : "memory");
                sinfo[0] = pr; sinfo[1] = hA;
                if (b >= 128) atomicOr(&g_tick[4], (pr < 0 ? 4u : 1u) << ((b - 128) >> 1));
            }
        } else {
            mbar_wait_w(bars + 8 * B_ROLE, 0);
            pr = sinfo[0];
        }
        TL(1)
        __syncwarp();
        bar_arrive(NB_A, 384);
        if (b >= 128 && pr < 0) bar_sync(NB_B, 64);
        if (pr >= 0) {
            const int pu = __reduce_max_sync(~0u, pr), c0 = (pu >> 1) * 128 + rank * 64, r0 = (pu & 1) * 512;
            bool fast = false;
#pragma unroll 1
            for (int n = 0; n < 12; n++) {
                const int rot = b >= 128 ? 8 : 0, i = (n + rot) % 12;
                if (rot && n == 4) bar_sync(NB_B, 64);
                if (n >= W_INFL && !fast) {
                    const uint32_t v = ldg_rlx1(&g_tick[32 + (lane & 3) * 8]);
                    mbar_wait_w(bars + 8 * (B_W + (n - W_INFL + rot) % 12), 0);
                    fast = __all_sync(~0u, v != 0);
                }
                const int m = i < 8 ? i & 1 : 2, k = i < 8 ? i >> 1 : i - 8;
                const uint32_t dst = sb + m * 65536 + k * 16384, br = bars + 8 * (B_W + i);
                if (lane == 0) {
                    mbar_expect(br, 16384);
#pragma unroll
                    for (int u = 0; u < 2; u++) {
                        if (EF & 8) asm volatile("cp.async.bulk.tensor.2d.shared::cluster.global.mbarrier::complete_tx::bytes.L2::cache_hint [%0], [%1, {%3, %4}], [%2], %5;"
                                                 ::"r"(dst + u * 8192), "l"(&mp.wq + m), "r"(br), "r"(c0), "r"(r0 + k * 128 + u * 64), "l"(evict_first()) : "memory");
                        else tma2d(dst + u * 8192, &mp.wq + m, c0, r0 + k * 128 + u * 64, br);
                    }
                }
                __syncwarp();
            }
        }
    } else {
        bar_sync(NB_A, 384);
    }
    const int prr = __reduce_max_sync(~0u, sinfo[0]);
    hA = __reduce_max_sync(~0u, sinfo[1]);
    if (prr < 0) {
        int j = (b - 128) >> 1;
        if (b < 128) {
            uint32_t v;
            int it = 0;
#pragma unroll 1
            do { v = __reduce_max_sync(~0u, ldg_rlx1(&g_tick[4])); spin_guard(++it); } while (__popc(v) < 2);
            j = v == 3 ? -1 - prr : (v & 1) ^ 1;
        }
        rec_side((float*)smraw, p, j * 2 + rank);
        return;
    }
    const int role = (prr >> 1) * 4 + rank * 2 + (prr & 1);
    rec_main(sb, &mp.wo, arena, role, hA, wid >> 2, p.zero, p.tm);
}

__device__ __forceinline__ void wgmma_ss192(float* d, uint64_t a, uint64_t b, int sc) {
    asm volatile("{.reg .pred p; setp.ne.b32 p, %98, 0;\n wgmma.mma_async.sync.aligned.m64n192k16.f32.bf16.bf16 "
                 "{%0,%1,%2,%3,%4,%5,%6,%7,%8,%9,%10,%11,%12,%13,%14,%15,%16,%17,%18,%19,%20,%21,%22,%23,%24,%25,%26,%27,%28,%29,%30,%31,%32,%33,%34,%35,%36,%37,%38,%39,%40,%41,%42,%43,%44,%45,%46,%47,%48,%49,%50,%51,%52,%53,%54,%55,%56,%57,%58,%59,%60,%61,%62,%63,%64,%65,%66,%67,%68,%69,%70,%71,%72,%73,%74,%75,%76,%77,%78,%79,%80,%81,%82,%83,%84,%85,%86,%87,%88,%89,%90,%91,%92,%93,%94,%95}, %96, %97, p, 1, 1, 0, 1;}"
                 : F16(d, 0), F16(d, 16), F16(d, 32), F16(d, 48), F16(d, 64), F16(d, 80) : "l"(a), "l"(b), "r"(sc));
}

constexpr uint32_t P_B = 81920, P_PLANE = 40960, P_VEC = 212992, P_ROW = P_VEC + 6144, P_BAR = P_ROW + 4096, P_SMEM = P_BAR + 256;
constexpr uint32_t P_OUT = 180224, P_OUT3 = P_B + 2 * P_PLANE;
#define PPH 1
#define FLAG_ST "st.release.gpu.global.u32"
#define FLAG_LD "ld.acquire.gpu.global.u32"
#define EFA 0x1e7
#define EFB 0x1ff
#define ALIAS 0
#define E0 3
#define SL_B0 0x5555
#define SL_B1 0xaaaa
#define SL_C 0x2492490
#define SL_A0 0x7777
#define SL_A1 0x77dd
#define HFENCE 2
#define X_DLY 4000
#define OWN 1
constexpr int P_ST = 5, P_ST0 = 4;
constexpr int PB_F = 0, PB_E = 5, PB_X = 10, PB_OUT = 12;
enum { C_Y = 0, C_G = 1, C_X1 = 2, C_U = 3, C_S1 = 8, C_S3 = 9 };
enum { V_GA = 0, V_A = 1, V_B = 2, V_GB = 3, V_VA = 4, V_VB = 5, V_VC = 6, V_C3 = 7 };
struct PostMaps { CUtensorMap o, wo, y, w1, g, w2, x1, w3, u, w4, out, x; };

struct GeluK { float k0, k1, kh; };
__device__ __forceinline__ GeluK gelu_k(float c) { return {0.7978845608028654f * c, 0.7978845608028654f * 0.044715f * c * c * c, 0.5f * c}; }
__device__ __forceinline__ float gelu_s(float t, const GeluK& k) {
    const float u = t * fmaf(t * t, k.k1, k.k0);
    float th; asm("tanh.approx.f32 %0, %1;" : "=f"(th) : "f"(u));
    const float hx = k.kh * t;
    return fmaf(hx, th, hx);
}
__device__ __forceinline__ float2 ldsv(uint32_t a) {
    float2 v; asm("ld.shared.v2.f32 {%0,%1}, [%2];" : "=f"(v.x), "=f"(v.y) : "r"(a)); return v;
}
__device__ __forceinline__ void wait_smem(uint32_t a, int target) {
    int it = 0;
#pragma unroll 1
    while (true) {
        int v;
        asm volatile("ld.acquire.cta.shared.u32 %0, [%1];" : "=r"(v) : "r"(a) : "memory");
        if (__all_sync(~0u, v >= target)) break;
        spin_guard(++it);
    }
}

#define PP(i)
#define PH_(c, w, i)
struct Pipe { int st, ph; };
__device__ __forceinline__ void adv(Pipe& p) { if (++p.st == P_ST) { p.st = 0; p.ph ^= 1; } }
__device__ __forceinline__ int u_col(int r, int nb) { return r ? 512 + r * 1024 + nb * 128 : nb * 192; }

template <bool A>
__device__ __forceinline__ void post_produce(uint32_t sb, const PostMaps& mp, int mb, int nb, int rank) {
    const int rh = 2 * mb + rank, lane = threadIdx.x & 31;
    const uint32_t full = sb + P_BAR + 8 * PB_F, empty = sb + P_BAR + 8 * PB_E;
    Pipe p = {(P_ST0 + E0) % P_ST, !E0};
#pragma unroll 1
    for (int ph = 0; ph < 9; ph++) {
        const int GS = ph == 0 ? 8 : ph == 6 ? 3 : 2, kb0 = ph < 7 ? 0 : ph * 16 - 88;
        const CUtensorMap* tm = &mp.o + 2 * (ph < 3 ? ph : ph < 6 ? 3 : 4) + !A;
        const uint64_t pol = ((A ? EFA : EFB) >> ph) & 1 ? evict_first() : evict_normal();
        const bool own = OWN && (ph == 1 || ph == 3);
        const int n0 = ph >= 3 && ph < 6 ? u_col(ph - 3, nb) : nb * 128;
        const int amul = ph == 0 ? 256 : 64, arow = ph == 0 ? rh * 8 : rh * 64;
        const int wr = ph == 2 ? min(max(rh + min(lane >> 3, 2) - 1, 0), 31) : rh ^ ((lane >> 3) & 1);
        const uint32_t* fl = &g_pflag[(ph < 3 ? ph - 1 : ph < 6 ? C_X1 : ph - 3) * 256 + wr * 8 + (lane & 7)];
        uint32_t have = ph == 0 || ph == 5 ? ~0u : 0u;
        PH_(A && ph == PPH, 0, 26) PH_(A && ph == PPH, 1, 26)
#pragma unroll 1
        for (int q = 0; q < 8; q++) {
            const int src = own && q < 2 ? nb ^ q : (q + (nb & 6)) & 7;
            const bool skip = own && q == 0, both = own && q == 1;
            const uint32_t need = skip ? 0 : (ph == 2 ? 0x10101 : both ? 0x101 : 1) << src;
            if (A && (have & need) != need) {
                int it = 0;
#pragma unroll 1
                do {
                    uint32_t v;
                    asm volatile(FLAG_LD " %0, [%1];" : "=r"(v) : "l"(fl) : "memory");
                    have = __ballot_sync(~0u, v != 0);
                    spin_guard(++it);
                } while ((have & need) != need);
                PH_(ph == PPH && q == own, 0, 23) PH_(ph == PPH, 0, 24) PH_(ph == PPH && q == own, 1, 23) PH_(ph == PPH, 1, 24)
                asm volatile("fence.proxy.async.global;" ::: "memory");
            }
            if (!A && ph == 3 && q == 1) wait_smem(sb + P_BAR + 8 * (PB_OUT + (lane & 1)), 3);
            const int row = arow + (ph == 2 ? (int)((0x04000301u >> ((src & 6) * 4)) & 7) - 2 : 0);
            const uint32_t bytes = (skip ? 16384 : 32768) + (ph == 3 ? 8192 : 0);
            if ((ph | q) == 0) asm volatile("barrier.cluster.wait.aligned;" ::: "memory");
#pragma unroll 1
            for (int e = kb0 + (src + 1) * GS, kb = e - GS + (ph | q ? 0 : E0); kb < e; kb++) {
                const uint32_t f = full + 8 * p.st;
                mbar_wait_w(empty + 8 * p.st, p.ph ^ 1);
                if (A) {
                    const uint32_t a = sb + p.st * 16384 + rank * 8192;
                    if (both) { e_tma2d(a, tm, kb * 64, row, f, pol); e_tma2d(a + 8192 - rank * 16384, tm, kb * 64, row ^ 64, f, pol); }
                    else if (!skip) e_tma2d_mc(a, tm, kb * amul, row, f, pol);
                } else {
                    const uint32_t b = sb + P_B + p.st * 8192;
                    e_expect(f, bytes);
                    e_tma2d(b, tm, n0, kb * 64, f, pol);
                    e_tma2d(b + P_PLANE, tm, n0 + 64, kb * 64, f, pol);
                    if (ph == 3 && both) mbar_wait_w(empty + 8 * p.st - 16, p.ph);
                    if (ph == 3) e_tma2d(b + 2 * P_PLANE, tm, n0 + 128, kb * 64, f, pol);
                }
                PH_(PPH == 0 && ph == 0 && q == 0 && kb + GS == e + E0, 0, 20 + A) PH_(PPH == 0 && ph == 0 && q == 0 && kb + GS == e + E0, 1, 20 + A)
                adv(p);
            }
        }
    }
    if (A) {
#pragma unroll 1
        for (int i = 0; i < P_ST; i++) mbar_wait_w(empty + 8 * i, p.ph ^ (i >= p.st));
    }
}

#define I4(d, i) "f"(d[i]), "f"(d[i + 1]), "f"(d[i + 2]), "f"(d[i + 3])
#define I16(d, i) I4(d, i), I4(d, i + 4), I4(d, i + 8), I4(d, i + 12)
__device__ __forceinline__ void pick16(float* v, int n, const float* c1, float2 a, float2 b, const float* old) {
    asm volatile("{PKT: .branchtargets PK0, PK1, PK2, PK3, PK4, PK5, PK6, PK7, PK8, PK9, PK10, PK11; brx.idx.uni %8, PKT;\n"
                 "PK0: fma.rn.f32 %0, %9, %11, %15; fma.rn.f32 %1, %9, %12, %16; fma.rn.f32 %2, %10, %11, %17; fma.rn.f32 %3, %10, %12, %18; fma.rn.f32 %4, %9, %13, %19; fma.rn.f32 %5, %9, %14, %20; fma.rn.f32 %6, %10, %13, %21; fma.rn.f32 %7, %10, %14, %22; bra.uni PKE;\n"
                 "PK1: fma.rn.f32 %0, %9, %11, %23; fma.rn.f32 %1, %9, %12, %24; fma.rn.f32 %2, %10, %11, %25; fma.rn.f32 %3, %10, %12, %26; fma.rn.f32 %4, %9, %13, %27; fma.rn.f32 %5, %9, %14, %28; fma.rn.f32 %6, %10, %13, %29; fma.rn.f32 %7, %10, %14, %30; bra.uni PKE;\n"
                 "PK2: fma.rn.f32 %0, %9, %11, %31; fma.rn.f32 %1, %9, %12, %32; fma.rn.f32 %2, %10, %11, %33; fma.rn.f32 %3, %10, %12, %34; fma.rn.f32 %4, %9, %13, %35; fma.rn.f32 %5, %9, %14, %36; fma.rn.f32 %6, %10, %13, %37; fma.rn.f32 %7, %10, %14, %38; bra.uni PKE;\n"
                 "PK3: fma.rn.f32 %0, %9, %11, %39; fma.rn.f32 %1, %9, %12, %40; fma.rn.f32 %2, %10, %11, %41; fma.rn.f32 %3, %10, %12, %42; fma.rn.f32 %4, %9, %13, %43; fma.rn.f32 %5, %9, %14, %44; fma.rn.f32 %6, %10, %13, %45; fma.rn.f32 %7, %10, %14, %46; bra.uni PKE;\n"
                 "PK4: fma.rn.f32 %0, %9, %11, %47; fma.rn.f32 %1, %9, %12, %48; fma.rn.f32 %2, %10, %11, %49; fma.rn.f32 %3, %10, %12, %50; fma.rn.f32 %4, %9, %13, %51; fma.rn.f32 %5, %9, %14, %52; fma.rn.f32 %6, %10, %13, %53; fma.rn.f32 %7, %10, %14, %54; bra.uni PKE;\n"
                 "PK5: fma.rn.f32 %0, %9, %11, %55; fma.rn.f32 %1, %9, %12, %56; fma.rn.f32 %2, %10, %11, %57; fma.rn.f32 %3, %10, %12, %58; fma.rn.f32 %4, %9, %13, %59; fma.rn.f32 %5, %9, %14, %60; fma.rn.f32 %6, %10, %13, %61; fma.rn.f32 %7, %10, %14, %62; bra.uni PKE;\n"
                 "PK6: fma.rn.f32 %0, %9, %11, %63; fma.rn.f32 %1, %9, %12, %64; fma.rn.f32 %2, %10, %11, %65; fma.rn.f32 %3, %10, %12, %66; fma.rn.f32 %4, %9, %13, %67; fma.rn.f32 %5, %9, %14, %68; fma.rn.f32 %6, %10, %13, %69; fma.rn.f32 %7, %10, %14, %70; bra.uni PKE;\n"
                 "PK7: fma.rn.f32 %0, %9, %11, %71; fma.rn.f32 %1, %9, %12, %72; fma.rn.f32 %2, %10, %11, %73; fma.rn.f32 %3, %10, %12, %74; fma.rn.f32 %4, %9, %13, %75; fma.rn.f32 %5, %9, %14, %76; fma.rn.f32 %6, %10, %13, %77; fma.rn.f32 %7, %10, %14, %78; bra.uni PKE;\n"
                 "PK8: fma.rn.f32 %0, %9, %11, %79; fma.rn.f32 %1, %9, %12, %80; fma.rn.f32 %2, %10, %11, %81; fma.rn.f32 %3, %10, %12, %82; fma.rn.f32 %4, %9, %13, %83; fma.rn.f32 %5, %9, %14, %84; fma.rn.f32 %6, %10, %13, %85; fma.rn.f32 %7, %10, %14, %86; bra.uni PKE;\n"
                 "PK9: fma.rn.f32 %0, %9, %11, %87; fma.rn.f32 %1, %9, %12, %88; fma.rn.f32 %2, %10, %11, %89; fma.rn.f32 %3, %10, %12, %90; fma.rn.f32 %4, %9, %13, %91; fma.rn.f32 %5, %9, %14, %92; fma.rn.f32 %6, %10, %13, %93; fma.rn.f32 %7, %10, %14, %94; bra.uni PKE;\n"
                 "PK10: fma.rn.f32 %0, %9, %11, %95; fma.rn.f32 %1, %9, %12, %96; fma.rn.f32 %2, %10, %11, %97; fma.rn.f32 %3, %10, %12, %98; fma.rn.f32 %4, %9, %13, %99; fma.rn.f32 %5, %9, %14, %100; fma.rn.f32 %6, %10, %13, %101; fma.rn.f32 %7, %10, %14, %102; bra.uni PKE;\n"
                 "PK11: fma.rn.f32 %0, %9, %11, %103; fma.rn.f32 %1, %9, %12, %104; fma.rn.f32 %2, %10, %11, %105; fma.rn.f32 %3, %10, %12, %106; fma.rn.f32 %4, %9, %13, %107; fma.rn.f32 %5, %9, %14, %108; fma.rn.f32 %6, %10, %13, %109; fma.rn.f32 %7, %10, %14, %110;\n"
                 "PKE: }"
                 : "=f"(v[0]), "=f"(v[1]), "=f"(v[2]), "=f"(v[3]), "=f"(v[4]), "=f"(v[5]), "=f"(v[6]), "=f"(v[7])
                 : "r"(n), "f"(c1[0]), "f"(c1[1]), "f"(a.x), "f"(a.y), "f"(b.x), "f"(b.y), I16(old, 0), I16(old, 16), I16(old, 32), I16(old, 48), I16(old, 64), I16(old, 80));
}
template <int PH, class F>
__device__ __forceinline__ void post_mma(uint32_t sb, float* acc, Pipe& p, int NK, int wg, uint32_t rel, bool lead, int pi, F hook) {
    const uint32_t full = sb + P_BAR + 8 * PB_F;
    constexpr uint64_t DA = PH == 0 ? mkdesc(SB0, 128, 1024, 0) : mkdesc(SB0, 16, 1024, 1);
    constexpr uint64_t DB = mkdesc(SB0 + P_B, P_PLANE, 1024, 1);
    auto release = [&](uint32_t a) { asm volatile("{.reg .pred p; setp.gt.u32 p, %0, 63; @p mbarrier.arrive.shared::cluster.b64 _, [%0];}" ::"r"(a) : "memory"); };
    uint32_t prev = 0;
    if (OWN && (PH & 1)) { if (HFENCE == 2) fence_async_smem(); bar_sync(12 + wg, 128); }
    bool ok = false;
#pragma unroll 1
    for (int kb = 0; kb < NK; kb++) {
        if (!ok) mbar_wait_w(full + 8 * p.st, p.ph);
        const uint32_t a = (uint32_t)DA + (OWN && (PH & 1) && kb < 2 ? P_OUT / 16 + wg * 1024 + kb * 512 : p.st * 1024 + wg * 512), b = (uint32_t)DB + p.st * 512;
        wg_fence();
#pragma unroll
        for (int k = 0; k < 4; k++) {
            const uint64_t da = (DA & 0xffffffff00000000ull) | (a + k * (PH == 0 ? 16 : 2)), db = (DB & 0xffffffff00000000ull) | (b + k * 128);
            if (PH == 3) wgmma_ss192(acc, da, db, (kb | k) != 0);
            else wgmma_ss128<PH == 0>(acc, da, db, (kb | k) != 0);
        }
        wg_commit();
        if (kb == 0) { PP(pi) if (PH == 0 && wg == 0) TL(11) }
        const uint32_t cur = rel + 8 * p.st;
        adv(p);
        hook(-1);
        uint32_t t;
        asm volatile("{.reg .pred p; mbarrier.test_wait.parity.shared.b64 p, [%1], %2; selp.u32 %0, 1, 0, p;}" : "=r"(t) : "r"(full + 8 * p.st), "r"(p.ph) : "memory");
        wg_wait<1>();
        release(prev);
        ok = __all_sync(~0u, t);
        prev = cur;
        hook(kb);
    }
    wg_wait<0>();
    release(prev);
    PP(pi + 1)
}

__global__ void __cluster_dims__(2, 1, 1) __launch_bounds__(384, 1)
k_post(const __grid_constant__ PostMaps mp) {
    extern __shared__ uint8_t smraw[];
    const uint32_t sb = smem_u32(smraw);
    if ((sb & 0x3FFFF) != SB0) __trap();
    const int tid = threadIdx.x, lane = tid & 31;
    const int mb = blockIdx.x >> 3, nb = blockIdx.x & 7, rank = blockIdx.x & 1;
    const uint32_t bars = sb + P_BAR;
    PH_(PPH == 0 && tid == 0, 0, 22) PH_(PPH == 0 && tid == 0, 1, 22)
    const int w = __reduce_max_sync(~0u, (tid >> 5) - 8);
    if (w == 1) {
        if (lane == 0) {
#pragma unroll
            for (int i = 0; i < PB_OUT; i++) mbar_init(bars + 8 * i, i >= PB_E && i < PB_X ? 4 : 1);
            mbar_arrive(bars + 8 * (PB_F + P_ST0));
            asm volatile("mbarrier.arrive.shared.b64 _, [%0], 4;" ::"r"(bars + 8 * (PB_E + P_ST0)) : "memory");
            sts4(bars + 8 * PB_OUT, 0, 0, 0, 0);
            asm volatile("fence.mbarrier_init.release.cluster; fence.proxy.async.shared::cta;" ::: "memory");
        }
        __syncwarp();
    }
    asm volatile("barrier.cluster.arrive.relaxed.aligned;" ::: "memory");
    if (w == 1) {
#pragma unroll
        for (int i = 0; i < E0; i++) {
            const int st = (P_ST0 + i) % P_ST, kb = (nb & 6) * 8 + i;
            const uint32_t f = bars + 8 * (PB_F + st);
            e_expect(f, 32768);
#pragma unroll
            for (int h = 0; h < 2; h++) {
                e_tma2d(sb + st * 16384 + h * 8192, &mp.o, kb * 256, mb * 16 + h * 8, f, evict_first());
                e_tma2d(sb + P_B + st * 8192 + h * P_PLANE, &mp.wo, nb * 128 + h * 64, kb * 64, f, evict_first());
            }
        }
    }
    if (w != 0 && w != 3) asm volatile("barrier.cluster.wait.aligned;" ::: "memory");
    if (w >= 0) {
        asm volatile("setmaxnreg.dec.sync.aligned.u32 40;");
        if (w == 0) {
            post_produce<false>(sb, mp, mb, nb, rank);
        } else if (w < 3) {
            const int wg = w - 1, rh = 2 * mb + wg;
            float* rowc = (float*)(smraw + P_ROW) + (wg * 64 + lane * 2) * 8;
            int nout = 0, sig = 0;
            if (X_DLY) __nanosleep(X_DLY);
            if (wg && lane < 9) asm volatile("prefetch.tensormap [%0];" ::"l"(&mp.y + lane) : "memory");
            e_expect(bars + 8 * (PB_X + wg), 16384);
            e_tma2d(sb + P_OUT + wg * 16384, &mp.x, nb * 128, rh * 64, bars + 8 * (PB_X + wg), evict_first());
            e_tma2d(sb + P_OUT + wg * 16384 + 8192, &mp.x, nb * 128 + 64, rh * 64, bars + 8 * (PB_X + wg), evict_first());
            if (wg == 0) {
#pragma unroll 1
                for (int i = 0; i < 11; i++) {
                    const float* src = i < 4 ? g_mod + ((0x5342 >> (4 * i)) & 15) * DM + nb * 128 : g_vec + (i < 7 ? (i - 4) * DM + nb * 128 : 3 * DM + u_col(max(i - 8, 0), nb) + (i == 8) * 128);
                    if (i != 8 || lane < 16) cp_async16(sb + P_VEC + i * 512 - (i > 8) * 256 + lane * 16, src + lane * 4);
                }
                *(uint4*)&g_modp[blockIdx.x * 128 + lane * 4] = make_uint4(0, 0, 0, 0);
                if (blockIdx.x == 64) *(uint2*)&g_tick[lane * 2] = make_uint2(0, 0);
                asm volatile("cp.async.wait_all;" ::: "memory");
                const float4 a = lds4f(sb + P_VEC + V_A * 512 + lane * 16);
                sts4f(sb + P_VEC + V_A * 512 + lane * 16, 1.0f + a.x, 1.0f + a.y, 1.0f + a.z, 1.0f + a.w);
                bar_arrive(3, 288);
            }
#pragma unroll 1
            for (int i = 0; i < 9; i++) {
                const int cnt = i == 8 ? 6 : (0x54392180u >> (4 * i)) & 15;
                if (cnt < C_S1) {
                    const bool isu = cnt >= C_U && cnt < 6;
                    const int ng = cnt == C_U ? 3 : 2, c0 = isu ? u_col(cnt - C_U, nb) : nb * 128;
                    const uint32_t src = sb + (cnt == C_U ? P_OUT3 : P_OUT) + wg * ng * 8192;
#pragma unroll 1
                    for (int j = 0; j < ng; j++) {
                        bar_sync(4 + 4 * wg + (sig++ & 3), 160);
                        if (lane == 0) {
                            if (HFENCE) fence_async_smem();
                            PH_(cnt == PPH - 1, wg, 20)
                            asm volatile("cp.async.bulk.tensor.2d.global.shared::cta.bulk_group [%0, {%2, %3}], [%1]; cp.async.bulk.commit_group;"
                                         ::"l"(&mp.y + 2 * (isu ? 3 : min(cnt, 4))), "r"(src + j * 8192), "r"(c0 + j * 64), "r"(rh * 64) : "memory");
                        }
                        __syncwarp();
                    }
                    if (lane == 0) {
                        asm volatile("cp.async.bulk.wait_group 0; fence.proxy.async.global;" ::: "memory");
                        PH_(cnt == PPH - 1, wg, 21)
                        asm volatile("st.release.cta.shared.u32 [%0], %1;" ::"r"(bars + 8 * (PB_OUT + wg)), "r"(nout + 1) : "memory");
                        if (cnt < 6) asm volatile(FLAG_ST " [%0], %1;" ::"l"(&g_pflag[cnt * 256 + rh * 8 + nb]), "r"(1) : "memory");
                        PH_(cnt == PPH - 1, wg, 22)
                    }
                    nout++;
                    __syncwarp();
                    continue;
                }
                bar_sync(4 + 4 * wg + (sig++ & 3), 160);
#pragma unroll 1
                for (int q = 0; q < (cnt == C_S1 ? 3 : 1); q++) {
                    const float4 v = lds4f(sb + P_ROW + wg * 2048 + q * 512 + lane * 16);
                    asm volatile("red.relaxed.gpu.global.add.v4.f32 [%0], {%1, %2, %3, %4};"
                                 ::"l"((float4*)g_st + (cnt == C_S1 ? q : 3) * (S_ / 2) + rh * 32 + lane), "f"(v.x), "f"(v.y), "f"(v.z), "f"(v.w) : "memory");
                }
                __syncwarp();
                uint32_t* c = &g_pcnt[(cnt - C_S1) * 256 + rh * 8];
                if (lane == 0) { signal_count(c); wait_count1(c, 8); }
                __syncwarp();
                const float4* sp = (const float4*)g_st + rh * 32 + lane;
                float4 u[3] = {__ldcg(sp + (cnt == C_S1 ? 0 : 3) * (S_ / 2)), __ldcg(sp + S_ / 2), __ldcg(sp + S_)};
#pragma unroll 1
                for (int h = 0; h < 2; h++) {
                    const float id = 1.0f / DM;
                    const float m = u[0].x * id, var = fmaxf(u[0].y * id - m * m, 0.f) + 1e-5f, r = rsqrtf(var);
                    float sc = r, m2 = 0.f;
                    if (cnt == C_S1) {
                        m2 = r * (u[1].x * id - m * g_cst[0]) + g_cst[3];
                        const float e2 = r * r * (u[2].x * id - 2.0f * m * u[1].y * id + m * m * g_cst[1]) + 2.0f * r * (u[2].y * id - m * g_cst[2]) + g_cst[4];
                        sc = r * rsqrtf(fmaxf(e2 - m2 * m2, 0.f) + 1e-5f);
                    }
                    const GeluK k = gelu_k(sc);
                    *(float4*)(rowc + h * 8) = make_float4(k.k0, k.k1, k.kh, -m);
                    *(float4*)(rowc + h * 8 + 4) = make_float4(var * r, -m2 * var * r, r, -m * r);
#pragma unroll
                    for (int q = 0; q < 3; q++) { u[q].x = u[q].z; u[q].y = u[q].w; }
                }
                bar_arrive(1 + wg, 160);
            }
        } else {
            post_produce<true>(sb, mp, mb, nb, rank);
        }
    } else {
        asm volatile("setmaxnreg.inc.sync.aligned.u32 232;");
        const int wg = __reduce_max_sync(~0u, tid >> 7), wi = (tid >> 5) & 3, g = lane >> 2, tq = lane & 3;
        const bool lead = (tid & 127) == 0;
        uint32_t rel = 0;
        if ((tid & 127) < 2) asm("mapa.shared::cluster.u32 %0, %1, %2;" : "=r"(rel) : "r"(bars + 8 * PB_E), "r"(tid & 1));
        PP(0)
        if (tid == 0) TL(10)
        uint32_t vec = sb + P_VEC + tq * 8;
        const uint32_t stw = sb + (wi * 16 + ((lane >> 3) & 1) * 8 + (lane & 7)) * 128 + (((lane >> 4) ^ (lane & 7)) << 4);
        int sig = 0;
        auto signal = [&]() { bar_arrive(4 + 4 * wg + (sig++ & 3), 160); };
        auto put64 = [&](uint32_t o, const float* v) {
#pragma unroll
            for (int jj = 0; jj < 4; jj++, v += 8) stsm4((stw + o) ^ (jj << 5), pack2(v[0], v[1]), pack2(v[2], v[3]), pack2(v[4], v[5]), pack2(v[6], v[7]));
            if (HFENCE < 2) fence_async_smem();
            signal();
        };
        auto out_free = [&](int n) { wait_smem(bars + 8 * (PB_OUT + (lane & 1)), n); };
        const uint32_t rowc = sb + P_ROW + (wg * 64 + wi * 16 + g) * 32, o128 = P_OUT + wg * 16384;
        const uint32_t rsum = sb + P_ROW + wg * 2048 + (wi * 16 + g) * 8;
        Pipe pa = {P_ST0, 1};
        auto none = [](int) {};
        uint32_t keep[32];
#define KEEP(jn, e) (((e) & 1) ? bfhi(keep[2 * (jn) + ((e) >> 1)]) : bflo(keep[2 * (jn) + ((e) >> 1)]))
        float mu1[2], r1[2];
        {
            float acc[64];
            post_mma<0>(sb, acc, pa, 64, wg, rel, lead, 1, [&](int kb) {
                if (kb != 40) return;
                bar_sync(3, 288);
                mbar_wait_w(bars + 8 * (PB_X + wg), 0);
#pragma unroll
                for (int jj = 0; jj < 8; jj++) ldsm4(keep + jj * 4, (stw + o128 + (jj >> 2) * 8192) ^ ((jj & 3) << 5));
            });
            asm volatile("" : "+r"(vec) :: "memory");
            float st[2][6];
#pragma unroll
            for (int q = 0; q < 6; q++) st[0][q] = st[1][q] = 0.f;
#pragma unroll
            for (int jn = 0; jn < 16; jn++) {
                const float2 ga = ldsv(vec + V_GA * 512 + jn * 32), a = ldsv(vec + V_A * 512 + jn * 32);
                float xa[4];
#pragma unroll
                for (int e = 0; e < 4; e++) {
                    xa[e] = fmaf((e & 1) ? ga.y : ga.x, acc[4 * jn + e], KEEP(jn, e));
                    st[e >> 1][0] += xa[e]; st[e >> 1][1] = fmaf(xa[e], xa[e], st[e >> 1][1]);
                    acc[4 * jn + e] = ((e & 1) ? a.y : a.x) * xa[e];
                }
                keep[2 * jn] = pack2(xa[0], xa[1]); keep[2 * jn + 1] = pack2(xa[2], xa[3]);
                if ((jn & 7) == 7) put64(o128 + (jn >> 3) * 8192, acc + 4 * jn - 28);
            }
            PP(3)
#pragma unroll
            for (int jn = 0; jn < 16; jn++) {
                const float2 a = ldsv(vec + V_A * 512 + jn * 32), b = ldsv(vec + V_B * 512 + jn * 32);
#pragma unroll
                for (int e = 0; e < 4; e++) {
                    const float y = acc[4 * jn + e], aa = (e & 1) ? a.y : a.x, bb = (e & 1) ? b.y : b.x;
                    float* s = st[e >> 1];
                    s[2] += y; s[3] = fmaf(aa, y, s[3]); s[4] = fmaf(y, y, s[4]); s[5] = fmaf(bb, y, s[5]);
                }
            }
#pragma unroll
            for (int h = 0; h < 2; h++)
#pragma unroll
                for (int q = 0; q < 6; q++) { st[h][q] += __shfl_xor_sync(~0u, st[h][q], 1); st[h][q] += __shfl_xor_sync(~0u, st[h][q], 2); }
            if (tq < 3) {
#pragma unroll
                for (int h = 0; h < 2; h++)
                    sts2(rsum + tq * 512 + h * 64, tq == 0 ? st[h][0] : tq == 1 ? st[h][2] : st[h][4], tq == 0 ? st[h][1] : tq == 1 ? st[h][3] : st[h][5]);
            }
            signal();
            PP(29)
        }
        {
            float acc[64];
            post_mma<1>(sb, acc, pa, 16, wg, rel, lead, 4, none);
            float c1[2], c2[2], c3[2];
            GeluK gk[2];
            bar_sync(1 + wg, 160);
#pragma unroll
            for (int h = 0; h < 2; h++) {
                const float4 a = lds4f(rowc + h * 256), b = lds4f(rowc + h * 256 + 16);
                gk[h] = {a.x, a.y, a.z}; c1[h] = a.w; c2[h] = b.x; c3[h] = b.y; mu1[h] = b.w; r1[h] = b.z;
            }
#pragma unroll
            for (int jn = 0; jn < 16; jn++) {
                const float2 va = ldsv(vec + V_VA * 512 + jn * 32), vb = ldsv(vec + V_VB * 512 + jn * 32), vc = ldsv(vec + V_VC * 512 + jn * 32);
#pragma unroll
                for (int e = 0; e < 4; e++) {
                    const int h = e >> 1;
                    const float t = fmaf(c1[h], (e & 1) ? va.y : va.x, fmaf(c2[h], (e & 1) ? vb.y : vb.x, fmaf(c3[h], (e & 1) ? vc.y : vc.x, acc[4 * jn + e])));
                    acc[4 * jn + e] = gelu_s(t, gk[h]);
                }
                if ((jn & 7) == 7) put64(o128 + (jn >> 3) * 8192, acc + 4 * jn - 28);
            }
            PP(6)
        }
        {
            float acc[64];
            post_mma<2>(sb, acc, pa, 16, wg, rel, lead, 7, none);
#pragma unroll
            for (int jn = 0; jn < 16; jn++) {
                const float2 a = ldsv(vec + V_A * 512 + jn * 32), b = ldsv(vec + V_B * 512 + jn * 32);
#pragma unroll
                for (int e = 0; e < 4; e++) {
                    const int h = e >> 1;
                    acc[4 * jn + e] += fmaf(fmaf(KEEP(jn, e), r1[h], mu1[h]), (e & 1) ? a.y : a.x, (e & 1) ? b.y : b.x);
                }
                if ((jn & 7) == 7) put64(o128 + (jn >> 3) * 8192, acc + 4 * jn - 28);
            }
            PP(9)
            float st[2][2] = {{0.f, 0.f}, {0.f, 0.f}};
#pragma unroll
            for (int jn = 0; jn < 16; jn++) {
                const float2 gb = ldsv(vec + V_GB * 512 + jn * 32);
                float z[4];
#pragma unroll
                for (int e = 0; e < 4; e++) {
                    const float x1 = acc[4 * jn + e];
                    st[e >> 1][0] += x1; st[e >> 1][1] = fmaf(x1, x1, st[e >> 1][1]);
                    z[e] = fmaf((e & 1) ? gb.y : gb.x, x1, KEEP(jn, e));
                }
                keep[2 * jn] = pack2(z[0], z[1]); keep[2 * jn + 1] = pack2(z[2], z[3]);
            }
#pragma unroll
            for (int h = 0; h < 2; h++)
#pragma unroll
                for (int q = 0; q < 2; q++) { st[h][q] += __shfl_xor_sync(~0u, st[h][q], 1); st[h][q] += __shfl_xor_sync(~0u, st[h][q], 2); }
            if (tq < 2) sts2(rsum + tq * 64, tq ? st[1][0] : st[0][0], tq ? st[1][1] : st[0][1]);
            signal();
            PP(30)
        }
        {
            float old[96], acc[64];
            post_mma<3>(sb, old, pa, 16, wg, rel, lead, 10, none);
            uint32_t v3 = vec + V_C3 * 512;
            float c1[2];
            GeluK gk[2];
            bar_sync(1 + wg, 160);
#pragma unroll
            for (int h = 0; h < 2; h++) { const float4 a = lds4f(rowc + h * 256); gk[h] = {a.x, a.y, a.z}; c1[h] = a.w; }
            bar_sync(3, 256);
#pragma unroll 1
            for (int r = 0; r < 3; r++) {
                const uint32_t o = stw + (r ? o128 : P_OUT3 + wg * 24576);
                uint32_t when = r == 0 ? (wg ? SL_A1 : SL_A0) : r == 1 ? (wg ? SL_B1 : SL_B0) : SL_C << wg, n = 0;
                float2 va, vb;
                post_mma<2>(sb, acc, pa, r < 2 ? 16 : 56, wg, rel, lead, 12 + 2 * r, [&](int kb) {
                    if (kb < 0) { va = lds2f(v3); vb = lds2f(v3 + 32); return; }
                    const bool now = when & 1;
                    when >>= 1;
                    if (!now) return;
                    if (n == 0) out_free(3 + r);
                    float v[8];
                    pick16(v, n, c1, va, vb, old);
#pragma unroll
                    for (int e = 0; e < 8; e++) v[e] = gelu_s(v[e], gk[(e >> 1) & 1]);
                    stsm4((o + (n >> 2) * 8192) ^ ((n & 3) << 5), pack2(v[0], v[1]), pack2(v[2], v[3]), pack2(v[4], v[5]), pack2(v[6], v[7]));
                    v3 += 64;
                    if ((++n & 3) == 0) { if (!HFENCE) fence_async_smem(); signal(); }
                });
                if (r == 2) break;
#pragma unroll
                for (int i = 0; i < 64; i++) old[i] = acc[i];
            }
#pragma unroll
            for (int jn = 0; jn < 16; jn++) {
                const float2 gb = ldsv(vec + V_GB * 512 + jn * 32);
#pragma unroll
                for (int e = 0; e < 4; e++) acc[4 * jn + e] = fmaf((e & 1) ? gb.y : gb.x, acc[4 * jn + e], KEEP(jn, e));
                if ((jn & 7) == 7) put64(o128 + (jn >> 3) * 8192, acc + 4 * jn - 28);
            }
            PP(18)
            if (tid == 0) TL(12)
        }
    }
}

typedef CUresult (*EncFn)(CUtensorMap*, CUtensorMapDataType, cuuint32_t, void*, const cuuint64_t*, const cuuint64_t*, const cuuint32_t*,
                          const cuuint32_t*, CUtensorMapInterleave, CUtensorMapSwizzle, CUtensorMapL2promotion, CUtensorMapFloatOOBfill);

static CUtensorMap make_map(EncFn enc, const void* p, uint64_t inner, uint64_t outer, uint64_t pitch = 0) {
    const uint32_t bi = 64;
    CUtensorMap m;
    cuuint64_t dims[2] = {inner, outer};
    cuuint64_t str[1] = {(pitch ? pitch : inner) * 2};
    cuuint32_t box[2] = {bi, 64};
    cuuint32_t es[2] = {1, 1};
    enc(&m, CU_TENSOR_MAP_DATA_TYPE_BFLOAT16, 2, (void*)p, dims, str, box, es, CU_TENSOR_MAP_INTERLEAVE_NONE,
        bi == 64 ? CU_TENSOR_MAP_SWIZZLE_128B : CU_TENSOR_MAP_SWIZZLE_64B, CU_TENSOR_MAP_L2_PROMOTION_L2_256B, CU_TENSOR_MAP_FLOAT_OOB_FILL_NONE);
    return m;
}
static CUtensorMap make_map_o(EncFn enc, const void* p) {
    CUtensorMap m;
    cuuint64_t dims[2] = {16384, 256};
    cuuint64_t str[1] = {65536};
    cuuint32_t box[2] = {256, 8};
    cuuint32_t es[2] = {1, 1};
    enc(&m, CU_TENSOR_MAP_DATA_TYPE_UINT32, 2, (void*)p, dims, str, box, es, CU_TENSOR_MAP_INTERLEAVE_NONE, CU_TENSOR_MAP_SWIZZLE_NONE,
        CU_TENSOR_MAP_L2_PROMOTION_L2_256B, CU_TENSOR_MAP_FLOAT_OOB_FILL_NONE);
    return m;
}
template <class T> static T* sym(T& s) { void* p = nullptr; cudaGetSymbolAddress(&p, s); return (T*)p; }

constexpr RecTime g_time = {T_GO, T_X2, T_V, D_X2, D_V, H_D};
extern "C" void kernel_launch(void* const* d_in, const int* in_sizes, int n_in, void* d_out, int out_size) {
    const bf16* x = (const bf16*)d_in[0];
    const bf16* mem0 = (const bf16*)d_in[1];
    const bf16 *Wq = (const bf16*)d_in[2], *Wk = (const bf16*)d_in[3], *Wv = (const bf16*)d_in[4], *Wo = (const bf16*)d_in[5];
    const bf16 *w1 = (const bf16*)d_in[8], *w2 = (const bf16*)d_in[9], *w3 = (const bf16*)d_in[10], *w4 = (const bf16*)d_in[11];
    const bf16 *c = (const bf16*)d_in[12], *wmod = (const bf16*)d_in[13];
    bf16* out = (bf16*)d_out;

    EncFn enc = nullptr;
    cudaDriverEntryPointQueryResult qr;
    cudaGetDriverEntryPoint("cuTensorMapEncodeTiled", (void**)&enc, cudaEnableDefault, &qr);
    CUtensorMap tWq = make_map(enc, Wq, NH * DH, DM), tWk = make_map(enc, Wk, NH * DH, DM), tWv = make_map(enc, Wv, NH * DH, DM);
    PostMaps mp;
    mp.o = make_map_o(enc, sym(g_O)); mp.wo = make_map(enc, Wo, DM, NH * DH);
    mp.y = make_map(enc, sym(g_y), DM, S_); mp.w1 = make_map(enc, w1, DM, DM);
    mp.g = make_map(enc, sym(g_g), DM, S_); mp.w2 = make_map(enc, w2, DM, DM);
    mp.x1 = make_map(enc, ALIAS & 2 ? sym(g_y) : sym(g_x1), DM, S_); mp.w3 = make_map(enc, w3, FF, DM);
    mp.u = ALIAS & 1 ? make_map(enc, sym(g_O), FF, S_, NH * DH) : make_map(enc, sym(g_u), FF, S_); mp.w4 = make_map(enc, w4, DM, FF);
    mp.out = make_map(enc, out, DM, S_); mp.x = make_map(enc, x, DM, S_);
    cudaFuncSetAttribute(k_rec, cudaFuncAttributeMaxDynamicSharedMemorySize, SM_REC_TOTAL);
    cudaFuncSetAttribute(k_post, cudaFuncAttributeMaxDynamicSharedMemorySize, P_SMEM);

    uint8_t* arena = (uint8_t*)(((uintptr_t)sym(g_arena) + (2u << 20) - 1) & ~(uintptr_t)((2u << 20) - 1));
    const RecPtrs rp = {x, mem0, c, wmod, w1, w3, arena, 0u, w2, w4, Wo, g_time, Wq, Wk};
    const RecMaps rm = {tWq, tWk, tWv, mp.wo};
    k_rec<<<132, 384, SM_REC_TOTAL>>>(rm, rp);
    k_post<<<128, 384, P_SMEM>>>(mp);
}
```

```cpp
#include <cuda_runtime.h>
#include <cuda.h>
#include <cuda_bf16.h>
#include <stdint.h>
#include <limits.h>

typedef __nv_bfloat16 bf16;

constexpr int S_ = 2048, DM = 1024, NH = 32, DH = 128, NSEG = 64, FF = 3584;
constexpr int SPIN_LIMIT = 1 << 22;
#define W_INFL 3
#define XP 0
#define H_PIECES 8
#define NPROBE 3

__device__ uint8_t g_arena[10 << 20];
__device__ __align__(16) uint32_t g_tick[64];
__device__ __align__(16) uint32_t g_modp[8 * 2 * DM];
__host__ __device__ constexpr uint32_t blk(uint32_t lb, uint32_t par) {
    return (lb << 13) | ((((lb) ^ (lb >> 3) ^ (lb >> 4) ^ (lb >> 6) ^ par) & 1) << 12);
}
__host__ __device__ constexpr uint32_t lb_x2(uint32_t h) { return (h & 1) | ((h >> 1) << 3); }
__host__ __device__ constexpr uint32_t acc_slot(uint32_t s) { return (1u << 20) + (s & 1) * 32768 + (s & 2) * 131072; }
__host__ __device__ constexpr uint32_t acc_piece(uint32_t half, uint32_t qd, uint32_t mt) { return mt * 1024 + (qd & 1) * 4096 + half * 8192 + (qd >> 1) * 16384; }
constexpr uint32_t LB_STAMP = 6;
__host__ __device__ constexpr uint32_t stamp_line(uint32_t w, uint32_t q) { return ((w & 1) * 2 + (q >> 1)) * 1024 + (q & 1) * 256; }
constexpr uint32_t ACC_ONE = 0x3c000000u, ACC_ALL = 0x50000000u;
constexpr uint32_t LB_PROBE = 6 | 64;
__host__ __device__ constexpr uint32_t lb_tok(uint32_t h) { return (h & 1) | ((h >> 1) << 3); }
__device__ __align__(16) float g_mod[6 * DM];
__device__ __align__(1024) bf16 g_himg[(S_ + 32) * DM];
__device__ __align__(1024) bf16 g_O[S_ * NH * DH];
__device__ __align__(1024) bf16 g_y[S_ * DM];
__device__ __align__(1024) bf16 g_g[S_ * DM];
__device__ __align__(1024) bf16 g_x1[S_ * DM];
__device__ __align__(16) float g_st[4 * S_ * 2];
__device__ __align__(16) float g_vec[3 * DM + FF];
__device__ float g_cst[8];
__device__ uint32_t g_pcnt[2 * 32 * 8], g_pflag[6 * 32 * 8];
__device__ __align__(1024) bf16 g_u[S_ * FF];

#define TL(i) {}
#define TX(i) {}
#define TLC(i) {}
__device__ __forceinline__ uint32_t smem_u32(const void* p) { return (uint32_t)__cvta_generic_to_shared(p); }
__device__ __forceinline__ void spin_guard(int it) {
    asm volatile("{.reg .pred p; setp.gt.s32 p, %0, %1; @p st.global.u32 [%2], %0;}" ::"r"(it), "n"(SPIN_LIMIT), "l"(1ull));
}
__device__ __forceinline__ void wg_fence() { asm volatile("wgmma.fence.sync.aligned;" ::: "memory"); }
__device__ __forceinline__ void wg_commit() { asm volatile("wgmma.commit_group.sync.aligned;" ::: "memory"); }
template <int N> __device__ __forceinline__ void wg_wait() { asm volatile("wgmma.wait_group.sync.aligned %0;" ::"n"(N) : "memory"); }
__host__ __device__ constexpr uint64_t mkdesc(uint32_t addr, uint32_t lbo, uint32_t sbo, uint32_t swz) {
    return (uint64_t)((addr & 0x3FFFF) >> 4) | ((uint64_t)(lbo >> 4) << 16) | ((uint64_t)(sbo >> 4) << 32) | ((uint64_t)swz << 62);
}
__device__ __forceinline__ uint64_t dadd(uint64_t d, uint32_t o) { return (d & 0xffffffff00000000ull) | (uint32_t)((uint32_t)d + o); }
__device__ __forceinline__ void mbar_init(uint32_t b, uint32_t c) { asm volatile("mbarrier.init.shared.b64 [%0], %1;" ::"r"(b), "r"(c) : "memory"); }
__device__ __forceinline__ void mbar_expect(uint32_t b, uint32_t tx) { asm volatile("mbarrier.arrive.expect_tx.shared.b64 _, [%0], %1;" ::"r"(b), "r"(tx) : "memory"); }
__device__ __forceinline__ void mbar_arrive(uint32_t b) { asm volatile("mbarrier.arrive.shared.b64 _, [%0];" ::"r"(b) : "memory"); }
__device__ __forceinline__ void mbar_arrive_cluster(uint32_t b, uint32_t cta) {
    asm volatile("{.reg .b32 r; mapa.shared::cluster.u32 r, %0, %1; mbarrier.arrive.shared::cluster.b64 _, [r];}" ::"r"(b), "r"(cta) : "memory");
}
__device__ __forceinline__ void mbar_arrive_cluster_if(bool c, uint32_t b, uint32_t cta) {
    asm volatile("{.reg .pred p; .reg .b32 r; setp.ne.u32 p, %2, 0; mapa.shared::cluster.u32 r, %0, %1; @p mbarrier.arrive.shared::cluster.b64 _, [r];}" ::"r"(b), "r"(cta), "r"((uint32_t)c) : "memory");
}
__device__ __forceinline__ bool mbar_try(uint32_t b, uint32_t par) {
    uint32_t ok;
    asm volatile("{.reg .pred p; mbarrier.try_wait.parity.shared.b64 p, [%1], %2; selp.u32 %0, 1, 0, p;}" : "=r"(ok) : "r"(b), "r"(par) : "memory");
    return ok;
}
__device__ __forceinline__ void mbar_wait(uint32_t b, uint32_t par) {
    int it = 0;
#pragma unroll 1
    while (!mbar_try(b, par)) { spin_guard(++it); }
}
__device__ __forceinline__ void mbar_wait_w(uint32_t b, uint32_t par) {
    int it = 0;
    bool ok;
#pragma unroll 1
    do { ok = __all_sync(~0u, mbar_try(b, par)); spin_guard(++it); } while (!ok);
}
__device__ __forceinline__ void mbar_wait_cluster(uint32_t b, uint32_t par) {
    int it = 0;
    while (true) {
        uint32_t ok;
        asm volatile("{.reg .pred p; mbarrier.try_wait.parity.acquire.cluster.shared::cta.b64 p, [%1], %2; selp.u32 %0, 1, 0, p;}" : "=r"(ok) : "r"(b), "r"(par) : "memory");
        if (ok) break;
        spin_guard(++it);
    }
}
__device__ __forceinline__ void tma2d(uint32_t dst, const CUtensorMap* m, int c0, int c1, uint32_t bar) {
    asm volatile("cp.async.bulk.tensor.2d.shared::cluster.global.mbarrier::complete_tx::bytes [%0], [%1, {%3, %4}], [%2];" ::"r"(dst), "l"(m), "r"(bar), "r"(c0), "r"(c1) : "memory");
}
__device__ __forceinline__ void tma2d_mc(uint32_t dst, const CUtensorMap* m, int c0, int c1, uint32_t bar, uint16_t mask) {
    asm volatile("cp.async.bulk.tensor.2d.shared::cluster.global.mbarrier::complete_tx::bytes.multicast::cluster [%0], [%1, {%3, %4}], [%2], %5;" ::"r"(dst), "l"(m), "r"(bar), "r"(c0), "r"(c1), "h"(mask) : "memory");
}
__device__ __forceinline__ void bulk_g2s(uint32_t dst, const void* src, uint32_t bytes, uint32_t bar) {
    asm volatile("cp.async.bulk.shared::cluster.global.mbarrier::complete_tx::bytes [%0], [%1], %2, [%3];" ::"r"(dst), "l"(src), "r"(bytes), "r"(bar) : "memory");
}
__device__ __forceinline__ void bar_sync(int id, int n) { asm volatile("bar.sync %0, %1;" ::"r"(id), "r"(n) : "memory"); }
__device__ __forceinline__ void bar_arrive(int id, int n) { asm volatile("bar.arrive %0, %1;" ::"r"(id), "r"(n) : "memory"); }
__device__ __forceinline__ void cluster_sync_all() { asm volatile("barrier.cluster.arrive.aligned; barrier.cluster.wait.aligned;" ::: "memory"); }
__device__ __forceinline__ void fence_async_smem() { asm volatile("fence.proxy.async.shared::cta;" ::: "memory"); }
__device__ __forceinline__ void ldsm4t(uint32_t* r, uint32_t a) {
    asm volatile("ldmatrix.sync.aligned.m8n8.x4.trans.shared.b16 {%0,%1,%2,%3}, [%4];" : "=r"(r[0]), "=r"(r[1]), "=r"(r[2]), "=r"(r[3]) : "r"(a) : "memory");
}
__device__ __forceinline__ void ldsm4(uint32_t* r, uint32_t a) {
    asm volatile("ldmatrix.sync.aligned.m8n8.x4.shared.b16 {%0,%1,%2,%3}, [%4];" : "=r"(r[0]), "=r"(r[1]), "=r"(r[2]), "=r"(r[3]) : "r"(a) : "memory");
}
__device__ __forceinline__ uint32_t movm(uint32_t a) {
    uint32_t d; asm volatile("movmatrix.sync.aligned.m8n8.trans.b16 %0, %1;" : "=r"(d) : "r"(a)); return d;
}
__device__ __forceinline__ void mma16816(float* d, uint32_t a0, uint32_t a1, uint32_t a2, uint32_t a3, uint32_t b0, uint32_t b1) {
    asm volatile("mma.sync.aligned.m16n8k16.row.col.f32.bf16.bf16.f32 {%0,%1,%2,%3},{%4,%5,%6,%7},{%8,%9},{%0,%1,%2,%3};"
                 : "+f"(d[0]), "+f"(d[1]), "+f"(d[2]), "+f"(d[3]) : "r"(a0), "r"(a1), "r"(a2), "r"(a3), "r"(b0), "r"(b1));
}
__device__ __forceinline__ void mma16816z(float* d, const uint32_t* a, uint32_t b0, uint32_t b1) {
    asm volatile("mma.sync.aligned.m16n8k16.row.col.f32.bf16.bf16.f32 {%0,%1,%2,%3},{%4,%5,%6,%7},{%8,%9},{%10,%10,%10,%10};"
                 : "=f"(d[0]), "=f"(d[1]), "=f"(d[2]), "=f"(d[3]) : "r"(a[0]), "r"(a[1]), "r"(a[2]), "r"(a[3]), "r"(b0), "r"(b1), "f"(0.f));
}
__device__ __forceinline__ void mma1688(float* d, uint32_t a0, uint32_t a1, uint32_t b0) {
    asm volatile("mma.sync.aligned.m16n8k8.row.col.f32.bf16.bf16.f32 {%0,%1,%2,%3},{%4,%5},{%6},{%0,%1,%2,%3};"
                 : "+f"(d[0]), "+f"(d[1]), "+f"(d[2]), "+f"(d[3]) : "r"(a0), "r"(a1), "r"(b0));
}
__device__ __forceinline__ uint32_t pack2(float lo, float hi) {
    uint32_t r; asm("cvt.rn.bf16x2.f32 %0, %1, %2;" : "=r"(r) : "f"(hi), "f"(lo)); return r;
}
__device__ __forceinline__ uint32_t hadd2(uint32_t a, uint32_t b) {
    uint32_t r; asm("add.rn.bf16x2 %0, %1, %2;" : "=r"(r) : "r"(a), "r"(b)); return r;
}
__device__ __forceinline__ uint32_t hadd2v(uint32_t a, uint32_t b) {
    uint32_t r; asm volatile("add.rn.bf16x2 %0, %1, %2;" : "=r"(r) : "r"(a), "r"(b)); return r;
}
__device__ __forceinline__ float bflo(uint32_t u) { return __uint_as_float(u << 16); }
__device__ __forceinline__ float bfhi(uint32_t u) { return __uint_as_float(u & 0xffff0000u); }
__device__ __forceinline__ float ex2(float x) { float r; asm("ex2.approx.ftz.f32 %0, %1;" : "=f"(r) : "f"(x)); return r; }
__device__ __forceinline__ uint4 ldg_rlx4(const void* p) {
    uint4 v; asm volatile("ld.relaxed.gpu.global.v4.u32 {%0,%1,%2,%3}, [%4];" : "=r"(v.x), "=r"(v.y), "=r"(v.z), "=r"(v.w) : "l"(p) : "memory"); return v;
}
__device__ __forceinline__ uint2 ldg_rlx2(const void* p) {
    unsigned long long v; asm volatile("ld.relaxed.gpu.global.b64 %0, [%1];" : "=l"(v) : "l"(p) : "memory");
    return make_uint2((uint32_t)v, (uint32_t)(v >> 32));
}
__device__ __forceinline__ uint32_t ldg_rlx1(const void* p) {
    uint32_t v; asm volatile("ld.relaxed.gpu.global.u32 %0, [%1];" : "=r"(v) : "l"(p) : "memory"); return v;
}
__device__ __forceinline__ void stg_rlx1(void* p, uint32_t v) { asm volatile("st.relaxed.gpu.global.u32 [%0], %1;" ::"l"(p), "r"(v) : "memory"); }
__device__ __forceinline__ void stg_rlx2(void* p, uint32_t x, uint32_t y) {
    unsigned long long v = (unsigned long long)x | ((unsigned long long)y << 32);
    asm volatile("st.relaxed.gpu.global.b64 [%0], %1;" ::"l"(p), "l"(v) : "memory");
}
__device__ __forceinline__ void stg_rlx4(void* p, uint32_t x, uint32_t y, uint32_t z, uint32_t w) {
    asm volatile("st.relaxed.gpu.global.v4.u32 [%0], {%1,%2,%3,%4};" ::"l"(p), "r"(x), "r"(y), "r"(z), "r"(w) : "memory");
}
__device__ __forceinline__ void sts4(uint32_t a, uint32_t x, uint32_t y, uint32_t z, uint32_t w) {
    asm volatile("st.shared.v4.u32 [%0], {%1,%2,%3,%4};" ::"r"(a), "r"(x), "r"(y), "r"(z), "r"(w) : "memory");
}
__device__ __forceinline__ uint4 lds4(uint32_t a) {
    uint4 v; asm volatile("ld.shared.v4.u32 {%0,%1,%2,%3}, [%4];" : "=r"(v.x), "=r"(v.y), "=r"(v.z), "=r"(v.w) : "r"(a) : "memory"); return v;
}
__device__ __forceinline__ void st_async4(uint32_t a, float x, float y, float z, float w, uint32_t bar) {
    asm volatile("st.async.shared::cluster.mbarrier::complete_tx::bytes.v4.f32 [%0], {%1,%2,%3,%4}, [%5];" ::"r"(a), "f"(x), "f"(y), "f"(z), "f"(w), "r"(bar) : "memory");
}
#define F4(d, i) "+f"(d[i]), "+f"(d[i + 1]), "+f"(d[i + 2]), "+f"(d[i + 3])
template <bool V> __device__ __forceinline__ void wgmma_tok_rs(float* d, const uint32_t* a, uint64_t b, int sc) {
    if (V) asm volatile("{.reg .pred p; setp.ne.b32 p, %25, 0;\n wgmma.mma_async.sync.aligned.m64n40k16.f32.bf16.bf16 {%0,%1,%2,%3,%4,%5,%6,%7,%8,%9,%10,%11,%12,%13,%14,%15,%16,%17,%18,%19}, {%20,%21,%22,%23}, %24, p, 1, 1, 0;}"
                        : F4(d, 0), F4(d, 4), F4(d, 8), F4(d, 12), F4(d, 16) : "r"(a[0]), "r"(a[1]), "r"(a[2]), "r"(a[3]), "l"(b), "r"(sc));
    else asm volatile("{.reg .pred p; setp.ne.b32 p, %21, 0;\n wgmma.mma_async.sync.aligned.m64n32k16.f32.bf16.bf16 {%0,%1,%2,%3,%4,%5,%6,%7,%8,%9,%10,%11,%12,%13,%14,%15}, {%16,%17,%18,%19}, %20, p, 1, 1, 0;}"
                      : F4(d, 0), F4(d, 4), F4(d, 8), F4(d, 12) : "r"(a[0]), "r"(a[1]), "r"(a[2]), "r"(a[3]), "l"(b), "r"(sc));
}
template <bool V> __device__ __forceinline__ void wgmma_tok_ss(float* d, uint64_t a, uint64_t b) {
    if (V) asm volatile("wgmma.mma_async.sync.aligned.m64n40k16.f32.bf16.bf16 {%0,%1,%2,%3,%4,%5,%6,%7,%8,%9,%10,%11,%12,%13,%14,%15,%16,%17,%18,%19}, %20, %21, 1, 1, 1, 1, 0;"
                        : F4(d, 0), F4(d, 4), F4(d, 8), F4(d, 12), F4(d, 16) : "l"(a), "l"(b));
    else asm volatile("wgmma.mma_async.sync.aligned.m64n32k16.f32.bf16.bf16 {%0,%1,%2,%3,%4,%5,%6,%7,%8,%9,%10,%11,%12,%13,%14,%15}, %16, %17, 1, 1, 1, 1, 0;"
                      : F4(d, 0), F4(d, 4), F4(d, 8), F4(d, 12) : "l"(a), "l"(b));
}
#define F16(d, i) F4(d, i), F4(d, i + 4), F4(d, i + 8), F4(d, i + 12)
template <int TA>
__device__ __forceinline__ void wgmma_ss128(float* d, uint64_t a, uint64_t b, int sc) {
    asm volatile("{.reg .pred p; setp.ne.b32 p, %66, 0;\n wgmma.mma_async.sync.aligned.m64n128k16.f32.bf16.bf16 "
                 "{%0,%1,%2,%3,%4,%5,%6,%7,%8,%9,%10,%11,%12,%13,%14,%15,%16,%17,%18,%19,%20,%21,%22,%23,%24,%25,%26,%27,%28,%29,%30,%31,"
                 "%32,%33,%34,%35,%36,%37,%38,%39,%40,%41,%42,%43,%44,%45,%46,%47,%48,%49,%50,%51,%52,%53,%54,%55,%56,%57,%58,%59,%60,%61,%62,%63}, %64, %65, p, 1, 1, %67, 1;}"
                 : F16(d, 0), F16(d, 16), F16(d, 32), F16(d, 48) : "l"(a), "l"(b), "r"(sc), "n"(TA));
}

__device__ __forceinline__ float warp_sum(float v) {
#pragma unroll
    for (int o = 16; o; o >>= 1) v += __shfl_xor_sync(~0u, v, o);
    return v;
}
__device__ __forceinline__ float bfround(float x) { return __bfloat162float(__float2bfloat16(x)); }

__device__ __forceinline__ void wait_count1(const uint32_t* p, uint32_t target) {
    int it = 0;
#pragma unroll 1
    while (true) {
        uint32_t v;
        asm volatile("ld.acquire.gpu.global.u32 %0, [%1];" : "=r"(v) : "l"(p) : "memory");
        if (v >= target) break;
        spin_guard(++it);
    }
}
__device__ __forceinline__ void red2(float* p, float a, float b) {
    asm volatile("red.relaxed.gpu.global.add.v2.f32 [%0], {%1, %2};" ::"l"(p), "f"(a), "f"(b) : "memory");
}
__device__ __forceinline__ void l2_prefetch(const void* p, uint32_t bytes) {
    asm volatile("cp.async.bulk.prefetch.L2.global [%0], %1;" ::"l"(p), "r"(bytes) : "memory");
}
__device__ __forceinline__ void signal_count(uint32_t* p) { asm volatile("red.release.gpu.global.add.u32 [%0], 1;" ::"l"(p) : "memory"); }
__device__ __forceinline__ void e_expect(uint32_t b, uint32_t tx) {
    asm volatile("{.reg .pred p; elect.sync _|p, 0xffffffff; @p mbarrier.arrive.expect_tx.shared.b64 _, [%0], %1;}" ::"r"(b), "r"(tx) : "memory");
}
__device__ __forceinline__ uint64_t evict_first() { uint64_t p; asm("createpolicy.fractional.L2::evict_first.b64 %0, 1.0;" : "=l"(p)); return p; }
__device__ __forceinline__ uint64_t evict_normal() { uint64_t p; asm("createpolicy.fractional.L2::evict_unchanged.b64 %0, 1.0;" : "=l"(p)); return p; }
__device__ __forceinline__ void e_tma2d(uint32_t dst, const CUtensorMap* m, int c0, int c1, uint32_t bar, uint64_t pol) {
    asm volatile("{.reg .pred p; elect.sync _|p, 0xffffffff;\n @p cp.async.bulk.tensor.2d.shared::cluster.global.mbarrier::complete_tx::bytes.L2::cache_hint [%0], [%1, {%3, %4}], [%2], %5;}"
                 ::"r"(dst), "l"(m), "r"(bar), "r"(c0), "r"(c1), "l"(pol) : "memory");
}
__device__ __forceinline__ void e_tma2d_mc(uint32_t dst, const CUtensorMap* m, int c0, int c1, uint32_t bar, uint64_t pol) {
    asm volatile("{.reg .pred p; elect.sync _|p, 0xffffffff;\n @p cp.async.bulk.tensor.2d.shared::cluster.global.mbarrier::complete_tx::bytes.multicast::cluster.L2::cache_hint [%0], [%1, {%3, %4}], [%2], %5, %6;}"
                 ::"r"(dst), "l"(m), "r"(bar), "r"(c0), "r"(c1), "h"((uint16_t)3), "l"(pol) : "memory");
}
__device__ __forceinline__ void e_prefetch(const void* p, uint32_t bytes) {
    asm volatile("{.reg .pred p; elect.sync _|p, 0xffffffff; @p cp.async.bulk.prefetch.L2.global [%0], %1;}" ::"l"(p), "r"(bytes) : "memory");
}
__device__ __forceinline__ uint32_t wait_count_w(const uint32_t* p, uint32_t target) {
    int it = 0;
#pragma unroll 1
    while (true) {
        uint32_t v;
        asm volatile("ld.acquire.gpu.global.u32 %0, [%1];" : "=r"(v) : "l"(p) : "memory");
        if (__all_sync(~0u, v >= target)) return v;
        spin_guard(++it);
    }
}

__device__ __forceinline__ uint4 pack8(const float* x) {
    return make_uint4(pack2(x[0], x[1]), pack2(x[2], x[3]), pack2(x[4], x[5]), pack2(x[6], x[7]));
}
#define NL 6
constexpr uint32_t HCH = 5120, HBUF = 8 * HCH;
constexpr uint32_t SM_SX = 0, SM_ST = 2560, SM_OX = 8192, SM_LX = 10240, SM_PX = 11392, SM_PA = 12288, SM_VF = 18432, SM_TAB = 26624, SM_WL2 = 41984, SM_HB = 49152, SM_WO = 131072,
                   SM_WL = 196608, SM_PRE = SM_WL, SM_BAR = 227328, SM_SV = SM_BAR + 256, SM_TRC = SM_SV + 2048, SM_REC_TOTAL = SM_TRC + 2688;
__host__ __device__ constexpr uint32_t sm_wl(int i) { return i < 5 ? SM_WL + i * 6144 : SM_WL2; }
constexpr uint32_t SB0 = 1024;
constexpr int B_WO = 0, B_HE = 1, B_ROLE = 2, B_HB = 3, B_W = 5;
constexpr int NB_MEM = 1, NB_QK = 2, NB_X1 = 3, NB_X2 = 4, NB_WIN = 5, NB_WG = 6, NB_FAR = 6, NB_KDONE = 7, NB_FIN0 = 8, NB_LN = 9, NB_MEM2 = 10, NB_H = 11, NB_A = 12, NB_B = 13, NB_C = 14, NB_F = 15;
#define ST_GATE 1
#define TPV_DLY 6
#define L_AT 1
#define D_X2 300
#define D_V 150
#define NPF1 6
#define NPF 11
#define ROTM 7
#define T_GO 29
#define GATE_AT 26
#define T_X2 1850
#define T_V 400
#define QK_EARLY 0
#define NOB 1
#define VP_AT 1
#define KQ_AT 17
#define PD 4
#define PFENCE 1
#define SH3 1
#define PV_FENCE 0
#define SV_AT 2
#define SSG 4
#define SSG_V 4
#define SS0_K 2
#define SS0_V 4
#define W0_AT -1
#define NPF0 3
#define STG_FENCE 1
#define O_LATE 1
#define WO_AT 0x1100
#define W_PF 4
#define EF 13
#define TWO 0
#define Q_LATE 0
#define W0_F 2
#define ACC_PIN 0
#define INIT_F 0
#define ZFILL 1
#define NPF2 9
#define PF_DLY 6
#define H_AT 3
#define H_D 200
#define REQ_LATE 2
#define PIN_EPI 1

#define PROF_INIT
#define PROF(i)
#define PROFV(i, v)
#define PROF_OUT

__device__ __forceinline__ uint32_t clk32() { uint32_t t; asm volatile("mov.u32 %0, %%clock;" : "=r"(t) :: "memory"); return t; }
__device__ __forceinline__ uint32_t gtime32() { uint32_t t; asm volatile("mov.u32 %0, %%globaltimer_lo;" : "=r"(t) :: "memory"); return t; }
__device__ __forceinline__ void spin_until(uint32_t t0, uint32_t d) { while (clk32() - t0 < d) {} }
template <int N> __device__ __forceinline__ uint32_t delay(uint32_t zero) {
    float x = __uint_as_float(clk32());
#pragma unroll
    for (int i = 0; i < N; i++) asm volatile("ex2.approx.ftz.f32 %0, %0;" : "+f"(x));
    return __float_as_uint(x) & zero;
}
__device__ __forceinline__ uint32_t clk_after(uint32_t x, uint32_t zero) {
    unsigned long long c = 0;
    asm volatile("{.reg .pred p; setp.eq.u32 p, %1, 0; @p mov.u64 %0, %%clock64;}" : "+l"(c) : "r"(x & zero) : "memory");
    return (uint32_t)c;
}
__device__ __forceinline__ uint32_t later(uint32_t a, uint32_t b) { return a + max((int)(b - a), 0); }
__device__ __forceinline__ void wait_clk(uint32_t t) {
#pragma unroll 1
    while (true) {
        unsigned long long c;
        asm volatile("mov.u64 %0, %%clock64;" : "=l"(c) :: "memory");
        if ((int)((uint32_t)c - t) >= 0) break;
    }
}
__device__ __forceinline__ uint32_t opaque(uint32_t v) { return __shfl_sync(~0u, v, threadIdx.x & 31); }
__device__ __forceinline__ uint32_t xor_or(uint32_t a, uint32_t b, uint32_t t) {
    uint32_t r; asm volatile("lop3.b32 %0, %1, %2, %3, 0x7E;" : "=r"(r) : "r"(a), "r"(b), "r"(t)); return r;
}
__device__ __forceinline__ uint32_t or3(uint32_t a, uint32_t b, uint32_t c) {
    uint32_t r; asm volatile("lop3.b32 %0, %1, %2, %3, 0xFE;" : "=r"(r) : "r"(a), "r"(b), "r"(c)); return r;
}
__device__ __forceinline__ uint32_t settag(uint32_t v, uint32_t tag) {
    uint32_t r; asm("lop3.b32 %0, %1, 1, %2, 0xB8;" : "=r"(r) : "r"(v), "r"(tag)); return r;
}
__device__ __forceinline__ void ldg4_if(uint4& v, const void* p, bool c) {
    asm volatile("{.reg .pred p; setp.ne.u32 p, %5, 0; @p ld.relaxed.gpu.global.v4.u32 {%0,%1,%2,%3}, [%4];}"
                 : "+r"(v.x), "+r"(v.y), "+r"(v.z), "+r"(v.w) : "l"(p), "r"((uint32_t)c) : "memory");
}
__device__ __forceinline__ uint4 ldg_rlx2x2(const void* p) {
    unsigned long long a, b;
    asm volatile("ld.relaxed.gpu.global.v2.b64 {%0,%1}, [%2];" : "=l"(a), "=l"(b) : "l"(p) : "memory");
    return make_uint4((uint32_t)a, (uint32_t)(a >> 32), (uint32_t)b, (uint32_t)(b >> 32));
}
__device__ __forceinline__ void stg_rlx2x2(void* p, uint32_t x, uint32_t y, uint32_t z, uint32_t w) {
    asm volatile("{.reg .b64 a, b; mov.b64 a, {%1,%2}; mov.b64 b, {%3,%4}; st.relaxed.gpu.global.v2.b64 [%0], {a, b};}" ::"l"(p), "r"(x), "r"(y), "r"(z), "r"(w) : "memory");
}
__device__ __forceinline__ void ldg1_if(uint32_t& v, const void* p, bool c) {
    asm volatile("{.reg .pred p; setp.ne.u32 p, %2, 0; @p ld.relaxed.gpu.global.u32 %0, [%1];}" : "+r"(v) : "l"(p), "r"((uint32_t)c) : "memory");
}
__device__ __forceinline__ void sts2(uint32_t a, float x, float y) { asm volatile("st.shared.v2.f32 [%0], {%1,%2};" ::"r"(a), "f"(x), "f"(y) : "memory"); }
__device__ __forceinline__ void sts4f(uint32_t a, float x, float y, float z, float w) {
    asm volatile("st.shared.v4.f32 [%0], {%1,%2,%3,%4};" ::"r"(a), "f"(x), "f"(y), "f"(z), "f"(w) : "memory");
}
__device__ __forceinline__ void sts1(uint32_t a, uint32_t x) { asm volatile("st.shared.u32 [%0], %1;" ::"r"(a), "r"(x) : "memory"); }
__device__ __forceinline__ uint32_t lds1(uint32_t a) { uint32_t v; asm volatile("ld.shared.u32 %0, [%1];" : "=r"(v) : "r"(a) : "memory"); return v; }
__device__ __forceinline__ float4 lds4f(uint32_t a) {
    float4 v; asm volatile("ld.shared.v4.f32 {%0,%1,%2,%3}, [%4];" : "=f"(v.x), "=f"(v.y), "=f"(v.z), "=f"(v.w) : "r"(a) : "memory"); return v;
}
__device__ __forceinline__ float2 lds2f(uint32_t a) {
    float2 v; asm volatile("ld.shared.v2.f32 {%0,%1}, [%2];" : "=f"(v.x), "=f"(v.y) : "r"(a) : "memory"); return v;
}
__device__ __forceinline__ bool any_bit0(uint32_t x) {
    uint32_t r;
    asm volatile("{.reg .pred p, q; .reg .b32 t; and.b32 t, %1, 1; setp.ne.u32 p, t, 0; vote.sync.any.pred q, p, 0xffffffff; selp.u32 %0, 1, 0, q;}" : "=r"(r) : "r"(x));
    return r;
}
__device__ __forceinline__ float rcp_fast(float x) { float r; asm("rcp.approx.ftz.f32 %0, %1;" : "=f"(r) : "f"(x)); return r; }
__device__ __forceinline__ void stsm4(uint32_t a, uint32_t r0, uint32_t r1, uint32_t r2, uint32_t r3) {
    asm volatile("stmatrix.sync.aligned.m8n8.x4.shared.b16 [%0], {%1,%2,%3,%4};" ::"r"(a), "r"(r0), "r"(r1), "r"(r2), "r"(r3) : "memory");
}
__device__ __forceinline__ void stsm4t(uint32_t a, uint32_t r0, uint32_t r1, uint32_t r2, uint32_t r3) {
    asm volatile("stmatrix.sync.aligned.m8n8.x4.trans.shared.b16 [%0], {%1,%2,%3,%4};" ::"r"(a), "r"(r0), "r"(r1), "r"(r2), "r"(r3) : "memory");
}
__device__ __forceinline__ void stg_b64_if(bool c, void* p, uint32_t x, uint32_t y) {
    asm volatile("{.reg .pred p; .reg .b64 a; setp.ne.u32 p, %3, 0; mov.b64 a, {%1,%2}; @p st.relaxed.gpu.global.b64 [%0], a;}" ::"l"(p), "r"(x), "r"(y), "r"((uint32_t)c) : "memory");
}
__device__ __forceinline__ void cp_async16(uint32_t dst, const void* src) { asm volatile("cp.async.cg.shared.global [%0], [%1], 16;" ::"r"(dst), "l"(src) : "memory"); }
__device__ __forceinline__ void cp_async16_ef(uint32_t dst, const void* src) {
    asm volatile("cp.async.cg.shared.global.L2::cache_hint [%0], [%1], 16, %2;" ::"r"(dst), "l"(src), "l"(evict_first()) : "memory");
}
__device__ __forceinline__ uint32_t prmt(uint32_t a, uint32_t b, uint32_t c) { uint32_t r; asm("prmt.b32 %0, %1, %2, %3;" : "=r"(r) : "r"(a), "r"(b), "r"(c)); return r; }
__device__ __forceinline__ uint32_t hadd2h(uint32_t a, uint32_t b) { uint32_t r; asm("add.rn.f16x2 %0, %1, %2;" : "=r"(r) : "r"(a), "r"(b)); return r; }
__device__ __forceinline__ uint32_t hmax2h(uint32_t a, uint32_t b) { uint32_t r; asm("max.f16x2 %0, %1, %2;" : "=r"(r) : "r"(a), "r"(b)); return r; }
__device__ __forceinline__ uint32_t max3u(uint32_t a, uint32_t b, uint32_t c) { return __vimax3_u32(a, b, c); }
__device__ __forceinline__ void fence_gpu() { asm volatile("fence.acq_rel.gpu;" ::: "memory"); }

__device__ __forceinline__ void h_load(uint32_t sb, const uint8_t* hsrc, int pass, uint32_t slot0, uint32_t rot, uint32_t wq, bool arm = true, uint32_t skip = 0) {
    const uint32_t bar = sb + SM_BAR + 8 * (B_HB + (pass & 1)), c = (wq + rot) & 3, dst = sb + SM_HB + (pass & 1) * HBUF + (slot0 ^ c) * HCH + skip;
    const uint8_t* src = hsrc + ((size_t)pass * 65536 + c * 4096 + skip);
    if (arm && wq == 0) e_expect(bar, 32768 - 8 * skip);
    asm volatile("{.reg .pred p; elect.sync _|p, 0xffffffff;\n"
                 " @p cp.async.bulk.shared::cluster.global.mbarrier::complete_tx::bytes.multicast::cluster.L2::cache_hint [%0], [%1], %4, [%2], %3, %5;}"
                 ::"r"(dst), "l"(src), "r"(bar), "h"((uint16_t)3), "r"(4096 - skip), "l"(evict_first()) : "memory");
}
__device__ __forceinline__ uint4 ldg_b128(const void* p) {
    uint4 v;
    asm volatile("{.reg .b128 t; .reg .b64 a, b; ld.relaxed.gpu.global.b128 t, [%4]; mov.b128 {a, b}, t; mov.b64 {%0,%1}, a; mov.b64 {%2,%3}, b;}"
                 : "=r"(v.x), "=r"(v.y), "=r"(v.z), "=r"(v.w) : "l"(p) : "memory");
    return v;
}
__device__ __forceinline__ void stg_b128_if(bool c, void* p, uint32_t x, uint32_t y, uint32_t z, uint32_t w) {
    asm volatile("{.reg .pred p; .reg .b128 t; .reg .b64 a, b; setp.ne.u32 p, %5, 0; mov.b64 a, {%1,%2}; mov.b64 b, {%3,%4}; mov.b128 t, {a, b}; @p st.relaxed.gpu.global.b128 [%0], t;}"
                 ::"l"(p), "r"(x), "r"(y), "r"(z), "r"(w), "r"((uint32_t)c) : "memory");
}
__device__ __forceinline__ float pretag(float x, uint32_t add, uint32_t keep) { return __uint_as_float((__float_as_uint(x) + add) & keep); }

template <bool MASK, class F>
__device__ __forceinline__ void softmax_rows(uint32_t src, uint32_t dst, uint32_t g16, int row0, F mid) {
    const uint32_t u = (g16 >> 7) & 3, e = ((g16 >> 9) << 3) | ((g16 >> 4) & 7);
    const uint32_t se = src + e * 8, su = se + u * 1088;
    const float2 p0 = lds2f(su), p1 = lds2f(su + 256), p2 = lds2f(su + 512), p3 = lds2f(su + 768);
    const float2 m0 = lds2f(se + 4352), m1 = lds2f(se + 4352 + 256), m2 = lds2f(se + 4352 + 512), m3 = lds2f(se + 4352 + 768);
    float a0 = (p0.x + p1.x) + (p2.x + p3.x), a1 = (p0.y + p1.y) + (p2.y + p3.y);
    const float a2 = (m0.x + m1.x) + (m2.x + m3.x), a3 = (m0.y + m1.y) + (m2.y + m3.y);
    mid(__float_as_uint(a3));
    if (MASK) {
        const int vis = row0 + (e >> 2) - 2 * (e & 3) - 8 * u;
        if (vis < 0) a0 = -1e9f / 0.08838834764831845f;
        if (vis < 1) a1 = -1e9f / 0.08838834764831845f;
    }
    int k = __float_as_int(fmaxf(fmaxf(a0, a1), fmaxf(a2, a3)));
    k ^= (k >> 31) & 0x7fffffff;
    const bool hi = g16 & 64;
    const int k0 = __reduce_max_sync(~0u, hi ? INT_MIN : k), k1 = __reduce_max_sync(~0u, hi ? k : INT_MIN);
    k = hi ? k1 : k0;
    const float m = __int_as_float(k ^ ((k >> 31) & 0x7fffffff));
    const float sl2 = 0.08838834764831845f * 1.4426950408889634f, mb = -m * sl2;
    sts1(dst + e * 16 + u * 4, pack2(ex2(fmaf(a0, sl2, mb)), ex2(fmaf(a1, sl2, mb))));
    sts1(dst + 512 + e * 4, pack2(ex2(fmaf(a2, sl2, mb)), ex2(fmaf(a3, sl2, mb))));
}

__device__ __forceinline__ uint32_t pack_h2(float lo, float hi) {
    uint32_t r; asm("cvt.rn.satfinite.f16x2.f32 %0, %1, %2;" : "=r"(r) : "f"(hi), "f"(lo)); return r;
}
__device__ __forceinline__ float2 unpack_h2(uint32_t u) {
    float2 r; asm("{.reg .b16 l, h; mov.b32 {l, h}, %2; cvt.f32.f16 %0, l; cvt.f32.f16 %1, h;}" : "=f"(r.x), "=f"(r.y) : "r"(u)); return r;
}
__device__ __forceinline__ uint32_t h2bf(uint32_t u) {
    uint32_t r;
    asm volatile("{.reg .b16 l, h; .reg .f32 a, b; mov.b32 {l, h}, %1; cvt.f32.f16 a, l; cvt.f32.f16 b, h; cvt.rn.bf16x2.f32 %0, b, a;}" : "=r"(r) : "r"(u));
    return r;
}
__device__ __forceinline__ void red_h8(void* p, uint32_t x, uint32_t y, uint32_t z, uint32_t w) {
    asm volatile("red.relaxed.gpu.global.add.noftz.v4.f16x2 [%0], {%1,%2,%3,%4};" ::"l"(p), "r"(x), "r"(y), "r"(z), "r"(w) : "memory");
}
__device__ __forceinline__ void red_h2_if(bool c, void* p, uint32_t x) {
    asm volatile("{.reg .pred p; setp.ne.u32 p, %2, 0; @p red.relaxed.gpu.global.add.noftz.f16x2 [%0], %1;}" ::"l"(p), "r"(x), "r"((uint32_t)c) : "memory");
}
__device__ __forceinline__ void red_h10(bool c, void* p, void* q, uint32_t x, uint32_t y, uint32_t z, uint32_t w, uint32_t e) {
    asm volatile("{.reg .pred p; setp.ne.u32 p, %7, 0; red.relaxed.gpu.global.add.noftz.v4.f16x2 [%0], {%2,%3,%4,%5};\n"
                 " @p red.relaxed.gpu.global.add.noftz.f16x2 [%1], %6;}" ::"l"(p), "l"(q), "r"(x), "r"(y), "r"(z), "r"(w), "r"(e), "r"((uint32_t)c) : "memory");
}
constexpr float SM_L2E = 0.08838834764831845f * 1.4426950408889634f;
template <int V> struct IC { static constexpr int value = V; };
typedef unsigned long long u64;
__device__ __forceinline__ uint32_t lo32(u64 v) { return (uint32_t)v; }
__device__ __forceinline__ uint32_t hi32(u64 v) { return (uint32_t)(v >> 32); }
__device__ __forceinline__ u64 ldg_u64(const void* p) { u64 v; asm volatile("ld.relaxed.gpu.global.b64 %0, [%1];" : "=l"(v) : "l"(p) : "memory"); return v; }
__device__ __forceinline__ void ldg_u64_if(u64& v, const void* p, bool c) {
    asm volatile("{.reg .pred p; setp.ne.u32 p, %2, 0; @p ld.relaxed.gpu.global.b64 %0, [%1];}" : "+l"(v) : "l"(p), "r"((uint32_t)c) : "memory");
}
struct RecTime { uint32_t go, x2, v, dx2, dv, h; };
__device__ __forceinline__ void rec_main(uint32_t sb, const CUtensorMap* tWo, uint8_t* arena, int role, int hinfo, int wg, uint32_t zero, const RecTime& tm) {
    const int hA = hinfo & 255;
    const int tid = threadIdx.x, t = tid & 127, lane = tid & 31, wi = t >> 5;
    const uint32_t bars = sb + SM_BAR;
    const int head = role >> 2, qd = role & 3, j = blockIdx.x & 1, kh = role & 1;
    const uint32_t mypar = head >= hA;
    const uint32_t nf = kh ^ mypar, slot0 = j * 4 + nf * 2;
    const uint32_t wiu = __reduce_max_sync(~0u, wi);
    const bool warp0 = wiu == 0;
    const uint8_t* hsrc = (const uint8_t*)g_himg + kh * 32768 + j * 16384;
    auto tokbase = [&](int ty) { return ((ty + 1) << 21) + blk(lb_tok(head), mypar ^ ((hinfo >> (8 + ty)) & 1)); };
    const uint32_t tbw = tokbase(wg), tbq = tokbase(0) + (qd >> 1) * 2048 + (qd & 1) * 8;
#define SLOT(it) (((it) & 1) + ((it) >> 3) * 2 + ((it) & 2) * 2)
#define KS(p) (4 * SLOT((p) >> 1) + (((p) >> 3) & 1) + 2 * ((p) & 1))
    uint32_t w[32 - NL][4];
    uint4 wl5;
    if (wg == 2) bar_arrive(NB_WIN, 384);
    const uint32_t po = (1 << 20) + j * 16384 + kh * 2048;
    const uint32_t c16 = kh * 2048 + ((2 * j + (wi >> 1)) * 32 + lane) * 16, xso = blk(lb_x2(head), mypar);
    const uint32_t x2o = xso + wg * 16384 + (wi & 1) * 2048 + (c16 >> 1), tko = tbw + (wi & 1) * 16384 + c16;
    if (ZFILL) {
        stg_rlx2(arena + x2o, 0, 0);
#pragma unroll
        for (int i = 0; i < 4; i++) stg_rlx4(arena + ((i & 1 ? tko : tbw + (po ^ 2048) + t * 16) + (i >> 1) * 32768), 0, 0, 0, 0);
    }
    const uint32_t frow = ((lane >> 4) * 8 + (lane & 7)) * 128, fx = ((lane >> 3) & 1) ^ (lane & 7);
    {
#pragma unroll 1
        for (int i = 0; i < 4; i++) mbar_wait_w(bars + 8 * (B_W + (wg == 2 ? 8 + i : 2 * i + wg)), 0);
        const uint32_t stg = sb + wg * 65536;
#pragma unroll
        for (int p = NL; p < 32; p++) ldsm4t(w[p - NL], stg + (KS(p) ^ nf * 8) * 2048 + frow + ((fx ^ (2 * wi)) << 4));
#pragma unroll
        for (int i = 0; i < NL; i++) {
            wl5 = lds4(stg + (KS(i) ^ nf * 8) * 2048 + t * 16);
            if (i < 5) sts4(sb + sm_wl(i) + tid * 16, wl5.x, wl5.y, wl5.z, wl5.w);
        }
        fence_async_smem();
        if (wg < 2) bar_sync(NB_WG, 256);
        if (wg > 0) wait_count_w(&g_tick[32 + (lane & 3) * 8], wg);
        if (wg == 1) {
            mbar_arrive_cluster_if(t == 0, bars + 8 * B_HE, j ^ 1);
            asm volatile("fence.proxy.async.global;" ::: "memory");
            mbar_wait_w(bars + 8 * B_HE, 0);
#pragma unroll 1
            for (int i = 0; i < 2; i++) h_load(sb, hsrc, i, slot0, head, wiu, true, i ? 0 : 2048);
        }
        TL(3 + wg)
    }
    uint32_t g16 = opaque(t * 16);
    {
        const uint32_t wr = ((wg * 4 + wi) ^ (head & ROTM)) & 7;
        const uint32_t pc = wg < 2 ? acc_piece(wr >> 2, qd, wr & 3) : acc_piece(kh, (nf ^ (wi >> 1)) + 2 * (wi & 1), 0);
        const uint32_t lm = sb + SM_HB + 4096 + (lane & 7) * 128;
        const uint32_t a0 = wg < 2 ? sb + SM_WL + wg * 2048 + frow + ((fx ^ (2 * wi)) << 4) : blk(LB_STAMP + (wi >> 1), mypar) + stamp_line(wi, lane >> 3) + (lane & 7) * 16;
        const uint32_t a1 = pc + lane * 16;
        const uint32_t a2 = wg < 2 ? pc + 512 + (lane >> 3) * 4 : (role >> 2) * 1024 + (lane < 8 ? (role & 3) * 128 : 384) + lane * 16;
        const uint32_t a3 = wg < 2 ? sb + SM_WO + (wr >> 2) * 32768 + frow + ((fx ^ (2 * (wr & 3))) << 4) : qd * 65536 + head * 2048 + wi * 512 + lane * 4;
        const uint32_t a4 = wg < 2 ? lm + ((fx ^ ((lane >> 4) * 4)) << 4) : lm + (fx << 4) + ((lane >> 4) + (wi & 2) + 4 * (wi & 1)) * HCH;
        if (wg < 2) bar_arrive(NB_X2, 384);
        else bar_sync(NB_X2, 384);
        if (NL > 5) {
            sts4(sb + SM_WL2 + tid * 16, wl5.x, wl5.y, wl5.z, wl5.w);
            fence_async_smem();
            bar_sync(NB_WG + 1 + wg, 128);
        }
        sts4(sb + SM_TAB + wg * 5120 + g16, a0, x2o,
             wg ? xso + (wg == 2 ? 32768 : 0) + t * 8 : blk(LB_STAMP + ((lane >> 1) & 1), (lane >> 2) & 1) + stamp_line(lane, qd) + head * 4, tko);
        sts4(sb + SM_TAB + wg * 5120 + 2048 + g16, a1, a2, a3, a4);
        sts2(sb + SM_TAB + wg * 5120 + 4096 + t * 8, __uint_as_float(tbw + t * 16), __uint_as_float((wg ? tbq : tokbase(1)) + t * 16));
    }
    const uint32_t ONES = 0x3f803f80u, tabw = sb + SM_TAB + wg * 5120;
#define LAST ((g16 & 0x70) == 0x70)
    PROF_INIT

    auto pa_ptr = [&](int p) { return arena + (((p & 1) ^ 1) * 32768 + po + lds1(tabw + 4096 + (g16 >> 1))); };
    auto pa_request = [&](int p) { cp_async16(sb + SM_PA + wg * 2048 + g16, pa_ptr(p)); };
    auto pa_get = [&](int p) {
        asm volatile("cp.async.wait_all;" ::: "memory");
        uint4 pa = lds4(sb + SM_PA + wg * 2048 + g16);
        int it = 0;
#pragma unroll 1
        while (any_bit0(pa.x ^ ((p - 1) >> 1) ^ 1) && p > 0 && p <= NSEG) { pa = ldg_b128(pa_ptr(p)); spin_guard(++it); }
        return pa;
    };
    auto pass_init = [&](float* acc, int n, uint4 pa) {
#pragma unroll
        for (int i = 0; i < 4; i++) { acc[2 * i] = bflo((&pa.x)[i]); acc[2 * i + 1] = bfhi((&pa.x)[i]); }
#pragma unroll
        for (int i = 8; i < n; i++) acc[i] = 0.f;
    };
    auto pass_run = [&](auto vc, int p, float* acc, auto mid) {
        constexpr bool V = decltype(vc)::value;
#define HB(ks) dadd(mkdesc(SB0 + SM_HB + ((ks) >> 2) * HCH + ((ks) & 3) * 32, 16, 1024, 1), (p & 1) * (HBUF / 16))
        wg_fence();
#pragma unroll
        for (int i = 0; i < 32; i++) {
            constexpr int GAP = V ? SSG_V : SSG, SS0 = V ? SS0_V : SS0_K;
            const int u = i < SS0 ? 0 : (i - SS0 + GAP - 1) / GAP, q = i - (u < NL ? u : NL);
            if (i >= SS0 && (i - SS0) % GAP == 0 && u < NL) wgmma_tok_ss<V>(acc, dadd(mkdesc(SB0 + sm_wl(u), 8192, 1024, 1), (V ? 2 : wg) * 128), HB(KS(u)));
            else wgmma_tok_rs<V>(acc, w[q], HB(KS(NL + q)), 1);
            mid(i);
        }
        wg_commit();
    };
    auto pass_out = [&](auto tc, int p, float* acc, auto mid) {
        constexpr int TY = decltype(tc)::value;
        const bool V = TY == 2 || (TY == 4 && wg == 2), Q = TY == 0 || (TY >= 3 && wg == 0);
        const int b = p & 1, s = p - 2;
        (void)s;
        const uint32_t ftag = (((p - 1) >> 1) & 1) ^ 1, ptag = ((p >> 1) & 1) ^ 1;
        const bool tg = V || !(g16 & 64);
        const uint32_t add = tg ? (ftag ^ 1) << 16 : 0u, keep = tg ? 0xfffe0000u : ~0u;
        const uint32_t add1 = V ? 0u : add, keep1 = V ? ~0u : keep;
        const uint32_t add2 = Q ? add : 0u, keep2 = Q ? keep : ~0u;
        uint8_t* pdst = arena + (b * 32768 + (po ^ 2048) + lds1(tabw + 4096 + (g16 >> 1)));
        uint8_t* fdst = arena + ((b ^ 1) * 32768 + lds1(tabw + 12 + g16));
        if (PIN_EPI) asm volatile("" : "+l"(pdst), "+l"(fdst));
        mid(0);
        uint32_t r0 = pack2(pretag(acc[0], add, keep), pretag(acc[1], add1, keep1));
        uint32_t r1 = pack2(acc[2], acc[3]), r3 = pack2(acc[6], acc[7]);
        uint32_t r2 = pack2(pretag(acc[4], add2, keep2), pretag(acc[5], add2, keep2));
        if (!V) { r0 = movm(r0); r1 = movm(r1); r2 = movm(r2); r3 = movm(r3); }
        mid(1);
        if (TY == 0) stg_b128_if(p > 0 && p <= NSEG, fdst, settag(r0, ftag), r1, settag(r2, ftag), r3);
        stg_b128_if(p < NSEG, pdst, settag(pack2(pretag(acc[8], (ptag ^ 1) << 16, 0xfffe0000u), acc[9]), ptag), pack2(acc[10], acc[11]), pack2(acc[12], acc[13]), pack2(acc[14], acc[15]));
        if (TY != 0) stg_b128_if(p > 0 && p <= NSEG, fdst, settag(r0, ftag), r1, Q ? settag(r2, ftag) : r2, r3);
        PROF(10)
    };
    auto nop = [](int) {};
    auto wait0 = [](int i) { if (i == 0) wg_wait<0>(); };
    uint4 tf[2][2];
    auto load_tok = [&](int s, uint32_t o) {
        const uint8_t* ts = arena + ((s & 1) * 32768 + o);
#pragma unroll
        for (int a = 0; a < 2; a++)
#pragma unroll
            for (int b = 0; b < 2; b++) tf[a][b] = ldg_b128(ts + a * 16384 + b * 2048);
    };

    auto wo_load = [&](int stage) {
        if (wg == 2 && ((WO_AT >> (4 * wiu)) & 15) == stage) {
            const int c0 = (wiu >> 1) * 512 + qd * 128 + (wiu & 1) * 64;
            e_expect(bars + 8 * B_WO, 16384);
            e_tma2d(sb + SM_WO + wiu * 16384, tWo, c0, head * DH, bars + 8 * B_WO, evict_normal());
            e_tma2d(sb + SM_WO + wiu * 16384 + 8192, tWo, c0, head * DH + 64, bars + 8 * B_WO, evict_normal());
        }
    };
#pragma unroll 1
    for (int p = 0; p <= (wg >> 1); p++) {
        mbar_wait_w(bars + 8 * (B_HB + p), 0);
        float acc[16];
        pass_init(acc, 16, pa_get(p));
        if (wg == 2) TX(2 + 3 * p)
        wo_load(p);
        pass_run(IC<0>(), p, acc, nop);
        if (p) {
            mbar_wait_w(bars + 8 * B_HE, 1);
            asm volatile("fence.proxy.async.global;" ::: "memory");
            h_load(sb, hsrc, 2, slot0, head, wiu);
        }
        pass_out(IC<4>(), p, acc, wait0);
        if (wg < 2) {
            bar_arrive(NB_C, 384);
            if (wg == 0) bar_arrive(NB_WIN, 384);
        } else if (p == 0) {
            TX(3)
            bar_sync(NB_C, 384);
            mbar_arrive_cluster_if(g16 == 0, bars + 8 * B_HE, j ^ 1);
        }
        pa_request(p + 1);
    }
    if (wg < 2) {
        mbar_wait_w(bars + 8 * (B_HB + 1), 0);
        uint4 pa = pa_get(1);
        uint32_t wl = lds1(tabw + g16);
#pragma unroll 1
        for (int s = 0; s < NSEG; s++) {
            uint32_t w0[NL][4], xo, lm, fz = 0;
            float acc[16];
#pragma unroll
            for (int i = 0; i < 4; i++)
                asm volatile("shl.b32 %0, %4, 16; and.b32 %1, %4, 0xffff0000; mov.b32 %2, %5; mov.b32 %3, %5;"
                             : "=&f"(acc[2 * i]), "=f"(acc[2 * i + 1]), "=f"(acc[8 + 2 * i]), "=f"(acc[9 + 2 * i]) : "r"((&pa.x)[i]), "r"(zero));
            if (W0_AT < 0) {
#pragma unroll
                for (int i = 0; i < NL; i++) ldsm4t(w0[i], wl + (sm_wl(i) - SM_WL));
            }
            if (INIT_F) fz = clk32();
            uint32_t kq;
            if (wg == 0) bar_sync(NB_B, 256);
            else bar_sync(NB_WIN, 384);
            pass_run(IC<0>(), s + 1, acc, [&](int i) {
                if (i == W0_AT) {
                    if (W0_F & 1) fz |= clk32();
#pragma unroll
                    for (int i = 0; i < NL; i++) ldsm4t(w0[i], wl + (sm_wl(i) - SM_WL));
                    if (W0_F & 2) fz |= clk32();
                }
                if (i == GATE_AT && wg) bar_arrive(NB_B, 256);
            });
            xo = lds1(tabw + 4 + g16);
            lm = lds1(tabw + 2060 + g16) + (s & 1) * HBUF;
            if (KQ_AT <= 16) kq = lds1(tabw + 4096 + (g16 >> 1) * wg);
            auto done = [&](int i) {
                if (i == 0) {
                    wg_wait<0>();
                    if (wg == 0) bar_arrive(NB_MEM, TWO ? 320 : 384);
                    fz |= clk32();
                    { const int s_ = s; { const int s = s_ - 1; (void)s; PROF(9) } }
                }
                if (i == 1 && ST_GATE && wg) bar_sync(NB_F, 256);
            };
            if (!Q_LATE) pass_out(IC<3>(), s + 1, acc, done);
            else { done(0); if (wg) pass_out(IC<1>(), s + 1, acc, [&](int i) { if (i) done(1); }); }
            asm volatile("" : "+r"(lm));
            if (wg == 0) bar_sync(NB_MEM2, TWO ? 192 : 256);
            else bar_sync(NB_MEM, TWO ? 320 : 384);
            PROF(1)
            float c[4][4];
            uint32_t bq[PD][4];
#define MEMF(it) ((lm ^ (((it) & 4) * 8)) + SLOT(it) * HCH)
#pragma unroll
            for (int it = 0; it < PD; it++) ldsm4(bq[it], MEMF(it));
#pragma unroll
            for (int it = 0; it < 16; it++) {
                uint32_t* bfr = bq[it % PD];
                const uint32_t* wa = 2 * it < NL ? w0[2 * it < NL ? 2 * it : 0] : w[2 * it < NL ? 0 : 2 * it - NL];
                const uint32_t* wb = 2 * it + 1 < NL ? w0[2 * it + 1 < NL ? 2 * it + 1 : 0] : w[2 * it + 1 < NL ? 0 : 2 * it + 1 - NL];
                float *ca = c[(2 * it) & 3], *cb = c[(2 * it + 1) & 3];
                if (it < 2) { mma16816z(ca, wa, bfr[0], bfr[1]); mma16816z(cb, wb, bfr[2], bfr[3]); }
                else { mma16816(ca, wa[0], wa[1], wa[2], wa[3], bfr[0], bfr[1]); mma16816(cb, wb[0], wb[1], wb[2], wb[3], bfr[2], bfr[3]); }
                if (TWO && it + PD == 8) bar_sync(NB_FAR + wg, 192);
                if (it + PD < 16) ldsm4(bfr, MEMF(it + PD));
                if (it == KQ_AT) {
                    if (PFENCE) fz |= clk32();
                    load_tok(s, kq);
                }
            }
            if (QK_EARLY) bar_arrive(NB_QK + (__float_as_uint(c[0][0]) & zero), 384);
            const uint32_t r0 = pack2((c[0][0] + c[1][0]) + (c[2][0] + c[3][0]), (c[0][1] + c[1][1]) + (c[2][1] + c[3][1]));
            const uint32_t r1 = pack2((c[0][2] + c[1][2]) + (c[2][2] + c[3][2]), (c[0][3] + c[1][3]) + (c[2][3] + c[3][3]));
            if (!QK_EARLY) bar_arrive(NB_QK + (r0 & zero), 384);
            stg_rlx2(arena + xo, settag(movm(r0), (s & 1) ^ 1), movm(r1));
            const uint32_t tx = later(lds1(sb + SM_LX + 1040) + tm.x2, clk_after(r0, zero) + tm.dx2);
            g16 |= (fz | tx) & zero;
            PROF(2)
            {
                const uint32_t l16 = sb + (g16 & 0x1f0), g8 = g16 >> 1;
                const uint32_t tag = (s & 1) ^ 1, ttag = ((s >> 1) & 1) ^ 1;
                uint32_t wf[NPF][4], a3;
#define WF(f) (a3 + ((f) & 1) * 16384 + ((f) >> 1) * 2048)
                if (wg == 1) {
                    float sc[5][4];
                    uint4 (&kf)[2][2] = tf;
                    uint32_t qa[2][4], km[4], fz;
                    int it = 0;
                    bool bad;
#pragma unroll 1
                    do {
                        u64 qf[2], x[8];
                        const float2 u = lds2f(tabw + 4096 + g8);
                        if (KQ_AT > 16) load_tok(s, __float_as_uint(u.x));
                        else {
#pragma unroll 1
                            for (int i = it; i > 0; i &= zero) load_tok(s, __float_as_uint(u.x));
                        }
                        const uint8_t *xp = arena + lds1(tabw + 8 + g16), *tq = arena + ((s & 1) * 32768 + __float_as_uint(u.y));
                        asm volatile("" : "+l"(xp));
                        asm volatile("" : "+l"(tq));
#pragma unroll
                        for (int a = 0; a < 2; a++) if (!Q_LATE) qf[a] = ldg_u64(tq + a * 16384);
                        spin_guard(++it);
                        wait_clk(tx);
                        PROF(8)
#pragma unroll
                        for (int i = 0; i < 8; i++) x[i] = ldg_u64(xp + (i >> 2) * 16384 + (i & 3) * 1024);
#pragma unroll
                        for (int a = 0; a < 2; a++) if (Q_LATE) qf[a] = ldg_u64(tq + a * 16384);
                        fz = clk32();
                        const uint32_t bt = or3(xor_or(lo32(qf[0]), lo32(qf[1]), ttag), xor_or(kf[0][0].x, kf[0][1].x, ttag), xor_or(kf[1][0].x, kf[1][1].x, ttag));
#pragma unroll
                        for (int a = 0; a < 2; a++) { qa[a][1] = or3(lo32(qf[a]), zero, 0); qa[a][3] = or3(hi32(qf[a]), zero, 0); }
                        fz |= clk32();
#pragma unroll
                        for (int a = 0; a < 2; a++) { qa[a][0] = hadd2v(lo32(x[2 * a]), lo32(x[2 * a + 1])); qa[a][2] = hadd2v(hi32(x[2 * a]), hi32(x[2 * a + 1])); }
#pragma unroll
                        for (int a = 0; a < 2; a++) { km[2 * a] = hadd2v(lo32(x[4 + 2 * a]), lo32(x[5 + 2 * a])); km[2 * a + 1] = hadd2v(hi32(x[4 + 2 * a]), hi32(x[5 + 2 * a])); }
                        bad = any_bit0(or3(or3(bt, xor_or(lo32(x[0]), lo32(x[1]), tag), xor_or(lo32(x[2]), lo32(x[3]), tag)), xor_or(lo32(x[4]), lo32(x[5]), tag), xor_or(lo32(x[6]), lo32(x[7]), tag)));
                    } while (bad);
                    PROFV(13, it - 1)
                    PROF(7)
                    mma16816z(sc[0], qa[0], kf[0][0].x, kf[0][0].y);
                    mma16816z(sc[1], qa[0], kf[0][0].z, kf[0][0].w);
                    mma16816z(sc[2], qa[0], kf[0][1].x, kf[0][1].y);
                    mma16816z(sc[3], qa[0], kf[0][1].z, kf[0][1].w);
                    mma16816z(sc[4], qa[0], km[0], km[1]);
                    mma16816(sc[0], qa[1][0], qa[1][1], qa[1][2], qa[1][3], kf[1][0].x, kf[1][0].y);
                    mma16816(sc[1], qa[1][0], qa[1][1], qa[1][2], qa[1][3], kf[1][0].z, kf[1][0].w);
                    mma16816(sc[2], qa[1][0], qa[1][1], qa[1][2], qa[1][3], kf[1][1].x, kf[1][1].y);
                    mma16816(sc[3], qa[1][0], qa[1][1], qa[1][2], qa[1][3], kf[1][1].z, kf[1][1].w);
                    mma16816(sc[4], qa[1][0], qa[1][1], qa[1][2], qa[1][3], km[2], km[3]);
                    const uint32_t sx = sb + SM_SX + (g16 & 0x1f0) * 5;
                    sts4(sx + (g16 >> 5 & 0x30), pack_h2(sc[0][0], sc[0][1]), pack_h2(sc[1][0], sc[1][1]),
                         pack_h2(sc[2][0], sc[2][1]), pack_h2(sc[3][0], sc[3][1]));
                    sts1(sx + 64 + (g16 >> 7 & 0xc), pack_h2(sc[4][0], sc[4][1]));
                    bar_arrive(NB_X1, 256);
                    if (s == 0) TX(15)
                    const uint32_t now = gtime32();
#pragma unroll
                    for (int n = 0; n < 5; n++) sts2(sb + SM_ST + g8 + n * 1088, sc[n][2], sc[n][3]);
                    bar_arrive(NB_H, 256);
                    PROF(3)
                    a3 = lds1(tabw + 2056 + g16) | (fz & zero);
                    asm volatile("{.reg .pred p; setp.lt.u32 p, %2, 128; @p red.relaxed.gpu.global.max.u32 [%0], %1;}"
                                 ::"l"(arena + lds1(sb + SM_TAB + 8 + g16)), "r"(__funnelshift_r(now * 8, s + 1, 8)), "r"(g16) : "memory");
                    auto h_next = [&]() {
                        asm volatile("fence.proxy.async.global;" ::: "memory");
                        if (s + 3 <= NSEG) h_load(sb, hsrc, s + 3, slot0, head, wiu);
                    };
                    if (H_AT == 0) h_next();
                    if (s == 0) mbar_wait_w(bars + 8 * B_WO, 0);
                    const uint32_t th = clk32() + tm.v;
                    if (PF_DLY) a3 += delay<PF_DLY>(zero);
#pragma unroll
                    for (int f = 0; f < NPF; f++) ldsm4t(wf[f], WF(f));
                    if (H_AT == 2) {
#pragma unroll 1
                        while ((int)(clk32() - th) < 0) {}
                        h_next();
                    }
                } else {
                    if (Q_LATE) pass_out(IC<0>(), s + 1, acc, nop);
                    if (H_AT == 1 && g16 == 0) mbar_arrive_cluster(bars + 8 * B_HE, j ^ 1);
                    if (s == 0) { TL(9) mbar_wait_w(bars + 8 * B_WO, 0); TL(6) }
                    if (warp0 && !(s & 3)) {
                        const uint32_t need = min((s + 4) / 4 + 2, 17), a = sb + SM_LX + 1024 + ((g16 >> 2) & 12);
                        if (s == 0 || __any_sync(~0u, lds1(a) < need)) sts1(a, wait_count_w(&g_tick[32 + ((g16 >> 4) & 3) * 8], need));
                    }
                    a3 = lds1(tabw + 2056 + g16);
#pragma unroll
                    for (int f = 0; f < NPF0; f++) ldsm4t(wf[f], WF(f));
                    const float2 u = lds2f(tabw + 4096 + g8);
                    const uint8_t *q0 = arena + (tag * 32768 + po + __float_as_uint(u.x)), *q1 = arena + (tag * 32768 + po + __float_as_uint(u.y));
                    if (H_AT == 1) {
                        mbar_wait_w(bars + 8 * B_HE, s & 1);
                        asm volatile("fence.proxy.async.global;" ::: "memory");
                    }
                    wait_clk(tx + tm.h);
                    int it = 0;
                    bool bad;
#pragma unroll 1
                    do {
                        const uint4 p0 = ldg_b128(q0), p1 = ldg_b128(q1);
                        if (H_AT == 1 && !it && s + 3 <= NSEG) h_load(sb, hsrc, s + 3, slot0, head, wiu);
                        spin_guard(++it);
                        if (NPF0 < NPF1) wait_clk(tx + tm.v);
#pragma unroll
                        for (int f = NPF0; f < NPF1; f++) ldsm4t(wf[f], WF(f));
                        sts4(sb + SM_PA + g16, p0.x, p0.y, p0.z, p0.w);
                        sts4(sb + SM_PA + 2048 + g16, p1.x, p1.y, p1.z, p1.w);
                        bad = any_bit0(xor_or(p0.x, p1.x, ((s + 1) >> 1) ^ 1)) && s + 2 <= NSEG;
                    } while (bad);
                    bar_sync(NB_H, 256);
                    PROF(3)
                    softmax_rows<true>(sb + SM_ST, sb + SM_PX, g16, qd * 8, [&](uint32_t v) {
                        a3 += v & zero;
#pragma unroll
                        for (int f = NPF1; f < NPF2; f++) ldsm4t(wf[f], WF(f));
                    });
#pragma unroll
                    for (int f = NPF2; f < NPF; f++) ldsm4t(wf[f], WF(f));
                }
                PROF(5)
                float2 ls, a12;
                uint32_t fy = 0;
                uint8_t *d0, *d1;
                bar_sync(NB_X2, 384);
                float c[4][4];
                uint32_t obs[4][4];
#pragma unroll
                for (int q = 0; q < NOB; q++) ldsm4t(obs[q], l16 + SM_OX + q * 512);
                if (NOB > 1) __syncwarp();
#pragma unroll
                for (int q = 0; q < 4; q++) {
                    const uint32_t* ob = obs[q];
                    if (q > 0 && q + NOB - 1 < 4) ldsm4t(obs[q + NOB - 1], l16 + SM_OX + (q + NOB - 1) * 512);
                    if (q == L_AT) ls = lds2f(sb + SM_LX + g8);
                    if (q == 2) { pa = lds4(sb + SM_PA + wg * 2048 + g16); wl = lds1(tabw + g16); }
                    if (q == 3 && ACC_PIN == 2) fy = clk32();
                    if (q == 2) { a12 = lds2f(tabw + 2048 + g16); d0 = arena + (acc_slot(s + 1) + __float_as_uint(a12.x)); d1 = arena + (acc_slot(s + 1) + __float_as_uint(a12.y)); }
#pragma unroll
                    for (int f = 4 * q; f < 4 * q + 4; f++) {
                        const uint32_t* a = wf[f % NPF];
                        if (f < 4) mma16816z(c[f], a, ob[f & 2], ob[(f & 2) + 1]);
                        else mma16816(c[f & 3], a[0], a[1], a[2], a[3], ob[f & 2], ob[(f & 2) + 1]);
                        if (f + NPF < 16) ldsm4t(wf[f % NPF], WF(f + NPF));
                    }
                }
                if (ACC_PIN == 1) fy = clk32();
                if (wg == 0) bar_arrive(NB_WIN, 384);
                float i0 = rcp_fast(ls.x), i1 = rcp_fast(ls.y);
                uint32_t sel = LAST ? 0x7610 : 0x3210;
                if (ACC_PIN) {
                    asm volatile("" : "+f"(i0), "+f"(i1), "+l"(d0), "+l"(d1), "+r"(sel));
                    fy |= clk32();
                }
                uint32_t v[4];
#pragma unroll
                for (int m = 0; m < 4; m++) v[m] = pack_h2((c[m >> 1][(m & 1) * 2] + c[(m >> 1) + 2][(m & 1) * 2]) * i0, (c[m >> 1][(m & 1) * 2 + 1] + c[(m >> 1) + 2][(m & 1) * 2 + 1]) * i1);
                red_h10(sel > 0x4000, d0, d1, v[0], v[1], v[2], prmt(v[3], ACC_ONE, sel), __byte_perm(v[3], ACC_ONE, 0x7632));
                g16 |= (v[0] | fy) & zero;
                PROF(6)
            }
        }
        if (wg) bar_sync(NB_WIN, 384);
    } else {
        TLC(0)
        auto request = [&](int s, uint32_t o) {
            cp_async16(sb + SM_PA + 4096 + g16, arena + (((s & 1) ^ 1) * 32768 + po + o));
            const uint8_t* ts = arena + ((s & 1) * 32768 + o);
#pragma unroll
            for (int i = 0; i < 4; i++) cp_async16(sb + SM_VF + i * 2048 + g16, ts + (i >> 1) * 16384 + (i & 1) * 2048);
        };
        auto fetch = [&](int s, uint4 t1, auto wait, auto after) {
            const uint32_t mo = acc_slot(s) + t1.x, eo = mo - (g16 & 0x1f0) + 512 + ((g16 >> 5) & 12);
            const uint8_t *ms = arena + mo, *es = arena + eo;
            uint32_t e[4] = {0, 0, 0, 0}, sel = LAST ? 0x5410 : 0x3210, dst[4];
            const bool far = g16 & 0x400;
            uint32_t b1 = far ? NB_FAR + 1 : NB_MEM, n1 = far ? 192 : 320, b2 = far ? NB_FAR : NB_MEM2;
#pragma unroll
            for (int i = 0; i < 4; i++) dst[i] = (t1.w + (s & 1) * HBUF) ^ (i * 32);
            asm volatile("" : "+l"(ms), "+l"(es), "+r"(e[0]), "+r"(e[1]), "+r"(e[2]), "+r"(e[3]), "+r"(sel), "+r"(dst[0]), "+r"(dst[1]), "+r"(dst[2]), "+r"(dst[3]), "+r"(b1), "+r"(n1), "+r"(b2));
            uint32_t late = wait(), fz;
            PROF(11) PROFV(0, gtime32())
            int it = 0;
            bool bad;
#pragma unroll 1
            do {
                uint4 m[4];
                uint32_t b = 0;
#pragma unroll
                for (int i = 0; i < 4; i++) {
                    m[i] = ldg_rlx4(ms + i * 1024);
                    ldg1_if(e[i], es + i * 1024, LAST);
                }
                if (ST_GATE && it == 0) bar_arrive(NB_F, 256);
                const uint32_t now = clk32();
                fz = now;
                after(now & zero);
                sts1(sb + SM_LX + 1040, now - min(late >> 8, 8u) * 57);
                late = 0;
                spin_guard(++it);
#pragma unroll
                for (int n = 0; n < 4; n++) {
                    const int i = n;
                    if (STG_FENCE >> n & 1) fz |= clk32();
                    b |= xor_or(m[i].w, e[i], ACC_ALL);
                    stsm4t(dst[i], h2bf(m[i].x), h2bf(m[i].y), h2bf(m[i].z), h2bf(prmt(m[i].w, e[i], sel)));
                }
                bad = __any_sync(~0u, LAST && b > 0xffffu);
            } while (bad);
            if (TWO) { bar_arrive(b1, n1); bar_arrive(b2, 192); }
            else { bar_arrive(NB_MEM, 384); bar_arrive(NB_MEM2, 256); }
            g16 |= fz & zero;
            PROFV(12, it - 1) PROF(1)
        };
        TX(6)
        fetch(0, lds4(tabw + 2048 + g16), []() { return 0u; }, [&](uint32_t z) { request(0, lds1(tabw + 4096 + (g16 >> 1)) + z); });
        wo_load(2);
        TX(7)
#pragma unroll 1
        for (int s = 0;; s++) {
            const uint32_t tag = (s & 1) ^ 1, ttag = ((s >> 1) & 1) ^ 1, l16 = sb + (g16 & 0x1f0), g8 = g16 >> 1;
            const int p = s + 2;
            if (s == 1) TL(7)
            if (s == 0) TL(13)
            fence_async_smem();
            stg_b128_if(g16 < ((role & 3) ? 128 : 160), arena + (acc_slot(s + 3) + lds1(tabw + 2052 + g16)), 0, 0, 0, 0);
            const uint4 pa = pa_get(p);
            if (p <= NSEG) mbar_wait_w(bars + 8 * (B_HB + (p & 1)), (p >> 1) & 1);
            if (H_AT >= 3) {
                asm volatile("fence.proxy.async.global;" ::: "memory");
                if (warp0 && s + 3 <= NSEG) e_expect(bars + 8 * (B_HB + ((s + 3) & 1)), 32768);
            }
            uint8_t* xd = arena + lds1(tabw + 4 + g16);
            uint32_t tx;
            float acc[20];
            pass_init(acc, 20, pa);
            if (s == 0) TX(10)
            bar_sync(NB_QK, 384);
            pass_run(IC<1>(), p, acc, nop);
            pass_out(IC<2>(), p, acc, [&](int i) {
                if (i) return;
                wg_wait<0>();
                const uint32_t r0 = pack2(acc[16], acc[17]);
                stg_rlx2(xd, settag(r0, tag), pack2(acc[18], acc[19]));
                tx = clk_after(r0, zero) + tm.dv;
                PROF(2)
            });
            uint4 (&vf)[2][2] = tf;
#pragma unroll
            for (int i = 0; i < 4; i++) vf[i >> 1][i & 1] = lds4(sb + SM_VF + i * 2048 + g16);
            uint32_t xv[4] = {0, 0, 0, 0};
            float oc[2][4], lc[4];
            auto pv = [&](uint32_t p0, uint32_t p1, uint32_t p2, uint32_t p3, uint32_t p4, auto mid) {
                lc[0] = lc[1] = lc[2] = lc[3] = 0.f;
                mma16816z(oc[0], &vf[0][0].x, p0, p1);
                mma16816z(oc[1], &vf[1][0].x, p0, p1);
                mma16816(lc, ONES, ONES, ONES, ONES, p0, p1);
                mma16816(oc[0], vf[0][1].x, vf[0][1].y, vf[0][1].z, vf[0][1].w, p2, p3);
                mma16816(oc[1], vf[1][1].x, vf[1][1].y, vf[1][1].z, vf[1][1].w, p2, p3);
                mma16816(lc, ONES, ONES, ONES, ONES, p2, p3);
                mid();
                mma1688(oc[0], xv[0], xv[1], p4);
                mma1688(oc[1], xv[2], xv[3], p4);
                mma1688(lc, ONES, ONES, p4);
            };
            uint32_t so, to, fz = 0;
            uint4 t1;
            int it = 0;
            bool bad;
#pragma unroll 1
            do {
#pragma unroll 1
                for (int i = it; i > 0; i &= zero) load_tok(s, lds1(tabw + 4096 + g8));
                u64 xr[4];
                const uint8_t* xp = arena + lds1(tabw + 8 + g16);
                asm volatile("" : "+l"(xp));
                auto load_v = [&](uint32_t z) {
#pragma unroll
                    for (int i = 0; i < 4; i++) xr[i] = ldg_u64(xp + z + i * 1024);
                };
                const uint32_t bt = or3(xor_or(vf[0][0].x, vf[0][1].x, ttag), xor_or(vf[1][0].x, vf[1][1].x, ttag), 0);
                uint32_t sa = sb + SM_SX + (g16 & 0x1f0) * 5;
                asm volatile("" : "+r"(sa));
                spin_guard(it);
                wait_clk(tx);
                PROF(3)
                if (s == 0 && it == 0) TX(11)
                if (it++ == 0) bar_sync(NB_X1, 256);
                if (VP_AT == 0) load_v(0);
                uint4 sx[5];
#pragma unroll
                for (int i = 0; i < 5; i++) sx[i] = lds4(sa + i * 16);
                __syncwarp();
                if (VP_AT == 1) load_v(0);
                if (VP_AT == 2) load_v(sx[0].x & zero);
                if (VP_AT == 3) load_v(sx[4].x & zero);
                uint32_t pm[5];
                uint32_t a[5];
#pragma unroll
                for (int n = 0; n < 5; n++) {
                    uint32_t u[4];
#pragma unroll
                    for (int w = 0; w < 4; w++) u[w] = n < 4 ? (&sx[w].x)[n] : (&sx[4].x)[w];
                    a[n] = hadd2h(hadd2h(u[0], u[1]), hadd2h(u[2], u[3]));
                }
                uint32_t m = hmax2h(hmax2h(hmax2h(a[0], a[1]), hmax2h(a[2], a[3])), a[4]);
                if (SH3) {
                    const uint32_t m1 = __shfl_xor_sync(~0u, m, 1), m2 = __shfl_xor_sync(~0u, m, 2), m3 = __shfl_xor_sync(~0u, m, 3);
                    m = hmax2h(hmax2h(m, m1), hmax2h(m2, m3));
                } else {
                    m = hmax2h(m, __shfl_xor_sync(~0u, m, 1));
                    m = hmax2h(m, __shfl_xor_sync(~0u, m, 2));
                }
                if (VP_AT == 4) load_v(m & zero);
                so = lds1(tabw + g16); t1 = lds4(tabw + 2048 + g16); to = lds1(tabw + 4096 + g8);
                const float2 mm = unpack_h2(m);
                const float mf = -SM_L2E * fmaxf(mm.x, mm.y);
#pragma unroll
                for (int n = 0; n < 5; n++) { const float2 u = unpack_h2(a[n]); pm[n] = pack2(ex2(fmaf(u.x, SM_L2E, mf)), ex2(fmaf(u.y, SM_L2E, mf))); }
                PROF(4)
                pv(pm[0], pm[1], pm[2], pm[3], pm[4], [&]() {
                    if (PV_FENCE & 1) fz = clk32();
#pragma unroll
                    for (int i = 0; i < 2; i++) { xv[2 * i] = hadd2v(lo32(xr[2 * i]), lo32(xr[2 * i + 1])); xv[2 * i + 1] = hadd2v(hi32(xr[2 * i]), hi32(xr[2 * i + 1])); }
                });
                bad = any_bit0(or3(bt, xor_or(lo32(xr[0]), lo32(xr[1]), tag), xor_or(lo32(xr[2]), lo32(xr[3]), tag)));
                if (PV_FENCE & 2) fz |= clk32();
                stsm4(sb + SM_OX + g16, pack2(oc[0][0], oc[0][1]), pack2(oc[0][2], oc[0][3]), pack2(oc[1][0], oc[1][1]), pack2(oc[1][2], oc[1][3]));
                sts2(sb + SM_LX + g8, lc[0], lc[1]);
            } while (bad);
            if (s == 0) TX(12)
            PROFV(14, it - 1)
            PROF(5)
            bar_sync(NB_X2, 384);
            const uint8_t* sp = arena + so;
            uint4 sv;
            if (SV_AT != 1) sv = ldg_rlx4(sp);
            if (s == 0) TX(13)
            auto h_next = [&]() { if (s + 3 <= NSEG) h_load(sb, hsrc, s + 3, slot0, head, wiu, false); };
            if (H_AT == 3) h_next();
            if (!REQ_LATE) request(s + 1, to);
            const uint32_t dz = TPV_DLY ? delay<TPV_DLY>(zero) : 0;
            {
                const uint4 pp = lds4(l16 + SM_PX + dz);
                pv(pp.x, pp.y, pp.z, pp.w, lds1(sb + SM_PX + 512 + ((g16 >> 2) & 0x7c)), [&]() {
                    if (SV_AT) fz |= clk32();
                    if (SV_AT == 1) sv = ldg_rlx4(sp);
                    if (SV_AT == 2) cp_async16(sb + SM_SV + g16, sp);
                });
            }
            const float i0 = rcp_fast(lc[0]), i1 = rcp_fast(lc[1]);
            bar_arrive(NB_WIN + ((__float_as_uint(i0) | fz) & zero), 384);
            if (H_AT == 4) h_next();
            uint8_t* od = (uint8_t*)g_O + ((size_t)s * (32 * NH * DH * 2) + t1.z);
            const uint32_t ov[4] = {pack2(oc[0][0] * i0, oc[0][1] * i1), pack2(oc[0][2] * i0, oc[0][3] * i1), pack2(oc[1][0] * i0, oc[1][1] * i1), pack2(oc[1][2] * i0, oc[1][3] * i1)};
#pragma unroll
            for (int a = 0; a < 4; a++) if (!O_LATE || s + 1 == NSEG) stg_rlx1(od + a * 128, ov[a]);
            if (REQ_LATE == 1) request(s + 1, to);
            PROF(6)
            if (s + 1 == NSEG) break;
            fetch(s + 1, t1, [&]() {
                int it = 0;
#pragma unroll 1
                while (__any_sync(~0u, (int)(min(__vimin3_u32(sv.x, sv.y, sv.z), sv.w) >> 24) <= s)) {
                    if (SV_AT == 2 && it == 0) { asm volatile("cp.async.wait_all;" ::: "memory"); sv = lds4(sb + SM_SV + g16); }
                    else sv = ldg_rlx4(sp);
                    spin_guard(++it);
                }
                if (s == 0) TX(14)
                PROFV(15, it)
                const uint32_t tgo = (__reduce_max_sync(~0u, max(max3u(sv.x, sv.y, sv.z), sv.w)) + tm.go + (sv.x & zero)) << 8;
                PROF(7)
                int late;
#pragma unroll 1
                do { late = gtime32() * 8 - tgo; } while (late < 0);
                __syncwarp();
                return (uint32_t)late;
            }, [&](uint32_t z) {
#pragma unroll
                for (int a = 0; a < 4; a++) if (O_LATE) stg_rlx1(od + a * 128, ov[a]);
                if (REQ_LATE == 2) request(s + 1, to + z);
            });
            if (REQ_LATE == 3) request(s + 1, to);
        }
        TL(8) TLC(1)
    }
    asm volatile("cp.async.wait_all;" ::: "memory");
    PROF_OUT
}

struct RecMaps { CUtensorMap wq, wk, wv, wo; };
struct RecPtrs { const bf16 *x, *mem0, *c, *wmod, *w1, *w3; uint8_t* arena; uint32_t zero; RecTime tm; const bf16 *wq, *wk; };

__device__ __forceinline__ float silu_bf(const bf16* c, int i) {
    const float v = __bfloat162float(c[i]);
    return bfround(__fdividef(v, 1.0f + __expf(-v)));
}
__device__ __noinline__ void rec_ln(float* coef, const RecPtrs& p, int id, int r0) {
    int r1 = 32;
    const int tid = threadIdx.x;
    const int lane = tid & 31, wid = tid >> 5;
    const uint32_t ring = smem_u32(coef) - SM_PRE + wid * 8192 + lane * 16;
    auto fetch = [&](int r) {
        if (r < r1) {
            const bf16* src = p.x + (size_t)(r * 64 + (id * 8 + wid) * 2) * DM + lane * 8;
#pragma unroll
            for (int i = 0; i < 8; i++) {
                if (EF & 2) cp_async16_ef(ring + (r & 1) * 4096 + i * 512, src + i * 256);
                else cp_async16(ring + (r & 1) * 4096 + i * 512, src + i * 256);
            }
        }
        asm volatile("cp.async.commit_group;" ::: "memory");
    };
    auto row8 = [&](uint32_t a, float* f) {
        const uint4 v = lds4(a);
        f[0] = bflo(v.x); f[1] = bfhi(v.x); f[2] = bflo(v.y); f[3] = bfhi(v.y); f[4] = bflo(v.z); f[5] = bfhi(v.z); f[6] = bflo(v.w); f[7] = bfhi(v.w);
    };
#pragma unroll 1
    for (int r = r0 - 2; r < r1; r++) {
        if (r >= r0) {
            asm volatile("cp.async.wait_group 1;" ::: "memory");
            const uint32_t a = ring + (r & 1) * 4096;
            float m[2] = {0.f, 0.f}, t[2];
#pragma unroll 1
            for (int ps = 0; ps < 2; ps++) {
                t[0] = t[1] = 0.f;
#pragma unroll 1
                for (int i = 0; i < 4; i++)
#pragma unroll
                    for (int h = 0; h < 2; h++) {
                        float f[8];
                        row8(a + h * 2048 + i * 512, f);
#pragma unroll
                        for (int e = 0; e < 8; e++) { const float d = f[e] - m[h]; t[h] = fmaf(d, ps ? d : 1.0f, t[h]); }
                    }
#pragma unroll
                for (int o = 16; o; o >>= 1) { t[0] += __shfl_xor_sync(~0u, t[0], o); t[1] += __shfl_xor_sync(~0u, t[1], o); }
                if (ps == 0) { m[0] = t[0] * (1.0f / DM); m[1] = t[1] * (1.0f / DM); }
            }
            t[0] = rsqrtf(t[0] * (1.0f / DM) + 1e-5f); t[1] = rsqrtf(t[1] * (1.0f / DM) + 1e-5f);
            if (r == r0) {
#pragma unroll 1
                for (int i = tid; i < 2 * DM / 4; i += 256) {
                    float4 u;
                    int it = 0;
                    uint32_t ok;
#pragma unroll 1
                    do {
                        uint4 v[8];
#pragma unroll
                        for (int k = 0; k < 8; k++) v[k] = ldg_rlx4(g_modp + k * 2 * DM + i * 4);
                        ok = 1;
                        u = make_float4(0.f, 0.f, 0.f, 0.f);
#pragma unroll
                        for (int k = 0; k < 8; k++) {
                            ok &= v[k].x & v[k].y & v[k].z & v[k].w;
                            u.x += __uint_as_float(v[k].x); u.y += __uint_as_float(v[k].y); u.z += __uint_as_float(v[k].z); u.w += __uint_as_float(v[k].w);
                        }
                        spin_guard(++it);
                    } while (!ok);
                    const uint32_t lo = pack2(u.x, u.y), hi = pack2(u.z, u.w);
                    const float one = i >= DM / 4 ? 1.0f : 0.0f;
                    *(float4*)(coef + i * 4) = make_float4(bflo(lo) + one, bfhi(lo) + one, bflo(hi) + one, bfhi(hi) + one);
                }
                bar_sync(NB_FIN0, 256);
                if (tid == 0 && r0 == 0) TL(2)
            }
            const int row = r * 64 + (id * 8 + wid) * 2;
#pragma unroll 1
            for (int i = 0; i < 4; i++) {
                const float4* cf = (const float4*)(coef + i * 256 + lane * 8);
                const float4 s0 = cf[0], s1 = cf[1], c0 = cf[256], c1 = cf[257];
                const float sh[8] = {s0.x, s0.y, s0.z, s0.w, s1.x, s1.y, s1.z, s1.w}, sc[8] = {c0.x, c0.y, c0.z, c0.w, c1.x, c1.y, c1.z, c1.w};
                const int own = ((row >> 4) & 1) == (i >> 1), rr = row & 15;
                const uint32_t off = ((row >> 5) + own) * 65536 + (i * 4 + (lane >> 3)) * 4096 + (rr + (own ? 0 : 16)) * 128 + (((lane & 7) ^ (rr & 7)) << 4);
#pragma unroll
                for (int h = 0; h < 2; h++) {
                    float y[8];
                    row8(a + h * 2048 + i * 512, y);
#pragma unroll
                    for (int e = 0; e < 8; e++) y[e] = fmaf((y[e] - m[h]) * t[h], sc[e], sh[e]);
                    *(uint4*)((uint8_t*)g_himg + (off ^ (h * 144))) = pack8(y);
                }
            }
            if (r == 0) {
                int v, it = 0;
#pragma unroll 1
                do { v = *(volatile int*)((uint8_t*)coef - SM_PRE + SM_BAR + 192); spin_guard(++it); } while (v == INT_MIN);
                if (v >= 0) r1 = 2;
            }
        }
        fetch(r + 2);
        if (r < r0 || (r > 0 && !(r & 1))) continue;
        bar_sync(r == 0 ? NB_C : r == 1 ? NB_FIN0 : NB_LN, r == 0 ? 320 : r == 1 ? 256 : 288);
        if (r < 2 && wid == r) {
            if (r == 1) bar_arrive(NB_B, 64);
            if (lane == 0) { signal_count(&g_tick[32 + id * 8]); TL(13) }
            __syncwarp();
        }
    }
}
template <int NQ, int CG>
__device__ __forceinline__ void side_gemv(const bf16* w, int ld, int ncol, const float* coef, float* red, float* out, int ostride, bool round) {
    constexpr int KG = 384 / CG, W = CG * 8;
    const int tid = threadIdx.x, cg = tid % CG, kg = tid / CG;
    float acc[NQ][8];
#pragma unroll
    for (int q = 0; q < NQ; q++)
#pragma unroll
        for (int j = 0; j < 8; j++) acc[q][j] = 0.f;
    if (cg * 8 < ncol) {
        const bf16* src = w + cg * 8;
        const uint32_t ring = smem_u32(red) + 36864 + tid * 16;
        auto fetch = [&](int k0, int slot) {
#pragma unroll
            for (int i = 0; i < 4; i++)
                if (k0 + i * KG < DM) {
                    if (EF & 1) cp_async16_ef(ring + (slot * 4 + i) * 6144, src + (size_t)(k0 + i * KG) * ld);
                    else cp_async16(ring + (slot * 4 + i) * 6144, src + (size_t)(k0 + i * KG) * ld);
                }
            asm volatile("cp.async.commit_group;" ::: "memory");
        };
#pragma unroll 1
        for (int g = 0; g < 5; g++) fetch(kg + g * 4 * KG, g);
#pragma unroll 1
        for (int k0 = kg, slot = 0; k0 < DM; k0 += 4 * KG) {
            fetch(k0 + 20 * KG, slot ? slot - 1 : 5);
            asm volatile("cp.async.wait_group 5;" ::: "memory");
#pragma unroll
            for (int i = 0; i < 4; i++) {
                const int k = k0 + i * KG;
                if (k < DM) {
                    const uint4 v = lds4(ring + (slot * 4 + i) * 6144);
                    const float f[8] = {bflo(v.x), bfhi(v.x), bflo(v.y), bfhi(v.y), bflo(v.z), bfhi(v.z), bflo(v.w), bfhi(v.w)};
#pragma unroll
                    for (int q = 0; q < NQ; q++) {
                        const float cf = coef[q * DM + k];
#pragma unroll
                        for (int j = 0; j < 8; j++) acc[q][j] = fmaf(cf, f[j], acc[q][j]);
                    }
                }
            }
            slot = slot == 5 ? 0 : slot + 1;
        }
    }
    __syncthreads();
#pragma unroll
    for (int q = 0; q < NQ; q++)
#pragma unroll
        for (int j = 0; j < 8; j++) red[(kg * NQ + q) * W + cg * 8 + j] = acc[q][j];
    __syncthreads();
#pragma unroll 1
    for (int i = tid; i < NQ * W; i += 384) {
        const int q = i / W, cidx = i % W;
        float t = 0.f;
#pragma unroll
        for (int k = 0; k < KG; k++) t += red[k * NQ * W + i];
        if (cidx < ncol) out[q * ostride + cidx] = round ? bfround(t) : t;
    }
}
__device__ __noinline__ void rec_side(float* sm, const RecPtrs& p, int id) {
    const int tid = threadIdx.x;
    float *coef = sm, *red = sm + 3 * DM;
    if (tid < 256 && blockIdx.x < 128) rec_ln(sm + SM_PRE / 4, p, id, 2);
    if (tid >> 5 == 8) {
#pragma unroll 1
        for (int n = 1; n < 16; n++) {
            bar_sync(NB_LN, 288);
            if (tid == 256) { if (n == 1) wait_count1(&g_tick[32 + id * 8], 2); signal_count(&g_tick[32 + id * 8]); }
            __syncwarp();
        }
    }
    __syncthreads();
    for (int i = tid; i < 2 * S_; i += 384) g_st[id * 2 * S_ + i] = 0.f;
    if (id == 0) for (int i = tid; i < 2 * 32; i += 384) g_pcnt[i * 8] = 0;
    if (id == 1) for (int i = tid; i < 6 * 256; i += 384) g_pflag[i] = 0;
    for (int i = tid; i < DM; i += 384) { coef[i] = silu_bf(p.c, i); coef[2 * DM + i] = 1.0f; }
    __syncthreads();
    if (tid == 0) TL(3)
    side_gemv<1, 128>(p.wmod + (2 + id) * DM, 6 * DM, DM, coef, red, g_mod + (2 + id) * DM, 0, true);
    __syncthreads();
    if (tid == 0) signal_count(&g_tick[8]);
    if (tid == 0) TL(4)
    side_gemv<1, 128>(p.w3 + id * (FF / 4), FF, FF / 4, coef + 2 * DM, red, g_vec + 3 * DM + id * (FF / 4), 0, false);
    if (tid == 0) wait_count1(&g_tick[8], 4);
    __syncthreads();
    for (int i = tid; i < DM; i += 384) { coef[i] = 1.0f + __ldcg(g_mod + 4 * DM + i); coef[DM + i] = __ldcg(g_mod + 3 * DM + i); }
    __syncthreads();
    if (id == 1 && tid < 32) {
        float t[5] = {0, 0, 0, 0, 0};
        for (int i = tid; i < DM; i += 32) {
            const float a = coef[i], b = coef[DM + i];
            t[0] += a; t[1] += a * a; t[2] += a * b; t[3] += b; t[4] += b * b;
        }
#pragma unroll
        for (int q = 0; q < 5; q++) { const float r = warp_sum(t[q]); if (tid == 0) g_cst[q] = r * (1.0f / DM); }
    }
    side_gemv<3, 32>(p.w1 + id * 256, DM, 256, coef, red, g_vec + id * 256, DM, false);
    if (tid == 0) TL(9)
}

__global__ void __cluster_dims__(2, 1, 1) __launch_bounds__(384, 1)
k_rec(const __grid_constant__ RecMaps mp, const __grid_constant__ RecPtrs p) {
    extern __shared__ uint8_t smraw[];
    const uint32_t sb = smem_u32(smraw);
    if ((sb & 0x3FFFF) != SB0) __trap();
    const uint32_t bars = sb + SM_BAR;
    const int tid = threadIdx.x, lane = tid & 31, b = blockIdx.x;
    const int wid = __reduce_max_sync(~0u, tid >> 5);
    const uint32_t rank = b & 1;
    uint8_t* arena = p.arena;
    volatile int* sinfo = (volatile int*)(smraw + SM_BAR + 192);
    if (tid == 0) TL(0)
    if (tid == 0) sinfo[0] = INT_MIN;
    if (tid == 352) {
        for (int i = 0; i < 17; i++) mbar_init(bars + 8 * i, i == B_WO ? 4 : 1);
        asm volatile("fence.mbarrier_init.release.cluster;" ::: "memory");
        mbar_expect(bars + 8 * B_ROLE, 8);

    }
    __syncwarp();
    asm volatile("barrier.cluster.arrive.relaxed.aligned;" ::: "memory");
    int pr = 0, hA = 0;
    if (wid < 8) {
        if (b < 128) {
            const int cb = (b & 15) * 128, k0 = (b >> 4) * 128 + (tid >> 4);
            uint4 v[8];
#pragma unroll
            for (int i = 0; i < 8; i++) v[i] = __ldg((const uint4*)(p.wmod + (size_t)(k0 + 16 * i) * (6 * DM) + cb + (tid & 15) * 8));
            float acc[8] = {0, 0, 0, 0, 0, 0, 0, 0};
            const float sl = silu_bf(p.c, k0 + 16 * (lane & 7));
#pragma unroll
            for (int i = 0; i < 8; i++) {
                const float sv = __shfl_sync(~0u, sl, i, 16);
                acc[0] += sv * bflo(v[i].x); acc[1] += sv * bfhi(v[i].x); acc[2] += sv * bflo(v[i].y); acc[3] += sv * bfhi(v[i].y);
                acc[4] += sv * bflo(v[i].z); acc[5] += sv * bfhi(v[i].z); acc[6] += sv * bflo(v[i].w); acc[7] += sv * bfhi(v[i].w);
            }
            float* red = (float*)(smraw + SM_PRE);
            *(float4*)(red + (tid >> 4) * 128 + (tid & 15) * 8) = make_float4(acc[0], acc[1], acc[2], acc[3]);
            *(float4*)(red + (tid >> 4) * 128 + (tid & 15) * 8 + 4) = make_float4(acc[4], acc[5], acc[6], acc[7]);
            bar_sync(NB_FIN0, 256);
            if (wid < 4) {
                float t = 0;
#pragma unroll
                for (int i = 0; i < 16; i++) t += red[i * 128 + tid];
                stg_rlx1(&g_modp[(b >> 4) * 2 * DM + cb + tid], __float_as_uint(t) | 1u);
                if (rank) TL(2)
            }
        } else {
            rec_ln((float*)(smraw + SM_PRE), p, b - 128, 0);
        }
    } else if (wid >= 10 && b >= 128) {
        {
            const int u = (b - 128) * 2 + wid - 10;
            const uint16_t* src = (const uint16_t*)p.mem0 + (lane & 3) * 2 * DM + (u >> 1) * 128 + (u & 1) * 32 + (lane >> 2);
            stg_rlx4(arena + (LB_STAMP << 13) + u * 2048 + (lane >> 4) * 1024 + ((lane >> 3) & 1) * 256 + (lane & 7) * 16, 0, 0, 0, 0);
#pragma unroll 1
            for (int r = 0; r < 4; r++) {
                uint32_t w[5];
#pragma unroll
                for (int e = 0; e < 4; e++) {
                    const uint16_t* q = src + (r >> 1) * 512 + (r & 1) * 16 + (e & 2) * 32 + (e & 1) * 8;
                    w[e] = pack_h2(bflo(q[0]), bflo(q[DM]));
                }
                w[4] = __shfl_sync(~0u, __byte_perm(w[3], ACC_ALL, 0x7632), lane * 8 + 7);
                w[3] = __byte_perm(w[3], ACC_ALL, (lane & 7) == 7 ? 0x7610 : 0x3210);
#pragma unroll 1
                for (int i = 0; i < 3; i++) {
                    uint8_t* d = arena + acc_slot(i) + acc_piece(r >> 1, u >> 1, (u & 1) * 2 + (r & 1));
                    stg_rlx4(d + lane * 16, w[0], w[1], w[2], w[3]);
                    if (lane < 8) stg_rlx1(d + 512 + lane * 4, w[4]);
                    w[0] = w[1] = w[2] = w[3] = w[4] = 0;
                }
            }
            bar_arrive(NB_C, 320);
        }
    } else if (rank == 0) {
        uint32_t best = ~0u;
        const int pg = wid < 10 ? 0 : 1 + (b >> 1) % 3;
        uint32_t* q = (uint32_t*)(arena + (pg << 21) + (pg ? blk(b >> 1, wid & 1) : blk(LB_PROBE, wid & 1) + b * 16));
        if (lane < 8) stg_rlx1(q + lane, 0);
        uint2 tk2 = ldg_rlx2(&g_tick[0]);
        __syncwarp();
        if (lane == 0) {
            q += 3;
            uint32_t v = atomicAdd(q, 1u);
#pragma unroll 1
            for (int r = 0; r < NPROBE; r++) {
                const uint32_t t0 = clk32() + (v >> 8);
                v = atomicAdd(q + (v >> 8), 1u);
                uint32_t t1;
                asm volatile("{.reg .pred p; setp.eq.u32 p, %1, 0xffffffff; @p exit; mov.u32 %0, %%clock;}" : "=r"(t1) : "r"(v) : "memory");
                best = min(best, t1 - t0);
            }
            sinfo[wid - 6] = best;
        }
        bar_sync(NB_KDONE, b < 128 ? 128 : 64);
        if (W_PF && wid == 9 && b < 128) {
#pragma unroll 1
            for (int i = lane; i < W_PF * 16; i += 32) {
                const int r = (b >> 1) + 64 * (i >> 4);
                l2_prefetch((i & 8 ? p.wk : p.wq) + (size_t)((r >> 1) + (r & 1) * 512) * (NH * DH) + (i & 7) * 512, 1024);
            }
        }
        if (wid == 8) {
            if (b < 128) TL(2)
            const int par = sinfo[2] <= sinfo[3] ? 0 : 1, ncl = gridDim.x >> 1;
            int tk = 0, it = 0;
            const uint32_t vote = b < 128 && (sinfo[4] <= sinfo[5] ? 0 : 1) != par ? 256u << (8 * ((b >> 1) % 3)) : 0u;
            if (b >= 128) {
#pragma unroll 1
                while (!__all_sync(~0u, (int)((tk2.x + tk2.y) & 255) >= ncl - 2)) { tk2 = ldg_rlx2(&g_tick[0]); spin_guard(++it); }
            }
            if (lane == 0) tk = atomicAdd(&g_tick[par], 1u + vote) & 255;
#pragma unroll 1
            while (!__all_sync(~0u, (int)((tk2.x + tk2.y) & 255) >= ncl)) { tk2 = ldg_rlx2(&g_tick[0]); spin_guard(++it); }
            tk = __shfl_sync(~0u, tk, 0);
            const int n0 = tk2.x & 255, n1 = tk2.y & 255;
            hA = min(n0 >> 1, NH);
            const int q0 = 2 * hA, q1 = 2 * NH - q0;
            const int over = tk - (par ? q1 : q0), lack = max(par ? q0 - n0 : q1 - n1, 0);
            if (over < 0) pr = par ? q0 + tk : tk;
            else if (over < lack) pr = (par ? n0 : q0 + n1) + over;
            else pr = -1 - (over - lack + (par ? max(n0 - q0, 0) : 0));
#pragma unroll
            for (int i = 0; i < 3; i++) hA |= (((tk2.x + tk2.y) >> (8 + 8 * i)) & 255) > 10 ? 256 << i : 0;
        }
    }
    asm volatile("barrier.cluster.wait.aligned;" ::: "memory");
    if (wid == 8) {
        if (rank == 0) {
            if (lane == 0) {
                uint32_t rsb;
                asm("mapa.shared::cluster.u32 %0, %1, 1;" : "=r"(rsb) : "r"(sb));
                asm volatile("st.async.shared::cluster.mbarrier::complete_tx::bytes.v2.u32 [%0], {%1, %2}, [%3];"
                             ::"r"(rsb + SM_BAR + 192), "r"(pr), "r"(hA), "r"(rsb + SM_BAR + 8 * B_ROLE) : "memory");
                sinfo[0] = pr; sinfo[1] = hA;
                if (b >= 128) atomicOr(&g_tick[4], (pr < 0 ? 4u : 1u) << ((b - 128) >> 1));
            }
        } else {
            mbar_wait_w(bars + 8 * B_ROLE, 0);
            pr = sinfo[0];
        }
        TL(1)
        __syncwarp();
        bar_arrive(NB_A, 384);
        if (b >= 128 && pr < 0) bar_sync(NB_B, 64);
        if (pr >= 0) {
            const int pu = __reduce_max_sync(~0u, pr), c0 = (pu >> 1) * 128 + rank * 64, r0 = (pu & 1) * 512;
            bool fast = false;
#pragma unroll 1
            for (int n = 0; n < 12; n++) {
                const int rot = b >= 128 ? 8 : 0, i = (n + rot) % 12;
                if (rot && n == 4) bar_sync(NB_B, 64);
                if (n >= W_INFL && !fast) {
                    const uint32_t v = ldg_rlx1(&g_tick[32 + (lane & 3) * 8]);
                    mbar_wait_w(bars + 8 * (B_W + (n - W_INFL + rot) % 12), 0);
                    fast = __all_sync(~0u, v != 0);
                }
                const int m = i < 8 ? i & 1 : 2, k = i < 8 ? i >> 1 : i - 8;
                const uint32_t dst = sb + m * 65536 + k * 16384, br = bars + 8 * (B_W + i);
                if (lane == 0) {
                    mbar_expect(br, 16384);
#pragma unroll
                    for (int u = 0; u < 2; u++) {
                        if (EF & 8) asm volatile("cp.async.bulk.tensor.2d.shared::cluster.global.mbarrier::complete_tx::bytes.L2::cache_hint [%0], [%1, {%3, %4}], [%2], %5;"
                                                 ::"r"(dst + u * 8192), "l"(&mp.wq + m), "r"(br), "r"(c0), "r"(r0 + k * 128 + u * 64), "l"(evict_first()) : "memory");
                        else tma2d(dst + u * 8192, &mp.wq + m, c0, r0 + k * 128 + u * 64, br);
                    }
                }
                __syncwarp();
            }
        }
    } else {
        bar_sync(NB_A, 384);
    }
    const int prr = __reduce_max_sync(~0u, sinfo[0]);
    hA = __reduce_max_sync(~0u, sinfo[1]);
    if (prr < 0) {
        int j = (b - 128) >> 1;
        if (b < 128) {
            uint32_t v;
            int it = 0;
#pragma unroll 1
            do { v = __reduce_max_sync(~0u, ldg_rlx1(&g_tick[4])); spin_guard(++it); } while (__popc(v) < 2);
            j = v == 3 ? -1 - prr : (v & 1) ^ 1;
        }
        rec_side((float*)smraw, p, j * 2 + rank);
        return;
    }
    const int role = (prr >> 1) * 4 + rank * 2 + (prr & 1);
    rec_main(sb, &mp.wo, arena, role, hA, wid >> 2, p.zero, p.tm);
}

__device__ __forceinline__ void wgmma_ss192(float* d, uint64_t a, uint64_t b, int sc) {
    asm volatile("{.reg .pred p; setp.ne.b32 p, %98, 0;\n wgmma.mma_async.sync.aligned.m64n192k16.f32.bf16.bf16 "
                 "{%0,%1,%2,%3,%4,%5,%6,%7,%8,%9,%10,%11,%12,%13,%14,%15,%16,%17,%18,%19,%20,%21,%22,%23,%24,%25,%26,%27,%28,%29,%30,%31,%32,%33,%34,%35,%36,%37,%38,%39,%40,%41,%42,%43,%44,%45,%46,%47,%48,%49,%50,%51,%52,%53,%54,%55,%56,%57,%58,%59,%60,%61,%62,%63,%64,%65,%66,%67,%68,%69,%70,%71,%72,%73,%74,%75,%76,%77,%78,%79,%80,%81,%82,%83,%84,%85,%86,%87,%88,%89,%90,%91,%92,%93,%94,%95}, %96, %97, p, 1, 1, 0, 1;}"
                 : F16(d, 0), F16(d, 16), F16(d, 32), F16(d, 48), F16(d, 64), F16(d, 80) : "l"(a), "l"(b), "r"(sc));
}

constexpr uint32_t P_B = 81920, P_PLANE = 40960, P_VEC = 212992, P_ROW = P_VEC + 6144, P_BAR = P_ROW + 4096, P_SMEM = P_BAR + 256;
constexpr uint32_t P_OUT = 180224, P_OUT3 = P_B + 2 * P_PLANE;
#define PPH 1
#define FLAG_ST "st.release.gpu.global.u32"
#define FLAG_LD "ld.acquire.gpu.global.u32"
#define EFA 0x1e7
#define EFB 0x1ff
#define ALIAS 0
#define E0 3
#define SL_B0 0x5555
#define SL_B1 0xaaaa
#define SL_C 0x2492490
#define SL_A0 0x7777
#define SL_A1 0x77dd
#define HFENCE 2
#define X_DLY 4000
#define OWN 1
constexpr int P_ST = 5, P_ST0 = 4;
constexpr int PB_F = 0, PB_E = 5, PB_X = 10, PB_OUT = 12;
enum { C_Y = 0, C_G = 1, C_X1 = 2, C_U = 3, C_S1 = 8, C_S3 = 9 };
enum { V_GA = 0, V_A = 1, V_B = 2, V_GB = 3, V_VA = 4, V_VB = 5, V_VC = 6, V_C3 = 7 };
struct PostMaps { CUtensorMap o, wo, y, w1, g, w2, x1, w3, u, w4, out, x; };

struct GeluK { float k0, k1, kh; };
__device__ __forceinline__ GeluK gelu_k(float c) { return {0.7978845608028654f * c, 0.7978845608028654f * 0.044715f * c * c * c, 0.5f * c}; }
__device__ __forceinline__ float gelu_s(float t, const GeluK& k) {
    const float u = t * fmaf(t * t, k.k1, k.k0);
    float th; asm("tanh.approx.f32 %0, %1;" : "=f"(th) : "f"(u));
    const float hx = k.kh * t;
    return fmaf(hx, th, hx);
}
__device__ __forceinline__ float2 ldsv(uint32_t a) {
    float2 v; asm("ld.shared.v2.f32 {%0,%1}, [%2];" : "=f"(v.x), "=f"(v.y) : "r"(a)); return v;
}
__device__ __forceinline__ void wait_smem(uint32_t a, int target) {
    int it = 0;
#pragma unroll 1
    while (true) {
        int v;
        asm volatile("ld.acquire.cta.shared.u32 %0, [%1];" : "=r"(v) : "r"(a) : "memory");
        if (__all_sync(~0u, v >= target)) break;
        spin_guard(++it);
    }
}

#define PP(i)
#define PH_(c, w, i)
struct Pipe { int st, ph; };
__device__ __forceinline__ void adv(Pipe& p) { if (++p.st == P_ST) { p.st = 0; p.ph ^= 1; } }
__device__ __forceinline__ int u_col(int r, int nb) { return r ? 512 + r * 1024 + nb * 128 : nb * 192; }

template <bool A>
__device__ __forceinline__ void post_produce(uint32_t sb, const PostMaps& mp, int mb, int nb, int rank) {
    const int rh = 2 * mb + rank, lane = threadIdx.x & 31;
    const uint32_t full = sb + P_BAR + 8 * PB_F, empty = sb + P_BAR + 8 * PB_E;
    Pipe p = {(P_ST0 + E0) % P_ST, !E0};
#pragma unroll 1
    for (int ph = 0; ph < 9; ph++) {
        const int GS = ph == 0 ? 8 : ph == 6 ? 3 : 2, kb0 = ph < 7 ? 0 : ph * 16 - 88;
        const CUtensorMap* tm = &mp.o + 2 * (ph < 3 ? ph : ph < 6 ? 3 : 4) + !A;
        const uint64_t pol = ((A ? EFA : EFB) >> ph) & 1 ? evict_first() : evict_normal();
        const bool own = OWN && (ph == 1 || ph == 3);
        const int n0 = ph >= 3 && ph < 6 ? u_col(ph - 3, nb) : nb * 128;
        const int amul = ph == 0 ? 256 : 64, arow = ph == 0 ? rh * 8 : rh * 64;
        const int wr = ph == 2 ? min(max(rh + min(lane >> 3, 2) - 1, 0), 31) : rh ^ ((lane >> 3) & 1);
        const uint32_t* fl = &g_pflag[(ph < 3 ? ph - 1 : ph < 6 ? C_X1 : ph - 3) * 256 + wr * 8 + (lane & 7)];
        uint32_t have = ph == 0 || ph == 5 ? ~0u : 0u;
        PH_(A && ph == PPH, 0, 26) PH_(A && ph == PPH, 1, 26)
#pragma unroll 1
        for (int q = 0; q < 8; q++) {
            const int src = own && q < 2 ? nb ^ q : (q + (nb & 6)) & 7;
            const bool skip = own && q == 0, both = own && q == 1;
            const uint32_t need = skip ? 0 : (ph == 2 ? 0x10101 : both ? 0x101 : 1) << src;
            if (A && (have & need) != need) {
                int it = 0;
#pragma unroll 1
                do {
                    uint32_t v;
                    asm volatile(FLAG_LD " %0, [%1];" : "=r"(v) : "l"(fl) : "memory");
                    have = __ballot_sync(~0u, v != 0);
                    spin_guard(++it);
                } while ((have & need) != need);
                PH_(ph == PPH && q == own, 0, 23) PH_(ph == PPH, 0, 24) PH_(ph == PPH && q == own, 1, 23) PH_(ph == PPH, 1, 24)
                asm volatile("fence.proxy.async.global;" ::: "memory");
            }
            if (!A && ph == 3 && q == 1) wait_smem(sb + P_BAR + 8 * (PB_OUT + (lane & 1)), 3);
            const int row = arow + (ph == 2 ? (int)((0x04000301u >> ((src & 6) * 4)) & 7) - 2 : 0);
            const uint32_t bytes = (skip ? 16384 : 32768) + (ph == 3 ? 8192 : 0);
            if ((ph | q) == 0) asm volatile("barrier.cluster.wait.aligned;" ::: "memory");
#pragma unroll 1
            for (int e = kb0 + (src + 1) * GS, kb = e - GS + (ph | q ? 0 : E0); kb < e; kb++) {
                const uint32_t f = full + 8 * p.st;
                mbar_wait_w(empty + 8 * p.st, p.ph ^ 1);
                if (A) {
                    const uint32_t a = sb + p.st * 16384 + rank * 8192;
                    if (both) { e_tma2d(a, tm, kb * 64, row, f, pol); e_tma2d(a + 8192 - rank * 16384, tm, kb * 64, row ^ 64, f, pol); }
                    else if (!skip) e_tma2d_mc(a, tm, kb * amul, row, f, pol);
                } else {
                    const uint32_t b = sb + P_B + p.st * 8192;
                    e_expect(f, bytes);
                    e_tma2d(b, tm, n0, kb * 64, f, pol);
                    e_tma2d(b + P_PLANE, tm, n0 + 64, kb * 64, f, pol);
                    if (ph == 3 && both) mbar_wait_w(empty + 8 * p.st - 16, p.ph);
                    if (ph == 3) e_tma2d(b + 2 * P_PLANE, tm, n0 + 128, kb * 64, f, pol);
                }
                PH_(PPH == 0 && ph == 0 && q == 0 && kb + GS == e + E0, 0, 20 + A) PH_(PPH == 0 && ph == 0 && q == 0 && kb + GS == e + E0, 1, 20 + A)
                adv(p);
            }
        }
    }
    if (A) {
#pragma unroll 1
        for (int i = 0; i < P_ST; i++) mbar_wait_w(empty + 8 * i, p.ph ^ (i >= p.st));
    }
}

#define I4(d, i) "f"(d[i]), "f"(d[i + 1]), "f"(d[i + 2]), "f"(d[i + 3])
#define I16(d, i) I4(d, i), I4(d, i + 4), I4(d, i + 8), I4(d, i + 12)
__device__ __forceinline__ void pick16(float* v, int n, const float* c1, float2 a, float2 b, const float* old) {
    asm volatile("{PKT: .branchtargets PK0, PK1, PK2, PK3, PK4, PK5, PK6, PK7, PK8, PK9, PK10, PK11; brx.idx.uni %8, PKT;\n"
                 "PK0: fma.rn.f32 %0, %9, %11, %15; fma.rn.f32 %1, %9, %12, %16; fma.rn.f32 %2, %10, %11, %17; fma.rn.f32 %3, %10, %12, %18; fma.rn.f32 %4, %9, %13, %19; fma.rn.f32 %5, %9, %14, %20; fma.rn.f32 %6, %10, %13, %21; fma.rn.f32 %7, %10, %14, %22; bra.uni PKE;\n"
                 "PK1: fma.rn.f32 %0, %9, %11, %23; fma.rn.f32 %1, %9, %12, %24; fma.rn.f32 %2, %10, %11, %25; fma.rn.f32 %3, %10, %12, %26; fma.rn.f32 %4, %9, %13, %27; fma.rn.f32 %5, %9, %14, %28; fma.rn.f32 %6, %10, %13, %29; fma.rn.f32 %7, %10, %14, %30; bra.uni PKE;\n"
                 "PK2: fma.rn.f32 %0, %9, %11, %31; fma.rn.f32 %1, %9, %12, %32; fma.rn.f32 %2, %10, %11, %33; fma.rn.f32 %3, %10, %12, %34; fma.rn.f32 %4, %9, %13, %35; fma.rn.f32 %5, %9, %14, %36; fma.rn.f32 %6, %10, %13, %37; fma.rn.f32 %7, %10, %14, %38; bra.uni PKE;\n"
                 "PK3: fma.rn.f32 %0, %9, %11, %39; fma.rn.f32 %1, %9, %12, %40; fma.rn.f32 %2, %10, %11, %41; fma.rn.f32 %3, %10, %12, %42; fma.rn.f32 %4, %9, %13, %43; fma.rn.f32 %5, %9, %14, %44; fma.rn.f32 %6, %10, %13, %45; fma.rn.f32 %7, %10, %14, %46; bra.uni PKE;\n"
                 "PK4: fma.rn.f32 %0, %9, %11, %47; fma.rn.f32 %1, %9, %12, %48; fma.rn.f32 %2, %10, %11, %49; fma.rn.f32 %3, %10, %12, %50; fma.rn.f32 %4, %9, %13, %51; fma.rn.f32 %5, %9, %14, %52; fma.rn.f32 %6, %10, %13, %53; fma.rn.f32 %7, %10, %14, %54; bra.uni PKE;\n"
                 "PK5: fma.rn.f32 %0, %9, %11, %55; fma.rn.f32 %1, %9, %12, %56; fma.rn.f32 %2, %10, %11, %57; fma.rn.f32 %3, %10, %12, %58; fma.rn.f32 %4, %9, %13, %59; fma.rn.f32 %5, %9, %14, %60; fma.rn.f32 %6, %10, %13, %61; fma.rn.f32 %7, %10, %14, %62; bra.uni PKE;\n"
                 "PK6: fma.rn.f32 %0, %9, %11, %63; fma.rn.f32 %1, %9, %12, %64; fma.rn.f32 %2, %10, %11, %65; fma.rn.f32 %3, %10, %12, %66; fma.rn.f32 %4, %9, %13, %67; fma.rn.f32 %5, %9, %14, %68; fma.rn.f32 %6, %10, %13, %69; fma.rn.f32 %7, %10, %14, %70; bra.uni PKE;\n"
                 "PK7: fma.rn.f32 %0, %9, %11, %71; fma.rn.f32 %1, %9, %12, %72; fma.rn.f32 %2, %10, %11, %73; fma.rn.f32 %3, %10, %12, %74; fma.rn.f32 %4, %9, %13, %75; fma.rn.f32 %5, %9, %14, %76; fma.rn.f32 %6, %10, %13, %77; fma.rn.f32 %7, %10, %14, %78; bra.uni PKE;\n"
                 "PK8: fma.rn.f32 %0, %9, %11, %79; fma.rn.f32 %1, %9, %12, %80; fma.rn.f32 %2, %10, %11, %81; fma.rn.f32 %3, %10, %12, %82; fma.rn.f32 %4, %9, %13, %83; fma.rn.f32 %5, %9, %14, %84; fma.rn.f32 %6, %10, %13, %85; fma.rn.f32 %7, %10, %14, %86; bra.uni PKE;\n"
                 "PK9: fma.rn.f32 %0, %9, %11, %87; fma.rn.f32 %1, %9, %12, %88; fma.rn.f32 %2, %10, %11, %89; fma.rn.f32 %3, %10, %12, %90; fma.rn.f32 %4, %9, %13, %91; fma.rn.f32 %5, %9, %14, %92; fma.rn.f32 %6, %10, %13, %93; fma.rn.f32 %7, %10, %14, %94; bra.uni PKE;\n"
                 "PK10: fma.rn.f32 %0, %9, %11, %95; fma.rn.f32 %1, %9, %12, %96; fma.rn.f32 %2, %10, %11, %97; fma.rn.f32 %3, %10, %12, %98; fma.rn.f32 %4, %9, %13, %99; fma.rn.f32 %5, %9, %14, %100; fma.rn.f32 %6, %10, %13, %101; fma.rn.f32 %7, %10, %14, %102; bra.uni PKE;\n"
                 "PK11: fma.rn.f32 %0, %9, %11, %103; fma.rn.f32 %1, %9, %12, %104; fma.rn.f32 %2, %10, %11, %105; fma.rn.f32 %3, %10, %12, %106; fma.rn.f32 %4, %9, %13, %107; fma.rn.f32 %5, %9, %14, %108; fma.rn.f32 %6, %10, %13, %109; fma.rn.f32 %7, %10, %14, %110;\n"
                 "PKE: }"
                 : "=f"(v[0]), "=f"(v[1]), "=f"(v[2]), "=f"(v[3]), "=f"(v[4]), "=f"(v[5]), "=f"(v[6]), "=f"(v[7])
                 : "r"(n), "f"(c1[0]), "f"(c1[1]), "f"(a.x), "f"(a.y), "f"(b.x), "f"(b.y), I16(old, 0), I16(old, 16), I16(old, 32), I16(old, 48), I16(old, 64), I16(old, 80));
}
template <int PH, class F>
__device__ __forceinline__ void post_mma(uint32_t sb, float* acc, Pipe& p, int NK, int wg, uint32_t rel, bool lead, int pi, F hook) {
    const uint32_t full = sb + P_BAR + 8 * PB_F;
    constexpr uint64_t DA = PH == 0 ? mkdesc(SB0, 128, 1024, 0) : mkdesc(SB0, 16, 1024, 1);
    constexpr uint64_t DB = mkdesc(SB0 + P_B, P_PLANE, 1024, 1);
    auto release = [&](uint32_t a) { asm volatile("{.reg .pred p; setp.gt.u32 p, %0, 63; @p mbarrier.arrive.shared::cluster.b64 _, [%0];}" ::"r"(a) : "memory"); };
    uint32_t prev = 0;
    if (OWN && (PH & 1)) { if (HFENCE == 2) fence_async_smem(); bar_sync(12 + wg, 128); }
    bool ok = false;
#pragma unroll 1
    for (int kb = 0; kb < NK; kb++) {
        if (!ok) mbar_wait_w(full + 8 * p.st, p.ph);
        const uint32_t a = (uint32_t)DA + (OWN && (PH & 1) && kb < 2 ? P_OUT / 16 + wg * 1024 + kb * 512 : p.st * 1024 + wg * 512), b = (uint32_t)DB + p.st * 512;
        wg_fence();
#pragma unroll
        for (int k = 0; k < 4; k++) {
            const uint64_t da = (DA & 0xffffffff00000000ull) | (a + k * (PH == 0 ? 16 : 2)), db = (DB & 0xffffffff00000000ull) | (b + k * 128);
            if (PH == 3) wgmma_ss192(acc, da, db, (kb | k) != 0);
            else wgmma_ss128<PH == 0>(acc, da, db, (kb | k) != 0);
        }
        wg_commit();
        if (kb == 0) { PP(pi) if (PH == 0 && wg == 0) TL(11) }
        const uint32_t cur = rel + 8 * p.st;
        adv(p);
        hook(-1);
        uint32_t t;
        asm volatile("{.reg .pred p; mbarrier.test_wait.parity.shared.b64 p, [%1], %2; selp.u32 %0, 1, 0, p;}" : "=r"(t) : "r"(full + 8 * p.st), "r"(p.ph) : "memory");
        wg_wait<1>();
        release(prev);
        ok = __all_sync(~0u, t);
        prev = cur;
        hook(kb);
    }
    wg_wait<0>();
    release(prev);
    PP(pi + 1)
}

__global__ void __cluster_dims__(2, 1, 1) __launch_bounds__(384, 1)
k_post(const __grid_constant__ PostMaps mp) {
    extern __shared__ uint8_t smraw[];
    const uint32_t sb = smem_u32(smraw);
    if ((sb & 0x3FFFF) != SB0) __trap();
    const int tid = threadIdx.x, lane = tid & 31;
    const int mb = blockIdx.x >> 3, nb = blockIdx.x & 7, rank = blockIdx.x & 1;
    const uint32_t bars = sb + P_BAR;
    PH_(PPH == 0 && tid == 0, 0, 22) PH_(PPH == 0 && tid == 0, 1, 22)
    const int w = __reduce_max_sync(~0u, (tid >> 5) - 8);
    if (w == 1) {
        if (lane == 0) {
#pragma unroll
            for (int i = 0; i < PB_OUT; i++) mbar_init(bars + 8 * i, i >= PB_E && i < PB_X ? 4 : 1);
            mbar_arrive(bars + 8 * (PB_F + P_ST0));
            asm volatile("mbarrier.arrive.shared.b64 _, [%0], 4;" ::"r"(bars + 8 * (PB_E + P_ST0)) : "memory");
            sts4(bars + 8 * PB_OUT, 0, 0, 0, 0);
            asm volatile("fence.mbarrier_init.release.cluster; fence.proxy.async.shared::cta;" ::: "memory");
        }
        __syncwarp();
    }
    asm volatile("barrier.cluster.arrive.relaxed.aligned;" ::: "memory");
    if (w == 1) {
#pragma unroll
        for (int i = 0; i < E0; i++) {
            const int st = (P_ST0 + i) % P_ST, kb = (nb & 6) * 8 + i;
            const uint32_t f = bars + 8 * (PB_F + st);
            e_expect(f, 32768);
#pragma unroll
            for (int h = 0; h < 2; h++) {
                e_tma2d(sb + st * 16384 + h * 8192, &mp.o, kb * 256, mb * 16 + h * 8, f, evict_first());
                e_tma2d(sb + P_B + st * 8192 + h * P_PLANE, &mp.wo, nb * 128 + h * 64, kb * 64, f, evict_first());
            }
        }
    }
    if (w != 0 && w != 3) asm volatile("barrier.cluster.wait.aligned;" ::: "memory");
    if (w >= 0) {
        asm volatile("setmaxnreg.dec.sync.aligned.u32 40;");
        if (w == 0) {
            post_produce<false>(sb, mp, mb, nb, rank);
        } else if (w < 3) {
            const int wg = w - 1, rh = 2 * mb + wg;
            float* rowc = (float*)(smraw + P_ROW) + (wg * 64 + lane * 2) * 8;
            int nout = 0, sig = 0;
            if (X_DLY) __nanosleep(X_DLY);
            if (wg && lane < 9) asm volatile("prefetch.tensormap [%0];" ::"l"(&mp.y + lane) : "memory");
            e_expect(bars + 8 * (PB_X + wg), 16384);
            e_tma2d(sb + P_OUT + wg * 16384, &mp.x, nb * 128, rh * 64, bars + 8 * (PB_X + wg), evict_first());
            e_tma2d(sb + P_OUT + wg * 16384 + 8192, &mp.x, nb * 128 + 64, rh * 64, bars + 8 * (PB_X + wg), evict_first());
            if (wg == 0) {
#pragma unroll 1
                for (int i = 0; i < 11; i++) {
                    const float* src = i < 4 ? g_mod + ((0x5342 >> (4 * i)) & 15) * DM + nb * 128 : g_vec + (i < 7 ? (i - 4) * DM + nb * 128 : 3 * DM + u_col(max(i - 8, 0), nb) + (i == 8) * 128);
                    if (i != 8 || lane < 16) cp_async16(sb + P_VEC + i * 512 - (i > 8) * 256 + lane * 16, src + lane * 4);
                }
                *(uint4*)&g_modp[blockIdx.x * 128 + lane * 4] = make_uint4(0, 0, 0, 0);
                if (blockIdx.x == 64) *(uint2*)&g_tick[lane * 2] = make_uint2(0, 0);
                asm volatile("cp.async.wait_all;" ::: "memory");
                const float4 a = lds4f(sb + P_VEC + V_A * 512 + lane * 16);
                sts4f(sb + P_VEC + V_A * 512 + lane * 16, 1.0f + a.x, 1.0f + a.y, 1.0f + a.z, 1.0f + a.w);
                bar_arrive(3, 288);
            }
#pragma unroll 1
            for (int i = 0; i < 9; i++) {
                const int cnt = i == 8 ? 6 : (0x54392180u >> (4 * i)) & 15;
                if (cnt < C_S1) {
                    const bool isu = cnt >= C_U && cnt < 6;
                    const int ng = cnt == C_U ? 3 : 2, c0 = isu ? u_col(cnt - C_U, nb) : nb * 128;
                    const uint32_t src = sb + (cnt == C_U ? P_OUT3 : P_OUT) + wg * ng * 8192;
#pragma unroll 1
                    for (int j = 0; j < ng; j++) {
                        bar_sync(4 + 4 * wg + (sig++ & 3), 160);
                        if (lane == 0) {
                            if (HFENCE) fence_async_smem();
                            PH_(cnt == PPH - 1, wg, 20)
                            asm volatile("cp.async.bulk.tensor.2d.global.shared::cta.bulk_group [%0, {%2, %3}], [%1]; cp.async.bulk.commit_group;"
                                         ::"l"(&mp.y + 2 * (isu ? 3 : min(cnt, 4))), "r"(src + j * 8192), "r"(c0 + j * 64), "r"(rh * 64) : "memory");
                        }
                        __syncwarp();
                    }
                    if (lane == 0) {
                        asm volatile("cp.async.bulk.wait_group 0; fence.proxy.async.global;" ::: "memory");
                        PH_(cnt == PPH - 1, wg, 21)
                        asm volatile("st.release.cta.shared.u32 [%0], %1;" ::"r"(bars + 8 * (PB_OUT + wg)), "r"(nout + 1) : "memory");
                        if (cnt < 6) asm volatile(FLAG_ST " [%0], %1;" ::"l"(&g_pflag[cnt * 256 + rh * 8 + nb]), "r"(1) : "memory");
                        PH_(cnt == PPH - 1, wg, 22)
                    }
                    nout++;
                    __syncwarp();
                    continue;
                }
                bar_sync(4 + 4 * wg + (sig++ & 3), 160);
#pragma unroll 1
                for (int q = 0; q < (cnt == C_S1 ? 3 : 1); q++) {
                    const float4 v = lds4f(sb + P_ROW + wg * 2048 + q * 512 + lane * 16);
                    asm volatile("red.relaxed.gpu.global.add.v4.f32 [%0], {%1, %2, %3, %4};"
                                 ::"l"((float4*)g_st + (cnt == C_S1 ? q : 3) * (S_ / 2) + rh * 32 + lane), "f"(v.x), "f"(v.y), "f"(v.z), "f"(v.w) : "memory");
                }
                __syncwarp();
                uint32_t* c = &g_pcnt[(cnt - C_S1) * 256 + rh * 8];
                if (lane == 0) { signal_count(c); wait_count1(c, 8); }
                __syncwarp();
                const float4* sp = (const float4*)g_st + rh * 32 + lane;
                float4 u[3] = {__ldcg(sp + (cnt == C_S1 ? 0 : 3) * (S_ / 2)), __ldcg(sp + S_ / 2), __ldcg(sp + S_)};
#pragma unroll 1
                for (int h = 0; h < 2; h++) {
                    const float id = 1.0f / DM;
                    const float m = u[0].x * id, var = fmaxf(u[0].y * id - m * m, 0.f) + 1e-5f, r = rsqrtf(var);
                    float sc = r, m2 = 0.f;
                    if (cnt == C_S1) {
                        m2 = r * (u[1].x * id - m * g_cst[0]) + g_cst[3];
                        const float e2 = r * r * (u[2].x * id - 2.0f * m * u[1].y * id + m * m * g_cst[1]) + 2.0f * r * (u[2].y * id - m * g_cst[2]) + g_cst[4];
                        sc = r * rsqrtf(fmaxf(e2 - m2 * m2, 0.f) + 1e-5f);
                    }
                    const GeluK k = gelu_k(sc);
                    *(float4*)(rowc + h * 8) = make_float4(k.k0, k.k1, k.kh, -m);
                    *(float4*)(rowc + h * 8 + 4) = make_float4(var * r, -m2 * var * r, r, -m * r);
#pragma unroll
                    for (int q = 0; q < 3; q++) { u[q].x = u[q].z; u[q].y = u[q].w; }
                }
                bar_arrive(1 + wg, 160);
            }
        } else {
            post_produce<true>(sb, mp, mb, nb, rank);
        }
    } else {
        asm volatile("setmaxnreg.inc.sync.aligned.u32 232;");
        const int wg = __reduce_max_sync(~0u, tid >> 7), wi = (tid >> 5) & 3, g = lane >> 2, tq = lane & 3;
        const bool lead = (tid & 127) == 0;
        uint32_t rel = 0;
        if ((tid & 127) < 2) asm("mapa.shared::cluster.u32 %0, %1, %2;" : "=r"(rel) : "r"(bars + 8 * PB_E), "r"(tid & 1));
        PP(0)
        if (tid == 0) TL(10)
        uint32_t vec = sb + P_VEC + tq * 8;
        const uint32_t stw = sb + (wi * 16 + ((lane >> 3) & 1) * 8 + (lane & 7)) * 128 + (((lane >> 4) ^ (lane & 7)) << 4);
        int sig = 0;
        auto signal = [&]() { bar_arrive(4 + 4 * wg + (sig++ & 3), 160); };
        auto put64 = [&](uint32_t o, const float* v) {
#pragma unroll
            for (int jj = 0; jj < 4; jj++, v += 8) stsm4((stw + o) ^ (jj << 5), pack2(v[0], v[1]), pack2(v[2], v[3]), pack2(v[4], v[5]), pack2(v[6], v[7]));
            if (HFENCE < 2) fence_async_smem();
            signal();
        };
        auto out_free = [&](int n) { wait_smem(bars + 8 * (PB_OUT + (lane & 1)), n); };
        const uint32_t rowc = sb + P_ROW + (wg * 64 + wi * 16 + g) * 32, o128 = P_OUT + wg * 16384;
        const uint32_t rsum = sb + P_ROW + wg * 2048 + (wi * 16 + g) * 8;
        Pipe pa = {P_ST0, 1};
        auto none = [](int) {};
        uint32_t keep[32];
#define KEEP(jn, e) (((e) & 1) ? bfhi(keep[2 * (jn) + ((e) >> 1)]) : bflo(keep[2 * (jn) + ((e) >> 1)]))
        float mu1[2], r1[2];
        {
            float acc[64];
            post_mma<0>(sb, acc, pa, 64, wg, rel, lead, 1, [&](int kb) {
                if (kb != 40) return;
                bar_sync(3, 288);
                mbar_wait_w(bars + 8 * (PB_X + wg), 0);
#pragma unroll
                for (int jj = 0; jj < 8; jj++) ldsm4(keep + jj * 4, (stw + o128 + (jj >> 2) * 8192) ^ ((jj & 3) << 5));
            });
            asm volatile("" : "+r"(vec) :: "memory");
            float st[2][6];
#pragma unroll
            for (int q = 0; q < 6; q++) st[0][q] = st[1][q] = 0.f;
#pragma unroll
            for (int jn = 0; jn < 16; jn++) {
                const float2 ga = ldsv(vec + V_GA * 512 + jn * 32), a = ldsv(vec + V_A * 512 + jn * 32);
                float xa[4];
#pragma unroll
                for (int e = 0; e < 4; e++) {
                    xa[e] = fmaf((e & 1) ? ga.y : ga.x, acc[4 * jn + e], KEEP(jn, e));
                    st[e >> 1][0] += xa[e]; st[e >> 1][1] = fmaf(xa[e], xa[e], st[e >> 1][1]);
                    acc[4 * jn + e] = ((e & 1) ? a.y : a.x) * xa[e];
                }
                keep[2 * jn] = pack2(xa[0], xa[1]); keep[2 * jn + 1] = pack2(xa[2], xa[3]);
                if ((jn & 7) == 7) put64(o128 + (jn >> 3) * 8192, acc + 4 * jn - 28);
            }
            PP(3)
#pragma unroll
            for (int jn = 0; jn < 16; jn++) {
                const float2 a = ldsv(vec + V_A * 512 + jn * 32), b = ldsv(vec + V_B * 512 + jn * 32);
#pragma unroll
                for (int e = 0; e < 4; e++) {
                    const float y = acc[4 * jn + e], aa = (e & 1) ? a.y : a.x, bb = (e & 1) ? b.y : b.x;
                    float* s = st[e >> 1];
                    s[2] += y; s[3] = fmaf(aa, y, s[3]); s[4] = fmaf(y, y, s[4]); s[5] = fmaf(bb, y, s[5]);
                }
            }
#pragma unroll
            for (int h = 0; h < 2; h++)
#pragma unroll
                for (int q = 0; q < 6; q++) { st[h][q] += __shfl_xor_sync(~0u, st[h][q], 1); st[h][q] += __shfl_xor_sync(~0u, st[h][q], 2); }
            if (tq < 3) {
#pragma unroll
                for (int h = 0; h < 2; h++)
                    sts2(rsum + tq * 512 + h * 64, tq == 0 ? st[h][0] : tq == 1 ? st[h][2] : st[h][4], tq == 0 ? st[h][1] : tq == 1 ? st[h][3] : st[h][5]);
            }
            signal();
            PP(29)
        }
        {
            float acc[64];
            post_mma<1>(sb, acc, pa, 16, wg, rel, lead, 4, none);
            float c1[2], c2[2], c3[2];
            GeluK gk[2];
            bar_sync(1 + wg, 160);
#pragma unroll
            for (int h = 0; h < 2; h++) {
                const float4 a = lds4f(rowc + h * 256), b = lds4f(rowc + h * 256 + 16);
                gk[h] = {a.x, a.y, a.z}; c1[h] = a.w; c2[h] = b.x; c3[h] = b.y; mu1[h] = b.w; r1[h] = b.z;
            }
#pragma unroll
            for (int jn = 0; jn < 16; jn++) {
                const float2 va = ldsv(vec + V_VA * 512 + jn * 32), vb = ldsv(vec + V_VB * 512 + jn * 32), vc = ldsv(vec + V_VC * 512 + jn * 32);
#pragma unroll
                for (int e = 0; e < 4; e++) {
                    const int h = e >> 1;
                    const float t = fmaf(c1[h], (e & 1) ? va.y : va.x, fmaf(c2[h], (e & 1) ? vb.y : vb.x, fmaf(c3[h], (e & 1) ? vc.y : vc.x, acc[4 * jn + e])));
                    acc[4 * jn + e] = gelu_s(t, gk[h]);
                }
                if ((jn & 7) == 7) put64(o128 + (jn >> 3) * 8192, acc + 4 * jn - 28);
            }
            PP(6)
        }
        {
            float acc[64];
            post_mma<2>(sb, acc, pa, 16, wg, rel, lead, 7, none);
#pragma unroll
            for (int jn = 0; jn < 16; jn++) {
                const float2 a = ldsv(vec + V_A * 512 + jn * 32), b = ldsv(vec + V_B * 512 + jn * 32);
#pragma unroll
                for (int e = 0; e < 4; e++) {
                    const int h = e >> 1;
                    acc[4 * jn + e] += fmaf(fmaf(KEEP(jn, e), r1[h], mu1[h]), (e & 1) ? a.y : a.x, (e & 1) ? b.y : b.x);
                }
                if ((jn & 7) == 7) put64(o128 + (jn >> 3) * 8192, acc + 4 * jn - 28);
            }
            PP(9)
            float st[2][2] = {{0.f, 0.f}, {0.f, 0.f}};
#pragma unroll
            for (int jn = 0; jn < 16; jn++) {
                const float2 gb = ldsv(vec + V_GB * 512 + jn * 32);
                float z[4];
#pragma unroll
                for (int e = 0; e < 4; e++) {
                    const float x1 = acc[4 * jn + e];
                    st[e >> 1][0] += x1; st[e >> 1][1] = fmaf(x1, x1, st[e >> 1][1]);
                    z[e] = fmaf((e & 1) ? gb.y : gb.x, x1, KEEP(jn, e));
                }
                keep[2 * jn] = pack2(z[0], z[1]); keep[2 * jn + 1] = pack2(z[2], z[3]);
            }
#pragma unroll
            for (int h = 0; h < 2; h++)
#pragma unroll
                for (int q = 0; q < 2; q++) { st[h][q] += __shfl_xor_sync(~0u, st[h][q], 1); st[h][q] += __shfl_xor_sync(~0u, st[h][q], 2); }
            if (tq < 2) sts2(rsum + tq * 64, tq ? st[1][0] : st[0][0], tq ? st[1][1] : st[0][1]);
            signal();
            PP(30)
        }
        {
            float old[96], acc[64];
            post_mma<3>(sb, old, pa, 16, wg, rel, lead, 10, none);
            uint32_t v3 = vec + V_C3 * 512;
            float c1[2];
            GeluK gk[2];
            bar_sync(1 + wg, 160);
#pragma unroll
            for (int h = 0; h < 2; h++) { const float4 a = lds4f(rowc + h * 256); gk[h] = {a.x, a.y, a.z}; c1[h] = a.w; }
            bar_sync(3, 256);
#pragma unroll 1
            for (int r = 0; r < 3; r++) {
                const uint32_t o = stw + (r ? o128 : P_OUT3 + wg * 24576);
                uint32_t when = r == 0 ? (wg ? SL_A1 : SL_A0) : r == 1 ? (wg ? SL_B1 : SL_B0) : SL_C << wg, n = 0;
                float2 va, vb;
                post_mma<2>(sb, acc, pa, r < 2 ? 16 : 56, wg, rel, lead, 12 + 2 * r, [&](int kb) {
                    if (kb < 0) { va = lds2f(v3); vb = lds2f(v3 + 32); return; }
                    const bool now = when & 1;
                    when >>= 1;
                    if (!now) return;
                    if (n == 0) out_free(3 + r);
                    float v[8];
                    pick16(v, n, c1, va, vb, old);
#pragma unroll
                    for (int e = 0; e < 8; e++) v[e] = gelu_s(v[e], gk[(e >> 1) & 1]);
                    stsm4((o + (n >> 2) * 8192) ^ ((n & 3) << 5), pack2(v[0], v[1]), pack2(v[2], v[3]), pack2(v[4], v[5]), pack2(v[6], v[7]));
                    v3 += 64;
                    if ((++n & 3) == 0) { if (!HFENCE) fence_async_smem(); signal(); }
                });
                if (r == 2) break;
#pragma unroll
                for (int i = 0; i < 64; i++) old[i] = acc[i];
            }
#pragma unroll
            for (int jn = 0; jn < 16; jn++) {
                const float2 gb = ldsv(vec + V_GB * 512 + jn * 32);
#pragma unroll
                for (int e = 0; e < 4; e++) acc[4 * jn + e] = fmaf((e & 1) ? gb.y : gb.x, acc[4 * jn + e], KEEP(jn, e));
                if ((jn & 7) == 7) put64(o128 + (jn >> 3) * 8192, acc + 4 * jn - 28);
            }
            PP(18)
            if (tid == 0) TL(12)
        }
    }
}

typedef CUresult (*EncFn)(CUtensorMap*, CUtensorMapDataType, cuuint32_t, void*, const cuuint64_t*, const cuuint64_t*, const cuuint32_t*,
                          const cuuint32_t*, CUtensorMapInterleave, CUtensorMapSwizzle, CUtensorMapL2promotion, CUtensorMapFloatOOBfill);

static CUtensorMap make_map(EncFn enc, const void* p, uint64_t inner, uint64_t outer, uint64_t pitch = 0) {
    const uint32_t bi = 64;
    CUtensorMap m;
    cuuint64_t dims[2] = {inner, outer};
    cuuint64_t str[1] = {(pitch ? pitch : inner) * 2};
    cuuint32_t box[2] = {bi, 64};
    cuuint32_t es[2] = {1, 1};
    enc(&m, CU_TENSOR_MAP_DATA_TYPE_BFLOAT16, 2, (void*)p, dims, str, box, es, CU_TENSOR_MAP_INTERLEAVE_NONE,
        bi == 64 ? CU_TENSOR_MAP_SWIZZLE_128B : CU_TENSOR_MAP_SWIZZLE_64B, CU_TENSOR_MAP_L2_PROMOTION_L2_256B, CU_TENSOR_MAP_FLOAT_OOB_FILL_NONE);
    return m;
}
static CUtensorMap make_map_o(EncFn enc, const void* p) {
    CUtensorMap m;
    cuuint64_t dims[2] = {16384, 256};
    cuuint64_t str[1] = {65536};
    cuuint32_t box[2] = {256, 8};
    cuuint32_t es[2] = {1, 1};
    enc(&m, CU_TENSOR_MAP_DATA_TYPE_UINT32, 2, (void*)p, dims, str, box, es, CU_TENSOR_MAP_INTERLEAVE_NONE, CU_TENSOR_MAP_SWIZZLE_NONE,
        CU_TENSOR_MAP_L2_PROMOTION_L2_256B, CU_TENSOR_MAP_FLOAT_OOB_FILL_NONE);
    return m;
}
template <class T> static T* sym(T& s) { void* p = nullptr; cudaGetSymbolAddress(&p, s); return (T*)p; }

constexpr RecTime g_time = {T_GO, T_X2, T_V, D_X2, D_V, H_D};
extern "C" void kernel_launch(void* const* d_in, const int* in_sizes, int n_in, void* d_out, int out_size) {
    const bf16* x = (const bf16*)d_in[0];
    const bf16* mem0 = (const bf16*)d_in[1];
    const bf16 *Wq = (const bf16*)d_in[2], *Wk = (const bf16*)d_in[3], *Wv = (const bf16*)d_in[4], *Wo = (const bf16*)d_in[5];
    const bf16 *w1 = (const bf16*)d_in[8], *w2 = (const bf16*)d_in[9], *w3 = (const bf16*)d_in[10], *w4 = (const bf16*)d_in[11];
    const bf16 *c = (const bf16*)d_in[12], *wmod = (const bf16*)d_in[13];
    bf16* out = (bf16*)d_out;

    EncFn enc = nullptr;
    cudaDriverEntryPointQueryResult qr;
    cudaGetDriverEntryPoint("cuTensorMapEncodeTiled", (void**)&enc, cudaEnableDefault, &qr);
    CUtensorMap tWq = make_map(enc, Wq, NH * DH, DM), tWk = make_map(enc, Wk, NH * DH, DM), tWv = make_map(enc, Wv, NH * DH, DM);
    PostMaps mp;
    mp.o = make_map_o(enc, sym(g_O)); mp.wo = make_map(enc, Wo, DM, NH * DH);
    mp.y = make_map(enc, sym(g_y), DM, S_); mp.w1 = make_map(enc, w1, DM, DM);
    mp.g = make_map(enc, sym(g_g), DM, S_); mp.w2 = make_map(enc, w2, DM, DM);
    mp.x1 = make_map(enc, ALIAS & 2 ? sym(g_y) : sym(g_x1), DM, S_); mp.w3 = make_map(enc, w3, FF, DM);
    mp.u = ALIAS & 1 ? make_map(enc, sym(g_O), FF, S_, NH * DH) : make_map(enc, sym(g_u), FF, S_); mp.w4 = make_map(enc, w4, DM, FF);
    mp.out = make_map(enc, out, DM, S_); mp.x = make_map(enc, x, DM, S_);
    cudaFuncSetAttribute(k_rec, cudaFuncAttributeMaxDynamicSharedMemorySize, SM_REC_TOTAL);
    cudaFuncSetAttribute(k_post, cudaFuncAttributeMaxDynamicSharedMemorySize, P_SMEM);

    uint8_t* arena = (uint8_t*)(((uintptr_t)sym(g_arena) + (2u << 20) - 1) & ~(uintptr_t)((2u << 20) - 1));
    const RecPtrs rp = {x, mem0, c, wmod, w1, w3, arena, 0u, g_time, Wq, Wk};
    const RecMaps rm = {tWq, tWk, tWv, mp.wo};
    k_rec<<<132, 384, SM_REC_TOTAL>>>(rm, rp);
    k_post<<<128, 384, P_SMEM>>>(mp);
}
```

```cpp
#include <cuda_runtime.h>
#include <cuda.h>
#include <cuda_bf16.h>
#include <stdint.h>
#include <limits.h>

typedef __nv_bfloat16 bf16;

constexpr int S_ = 2048, DM = 1024, NH = 32, DH = 128, NSEG = 64, FF = 3584;
constexpr int SPIN_LIMIT = 1 << 22;
#define W_INFL 2
#define NPROBE 3

__device__ uint8_t g_arena[10 << 20];
__device__ __align__(16) uint32_t g_tick[64];
__device__ __align__(16) uint32_t g_modp[8 * 2 * DM];
__host__ __device__ constexpr uint32_t blk(uint32_t lb, uint32_t par) {
    return (lb << 13) | ((((lb) ^ (lb >> 3) ^ (lb >> 4) ^ (lb >> 6) ^ par) & 1) << 12);
}
__host__ __device__ constexpr uint32_t lb_x2(uint32_t h) { return (h & 1) | ((h >> 1) << 3); }
__host__ __device__ constexpr uint32_t acc_slot(uint32_t s) { return (1u << 20) + (s & 1) * 32768 + (s & 2) * 131072; }
__host__ __device__ constexpr uint32_t acc_piece(uint32_t half, uint32_t qd, uint32_t mt) { return mt * 1024 + (qd & 1) * 4096 + half * 8192 + (qd >> 1) * 16384; }
constexpr uint32_t LB_STAMP = 6;
__host__ __device__ constexpr uint32_t stamp_line(uint32_t w, uint32_t q) { return ((w & 1) * 2 + (q >> 1)) * 1024 + (q & 1) * 256; }
constexpr uint32_t ACC_ONE = 0x3c000000u, ACC_ALL = 0x50000000u;
constexpr uint32_t LB_PROBE = 6 | 64;
__host__ __device__ constexpr uint32_t lb_tok(uint32_t h) { return (h & 1) | ((h >> 1) << 3); }
__device__ __align__(16) float g_mod[6 * DM];
__device__ __align__(1024) bf16 g_himg[(S_ + 32) * DM];
__device__ __align__(1024) bf16 g_O[S_ * NH * DH];
__device__ __align__(1024) bf16 g_y[S_ * DM];
__device__ __align__(1024) bf16 g_g[S_ * DM];
__device__ __align__(1024) bf16 g_x1[S_ * DM];
__device__ __align__(16) float g_st[4 * S_ * 2];
__device__ __align__(16) float g_vec[3 * DM + FF];
__device__ float g_cst[8];
__device__ uint32_t g_pcnt[2 * 32 * 8], g_pflag[6 * 32 * 8];
__device__ __align__(1024) bf16 g_u[S_ * FF];

#define TL(i) {}
#define TX(i) {}
#define TLC(i) {}
__device__ __forceinline__ uint32_t smem_u32(const void* p) { return (uint32_t)__cvta_generic_to_shared(p); }
__device__ __forceinline__ void spin_guard(int it) {
    asm volatile("{.reg .pred p; setp.gt.s32 p, %0, %1; @p st.global.u32 [%2], %0;}" ::"r"(it), "n"(SPIN_LIMIT), "l"(1ull));
}
__device__ __forceinline__ void wg_fence() { asm volatile("wgmma.fence.sync.aligned;" ::: "memory"); }
__device__ __forceinline__ void wg_commit() { asm volatile("wgmma.commit_group.sync.aligned;" ::: "memory"); }
template <int N> __device__ __forceinline__ void wg_wait() { asm volatile("wgmma.wait_group.sync.aligned %0;" ::"n"(N) : "memory"); }
__host__ __device__ constexpr uint64_t mkdesc(uint32_t addr, uint32_t lbo, uint32_t sbo, uint32_t swz) {
    return (uint64_t)((addr & 0x3FFFF) >> 4) | ((uint64_t)(lbo >> 4) << 16) | ((uint64_t)(sbo >> 4) << 32) | ((uint64_t)swz << 62);
}
__device__ __forceinline__ uint64_t dadd(uint64_t d, uint32_t o) { return (d & 0xffffffff00000000ull) | (uint32_t)((uint32_t)d + o); }
__device__ __forceinline__ void mbar_init(uint32_t b, uint32_t c) { asm volatile("mbarrier.init.shared.b64 [%0], %1;" ::"r"(b), "r"(c) : "memory"); }
__device__ __forceinline__ void mbar_expect(uint32_t b, uint32_t tx) { asm volatile("mbarrier.arrive.expect_tx.shared.b64 _, [%0], %1;" ::"r"(b), "r"(tx) : "memory"); }
__device__ __forceinline__ void mbar_arrive(uint32_t b) { asm volatile("mbarrier.arrive.shared.b64 _, [%0];" ::"r"(b) : "memory"); }
__device__ __forceinline__ void mbar_arrive_cluster(uint32_t b, uint32_t cta) {
    asm volatile("{.reg .b32 r; mapa.shared::cluster.u32 r, %0, %1; mbarrier.arrive.shared::cluster.b64 _, [r];}" ::"r"(b), "r"(cta) : "memory");
}
__device__ __forceinline__ void mbar_arrive_cluster_if(bool c, uint32_t b, uint32_t cta) {
    asm volatile("{.reg .pred p; .reg .b32 r; setp.ne.u32 p, %2, 0; mapa.shared::cluster.u32 r, %0, %1; @p mbarrier.arrive.shared::cluster.b64 _, [r];}" ::"r"(b), "r"(cta), "r"((uint32_t)c) : "memory");
}
__device__ __forceinline__ bool mbar_try(uint32_t b, uint32_t par) {
    uint32_t ok;
    asm volatile("{.reg .pred p; mbarrier.try_wait.parity.shared.b64 p, [%1], %2; selp.u32 %0, 1, 0, p;}" : "=r"(ok) : "r"(b), "r"(par) : "memory");
    return ok;
}
__device__ __forceinline__ void mbar_wait(uint32_t b, uint32_t par) {
    int it = 0;
#pragma unroll 1
    while (!mbar_try(b, par)) { spin_guard(++it); }
}
__device__ __forceinline__ void mbar_wait_w(uint32_t b, uint32_t par) {
    int it = 0;
    bool ok;
#pragma unroll 1
    do { ok = __all_sync(~0u, mbar_try(b, par)); spin_guard(++it); } while (!ok);
}
__device__ __forceinline__ void mbar_wait_cluster(uint32_t b, uint32_t par) {
    int it = 0;
    while (true) {
        uint32_t ok;
        asm volatile("{.reg .pred p; mbarrier.try_wait.parity.acquire.cluster.shared::cta.b64 p, [%1], %2; selp.u32 %0, 1, 0, p;}" : "=r"(ok) : "r"(b), "r"(par) : "memory");
        if (ok) break;
        spin_guard(++it);
    }
}
__device__ __forceinline__ void tma2d(uint32_t dst, const CUtensorMap* m, int c0, int c1, uint32_t bar) {
    asm volatile("cp.async.bulk.tensor.2d.shared::cluster.global.mbarrier::complete_tx::bytes [%0], [%1, {%3, %4}], [%2];" ::"r"(dst), "l"(m), "r"(bar), "r"(c0), "r"(c1) : "memory");
}
__device__ __forceinline__ void tma2d_mc(uint32_t dst, const CUtensorMap* m, int c0, int c1, uint32_t bar, uint16_t mask) {
    asm volatile("cp.async.bulk.tensor.2d.shared::cluster.global.mbarrier::complete_tx::bytes.multicast::cluster [%0], [%1, {%3, %4}], [%2], %5;" ::"r"(dst), "l"(m), "r"(bar), "r"(c0), "r"(c1), "h"(mask) : "memory");
}
__device__ __forceinline__ void bulk_g2s(uint32_t dst, const void* src, uint32_t bytes, uint32_t bar) {
    asm volatile("cp.async.bulk.shared::cluster.global.mbarrier::complete_tx::bytes [%0], [%1], %2, [%3];" ::"r"(dst), "l"(src), "r"(bytes), "r"(bar) : "memory");
}
__device__ __forceinline__ void bar_sync(int id, int n) { asm volatile("bar.sync %0, %1;" ::"r"(id), "r"(n) : "memory"); }
__device__ __forceinline__ void bar_arrive(int id, int n) { asm volatile("bar.arrive %0, %1;" ::"r"(id), "r"(n) : "memory"); }
__device__ __forceinline__ void cluster_sync_all() { asm volatile("barrier.cluster.arrive.aligned; barrier.cluster.wait.aligned;" ::: "memory"); }
__device__ __forceinline__ void fence_async_smem() { asm volatile("fence.proxy.async.shared::cta;" ::: "memory"); }
__device__ __forceinline__ void ldsm4t(uint32_t* r, uint32_t a) {
    asm volatile("ldmatrix.sync.aligned.m8n8.x4.trans.shared.b16 {%0,%1,%2,%3}, [%4];" : "=r"(r[0]), "=r"(r[1]), "=r"(r[2]), "=r"(r[3]) : "r"(a) : "memory");
}
__device__ __forceinline__ void ldsm4(uint32_t* r, uint32_t a) {
    asm volatile("ldmatrix.sync.aligned.m8n8.x4.shared.b16 {%0,%1,%2,%3}, [%4];" : "=r"(r[0]), "=r"(r[1]), "=r"(r[2]), "=r"(r[3]) : "r"(a) : "memory");
}
__device__ __forceinline__ uint32_t movm(uint32_t a) {
    uint32_t d; asm volatile("movmatrix.sync.aligned.m8n8.trans.b16 %0, %1;" : "=r"(d) : "r"(a)); return d;
}
__device__ __forceinline__ void mma16816(float* d, uint32_t a0, uint32_t a1, uint32_t a2, uint32_t a3, uint32_t b0, uint32_t b1) {
    asm volatile("mma.sync.aligned.m16n8k16.row.col.f32.bf16.bf16.f32 {%0,%1,%2,%3},{%4,%5,%6,%7},{%8,%9},{%0,%1,%2,%3};"
                 : "+f"(d[0]), "+f"(d[1]), "+f"(d[2]), "+f"(d[3]) : "r"(a0), "r"(a1), "r"(a2), "r"(a3), "r"(b0), "r"(b1));
}
__device__ __forceinline__ void mma16816z(float* d, const uint32_t* a, uint32_t b0, uint32_t b1) {
    asm volatile("mma.sync.aligned.m16n8k16.row.col.f32.bf16.bf16.f32 {%0,%1,%2,%3},{%4,%5,%6,%7},{%8,%9},{%10,%10,%10,%10};"
                 : "=f"(d[0]), "=f"(d[1]), "=f"(d[2]), "=f"(d[3]) : "r"(a[0]), "r"(a[1]), "r"(a[2]), "r"(a[3]), "r"(b0), "r"(b1), "f"(0.f));
}
__device__ __forceinline__ void mma1688(float* d, uint32_t a0, uint32_t a1, uint32_t b0) {
    asm volatile("mma.sync.aligned.m16n8k8.row.col.f32.bf16.bf16.f32 {%0,%1,%2,%3},{%4,%5},{%6},{%0,%1,%2,%3};"
                 : "+f"(d[0]), "+f"(d[1]), "+f"(d[2]), "+f"(d[3]) : "r"(a0), "r"(a1), "r"(b0));
}
__device__ __forceinline__ uint32_t pack2(float lo, float hi) {
    uint32_t r; asm("cvt.rn.bf16x2.f32 %0, %1, %2;" : "=r"(r) : "f"(hi), "f"(lo)); return r;
}
__device__ __forceinline__ uint32_t hadd2(uint32_t a, uint32_t b) {
    uint32_t r; asm("add.rn.bf16x2 %0, %1, %2;" : "=r"(r) : "r"(a), "r"(b)); return r;
}
__device__ __forceinline__ uint32_t hadd2v(uint32_t a, uint32_t b) {
    uint32_t r; asm volatile("add.rn.bf16x2 %0, %1, %2;" : "=r"(r) : "r"(a), "r"(b)); return r;
}
__device__ __forceinline__ float bflo(uint32_t u) { return __uint_as_float(u << 16); }
__device__ __forceinline__ float bfhi(uint32_t u) { return __uint_as_float(u & 0xffff0000u); }
__device__ __forceinline__ float ex2(float x) { float r; asm("ex2.approx.ftz.f32 %0, %1;" : "=f"(r) : "f"(x)); return r; }
__device__ __forceinline__ uint4 ldg_rlx4(const void* p) {
    uint4 v; asm volatile("ld.relaxed.gpu.global.v4.u32 {%0,%1,%2,%3}, [%4];" : "=r"(v.x), "=r"(v.y), "=r"(v.z), "=r"(v.w) : "l"(p) : "memory"); return v;
}
__device__ __forceinline__ uint2 ldg_rlx2(const void* p) {
    unsigned long long v; asm volatile("ld.relaxed.gpu.global.b64 %0, [%1];" : "=l"(v) : "l"(p) : "memory");
    return make_uint2((uint32_t)v, (uint32_t)(v >> 32));
}
__device__ __forceinline__ uint32_t ldg_rlx1(const void* p) {
    uint32_t v; asm volatile("ld.relaxed.gpu.global.u32 %0, [%1];" : "=r"(v) : "l"(p) : "memory"); return v;
}
__device__ __forceinline__ void stg_rlx1(void* p, uint32_t v) { asm volatile("st.relaxed.gpu.global.u32 [%0], %1;" ::"l"(p), "r"(v) : "memory"); }
__device__ __forceinline__ void stg_rlx2(void* p, uint32_t x, uint32_t y) {
    unsigned long long v = (unsigned long long)x | ((unsigned long long)y << 32);
    asm volatile("st.relaxed.gpu.global.b64 [%0], %1;" ::"l"(p), "l"(v) : "memory");
}
__device__ __forceinline__ void stg_rlx4(void* p, uint32_t x, uint32_t y, uint32_t z, uint32_t w) {
    asm volatile("st.relaxed.gpu.global.v4.u32 [%0], {%1,%2,%3,%4};" ::"l"(p), "r"(x), "r"(y), "r"(z), "r"(w) : "memory");
}
__device__ __forceinline__ void sts4(uint32_t a, uint32_t x, uint32_t y, uint32_t z, uint32_t w) {
    asm volatile("st.shared.v4.u32 [%0], {%1,%2,%3,%4};" ::"r"(a), "r"(x), "r"(y), "r"(z), "r"(w) : "memory");
}
__device__ __forceinline__ uint4 lds4(uint32_t a) {
    uint4 v; asm volatile("ld.shared.v4.u32 {%0,%1,%2,%3}, [%4];" : "=r"(v.x), "=r"(v.y), "=r"(v.z), "=r"(v.w) : "r"(a) : "memory"); return v;
}
__device__ __forceinline__ void st_async4(uint32_t a, float x, float y, float z, float w, uint32_t bar) {
    asm volatile("st.async.shared::cluster.mbarrier::complete_tx::bytes.v4.f32 [%0], {%1,%2,%3,%4}, [%5];" ::"r"(a), "f"(x), "f"(y), "f"(z), "f"(w), "r"(bar) : "memory");
}
#define F4(d, i) "+f"(d[i]), "+f"(d[i + 1]), "+f"(d[i + 2]), "+f"(d[i + 3])
template <bool V> __device__ __forceinline__ void wgmma_tok_rs(float* d, const uint32_t* a, uint64_t b, int sc) {
    if (V) asm volatile("{.reg .pred p; setp.ne.b32 p, %25, 0;\n wgmma.mma_async.sync.aligned.m64n40k16.f32.bf16.bf16 {%0,%1,%2,%3,%4,%5,%6,%7,%8,%9,%10,%11,%12,%13,%14,%15,%16,%17,%18,%19}, {%20,%21,%22,%23}, %24, p, 1, 1, 0;}"
                        : F4(d, 0), F4(d, 4), F4(d, 8), F4(d, 12), F4(d, 16) : "r"(a[0]), "r"(a[1]), "r"(a[2]), "r"(a[3]), "l"(b), "r"(sc));
    else asm volatile("{.reg .pred p; setp.ne.b32 p, %21, 0;\n wgmma.mma_async.sync.aligned.m64n32k16.f32.bf16.bf16 {%0,%1,%2,%3,%4,%5,%6,%7,%8,%9,%10,%11,%12,%13,%14,%15}, {%16,%17,%18,%19}, %20, p, 1, 1, 0;}"
                      : F4(d, 0), F4(d, 4), F4(d, 8), F4(d, 12) : "r"(a[0]), "r"(a[1]), "r"(a[2]), "r"(a[3]), "l"(b), "r"(sc));
}
template <bool V> __device__ __forceinline__ void wgmma_tok_ss(float* d, uint64_t a, uint64_t b) {
    if (V) asm volatile("wgmma.mma_async.sync.aligned.m64n40k16.f32.bf16.bf16 {%0,%1,%2,%3,%4,%5,%6,%7,%8,%9,%10,%11,%12,%13,%14,%15,%16,%17,%18,%19}, %20, %21, 1, 1, 1, 1, 0;"
                        : F4(d, 0), F4(d, 4), F4(d, 8), F4(d, 12), F4(d, 16) : "l"(a), "l"(b));
    else asm volatile("wgmma.mma_async.sync.aligned.m64n32k16.f32.bf16.bf16 {%0,%1,%2,%3,%4,%5,%6,%7,%8,%9,%10,%11,%12,%13,%14,%15}, %16, %17, 1, 1, 1, 1, 0;"
                      : F4(d, 0), F4(d, 4), F4(d, 8), F4(d, 12) : "l"(a), "l"(b));
}
#define F16(d, i) F4(d, i), F4(d, i + 4), F4(d, i + 8), F4(d, i + 12)
template <int TA>
__device__ __forceinline__ void wgmma_ss128(float* d, uint64_t a, uint64_t b, int sc) {
    asm volatile("{.reg .pred p; setp.ne.b32 p, %66, 0;\n wgmma.mma_async.sync.aligned.m64n128k16.f32.bf16.bf16 "
                 "{%0,%1,%2,%3,%4,%5,%6,%7,%8,%9,%10,%11,%12,%13,%14,%15,%16,%17,%18,%19,%20,%21,%22,%23,%24,%25,%26,%27,%28,%29,%30,%31,"
                 "%32,%33,%34,%35,%36,%37,%38,%39,%40,%41,%42,%43,%44,%45,%46,%47,%48,%49,%50,%51,%52,%53,%54,%55,%56,%57,%58,%59,%60,%61,%62,%63}, %64, %65, p, 1, 1, %67, 1;}"
                 : F16(d, 0), F16(d, 16), F16(d, 32), F16(d, 48) : "l"(a), "l"(b), "r"(sc), "n"(TA));
}

__device__ __forceinline__ float warp_sum(float v) {
#pragma unroll
    for (int o = 16; o; o >>= 1) v += __shfl_xor_sync(~0u, v, o);
    return v;
}
__device__ __forceinline__ float bfround(float x) { return __bfloat162float(__float2bfloat16(x)); }

__device__ __forceinline__ void wait_count1(const uint32_t* p, uint32_t target) {
    int it = 0;
#pragma unroll 1
    while (true) {
        uint32_t v;
        asm volatile("ld.acquire.gpu.global.u32 %0, [%1];" : "=r"(v) : "l"(p) : "memory");
        if (v >= target) break;
        spin_guard(++it);
    }
}
__device__ __forceinline__ void red2(float* p, float a, float b) {
    asm volatile("red.relaxed.gpu.global.add.v2.f32 [%0], {%1, %2};" ::"l"(p), "f"(a), "f"(b) : "memory");
}
__device__ __forceinline__ void l2_prefetch(const void* p, uint32_t bytes) {
    asm volatile("cp.async.bulk.prefetch.L2.global [%0], %1;" ::"l"(p), "r"(bytes) : "memory");
}
__device__ __forceinline__ void signal_count(uint32_t* p) { asm volatile("red.release.gpu.global.add.u32 [%0], 1;" ::"l"(p) : "memory"); }
__device__ __forceinline__ void e_expect(uint32_t b, uint32_t tx) {
    asm volatile("{.reg .pred p; elect.sync _|p, 0xffffffff; @p mbarrier.arrive.expect_tx.shared.b64 _, [%0], %1;}" ::"r"(b), "r"(tx) : "memory");
}
__device__ __forceinline__ uint64_t evict_first() { uint64_t p; asm("createpolicy.fractional.L2::evict_first.b64 %0, 1.0;" : "=l"(p)); return p; }
__device__ __forceinline__ uint64_t evict_normal() { uint64_t p; asm("createpolicy.fractional.L2::evict_unchanged.b64 %0, 1.0;" : "=l"(p)); return p; }
__device__ __forceinline__ void e_tma2d(uint32_t dst, const CUtensorMap* m, int c0, int c1, uint32_t bar, uint64_t pol) {
    asm volatile("{.reg .pred p; elect.sync _|p, 0xffffffff;\n @p cp.async.bulk.tensor.2d.shared::cluster.global.mbarrier::complete_tx::bytes.L2::cache_hint [%0], [%1, {%3, %4}], [%2], %5;}"
                 ::"r"(dst), "l"(m), "r"(bar), "r"(c0), "r"(c1), "l"(pol) : "memory");
}
__device__ __forceinline__ void e_tma2d_mc(uint32_t dst, const CUtensorMap* m, int c0, int c1, uint32_t bar, uint64_t pol) {
    asm volatile("{.reg .pred p; elect.sync _|p, 0xffffffff;\n @p cp.async.bulk.tensor.2d.shared::cluster.global.mbarrier::complete_tx::bytes.multicast::cluster.L2::cache_hint [%0], [%1, {%3, %4}], [%2], %5, %6;}"
                 ::"r"(dst), "l"(m), "r"(bar), "r"(c0), "r"(c1), "h"((uint16_t)3), "l"(pol) : "memory");
}
__device__ __forceinline__ void e_prefetch(const void* p, uint32_t bytes) {
    asm volatile("{.reg .pred p; elect.sync _|p, 0xffffffff; @p cp.async.bulk.prefetch.L2.global [%0], %1;}" ::"l"(p), "r"(bytes) : "memory");
}
__device__ __forceinline__ uint32_t wait_count_w(const uint32_t* p, uint32_t target) {
    int it = 0;
#pragma unroll 1
    while (true) {
        uint32_t v;
        asm volatile("ld.acquire.gpu.global.u32 %0, [%1];" : "=r"(v) : "l"(p) : "memory");
        if (__all_sync(~0u, v >= target)) return v;
        spin_guard(++it);
    }
}

__device__ __forceinline__ uint4 pack8(const float* x) {
    return make_uint4(pack2(x[0], x[1]), pack2(x[2], x[3]), pack2(x[4], x[5]), pack2(x[6], x[7]));
}
#define NL 6
constexpr uint32_t HCH = 5120, HBUF = 8 * HCH;
constexpr uint32_t SM_SX = 0, SM_ST = 2560, SM_OX = 8192, SM_LX = 10240, SM_PX = 11392, SM_PA = 12288, SM_VF = 18432, SM_TAB = 26624, SM_WL2 = 41984, SM_HB = 49152, SM_WO = 131072,
                   SM_WL = 196608, SM_PRE = SM_WL, SM_BAR = 227328, SM_TRC = SM_BAR + 256, SM_REC_TOTAL = SM_TRC + 2688;
__host__ __device__ constexpr uint32_t sm_wl(int i) { return i < 5 ? SM_WL + i * 6144 : SM_WL2; }
constexpr uint32_t SB0 = 1024;
constexpr int B_WO = 0, B_HE = 1, B_ROLE = 2, B_HB = 3, B_W = 5;
constexpr int NB_MEM = 1, NB_QK = 2, NB_X1 = 3, NB_X2 = 4, NB_WIN = 5, NB_WG = 6, NB_KDONE = 7, NB_FIN0 = 8, NB_LN = 9, NB_MEM2 = 10, NB_H = 11, NB_A = 12, NB_B = 13, NB_C = 14, NB_F = 15;
#define TPV_DLY 4
#define L_AT 1
#define D_X2 300
#define NPF1 6
#define NPF 11
#define T_GO 29
#define GATE_AT 25
#define T_X2 1875
#define T_V 300
#define VP_AT 1
#define PD 4
#define PV_FENCE 0
#define SSG 4
#define SSG_V 5
#define SS0_K 4
#define SS0_V 6
#define NPF0 4
#define STG_FENCE 1
#define WO_AT 0x1100
#define W_SPEC 6
#define KMAP 1
#define NO_GUESS 0
#define NPF2 9
#define PF_DLY 6
#define H_D 225
#define PIN_EPI 1

#define PROF_INIT
#define PROF(i)
#define PROFV(i, v)
#define PROF_OUT

__device__ __forceinline__ uint32_t clk32() { uint32_t t; asm volatile("mov.u32 %0, %%clock;" : "=r"(t) :: "memory"); return t; }
__device__ __forceinline__ uint32_t gtime32() { uint32_t t; asm volatile("mov.u32 %0, %%globaltimer_lo;" : "=r"(t) :: "memory"); return t; }
__device__ __forceinline__ void spin_until(uint32_t t0, uint32_t d) { while (clk32() - t0 < d) {} }
template <int N> __device__ __forceinline__ uint32_t delay(uint32_t zero) {
    float x = __uint_as_float(clk32());
#pragma unroll
    for (int i = 0; i < N; i++) asm volatile("ex2.approx.ftz.f32 %0, %0;" : "+f"(x));
    return __float_as_uint(x) & zero;
}
__device__ __forceinline__ uint32_t clk_after(uint32_t x, uint32_t zero) {
    unsigned long long c = 0;
    asm volatile("{.reg .pred p; setp.eq.u32 p, %1, 0; @p mov.u64 %0, %%clock64;}" : "+l"(c) : "r"(x & zero) : "memory");
    return (uint32_t)c;
}
__device__ __forceinline__ uint32_t later(uint32_t a, uint32_t b) { return a + max((int)(b - a), 0); }
__device__ __forceinline__ void wait_clk(uint32_t t) {
#pragma unroll 1
    while (true) {
        unsigned long long c;
        asm volatile("mov.u64 %0, %%clock64;" : "=l"(c) :: "memory");
        if ((int)((uint32_t)c - t) >= 0) break;
    }
}
__device__ __forceinline__ uint32_t opaque(uint32_t v) { return __shfl_sync(~0u, v, threadIdx.x & 31); }
__device__ __forceinline__ uint32_t xor_or(uint32_t a, uint32_t b, uint32_t t) {
    uint32_t r; asm volatile("lop3.b32 %0, %1, %2, %3, 0x7E;" : "=r"(r) : "r"(a), "r"(b), "r"(t)); return r;
}
__device__ __forceinline__ uint32_t or3(uint32_t a, uint32_t b, uint32_t c) {
    uint32_t r; asm volatile("lop3.b32 %0, %1, %2, %3, 0xFE;" : "=r"(r) : "r"(a), "r"(b), "r"(c)); return r;
}
__device__ __forceinline__ uint32_t settag(uint32_t v, uint32_t tag) {
    uint32_t r; asm("lop3.b32 %0, %1, 1, %2, 0xB8;" : "=r"(r) : "r"(v), "r"(tag)); return r;
}
__device__ __forceinline__ void ldg4_if(uint4& v, const void* p, bool c) {
    asm volatile("{.reg .pred p; setp.ne.u32 p, %5, 0; @p ld.relaxed.gpu.global.v4.u32 {%0,%1,%2,%3}, [%4];}"
                 : "+r"(v.x), "+r"(v.y), "+r"(v.z), "+r"(v.w) : "l"(p), "r"((uint32_t)c) : "memory");
}
__device__ __forceinline__ uint4 ldg_rlx2x2(const void* p) {
    unsigned long long a, b;
    asm volatile("ld.relaxed.gpu.global.v2.b64 {%0,%1}, [%2];" : "=l"(a), "=l"(b) : "l"(p) : "memory");
    return make_uint4((uint32_t)a, (uint32_t)(a >> 32), (uint32_t)b, (uint32_t)(b >> 32));
}
__device__ __forceinline__ void stg_rlx2x2(void* p, uint32_t x, uint32_t y, uint32_t z, uint32_t w) {
    asm volatile("{.reg .b64 a, b; mov.b64 a, {%1,%2}; mov.b64 b, {%3,%4}; st.relaxed.gpu.global.v2.b64 [%0], {a, b};}" ::"l"(p), "r"(x), "r"(y), "r"(z), "r"(w) : "memory");
}
__device__ __forceinline__ void ldg1_if(uint32_t& v, const void* p, bool c) {
    asm volatile("{.reg .pred p; setp.ne.u32 p, %2, 0; @p ld.relaxed.gpu.global.u32 %0, [%1];}" : "+r"(v) : "l"(p), "r"((uint32_t)c) : "memory");
}
__device__ __forceinline__ void sts2(uint32_t a, float x, float y) { asm volatile("st.shared.v2.f32 [%0], {%1,%2};" ::"r"(a), "f"(x), "f"(y) : "memory"); }
__device__ __forceinline__ void sts4f(uint32_t a, float x, float y, float z, float w) {
    asm volatile("st.shared.v4.f32 [%0], {%1,%2,%3,%4};" ::"r"(a), "f"(x), "f"(y), "f"(z), "f"(w) : "memory");
}
__device__ __forceinline__ void sts1(uint32_t a, uint32_t x) { asm volatile("st.shared.u32 [%0], %1;" ::"r"(a), "r"(x) : "memory"); }
__device__ __forceinline__ uint32_t lds1(uint32_t a) { uint32_t v; asm volatile("ld.shared.u32 %0, [%1];" : "=r"(v) : "r"(a) : "memory"); return v; }
__device__ __forceinline__ float4 lds4f(uint32_t a) {
    float4 v; asm volatile("ld.shared.v4.f32 {%0,%1,%2,%3}, [%4];" : "=f"(v.x), "=f"(v.y), "=f"(v.z), "=f"(v.w) : "r"(a) : "memory"); return v;
}
__device__ __forceinline__ float2 lds2f(uint32_t a) {
    float2 v; asm volatile("ld.shared.v2.f32 {%0,%1}, [%2];" : "=f"(v.x), "=f"(v.y) : "r"(a) : "memory"); return v;
}
__device__ __forceinline__ bool any_bit0(uint32_t x) {
    uint32_t r;
    asm volatile("{.reg .pred p, q; .reg .b32 t; and.b32 t, %1, 1; setp.ne.u32 p, t, 0; vote.sync.any.pred q, p, 0xffffffff; selp.u32 %0, 1, 0, q;}" : "=r"(r) : "r"(x));
    return r;
}
__device__ __forceinline__ float rcp_fast(float x) { float r; asm("rcp.approx.ftz.f32 %0, %1;" : "=f"(r) : "f"(x)); return r; }
__device__ __forceinline__ void stsm4(uint32_t a, uint32_t r0, uint32_t r1, uint32_t r2, uint32_t r3) {
    asm volatile("stmatrix.sync.aligned.m8n8.x4.shared.b16 [%0], {%1,%2,%3,%4};" ::"r"(a), "r"(r0), "r"(r1), "r"(r2), "r"(r3) : "memory");
}
__device__ __forceinline__ void stsm4t(uint32_t a, uint32_t r0, uint32_t r1, uint32_t r2, uint32_t r3) {
    asm volatile("stmatrix.sync.aligned.m8n8.x4.trans.shared.b16 [%0], {%1,%2,%3,%4};" ::"r"(a), "r"(r0), "r"(r1), "r"(r2), "r"(r3) : "memory");
}
__device__ __forceinline__ void stg_b64_if(bool c, void* p, uint32_t x, uint32_t y) {
    asm volatile("{.reg .pred p; .reg .b64 a; setp.ne.u32 p, %3, 0; mov.b64 a, {%1,%2}; @p st.relaxed.gpu.global.b64 [%0], a;}" ::"l"(p), "r"(x), "r"(y), "r"((uint32_t)c) : "memory");
}
__device__ __forceinline__ void cp_async16(uint32_t dst, const void* src) { asm volatile("cp.async.cg.shared.global [%0], [%1], 16;" ::"r"(dst), "l"(src) : "memory"); }
__device__ __forceinline__ void cp_async16_ef(uint32_t dst, const void* src) {
    asm volatile("cp.async.cg.shared.global.L2::cache_hint [%0], [%1], 16, %2;" ::"r"(dst), "l"(src), "l"(evict_first()) : "memory");
}
__device__ __forceinline__ uint32_t prmt(uint32_t a, uint32_t b, uint32_t c) { uint32_t r; asm("prmt.b32 %0, %1, %2, %3;" : "=r"(r) : "r"(a), "r"(b), "r"(c)); return r; }
__device__ __forceinline__ uint32_t hadd2h(uint32_t a, uint32_t b) { uint32_t r; asm("add.rn.f16x2 %0, %1, %2;" : "=r"(r) : "r"(a), "r"(b)); return r; }
__device__ __forceinline__ uint32_t hmin2h(uint32_t a, uint32_t b) { uint32_t r; asm("min.f16x2 %0, %1, %2;" : "=r"(r) : "r"(a), "r"(b)); return r; }
__device__ __forceinline__ uint32_t hmax2h(uint32_t a, uint32_t b) { uint32_t r; asm("max.f16x2 %0, %1, %2;" : "=r"(r) : "r"(a), "r"(b)); return r; }
__device__ __forceinline__ uint32_t max3u(uint32_t a, uint32_t b, uint32_t c) { return __vimax3_u32(a, b, c); }
__device__ __forceinline__ void fence_gpu() { asm volatile("fence.acq_rel.gpu;" ::: "memory"); }

__device__ __forceinline__ void h_load(uint32_t sb, const uint8_t* hsrc, int pass, uint32_t rank, uint32_t rot, uint32_t wq, bool arm = true, uint32_t skip = 0) {
    const uint32_t bar = sb + SM_BAR + 8 * (B_HB + (pass & 1)), c = (wq + rot) & 3, dst = sb + SM_HB + (pass & 1) * HBUF + (rank * 4 + c) * HCH + skip;
    const uint8_t* src = hsrc + ((size_t)pass * 65536 + c * 4096 + skip);
    if (arm && wq == 0) e_expect(bar, 32768 - 8 * skip);
    asm volatile("{.reg .pred p; elect.sync _|p, 0xffffffff;\n"
                 " @p cp.async.bulk.shared::cluster.global.mbarrier::complete_tx::bytes.multicast::cluster.L2::cache_hint [%0], [%1], %4, [%2], %3, %5;}"
                 ::"r"(dst), "l"(src), "r"(bar), "h"((uint16_t)3), "r"(4096 - skip), "l"(evict_first()) : "memory");
}
__device__ __forceinline__ uint4 ldg_b128(const void* p) {
    uint4 v;
    asm volatile("{.reg .b128 t; .reg .b64 a, b; ld.relaxed.gpu.global.b128 t, [%4]; mov.b128 {a, b}, t; mov.b64 {%0,%1}, a; mov.b64 {%2,%3}, b;}"
                 : "=r"(v.x), "=r"(v.y), "=r"(v.z), "=r"(v.w) : "l"(p) : "memory");
    return v;
}
__device__ __forceinline__ void stg_b128_if(bool c, void* p, uint32_t x, uint32_t y, uint32_t z, uint32_t w) {
    asm volatile("{.reg .pred p; .reg .b128 t; .reg .b64 a, b; setp.ne.u32 p, %5, 0; mov.b64 a, {%1,%2}; mov.b64 b, {%3,%4}; mov.b128 t, {a, b}; @p st.relaxed.gpu.global.b128 [%0], t;}"
                 ::"l"(p), "r"(x), "r"(y), "r"(z), "r"(w), "r"((uint32_t)c) : "memory");
}
__device__ __forceinline__ float pretag(float x, uint32_t add, uint32_t keep) { return __uint_as_float((__float_as_uint(x) + add) & keep); }

template <bool MASK, class F>
__device__ __forceinline__ void softmax_rows(uint32_t src, uint32_t dst, uint32_t g16, int row0, F mid) {
    const uint32_t u = (g16 >> 7) & 3, e = ((g16 >> 9) << 3) | ((g16 >> 4) & 7);
    const uint32_t se = src + e * 8, su = se + u * 1088;
    const float2 p0 = lds2f(su), p1 = lds2f(su + 256), p2 = lds2f(su + 512), p3 = lds2f(su + 768);
    const float2 m0 = lds2f(se + 4352), m1 = lds2f(se + 4352 + 256), m2 = lds2f(se + 4352 + 512), m3 = lds2f(se + 4352 + 768);
    float a0 = (p0.x + p1.x) + (p2.x + p3.x), a1 = (p0.y + p1.y) + (p2.y + p3.y);
    const float a2 = (m0.x + m1.x) + (m2.x + m3.x), a3 = (m0.y + m1.y) + (m2.y + m3.y);
    mid(__float_as_uint(a3));
    if (MASK) {
        const int vis = row0 + (e >> 2) - 2 * (e & 3) - 8 * u;
        if (vis < 0) a0 = -1e9f / 0.08838834764831845f;
        if (vis < 1) a1 = -1e9f / 0.08838834764831845f;
    }
    int k = __float_as_int(fmaxf(fmaxf(a0, a1), fmaxf(a2, a3)));
    k ^= (k >> 31) & 0x7fffffff;
    const bool hi = g16 & 64;
    const int k0 = __reduce_max_sync(~0u, hi ? INT_MIN : k), k1 = __reduce_max_sync(~0u, hi ? k : INT_MIN);
    k = hi ? k1 : k0;
    const float m = __int_as_float(k ^ ((k >> 31) & 0x7fffffff));
    const float sl2 = 0.08838834764831845f * 1.4426950408889634f, mb = -m * sl2;
    sts1(dst + e * 16 + u * 4, pack2(ex2(fmaf(a0, sl2, mb)), ex2(fmaf(a1, sl2, mb))));
    sts1(dst + 512 + e * 4, pack2(ex2(fmaf(a2, sl2, mb)), ex2(fmaf(a3, sl2, mb))));
}

__device__ __forceinline__ uint32_t pack_h2(float lo, float hi) {
    uint32_t r; asm("cvt.rn.satfinite.f16x2.f32 %0, %1, %2;" : "=r"(r) : "f"(hi), "f"(lo)); return r;
}
__device__ __forceinline__ float2 unpack_h2(uint32_t u) {
    float2 r; asm("{.reg .b16 l, h; mov.b32 {l, h}, %2; cvt.f32.f16 %0, l; cvt.f32.f16 %1, h;}" : "=f"(r.x), "=f"(r.y) : "r"(u)); return r;
}
__device__ __forceinline__ uint32_t h2bf(uint32_t u) {
    uint32_t r;
    asm volatile("{.reg .b16 l, h; .reg .f32 a, b; mov.b32 {l, h}, %1; cvt.f32.f16 a, l; cvt.f32.f16 b, h; cvt.rn.bf16x2.f32 %0, b, a;}" : "=r"(r) : "r"(u));
    return r;
}
__device__ __forceinline__ void red_h8(void* p, uint32_t x, uint32_t y, uint32_t z, uint32_t w) {
    asm volatile("red.relaxed.gpu.global.add.noftz.v4.f16x2 [%0], {%1,%2,%3,%4};" ::"l"(p), "r"(x), "r"(y), "r"(z), "r"(w) : "memory");
}
__device__ __forceinline__ void red_h2_if(bool c, void* p, uint32_t x) {
    asm volatile("{.reg .pred p; setp.ne.u32 p, %2, 0; @p red.relaxed.gpu.global.add.noftz.f16x2 [%0], %1;}" ::"l"(p), "r"(x), "r"((uint32_t)c) : "memory");
}
__device__ __forceinline__ void red_h10(bool c, void* p, void* q, uint32_t x, uint32_t y, uint32_t z, uint32_t w, uint32_t e) {
    asm volatile("{.reg .pred p; setp.ne.u32 p, %7, 0; red.relaxed.gpu.global.add.noftz.v4.f16x2 [%0], {%2,%3,%4,%5};\n"
                 " @p red.relaxed.gpu.global.add.noftz.f16x2 [%1], %6;}" ::"l"(p), "l"(q), "r"(x), "r"(y), "r"(z), "r"(w), "r"(e), "r"((uint32_t)c) : "memory");
}
constexpr float Q_SCALE = 1024.0f;
constexpr float SM_L2E = 0.08838834764831845f * 1.4426950408889634f * Q_SCALE;
template <int V> struct IC { static constexpr int value = V; };
typedef unsigned long long u64;
__device__ __forceinline__ uint32_t lo32(u64 v) { return (uint32_t)v; }
__device__ __forceinline__ uint32_t hi32(u64 v) { return (uint32_t)(v >> 32); }
__device__ __forceinline__ u64 ldg_u64(const void* p) { u64 v; asm volatile("ld.relaxed.gpu.global.b64 %0, [%1];" : "=l"(v) : "l"(p) : "memory"); return v; }
__device__ __forceinline__ void ldg_u64_if(u64& v, const void* p, bool c) {
    asm volatile("{.reg .pred p; setp.ne.u32 p, %2, 0; @p ld.relaxed.gpu.global.b64 %0, [%1];}" : "+l"(v) : "l"(p), "r"((uint32_t)c) : "memory");
}
struct RecTime { uint32_t go, x2, v, dx2, h; };
__device__ __forceinline__ void rec_main(uint32_t sb, const CUtensorMap* tWo, uint8_t* arena, int role, int hinfo, int wg, uint32_t zero, const RecTime& tm) {
    const int hA = hinfo & 255;
    const int tid = threadIdx.x, t = tid & 127, lane = tid & 31, wi = t >> 5;
    const uint32_t bars = sb + SM_BAR;
    const int head = role >> 2, qd = role & 3, j = blockIdx.x & 1, kh = role & 1;
    const uint32_t mypar = (head >= hA) ^ (hinfo >> 11);
    const uint32_t wiu = __reduce_max_sync(~0u, wi);
    const bool warp0 = wiu == 0;
    const uint8_t* hsrc = (const uint8_t*)g_himg + kh * 32768 + j * 16384;
    auto tokbase = [&](int ty) { return ((ty + 1) << 21) + blk(lb_tok(head), mypar ^ ((hinfo >> (8 + ty)) & 1)); };
    const uint32_t tbw = tokbase(wg), tbq = tokbase(0) + (qd >> 1) * 2048 + (qd & 1) * 8;
#define KS(p) (4 * (((p) >> 1) & 7) + ((p) >> 4) + 2 * ((p) & 1))
    uint32_t w[32 - NL][4];
    uint4 wl5;
    if (wg == 2) bar_arrive(NB_WIN, 384);
    const uint32_t po = (1 << 20) + j * 16384 + kh * 2048;
    const uint32_t c16 = kh * 2048 + ((2 * j + (wi >> 1)) * 32 + lane) * 16, xso = blk(lb_x2(head), mypar);
    const uint32_t x2o = xso + wg * 16384 + (wi & 1) * 2048 + (c16 >> 1), tko = tbw + (wi & 1) * 16384 + c16;
    {
        stg_rlx2(arena + x2o, 0, 0);
#pragma unroll
        for (int i = 0; i < 4; i++) stg_rlx4(arena + ((i & 1 ? tko : tbw + (po ^ 2048) + t * 16) + (i >> 1) * 32768), 0, 0, 0, 0);
    }
    const uint32_t frow = ((lane >> 4) * 8 + (lane & 7)) * 128, fx = ((lane >> 3) & 1) ^ (lane & 7);
    {
#pragma unroll 1
        for (int i = 0; i < 4; i++) mbar_wait_w(bars + 8 * (B_W + (wg == 2 ? 8 + i : 2 * i + wg)), 0);
        const uint32_t stg = sb + wg * 65536;
#pragma unroll
        for (int p = NL; p < 32; p++) ldsm4t(w[p - NL], stg + KS(p) * 2048 + frow + ((fx ^ (2 * wi)) << 4));
#pragma unroll
        for (int i = 0; i < NL; i++) {
            wl5 = lds4(stg + KS(i) * 2048 + t * 16);
            if (i < 5) sts4(sb + sm_wl(i) + tid * 16, wl5.x, wl5.y, wl5.z, wl5.w);
        }
        fence_async_smem();
        if (wg < 2) bar_sync(NB_WG, 256);
        if (wg > 0) wait_count_w(&g_tick[32 + (lane & 3) * 8], wg);
        if (wg == 1) {
            mbar_arrive_cluster_if(t == 0, bars + 8 * B_HE, j ^ 1);
            asm volatile("fence.proxy.async.global;" ::: "memory");
            mbar_wait_w(bars + 8 * B_HE, 0);
#pragma unroll 1
            for (int i = 0; i < 2; i++) h_load(sb, hsrc, i, j, head, wiu, true, i ? 0 : 2048);
        }
        TL(3 + wg)
    }
    uint32_t g16 = opaque(t * 16);
    {
        const uint32_t wr = ((wg * 4 + wi) ^ head) & 7;
        const uint32_t pc = wg < 2 ? acc_piece(wr >> 2, qd, wr & 3) : acc_piece(kh, wi, 0);
        const uint32_t lm = sb + SM_HB + 4096 + (lane & 7) * 128;
        const uint32_t a0 = wg < 2 ? sb + SM_WL + wg * 2048 + frow + ((fx ^ (2 * wi)) << 4) : blk(LB_STAMP + (wi >> 1), mypar) + stamp_line(wi, lane >> 3) + (lane & 7) * 16;
        const uint32_t a1 = pc + lane * 16;
        const uint32_t a2 = wg < 2 ? pc + 512 + (lane >> 3) * 4 : (role >> 2) * 1024 + (lane < 8 ? (role & 3) * 128 : 384) + lane * 16;
        const uint32_t a3 = wg < 2 ? sb + SM_WO + (wr >> 2) * 32768 + frow + ((fx ^ (2 * (wr & 3))) << 4) : qd * 65536 + head * 2048 + wi * 512 + lane * 4;
        const uint32_t a4 = wg < 2 ? lm + ((fx ^ ((lane >> 4) * 4)) << 4) : lm + (fx << 4) + ((lane >> 4) + 2 * wi) * HCH;
        if (wg < 2) bar_arrive(NB_X2, 384);
        else bar_sync(NB_X2, 384);
        if (NL > 5) {
            sts4(sb + SM_WL2 + tid * 16, wl5.x, wl5.y, wl5.z, wl5.w);
            fence_async_smem();
            bar_sync(NB_WG + 1 + wg, 128);
        }
        sts4(sb + SM_TAB + wg * 5120 + g16, a0, x2o,
             wg ? xso + (wg == 2 ? 32768 : 0) + t * 8 : blk(LB_STAMP + ((lane >> 1) & 1), (lane >> 2) & 1) + stamp_line(lane, qd) + head * 4, tko);
        sts4(sb + SM_TAB + wg * 5120 + 2048 + g16, a1, a2, a3, a4);
        sts2(sb + SM_TAB + wg * 5120 + 4096 + t * 8, __uint_as_float(tbw + t * 16), __uint_as_float((wg ? tbq : tokbase(1)) + t * 16));
    }
    const uint32_t ONES = 0x3f803f80u, tabw = sb + SM_TAB + wg * 5120;
#define LAST ((g16 & 0x70) == 0x70)
    PROF_INIT

    auto pa_ptr = [&](int p) { return arena + (((p & 1) ^ 1) * 32768 + po + lds1(tabw + 4096 + (g16 >> 1))); };
    auto pa_request = [&](int p) { cp_async16(sb + SM_PA + wg * 2048 + g16, pa_ptr(p)); };
    auto pa_get = [&](int p) {
        asm volatile("cp.async.wait_all;" ::: "memory");
        uint4 pa = lds4(sb + SM_PA + wg * 2048 + g16);
        int it = 0;
#pragma unroll 1
        while (any_bit0(pa.x ^ ((p - 1) >> 1) ^ 1) && p > 0 && p <= NSEG) { pa = ldg_b128(pa_ptr(p)); spin_guard(++it); }
        return pa;
    };
    auto pass_init = [&](float* acc, int n, uint4 pa) {
#pragma unroll
        for (int i = 0; i < 4; i++) { acc[2 * i] = bflo((&pa.x)[i]); acc[2 * i + 1] = bfhi((&pa.x)[i]); }
#pragma unroll
        for (int i = 8; i < n; i++) acc[i] = 0.f;
    };
    auto pass_run = [&](auto vc, int p, float* acc, auto mid) {
        constexpr bool V = decltype(vc)::value;
#define HB(ks) dadd(mkdesc(SB0 + SM_HB + ((ks) >> 2) * HCH + ((ks) & 3) * 32, 16, 1024, 1), (p & 1) * (HBUF / 16))
        wg_fence();
#pragma unroll
        for (int i = 0; i < 32; i++) {
            constexpr int GAP = V ? SSG_V : SSG, SS0 = V ? SS0_V : SS0_K;
            const int u = i < SS0 ? 0 : (i - SS0 + GAP - 1) / GAP, q = i - (u < NL ? u : NL);
            if (i >= SS0 && (i - SS0) % GAP == 0 && u < NL) wgmma_tok_ss<V>(acc, dadd(mkdesc(SB0 + sm_wl(u), 8192, 1024, 1), (V ? 2 : wg) * 128), HB(KS(u)));
            else wgmma_tok_rs<V>(acc, w[q], HB(KS(NL + q)), 1);
            mid(i);
        }
        wg_commit();
    };
    auto pass_out = [&](auto tc, int p, float* acc, auto mid) {
        constexpr int TY = decltype(tc)::value;
        const bool V = TY == 2 || (TY == 4 && wg == 2), Q = TY >= 3 && wg == 0;
        const int b = p & 1, s = p - 2;
        (void)s;
        const uint32_t ftag = (((p - 1) >> 1) & 1) ^ 1, ptag = ((p >> 1) & 1) ^ 1;
        const bool tg = V || !(g16 & 64);
        const uint32_t add = tg ? (ftag ^ 1) << 16 : 0u, keep = tg ? 0xfffe0000u : ~0u;
        const uint32_t add1 = V ? 0u : add, keep1 = V ? ~0u : keep;
        const uint32_t add2 = Q ? add : 0u, keep2 = Q ? keep : ~0u;
        uint8_t* pdst = arena + (b * 32768 + (po ^ 2048) + lds1(tabw + 4096 + (g16 >> 1)));
        uint8_t* fdst = arena + ((b ^ 1) * 32768 + lds1(tabw + 12 + g16));
        if (PIN_EPI) asm volatile("" : "+l"(pdst), "+l"(fdst));
        mid(0);
        uint32_t r0 = pack2(pretag(acc[0], add, keep), pretag(acc[1], add1, keep1));
        uint32_t r1 = pack2(acc[2], acc[3]), r3 = pack2(acc[6], acc[7]);
        uint32_t r2 = pack2(pretag(acc[4], add2, keep2), pretag(acc[5], add2, keep2));
        if (!V) { r0 = movm(r0); r1 = movm(r1); r2 = movm(r2); r3 = movm(r3); }
        mid(1);
        stg_b128_if(p < NSEG, pdst, settag(pack2(pretag(acc[8], (ptag ^ 1) << 16, 0xfffe0000u), acc[9]), ptag), pack2(acc[10], acc[11]), pack2(acc[12], acc[13]), pack2(acc[14], acc[15]));
        stg_b128_if(p > 0 && p <= NSEG, fdst, settag(r0, ftag), r1, Q ? settag(r2, ftag) : r2, r3);
        PROF(10)
    };
    auto nop = [](int) {};
    auto wait0 = [](int i) { if (i == 0) wg_wait<0>(); };
    uint4 tf[2][2];
    auto load_tok = [&](int s, uint32_t o) {
        const uint8_t* ts = arena + ((s & 1) * 32768 + o);
#pragma unroll
        for (int a = 0; a < 2; a++)
#pragma unroll
            for (int b = 0; b < 2; b++) tf[a][b] = ldg_b128(ts + a * 16384 + b * 2048);
    };

    auto wo_load = [&](int stage) {
        if (wg == 2 && ((WO_AT >> (4 * wiu)) & 15) == stage) {
            const int c0 = (wiu >> 1) * 512 + qd * 128 + (wiu & 1) * 64;
            e_expect(bars + 8 * B_WO, 16384);
            e_tma2d(sb + SM_WO + wiu * 16384, tWo, c0, head * DH, bars + 8 * B_WO, evict_normal());
            e_tma2d(sb + SM_WO + wiu * 16384 + 8192, tWo, c0, head * DH + 64, bars + 8 * B_WO, evict_normal());
        }
    };
#pragma unroll 1
    for (int p = 0; p <= (wg >> 1); p++) {
        mbar_wait_w(bars + 8 * (B_HB + p), 0);
        float acc[16];
        pass_init(acc, 16, pa_get(p));
        if (wg == 2) TX(2 + 3 * p)
        wo_load(p);
        pass_run(IC<0>(), p, acc, nop);
        if (p) {
            mbar_wait_w(bars + 8 * B_HE, 1);
            asm volatile("fence.proxy.async.global;" ::: "memory");
            h_load(sb, hsrc, 2, j, head, wiu);
        }
        pass_out(IC<4>(), p, acc, wait0);
        if (wg < 2) {
            bar_arrive(NB_C, 384);
            if (wg == 0) bar_arrive(NB_WIN, 384);
        } else if (p == 0) {
            TX(3)
            bar_sync(NB_C, 384);
            mbar_arrive_cluster_if(g16 == 0, bars + 8 * B_HE, j ^ 1);
        }
        pa_request(p + 1);
    }
    if (wg < 2) {
        mbar_wait_w(bars + 8 * (B_HB + 1), 0);
        uint4 pa = pa_get(1);
        uint32_t wl = lds1(tabw + g16);
#pragma unroll 1
        for (int s = 0; s < NSEG; s++) {
            uint32_t w0[NL][4], xo, lm, fz = 0;
            float acc[16];
#pragma unroll
            for (int i = 0; i < 4; i++)
                asm volatile("shl.b32 %0, %4, 16; and.b32 %1, %4, 0xffff0000; mov.b32 %2, %5; mov.b32 %3, %5;"
                             : "=&f"(acc[2 * i]), "=f"(acc[2 * i + 1]), "=f"(acc[8 + 2 * i]), "=f"(acc[9 + 2 * i]) : "r"((&pa.x)[i]), "r"(zero));
#pragma unroll
            for (int i = 0; i < NL; i++) ldsm4t(w0[i], wl + (sm_wl(i) - SM_WL));
            if (wg == 0) bar_sync(NB_B, 256);
            else bar_sync(NB_WIN, 384);
            pass_run(IC<0>(), s + 1, acc, [&](int i) { if (i == GATE_AT && wg) bar_arrive(NB_B, 256); });
            xo = lds1(tabw + 4 + g16);
            lm = lds1(tabw + 2060 + g16) + (s & 1) * HBUF;
            pass_out(IC<3>(), s + 1, acc, [&](int i) {
                if (i == 0) {
                    wg_wait<0>();
                    if (wg == 0) bar_arrive(NB_MEM, 384);
                    fz |= clk32();
                    { const int s_ = s; { const int s = s_ - 1; (void)s; PROF(9) } }
                }
                if (i == 1 && wg) bar_sync(NB_F, 256);
            });
            asm volatile("" : "+r"(lm));
            if (wg == 0) bar_sync(NB_MEM2, 256);
            else bar_sync(NB_MEM, 384);
            PROF(1)
            float c[4][4];
            uint32_t bq[PD][4];
#define MEMF(it) ((lm ^ (((it) >> 3) * 32)) + ((it) & 7) * HCH)
#pragma unroll
            for (int it = 0; it < PD; it++) ldsm4(bq[it], MEMF(it));
#pragma unroll
            for (int it = 0; it < 16; it++) {
                uint32_t* bfr = bq[it % PD];
                const uint32_t* wa = 2 * it < NL ? w0[2 * it < NL ? 2 * it : 0] : w[2 * it < NL ? 0 : 2 * it - NL];
                const uint32_t* wb = 2 * it + 1 < NL ? w0[2 * it + 1 < NL ? 2 * it + 1 : 0] : w[2 * it + 1 < NL ? 0 : 2 * it + 1 - NL];
                float *ca = c[(2 * it) & 3], *cb = c[(2 * it + 1) & 3];
                if (it < 2) { mma16816z(ca, wa, bfr[0], bfr[1]); mma16816z(cb, wb, bfr[2], bfr[3]); }
                else { mma16816(ca, wa[0], wa[1], wa[2], wa[3], bfr[0], bfr[1]); mma16816(cb, wb[0], wb[1], wb[2], wb[3], bfr[2], bfr[3]); }
                if (it + PD < 16) ldsm4(bfr, MEMF(it + PD));
            }
            const float qs = wg ? 1.0f : 1.0f / Q_SCALE;
#define CSUM(e) fmaf(c[2][e] + c[3][e], qs, (c[0][e] + c[1][e]) * qs)
            const uint32_t r0 = pack2(CSUM(0), CSUM(1)), r1 = pack2(CSUM(2), CSUM(3));
            bar_arrive(NB_QK + (r0 & zero), 384);
            stg_rlx2(arena + xo, settag(movm(r0), (s & 1) ^ 1), movm(r1));
            const uint32_t tx = later(lds1(sb + SM_LX + 1040) + tm.x2, clk_after(r0, zero) + tm.dx2);
            g16 |= (fz | tx) & zero;
            PROF(2)
            {
                const uint32_t l16 = sb + (g16 & 0x1f0), g8 = g16 >> 1;
                const uint32_t tag = (s & 1) ^ 1, ttag = ((s >> 1) & 1) ^ 1;
                uint32_t wf[NPF][4], a3;
#define WF(f) (a3 + ((f) & 1) * 16384 + ((f) >> 1) * 2048)
                if (wg == 1) {
                    float sc[5][4];
                    uint4 (&kf)[2][2] = tf;
                    uint32_t qa[2][4], km[4], fz;
                    const uint32_t sd = lds1(sb + SM_TAB + 8 + g16);
                    int it = 0;
                    bool bad;
#pragma unroll 1
                    do {
                        u64 qf[2], x[8];
                        const float2 u = lds2f(tabw + 4096 + g8);
                        load_tok(s, __float_as_uint(u.x));
                        const uint8_t *xp = arena + lds1(tabw + 8 + g16), *tq = arena + ((s & 1) * 32768 + __float_as_uint(u.y));
                        asm volatile("" : "+l"(xp));
                        asm volatile("" : "+l"(tq));
#pragma unroll
                        for (int a = 0; a < 2; a++) qf[a] = ldg_u64(tq + a * 16384);
                        spin_guard(++it);
                        wait_clk(tx);
                        PROF(8)
#pragma unroll
                        for (int i = 0; i < 8; i++) x[i] = ldg_u64(xp + (i >> 2) * 16384 + (i & 3) * 1024);
                        fz = clk32();
                        const uint32_t bt = or3(xor_or(lo32(qf[0]), lo32(qf[1]), ttag), xor_or(kf[0][0].x, kf[0][1].x, ttag), xor_or(kf[1][0].x, kf[1][1].x, ttag));
#pragma unroll
                        for (int a = 0; a < 2; a++) { qa[a][1] = or3(lo32(qf[a]), zero, 0); qa[a][3] = or3(hi32(qf[a]), zero, 0); }
                        fz |= clk32();
#pragma unroll
                        for (int a = 0; a < 2; a++) { qa[a][0] = hadd2v(lo32(x[2 * a]), lo32(x[2 * a + 1])); qa[a][2] = hadd2v(hi32(x[2 * a]), hi32(x[2 * a + 1])); }
#pragma unroll
                        for (int a = 0; a < 2; a++) { km[2 * a] = hadd2v(lo32(x[4 + 2 * a]), lo32(x[5 + 2 * a])); km[2 * a + 1] = hadd2v(hi32(x[4 + 2 * a]), hi32(x[5 + 2 * a])); }
                        bad = any_bit0(or3(or3(bt, xor_or(lo32(x[0]), lo32(x[1]), tag), xor_or(lo32(x[2]), lo32(x[3]), tag)), xor_or(lo32(x[4]), lo32(x[5]), tag), xor_or(lo32(x[6]), lo32(x[7]), tag)));
                    } while (bad);
                    PROFV(13, it - 1)
                    PROF(7)
                    mma16816z(sc[0], qa[0], kf[0][0].x, kf[0][0].y);
                    mma16816z(sc[1], qa[0], kf[0][0].z, kf[0][0].w);
                    mma16816z(sc[2], qa[0], kf[0][1].x, kf[0][1].y);
                    mma16816z(sc[3], qa[0], kf[0][1].z, kf[0][1].w);
                    mma16816z(sc[4], qa[0], km[0], km[1]);
                    mma16816(sc[0], qa[1][0], qa[1][1], qa[1][2], qa[1][3], kf[1][0].x, kf[1][0].y);
                    mma16816(sc[1], qa[1][0], qa[1][1], qa[1][2], qa[1][3], kf[1][0].z, kf[1][0].w);
                    mma16816(sc[2], qa[1][0], qa[1][1], qa[1][2], qa[1][3], kf[1][1].x, kf[1][1].y);
                    mma16816(sc[3], qa[1][0], qa[1][1], qa[1][2], qa[1][3], kf[1][1].z, kf[1][1].w);
                    mma16816(sc[4], qa[1][0], qa[1][1], qa[1][2], qa[1][3], km[2], km[3]);
                    const uint32_t sx = sb + SM_SX + (g16 & 0x1f0) * 5;
                    sts4(sx + (g16 >> 5 & 0x30), pack_h2(sc[0][0], sc[0][1]), pack_h2(sc[1][0], sc[1][1]),
                         pack_h2(sc[2][0], sc[2][1]), pack_h2(sc[3][0], sc[3][1]));
                    sts1(sx + 64 + (g16 >> 7 & 0xc), pack_h2(sc[4][0], sc[4][1]));
                    bar_arrive(NB_X1, 256);
                    if (s == 0) TX(15)
                    const uint32_t now = gtime32();
#pragma unroll
                    for (int n = 0; n < 5; n++) sts2(sb + SM_ST + g8 + n * 1088, sc[n][2], sc[n][3]);
                    bar_arrive(NB_H, 256);
                    PROF(3)
                    a3 = lds1(tabw + 2056 + g16) | (fz & zero);
                    asm volatile("{.reg .pred p; setp.lt.u32 p, %2, 128; @p red.relaxed.gpu.global.max.u32 [%0], %1;}"
                                 ::"l"(arena + sd), "r"(__funnelshift_r(now * 8, s + 1, 8)), "r"(g16) : "memory");
                    if (s == 0) mbar_wait_w(bars + 8 * B_WO, 0);
                    a3 += delay<PF_DLY>(zero);
#pragma unroll
                    for (int f = 0; f < NPF; f++) ldsm4t(wf[f], WF(f));
                } else {
                    if (s == 0) { TL(9) mbar_wait_w(bars + 8 * B_WO, 0); TL(6) }
                    if (warp0 && !(s & 3)) {
                        const uint32_t need = min((s + 4) / 4 + 2, 17), a = sb + SM_LX + 1024 + ((g16 >> 2) & 12);
                        if (s == 0 || __any_sync(~0u, lds1(a) < need)) sts1(a, wait_count_w(&g_tick[32 + ((g16 >> 4) & 3) * 8], need));
                    }
                    a3 = lds1(tabw + 2056 + g16);
#pragma unroll
                    for (int f = 0; f < NPF0; f++) ldsm4t(wf[f], WF(f));
                    const float2 u = lds2f(tabw + 4096 + g8);
                    const uint8_t *q0 = arena + (tag * 32768 + po + __float_as_uint(u.x)), *q1 = arena + (tag * 32768 + po + __float_as_uint(u.y));
                    wait_clk(tx + tm.h);
                    int it = 0;
                    bool bad;
#pragma unroll 1
                    do {
                        const uint4 p0 = ldg_b128(q0), p1 = ldg_b128(q1);
                        spin_guard(++it);
                        wait_clk(tx + tm.v);
#pragma unroll
                        for (int f = NPF0; f < NPF1; f++) ldsm4t(wf[f], WF(f));
                        sts4(sb + SM_PA + g16, p0.x, p0.y, p0.z, p0.w);
                        sts4(sb + SM_PA + 2048 + g16, p1.x, p1.y, p1.z, p1.w);
                        bad = any_bit0(xor_or(p0.x, p1.x, ((s + 1) >> 1) ^ 1)) && s + 2 <= NSEG;
                    } while (bad);
                    bar_sync(NB_H, 256);
                    PROF(3)
                    softmax_rows<true>(sb + SM_ST, sb + SM_PX, g16, qd * 8, [&](uint32_t v) {
                        a3 += v & zero;
#pragma unroll
                        for (int f = NPF1; f < NPF2; f++) ldsm4t(wf[f], WF(f));
                    });
#pragma unroll
                    for (int f = NPF2; f < NPF; f++) ldsm4t(wf[f], WF(f));
                }
                PROF(5)
                float2 ls, a12;
                uint8_t *d0, *d1;
                bar_sync(NB_X2, 384);
                float c[4][4];
#pragma unroll
                for (int q = 0; q < 4; q++) {
                    uint32_t ob[4];
                    ldsm4t(ob, l16 + SM_OX + q * 512);
                    if (q == L_AT) ls = lds2f(sb + SM_LX + g8);
                    if (q == 2) { pa = lds4(sb + SM_PA + wg * 2048 + g16); wl = lds1(tabw + g16); }
                    if (q == 2) { a12 = lds2f(tabw + 2048 + g16); d0 = arena + (acc_slot(s + 1) + __float_as_uint(a12.x)); d1 = arena + (acc_slot(s + 1) + __float_as_uint(a12.y)); }
#pragma unroll
                    for (int f = 4 * q; f < 4 * q + 4; f++) {
                        const uint32_t* a = wf[f % NPF];
                        if (f < 4) mma16816z(c[f], a, ob[f & 2], ob[(f & 2) + 1]);
                        else mma16816(c[f & 3], a[0], a[1], a[2], a[3], ob[f & 2], ob[(f & 2) + 1]);
                        if (f + NPF < 16) ldsm4t(wf[f % NPF], WF(f + NPF));
                    }
                }
                if (wg == 0) bar_arrive(NB_WIN, 384);
                const float i0 = rcp_fast(ls.x), i1 = rcp_fast(ls.y);
                uint32_t v[4];
#pragma unroll
                for (int m = 0; m < 4; m++) v[m] = pack_h2((c[m >> 1][(m & 1) * 2] + c[(m >> 1) + 2][(m & 1) * 2]) * i0, (c[m >> 1][(m & 1) * 2 + 1] + c[(m >> 1) + 2][(m & 1) * 2 + 1]) * i1);
                red_h10(LAST, d0, d1, v[0], v[1], v[2], prmt(v[3], ACC_ONE, LAST ? 0x7610 : 0x3210), prmt(v[3], ACC_ONE, 0x7632));
                g16 |= v[0] & zero;
                PROF(6)
            }
        }
        if (wg) bar_sync(NB_WIN, 384);
    } else {
        TLC(0)
        auto request = [&](int s, uint32_t o) {
            cp_async16(sb + SM_PA + 4096 + g16, arena + (((s & 1) ^ 1) * 32768 + po + o));
            const uint8_t* ts = arena + ((s & 1) * 32768 + o);
#pragma unroll
            for (int i = 0; i < 4; i++) cp_async16(sb + SM_VF + i * 2048 + g16, ts + (i >> 1) * 16384 + (i & 1) * 2048);
        };
        auto fetch = [&](int s, uint4 t1, auto wait, auto after) {
            const uint32_t mo = acc_slot(s) + t1.x, eo = mo - (g16 & 0x1f0) + 512 + ((g16 >> 5) & 12);
            const uint8_t *ms = arena + mo, *es = arena + eo;
            uint32_t e[4] = {0, 0, 0, 0}, sel = LAST ? 0x5410 : 0x3210, dst[4];
#pragma unroll
            for (int i = 0; i < 4; i++) dst[i] = (t1.w + (s & 1) * HBUF) ^ (i * 32);
            asm volatile("" : "+l"(ms), "+l"(es), "+r"(e[0]), "+r"(e[1]), "+r"(e[2]), "+r"(e[3]), "+r"(sel), "+r"(dst[0]), "+r"(dst[1]), "+r"(dst[2]), "+r"(dst[3]));
            uint32_t late = wait(), fz;
            PROF(11) PROFV(0, gtime32())
            int it = 0;
            bool bad;
#pragma unroll 1
            do {
                uint4 m[4];
                uint32_t b = 0;
#pragma unroll
                for (int i = 0; i < 4; i++) {
                    m[i] = ldg_rlx4(ms + i * 1024);
                    ldg1_if(e[i], es + i * 1024, LAST);
                }
                if (it == 0) bar_arrive(NB_F, 256);
                const uint32_t now = clk32();
                fz = now;
                after(now & zero);
                sts1(sb + SM_LX + 1040, now - min(late >> 8, 8u) * 57);
                late = 0;
                spin_guard(++it);
#pragma unroll
                for (int i = 0; i < 4; i++) {
                    if (STG_FENCE >> i & 1) fz |= clk32();
                    b |= xor_or(m[i].w, e[i], ACC_ALL);
                    stsm4t(dst[i], h2bf(m[i].x), h2bf(m[i].y), h2bf(m[i].z), h2bf(prmt(m[i].w, e[i], sel)));
                }
                bad = __any_sync(~0u, LAST && b > 0xffffu);
            } while (bad);
            bar_arrive(NB_MEM, 384);
            bar_arrive(NB_MEM2, 256);
            g16 |= fz & zero;
            PROFV(12, it - 1) PROF(1)
        };
        TX(6)
        fetch(0, lds4(tabw + 2048 + g16), []() { return 0u; }, [&](uint32_t z) { request(0, lds1(tabw + 4096 + (g16 >> 1)) + z); });
        wo_load(2);
        TX(7)
#pragma unroll 1
        for (int s = 0;; s++) {
            const uint32_t tag = (s & 1) ^ 1, ttag = ((s >> 1) & 1) ^ 1, l16 = sb + (g16 & 0x1f0), g8 = g16 >> 1;
            const int p = s + 2;
            if (s == 1) TL(7)
            if (s == 0) TL(13)
            fence_async_smem();
            stg_b128_if(g16 < ((role & 3) ? 128 : 160), arena + (acc_slot(s + 3) + lds1(tabw + 2052 + g16)), 0, 0, 0, 0);
            const uint4 pa = pa_get(p);
            if (p <= NSEG) mbar_wait_w(bars + 8 * (B_HB + (p & 1)), (p >> 1) & 1);
            asm volatile("fence.proxy.async.global;" ::: "memory");
            if (warp0 && s + 3 <= NSEG) e_expect(bars + 8 * (B_HB + ((s + 3) & 1)), 32768);
            uint8_t* xd = arena + lds1(tabw + 4 + g16);
            uint32_t tx;
            float acc[20];
            pass_init(acc, 20, pa);
            if (s == 0) TX(10)
            bar_sync(NB_QK, 384);
            pass_run(IC<1>(), p, acc, nop);
            pass_out(IC<2>(), p, acc, [&](int i) {
                if (i) return;
                wg_wait<0>();
                const uint32_t r0 = pack2(acc[16], acc[17]);
                stg_rlx2(xd, settag(r0, tag), pack2(acc[18], acc[19]));
                tx = clk_after(r0, zero) + 100;
                PROF(2)
            });
            uint4 (&vf)[2][2] = tf;
#pragma unroll
            for (int i = 0; i < 4; i++) vf[i >> 1][i & 1] = lds4(sb + SM_VF + i * 2048 + g16);
            uint32_t xv[4] = {0, 0, 0, 0};
            float oc[2][4], lc[4];
            auto pv = [&](uint32_t p0, uint32_t p1, uint32_t p2, uint32_t p3, uint32_t p4, auto mid) {
                lc[0] = lc[1] = lc[2] = lc[3] = 0.f;
                mma16816z(oc[0], &vf[0][0].x, p0, p1);
                mma16816z(oc[1], &vf[1][0].x, p0, p1);
                mma16816(lc, ONES, ONES, ONES, ONES, p0, p1);
                mma16816(oc[0], vf[0][1].x, vf[0][1].y, vf[0][1].z, vf[0][1].w, p2, p3);
                mma16816(oc[1], vf[1][1].x, vf[1][1].y, vf[1][1].z, vf[1][1].w, p2, p3);
                mma16816(lc, ONES, ONES, ONES, ONES, p2, p3);
                mid();
                mma1688(oc[0], xv[0], xv[1], p4);
                mma1688(oc[1], xv[2], xv[3], p4);
                mma1688(lc, ONES, ONES, p4);
            };
            uint32_t so, to, fz = 0;
            uint4 t1;
            int it = 0;
            bool bad;
#pragma unroll 1
            do {
#pragma unroll 1
                for (int i = it; i > 0; i &= zero) load_tok(s, lds1(tabw + 4096 + g8));
                u64 xr[4];
                const uint8_t* xp = arena + lds1(tabw + 8 + g16);
                asm volatile("" : "+l"(xp));
                const uint32_t bt = or3(xor_or(vf[0][0].x, vf[0][1].x, ttag), xor_or(vf[1][0].x, vf[1][1].x, ttag), 0);
                uint32_t sa = sb + SM_SX + (g16 & 0x1f0) * 5;
                asm volatile("" : "+r"(sa));
                spin_guard(it);
                wait_clk(tx);
                PROF(3)
                if (s == 0 && it == 0) TX(11)
                if (it++ == 0) bar_sync(NB_X1, 256);
                uint4 sx[5];
#pragma unroll
                for (int i = 0; i < 5; i++) sx[i] = lds4(sa + i * 16);
                __syncwarp();
#pragma unroll
                for (int i = 0; i < 4; i++) xr[i] = ldg_u64(xp + (VP_AT == 2 ? sx[0].x & zero : 0) + i * 1024);
                uint32_t a[5], pm[5];
#pragma unroll
                for (int n = 0; n < 5; n++) {
                    uint32_t u[4];
#pragma unroll
                    for (int w = 0; w < 4; w++) u[w] = n < 4 ? (&sx[w].x)[n] : (&sx[4].x)[w];
                    a[n] = hadd2h(hadd2h(u[0], u[1]), hadd2h(u[2], u[3]));
                }
                uint32_t m = hmax2h(hmax2h(hmax2h(a[0], a[1]), hmax2h(a[2], a[3])), a[4]);
                const uint32_t m1 = __shfl_xor_sync(~0u, m, 1), m2 = __shfl_xor_sync(~0u, m, 2), m3 = __shfl_xor_sync(~0u, m, 3);
                m = hmax2h(hmax2h(m, m1), hmax2h(m2, m3));
                so = lds1(tabw + g16); t1 = lds4(tabw + 2048 + g16); to = lds1(tabw + 4096 + g8);
                const float2 mm = unpack_h2(m);
                const float mf = -SM_L2E * fmaxf(mm.x, mm.y);
#pragma unroll
                for (int n = 0; n < 5; n++) { const float2 u = unpack_h2(a[n]); pm[n] = pack2(ex2(fmaf(u.x, SM_L2E, mf)), ex2(fmaf(u.y, SM_L2E, mf))); }
                PROF(4)
                pv(pm[0], pm[1], pm[2], pm[3], pm[4], [&]() {
                    if (PV_FENCE & 1) fz = clk32();
#pragma unroll
                    for (int i = 0; i < 2; i++) { xv[2 * i] = hadd2v(lo32(xr[2 * i]), lo32(xr[2 * i + 1])); xv[2 * i + 1] = hadd2v(hi32(xr[2 * i]), hi32(xr[2 * i + 1])); }
                });
                bad = any_bit0(or3(bt, xor_or(lo32(xr[0]), lo32(xr[1]), tag), xor_or(lo32(xr[2]), lo32(xr[3]), tag)));
                if (PV_FENCE & 2) fz |= clk32();
                stsm4(sb + SM_OX + g16, pack2(oc[0][0], oc[0][1]), pack2(oc[0][2], oc[0][3]), pack2(oc[1][0], oc[1][1]), pack2(oc[1][2], oc[1][3]));
                sts2(sb + SM_LX + g8, lc[0], lc[1]);
            } while (bad);
            if (s == 0) TX(12)
            PROFV(14, it - 1)
            PROF(5)
            bar_sync(NB_X2, 384);
            const uint8_t* sp = arena + so;
            uint4 sv = ldg_rlx4(sp);
            if (s == 0) TX(13)
            if (s + 3 <= NSEG) h_load(sb, hsrc, s + 3, j, head, wiu, false);
            const uint4 pp = lds4(l16 + SM_PX + delay<TPV_DLY>(zero));
            pv(pp.x, pp.y, pp.z, pp.w, lds1(sb + SM_PX + 512 + ((g16 >> 2) & 0x7c)), []() {});
            const float i0 = rcp_fast(lc[0]), i1 = rcp_fast(lc[1]);
            bar_arrive(NB_WIN + ((__float_as_uint(i0) | fz) & zero), 384);
            uint8_t* od = (uint8_t*)g_O + ((size_t)s * (32 * NH * DH * 2) + t1.z);
            const uint32_t ov[4] = {pack2(oc[0][0] * i0, oc[0][1] * i1), pack2(oc[0][2] * i0, oc[0][3] * i1), pack2(oc[1][0] * i0, oc[1][1] * i1), pack2(oc[1][2] * i0, oc[1][3] * i1)};
#pragma unroll
            for (int a = 0; a < 4; a++) if (s + 1 == NSEG) stg_rlx1(od + a * 128, ov[a]);
            PROF(6)
            if (s + 1 == NSEG) break;
            fetch(s + 1, t1, [&]() {
                int it = 0;
#pragma unroll 1
                while (__any_sync(~0u, (int)(min(__vimin3_u32(sv.x, sv.y, sv.z), sv.w) >> 24) <= s)) {
                    sv = ldg_rlx4(sp);
                    spin_guard(++it);
                }
                if (s == 0) TX(14)
                PROFV(15, it)
                const uint32_t tgo = (__reduce_max_sync(~0u, max(max3u(sv.x, sv.y, sv.z), sv.w)) + tm.go + (sv.x & zero)) << 8;
                PROF(7)
                int late;
#pragma unroll 1
                do { late = gtime32() * 8 - tgo; } while (late < 0);
                __syncwarp();
                return (uint32_t)late;
            }, [&](uint32_t z) {
#pragma unroll
                for (int a = 0; a < 4; a++) stg_rlx1(od + a * 128, ov[a]);
                request(s + 1, to + z);
            });
        }
        TL(8) TLC(1)
    }
    asm volatile("cp.async.wait_all;" ::: "memory");
    PROF_OUT
}

struct RecMaps { CUtensorMap wq, wk, wv, wo; };
struct RecPtrs { const bf16 *x, *mem0, *c, *wmod, *w1, *w3; uint8_t* arena; uint32_t zero; RecTime tm; };

__device__ __forceinline__ float silu_bf(const bf16* c, int i) {
    const float v = __bfloat162float(c[i]);
    return bfround(__fdividef(v, 1.0f + __expf(-v)));
}
__device__ __noinline__ void rec_ln(float* coef, const RecPtrs& p, int id, int r0) {
    int r1 = 32;
    const int tid = threadIdx.x;
    const int lane = tid & 31, wid = tid >> 5;
    const uint32_t ring = smem_u32(coef) - SM_PRE + wid * 8192 + lane * 16;
    auto fetch = [&](int r) {
        if (r < r1) {
            const bf16* src = p.x + (size_t)(r * 64 + (id * 8 + wid) * 2) * DM + lane * 8;
#pragma unroll
            for (int i = 0; i < 8; i++) cp_async16(ring + (r & 1) * 4096 + i * 512, src + i * 256);
        }
        asm volatile("cp.async.commit_group;" ::: "memory");
    };
    auto row8 = [&](uint32_t a, float* f) {
        const uint4 v = lds4(a);
        f[0] = bflo(v.x); f[1] = bfhi(v.x); f[2] = bflo(v.y); f[3] = bfhi(v.y); f[4] = bflo(v.z); f[5] = bfhi(v.z); f[6] = bflo(v.w); f[7] = bfhi(v.w);
    };
#pragma unroll 1
    for (int r = r0 - 2; r < r1; r++) {
        if (r >= r0) {
            asm volatile("cp.async.wait_group 1;" ::: "memory");
            const uint32_t a = ring + (r & 1) * 4096;
            float m[2] = {0.f, 0.f}, t[2];
#pragma unroll 1
            for (int ps = 0; ps < 2; ps++) {
                t[0] = t[1] = 0.f;
#pragma unroll 1
                for (int i = 0; i < 4; i++)
#pragma unroll
                    for (int h = 0; h < 2; h++) {
                        float f[8];
                        row8(a + h * 2048 + i * 512, f);
#pragma unroll
                        for (int e = 0; e < 8; e++) { const float d = f[e] - m[h]; t[h] = fmaf(d, ps ? d : 1.0f, t[h]); }
                    }
#pragma unroll
                for (int o = 16; o; o >>= 1) { t[0] += __shfl_xor_sync(~0u, t[0], o); t[1] += __shfl_xor_sync(~0u, t[1], o); }
                if (ps == 0) { m[0] = t[0] * (1.0f / DM); m[1] = t[1] * (1.0f / DM); }
            }
            t[0] = rsqrtf(t[0] * (1.0f / DM) + 1e-5f); t[1] = rsqrtf(t[1] * (1.0f / DM) + 1e-5f);
            if (r == r0) {
#pragma unroll 1
                for (int i = tid; i < 2 * DM / 4; i += 256) {
                    float4 u;
                    int it = 0;
                    uint32_t ok;
#pragma unroll 1
                    do {
                        uint4 v[8];
#pragma unroll
                        for (int k = 0; k < 8; k++) v[k] = ldg_rlx4(g_modp + k * 2 * DM + i * 4);
                        ok = 1;
                        u = make_float4(0.f, 0.f, 0.f, 0.f);
#pragma unroll
                        for (int k = 0; k < 8; k++) {
                            ok &= v[k].x & v[k].y & v[k].z & v[k].w;
                            u.x += __uint_as_float(v[k].x); u.y += __uint_as_float(v[k].y); u.z += __uint_as_float(v[k].z); u.w += __uint_as_float(v[k].w);
                        }
                        spin_guard(++it);
                    } while (!ok);
                    const uint32_t lo = pack2(u.x, u.y), hi = pack2(u.z, u.w);
                    const float one = i >= DM / 4 ? 1.0f : 0.0f;
                    *(float4*)(coef + i * 4) = make_float4(bflo(lo) + one, bfhi(lo) + one, bflo(hi) + one, bfhi(hi) + one);
                }
                bar_sync(NB_FIN0, 256);
                if (tid == 0 && r0 == 0) TL(2)
            }
            const int row = r * 64 + (id * 8 + wid) * 2;
#pragma unroll 1
            for (int i = 0; i < 4; i++) {
                const float4* cf = (const float4*)(coef + i * 256 + lane * 8);
                const float4 s0 = cf[0], s1 = cf[1], c0 = cf[256], c1 = cf[257];
                const float sh[8] = {s0.x, s0.y, s0.z, s0.w, s1.x, s1.y, s1.z, s1.w}, sc[8] = {c0.x, c0.y, c0.z, c0.w, c1.x, c1.y, c1.z, c1.w};
                const int own = ((row >> 4) & 1) == (i >> 1), rr = row & 15;
                const uint32_t off = ((row >> 5) + own) * 65536 + (i * 4 + (lane >> 3)) * 4096 + (rr + (own ? 0 : 16)) * 128 + (((lane & 7) ^ (rr & 7)) << 4);
#pragma unroll
                for (int h = 0; h < 2; h++) {
                    float y[8];
                    row8(a + h * 2048 + i * 512, y);
#pragma unroll
                    for (int e = 0; e < 8; e++) y[e] = fmaf((y[e] - m[h]) * t[h], sc[e], sh[e]);
                    *(uint4*)((uint8_t*)g_himg + (off ^ (h * 144))) = pack8(y);
                }
            }
            if (r == 0) {
                int v, it = 0;
#pragma unroll 1
                do { v = *(volatile int*)((uint8_t*)coef - SM_PRE + SM_BAR + 192); spin_guard(++it); } while (v == INT_MIN);
                if (v >= 0) r1 = 2;
            }
        }
        fetch(r + 2);
        if (r < r0 || (r > 0 && !(r & 1))) continue;
        bar_sync(r == 0 ? NB_C : r == 1 ? NB_FIN0 : NB_LN, r == 0 ? 320 : r == 1 ? 256 : 288);
        if (r < 2 && wid == r) {
            if (r == 1) bar_arrive(NB_B, 64);
            if (lane == 0) { signal_count(&g_tick[32 + id * 8]); TL(13) }
            __syncwarp();
        }
    }
}
template <int NQ, int CG>
__device__ __forceinline__ void side_gemv(const bf16* w, int ld, int ncol, const float* coef, float* red, float* out, int ostride, bool round) {
    constexpr int KG = 384 / CG, W = CG * 8;
    const int tid = threadIdx.x, cg = tid % CG, kg = tid / CG;
    float acc[NQ][8];
#pragma unroll
    for (int q = 0; q < NQ; q++)
#pragma unroll
        for (int j = 0; j < 8; j++) acc[q][j] = 0.f;
    if (cg * 8 < ncol) {
        const bf16* src = w + cg * 8;
        const uint32_t ring = smem_u32(red) + 36864 + tid * 16;
        auto fetch = [&](int k0, int slot) {
#pragma unroll
            for (int i = 0; i < 4; i++)
                if (k0 + i * KG < DM) cp_async16_ef(ring + (slot * 4 + i) * 6144, src + (size_t)(k0 + i * KG) * ld);
            asm volatile("cp.async.commit_group;" ::: "memory");
        };
#pragma unroll 1
        for (int g = 0; g < 5; g++) fetch(kg + g * 4 * KG, g);
#pragma unroll 1
        for (int k0 = kg, slot = 0; k0 < DM; k0 += 4 * KG) {
            fetch(k0 + 20 * KG, slot ? slot - 1 : 5);
            asm volatile("cp.async.wait_group 5;" ::: "memory");
#pragma unroll
            for (int i = 0; i < 4; i++) {
                const int k = k0 + i * KG;
                if (k < DM) {
                    const uint4 v = lds4(ring + (slot * 4 + i) * 6144);
                    const float f[8] = {bflo(v.x), bfhi(v.x), bflo(v.y), bfhi(v.y), bflo(v.z), bfhi(v.z), bflo(v.w), bfhi(v.w)};
#pragma unroll
                    for (int q = 0; q < NQ; q++) {
                        const float cf = coef[q * DM + k];
#pragma unroll
                        for (int j = 0; j < 8; j++) acc[q][j] = fmaf(cf, f[j], acc[q][j]);
                    }
                }
            }
            slot = slot == 5 ? 0 : slot + 1;
        }
    }
    __syncthreads();
#pragma unroll
    for (int q = 0; q < NQ; q++)
#pragma unroll
        for (int j = 0; j < 8; j++) red[(kg * NQ + q) * W + cg * 8 + j] = acc[q][j];
    __syncthreads();
#pragma unroll 1
    for (int i = tid; i < NQ * W; i += 384) {
        const int q = i / W, cidx = i % W;
        float t = 0.f;
#pragma unroll
        for (int k = 0; k < KG; k++) t += red[k * NQ * W + i];
        if (cidx < ncol) out[q * ostride + cidx] = round ? bfround(t) : t;
    }
}
__device__ __noinline__ void rec_side(float* sm, const RecPtrs& p, int id) {
    const int tid = threadIdx.x;
    float *coef = sm, *red = sm + 3 * DM;
    if (tid < 256 && blockIdx.x < 128) rec_ln(sm + SM_PRE / 4, p, id, 2);
    if (tid >> 5 == 8) {
#pragma unroll 1
        for (int n = 1; n < 16; n++) {
            bar_sync(NB_LN, 288);
            if (tid == 256) { if (n == 1) wait_count1(&g_tick[32 + id * 8], 2); signal_count(&g_tick[32 + id * 8]); }
            __syncwarp();
        }
    }
    __syncthreads();
    for (int i = tid; i < 2 * S_; i += 384) g_st[id * 2 * S_ + i] = 0.f;
    if (id == 0) for (int i = tid; i < 2 * 32; i += 384) g_pcnt[i * 8] = 0;
    if (id == 1) for (int i = tid; i < 6 * 256; i += 384) g_pflag[i] = 0;
    for (int i = tid; i < DM; i += 384) { coef[i] = silu_bf(p.c, i); coef[2 * DM + i] = 1.0f; }
    __syncthreads();
    if (tid == 0) TL(3)
    side_gemv<1, 128>(p.wmod + (2 + id) * DM, 6 * DM, DM, coef, red, g_mod + (2 + id) * DM, 0, true);
    __syncthreads();
    if (tid == 0) signal_count(&g_tick[8]);
    if (tid == 0) TL(4)
    side_gemv<1, 128>(p.w3 + id * (FF / 4), FF, FF / 4, coef + 2 * DM, red, g_vec + 3 * DM + id * (FF / 4), 0, false);
    if (tid == 0) wait_count1(&g_tick[8], 4);
    __syncthreads();
    for (int i = tid; i < DM; i += 384) { coef[i] = 1.0f + __ldcg(g_mod + 4 * DM + i); coef[DM + i] = __ldcg(g_mod + 3 * DM + i); }
    __syncthreads();
    if (id == 1 && tid < 32) {
        float t[5] = {0, 0, 0, 0, 0};
        for (int i = tid; i < DM; i += 32) {
            const float a = coef[i], b = coef[DM + i];
            t[0] += a; t[1] += a * a; t[2] += a * b; t[3] += b; t[4] += b * b;
        }
#pragma unroll
        for (int q = 0; q < 5; q++) { const float r = warp_sum(t[q]); if (tid == 0) g_cst[q] = r * (1.0f / DM); }
    }
    side_gemv<3, 32>(p.w1 + id * 256, DM, 256, coef, red, g_vec + id * 256, DM, false);
    if (tid == 0) TL(9)
}

__device__ __forceinline__ void pair_place(int c, int& d, int& pi) {
    const int c7 = ((c - 36) * 37) >> 8, d0 = c < 4 ? 0 : c < 36 ? (c - 4) & 7 : c - 35 - 7 * c7;
    pi = c < 4 ? c : c < 36 ? ((c - 4) >> 3) + (d0 ? 0 : 4) : 4 + c7;
    d = (0x73216540 >> (4 * d0)) & 7;
}
__global__ void __cluster_dims__(2, 1, 1) __launch_bounds__(384, 1)
k_rec(const __grid_constant__ RecMaps mp, const __grid_constant__ RecPtrs p) {
    extern __shared__ uint8_t smraw[];
    const uint32_t sb = smem_u32(smraw);
    if ((sb & 0x3FFFF) != SB0) __trap();
    const uint32_t bars = sb + SM_BAR;
    const int tid = threadIdx.x, lane = tid & 31, b = blockIdx.x;
    const int wid = __reduce_max_sync(~0u, tid >> 5);
    const uint32_t rank = b & 1;
    uint8_t* arena = p.arena;
    volatile int* sinfo = (volatile int*)(smraw + SM_BAR + 192);
    if (tid == 0) TL(0)
    if (tid == 0) sinfo[0] = INT_MIN;
    uint32_t smid;
    asm("mov.u32 %0, %%smid;" : "=r"(smid));
    smid = __reduce_max_sync(~0u, smid);
    int d, pi;
    pair_place(smid >= 124 ? (smid >> 1) - 62 : (smid >> 1) + 4, d, pi);
    const int guess = b < 128 && smid < 132 && (smid & ~3u) != 120 && (NO_GUESS == 0 || (NO_GUESS == 2 && b != 20)) ? (KMAP ? d * 8 + pi : (d >> 1) * 16 + pi * 2 + (d & 1)) : -9;
    if (wid == 8) {
        if (lane == 0) {
#pragma unroll
            for (int i = 0; i < 17; i++) mbar_init(bars + 8 * i, i == B_WO ? 4 : 1);
            asm volatile("fence.mbarrier_init.release.cluster; fence.proxy.async.shared::cta;" ::: "memory");
            mbar_expect(bars + 8 * B_ROLE, 8);
        }
        __syncwarp();
    }
    asm volatile("barrier.cluster.arrive.relaxed.aligned;" ::: "memory");
    int pr = 0, hA = 0;
    if (wid < 8) {
        if (b < 128) {
            const int cb = (b & 15) * 128, k0 = (b >> 4) * 128 + (tid >> 4);
            uint4 v[8];
#pragma unroll
            for (int i = 0; i < 8; i++) v[i] = __ldg((const uint4*)(p.wmod + (size_t)(k0 + 16 * i) * (6 * DM) + cb + (tid & 15) * 8));
            float acc[8] = {0, 0, 0, 0, 0, 0, 0, 0};
            const float sl = silu_bf(p.c, k0 + 16 * (lane & 7));
#pragma unroll
            for (int i = 0; i < 8; i++) {
                const float sv = __shfl_sync(~0u, sl, i, 16);
                acc[0] += sv * bflo(v[i].x); acc[1] += sv * bfhi(v[i].x); acc[2] += sv * bflo(v[i].y); acc[3] += sv * bfhi(v[i].y);
                acc[4] += sv * bflo(v[i].z); acc[5] += sv * bfhi(v[i].z); acc[6] += sv * bflo(v[i].w); acc[7] += sv * bfhi(v[i].w);
            }
            float* red = (float*)(smraw + SM_PRE);
            *(float4*)(red + (tid >> 4) * 128 + (tid & 15) * 8) = make_float4(acc[0], acc[1], acc[2], acc[3]);
            *(float4*)(red + (tid >> 4) * 128 + (tid & 15) * 8 + 4) = make_float4(acc[4], acc[5], acc[6], acc[7]);
            bar_sync(NB_FIN0, 256);
            if (wid < 4) {
                float t = 0;
#pragma unroll
                for (int i = 0; i < 16; i++) t += red[i * 128 + tid];
                stg_rlx1(&g_modp[(b >> 4) * 2 * DM + cb + tid], __float_as_uint(t) | 1u);
                if (rank) TL(2)
            }
        } else {
            rec_ln((float*)(smraw + SM_PRE), p, b - 128, 0);
        }
    } else if (wid >= 10 && b >= 128) {
        {
            const int u = (b - 128) * 2 + wid - 10;
            const uint16_t* src = (const uint16_t*)p.mem0 + (lane & 3) * 2 * DM + (u >> 1) * 128 + (u & 1) * 32 + (lane >> 2);
            stg_rlx4(arena + (LB_STAMP << 13) + u * 2048 + (lane >> 4) * 1024 + ((lane >> 3) & 1) * 256 + (lane & 7) * 16, 0, 0, 0, 0);
#pragma unroll 1
            for (int r = 0; r < 4; r++) {
                uint32_t w[5];
#pragma unroll
                for (int e = 0; e < 4; e++) {
                    const uint16_t* q = src + (r >> 1) * 512 + (r & 1) * 16 + (e & 2) * 32 + (e & 1) * 8;
                    w[e] = pack_h2(bflo(q[0]), bflo(q[DM]));
                }
                w[4] = __shfl_sync(~0u, __byte_perm(w[3], ACC_ALL, 0x7632), lane * 8 + 7);
                w[3] = __byte_perm(w[3], ACC_ALL, (lane & 7) == 7 ? 0x7610 : 0x3210);
#pragma unroll 1
                for (int i = 0; i < 3; i++) {
                    uint8_t* d = arena + acc_slot(i) + acc_piece(r >> 1, u >> 1, (u & 1) * 2 + (r & 1));
                    stg_rlx4(d + lane * 16, w[0], w[1], w[2], w[3]);
                    if (lane < 8) stg_rlx1(d + 512 + lane * 4, w[4]);
                    w[0] = w[1] = w[2] = w[3] = w[4] = 0;
                }
            }
            bar_arrive(NB_C, 320);
        }
    } else if (rank == 0 && (wid > 8 || b >= 128)) {
        uint32_t best = ~0u;
        const int pg = wid < 11 ? 0 : 1 + (b >> 1) % 3;
        uint32_t* q = (uint32_t*)(arena + (pg << 21) + (pg ? blk(b >> 1, 1) : blk(LB_PROBE, wid & 1) + b * 16));
        if (lane < 8) stg_rlx1(q + lane, 0);
        u64 tk2 = ldg_u64(&g_tick[0]);
        __syncwarp();
        if (lane == 0) {
            q += 3;
            uint32_t v = atomicAdd(q, 1u);
#pragma unroll 1
            for (int r = 0; r < NPROBE; r++) {
                const uint32_t t0 = clk32() + (v >> 8);
                v = atomicAdd(q + (v >> 8), 1u);
                uint32_t t1;
                asm volatile("{.reg .pred p; setp.eq.u32 p, %1, 0xffffffff; @p exit; mov.u32 %0, %%clock;}" : "=r"(t1) : "r"(v) : "memory");
                best = min(best, t1 - t0);
            }
            sinfo[pg ? 4 : 2 + (wid & 1)] = best;
        }
        bar_sync(NB_KDONE, b < 128 ? 96 : 64);
        if (wid == 9) {
            const int par = sinfo[2] > sinfo[3], ncl = gridDim.x >> 1;
            u64 add = (1u << (8 * par)) + 65536;
            if (b < 128) add += ((u64)((2 * sinfo[4] < sinfo[2] + sinfo[3]) != par) << (32 + 8 * ((b >> 1) % 3))) + (guess < 0 || (smid & 1) ? 1ull << 56 : (par ^ (guess >> 5)) << 24);
            int tk = 0, it = 0;
            if (b >= 128) {
#pragma unroll 1
                while (!__all_sync(~0u, (int)((lo32(tk2) >> 16) & 255) >= ncl - 2)) { tk2 = ldg_u64(&g_tick[0]); spin_guard(++it); }
            }
            if (lane == 0) tk = (atomicAdd((u64*)&g_tick[0], add) >> (8 * par)) & 255;
#pragma unroll 1
            while (!__all_sync(~0u, (int)((lo32(tk2) >> 16) & 255) >= ncl)) { tk2 = ldg_u64(&g_tick[0]); spin_guard(++it); }
            tk = __shfl_sync(~0u, tk, 0);
            const int n0 = tk2 & 255, n1 = (tk2 >> 8) & 255, other = lo32(tk2) >> 24;
            hA = min(n0 >> 1, NH);
            const int q0 = 2 * hA, q1 = 2 * NH - q0;
            const int over = tk - (par ? q1 : q0), lack = max(par ? q0 - n0 : q1 - n1, 0);
            if (over < 0) pr = par ? q0 + tk : tk;
            else if (over < lack) pr = (par ? n0 : q0 + n1) + over;
            else pr = -1 - (over - lack + (par ? max(n0 - q0, 0) : 0));
            if (!(tk2 >> 56) && !(other & 63)) { pr = guess; hA = NH / 2 + other * 32; }
#pragma unroll
            for (int i = 0; i < 3; i++) hA |= ((hi32(tk2) >> (8 * i)) & 255) > 10 ? 256 << i : 0;
        }
    }
    asm volatile("barrier.cluster.wait.aligned;" ::: "memory");
    if (wid == 9 && rank == 0) {
        asm volatile("{.reg .pred p; .reg .b32 a; setp.lt.u32 p, %3, 2; @p mapa.shared::cluster.u32 a, %0, %3;\n"
                     " @p st.async.shared::cluster.mbarrier::complete_tx::bytes.v2.u32 [a + 192], {%1, %2}, [a + %4];}"
                     ::"r"(bars), "r"(pr), "r"(hA), "r"(lane), "n"(8 * B_ROLE) : "memory");
        if (b >= 128) atomicOr(&g_tick[4], (pr < 0 ? 4u : 1u) << ((b - 128) >> 1));
    }
    if (wid == 8) {
        int pu = guess;
        bool fast = false, known = false;
#pragma unroll 1
        for (int n = 0; n < 12; n++) {
            if (!known && (n == W_SPEC || pu < 0)) {
                mbar_wait_w(bars + 8 * B_ROLE, 0);
                TL(1)
                known = true;
                const int r = __reduce_max_sync(~0u, sinfo[0]);
                if (r != pu) {
#pragma unroll 1
                    for (; n > 0; n--) {
                        mbar_wait_w(bars + 8 * (B_W + n - 1), 0);
                        asm volatile("{.reg .pred p; elect.sync _|p, 0xffffffff; @p mbarrier.arrive.shared.b64 _, [%0];}" ::"r"(bars + 8 * (B_W + n - 1)) : "memory");
                    }
                    pu = r;
                }
                bar_arrive(NB_A, 384);
                if (b >= 128 && pu < 0) bar_sync(NB_B, 64);
                if (pu < 0) break;
            }
            const int rot = b >= 128 ? 8 : 0, i = (n + rot) % 12;
            if (rot && n == 4) bar_sync(NB_B, 64);
            if (n >= W_INFL && !fast) {
                const uint32_t v = ldg_rlx1(&g_tick[32 + (lane & 3) * 8]);
                mbar_wait_w(bars + 8 * (B_W + (n - W_INFL + rot) % 12), 0);
                fast = __all_sync(~0u, v != 0);
            }
            const int m = i < 8 ? i & 1 : 2, k = i < 8 ? i >> 1 : i - 8, c0 = (pu >> 1) * 128 + rank * 64, r0 = (pu & 1) * 512;
            const uint32_t dst = sb + m * 65536 + k * 16384, br = bars + 8 * (B_W + i);
            e_expect(br, 16384);
            e_tma2d(dst, &mp.wq + m, c0, r0 + k * 128, br, evict_first());
            e_tma2d(dst + 8192, &mp.wq + m, c0, r0 + k * 128 + 64, br, evict_first());
        }
    } else {
        bar_sync(NB_A, 384);
    }
    const int prr = __reduce_max_sync(~0u, sinfo[0]);
    hA = __reduce_max_sync(~0u, sinfo[1]);
    if (prr < 0) {
        int j = (b - 128) >> 1;
        if (b < 128) {
            uint32_t v;
            int it = 0;
#pragma unroll 1
            do { v = __reduce_max_sync(~0u, ldg_rlx1(&g_tick[4])); spin_guard(++it); } while (__popc(v) < 2);
            j = v == 3 ? -1 - prr : (v & 1) ^ 1;
        }
        rec_side((float*)smraw, p, j * 2 + rank);
        return;
    }
    const int role = (prr >> 1) * 4 + rank * 2 + (prr & 1);
    rec_main(sb, &mp.wo, arena, role, hA, wid >> 2, p.zero, p.tm);
}

__device__ __forceinline__ void wgmma_ss192(float* d, uint64_t a, uint64_t b, int sc) {
    asm volatile("{.reg .pred p; setp.ne.b32 p, %98, 0;\n wgmma.mma_async.sync.aligned.m64n192k16.f32.bf16.bf16 "
                 "{%0,%1,%2,%3,%4,%5,%6,%7,%8,%9,%10,%11,%12,%13,%14,%15,%16,%17,%18,%19,%20,%21,%22,%23,%24,%25,%26,%27,%28,%29,%30,%31,%32,%33,%34,%35,%36,%37,%38,%39,%40,%41,%42,%43,%44,%45,%46,%47,%48,%49,%50,%51,%52,%53,%54,%55,%56,%57,%58,%59,%60,%61,%62,%63,%64,%65,%66,%67,%68,%69,%70,%71,%72,%73,%74,%75,%76,%77,%78,%79,%80,%81,%82,%83,%84,%85,%86,%87,%88,%89,%90,%91,%92,%93,%94,%95}, %96, %97, p, 1, 1, 0, 1;}"
                 : F16(d, 0), F16(d, 16), F16(d, 32), F16(d, 48), F16(d, 64), F16(d, 80) : "l"(a), "l"(b), "r"(sc));
}

constexpr uint32_t P_B = 81920, P_PLANE = 40960, P_VEC = 212992, P_ROW = P_VEC + 6144, P_BAR = P_ROW + 4096, P_SMEM = P_BAR + 256;
constexpr uint32_t P_OUT = 180224, P_OUT3 = P_B + 2 * P_PLANE;
#define PPH 1
#define FLAG_ST "st.release.gpu.global.u32"
#define FLAG_LD "ld.acquire.gpu.global.u32"
#define EFA 0x1e7
#define EFB 0x1ff
#define ALIAS 0
#define E0 3
#define SL_B0 0x5555
#define SL_B1 0xaaaa
#define SL_C 0x2492490
#define SL_A0 0x7777
#define SL_A1 0x77dd
#define HFENCE 2
#define X_DLY 4000
#define MAP 1
#define ROT 0x00e
#define OWN 1
constexpr int P_ST = 5, P_ST0 = 4;
constexpr int PB_F = 0, PB_E = 5, PB_X = 10, PB_OUT = 12;
enum { C_Y = 0, C_G = 1, C_X1 = 2, C_U = 3, C_S1 = 8, C_S3 = 9 };
enum { V_GA = 0, V_A = 1, V_B = 2, V_GB = 3, V_VA = 4, V_VB = 5, V_VC = 6, V_C3 = 7 };
struct PostMaps { CUtensorMap o, wo, y, w1, g, w2, x1, w3, u, w4, out, x; };

struct GeluK { float k0, k1, kh; };
__device__ __forceinline__ GeluK gelu_k(float c) { return {0.7978845608028654f * c, 0.7978845608028654f * 0.044715f * c * c * c, 0.5f * c}; }
__device__ __forceinline__ float gelu_s(float t, const GeluK& k) {
    const float u = t * fmaf(t * t, k.k1, k.k0);
    float th; asm("tanh.approx.f32 %0, %1;" : "=f"(th) : "f"(u));
    const float hx = k.kh * t;
    return fmaf(hx, th, hx);
}
__device__ __forceinline__ float2 ldsv(uint32_t a) {
    float2 v; asm("ld.shared.v2.f32 {%0,%1}, [%2];" : "=f"(v.x), "=f"(v.y) : "r"(a)); return v;
}
__device__ __forceinline__ void wait_smem(uint32_t a, int target) {
    int it = 0;
#pragma unroll 1
    while (true) {
        int v;
        asm volatile("ld.acquire.cta.shared.u32 %0, [%1];" : "=r"(v) : "r"(a) : "memory");
        if (__all_sync(~0u, v >= target)) break;
        spin_guard(++it);
    }
}

#define PP(i)
#define PH_(c, w, i)
struct Pipe { int st, ph; };
__device__ __forceinline__ void adv(Pipe& p) { if (++p.st == P_ST) { p.st = 0; p.ph ^= 1; } }
__device__ __forceinline__ int u_col(int r, int nb) { return r ? 512 + r * 1024 + nb * 128 : nb * 192; }

template <bool A>
__device__ __forceinline__ void post_produce(uint32_t sb, const PostMaps& mp, int mb, int nb, int rank) {
    const int rh = 2 * mb + rank, lane = threadIdx.x & 31;
    const uint32_t full = sb + P_BAR + 8 * PB_F, empty = sb + P_BAR + 8 * PB_E;
    Pipe p = {(P_ST0 + E0) % P_ST, !E0};
#pragma unroll 1
    for (int ph = 0; ph < 9; ph++) {
        const int GS = ph == 0 ? 8 : ph == 6 ? 3 : 2, kb0 = ph < 7 ? 0 : ph * 16 - 88;
        const CUtensorMap* tm = &mp.o + 2 * (ph < 3 ? ph : ph < 6 ? 3 : 4) + !A;
        const uint64_t pol = ((A ? EFA : EFB) >> ph) & 1 ? evict_first() : evict_normal();
        const bool own = OWN && (ph == 1 || ph == 3);
        const int n0 = ph >= 3 && ph < 6 ? u_col(ph - 3, nb) : nb * 128;
        const int amul = ph == 0 ? 256 : 64, arow = ph == 0 ? rh * 8 : rh * 64;
        const int wr = ph == 2 ? min(max(rh + min(lane >> 3, 2) - 1, 0), 31) : rh ^ ((lane >> 3) & 1);
        const uint32_t* fl = &g_pflag[(ph < 3 ? ph - 1 : ph < 6 ? C_X1 : ph - 3) * 256 + wr * 8 + (lane & 7)];
        uint32_t have = ph == 0 || ph == 5 ? ~0u : 0u;
        PH_(A && ph == PPH, 0, 26) PH_(A && ph == PPH, 1, 26)
#pragma unroll 1
        for (int q = 0; q < 8; q++) {
            const int src = own && q < 2 ? nb ^ q : (q + ((ROT >> ph) & 1 ? nb & 6 : 0)) & 7;
            const bool skip = own && q == 0, both = own && q == 1;
            const uint32_t need = skip ? 0 : (ph == 2 ? 0x10101 : both ? 0x101 : 1) << src;
            if (A && (have & need) != need) {
                int it = 0;
#pragma unroll 1
                do {
                    uint32_t v;
                    asm volatile(FLAG_LD " %0, [%1];" : "=r"(v) : "l"(fl) : "memory");
                    have = __ballot_sync(~0u, v != 0);
                    spin_guard(++it);
                } while ((have & need) != need);
                PH_(ph == PPH && q == own, 0, 23) PH_(ph == PPH, 0, 24) PH_(ph == PPH && q == own, 1, 23) PH_(ph == PPH, 1, 24)
                asm volatile("fence.proxy.async.global;" ::: "memory");
            }
            if (!A && ph == 3 && q == 1) wait_smem(sb + P_BAR + 8 * (PB_OUT + (lane & 1)), 3);
            const int row = arow + (ph == 2 ? (int)((0x04000301u >> ((src & 6) * 4)) & 7) - 2 : 0);
            const uint32_t bytes = (skip ? 16384 : 32768) + (ph == 3 ? 8192 : 0);
            if ((ph | q) == 0) asm volatile("barrier.cluster.wait.aligned;" ::: "memory");
#pragma unroll 1
            for (int e = kb0 + (src + 1) * GS, kb = e - GS + (ph | q ? 0 : E0); kb < e; kb++) {
                const uint32_t f = full + 8 * p.st;
                mbar_wait_w(empty + 8 * p.st, p.ph ^ 1);
                if (A) {
                    const uint32_t a = sb + p.st * 16384 + rank * 8192;
                    if (both) { e_tma2d(a, tm, kb * 64, row, f, pol); e_tma2d(a + 8192 - rank * 16384, tm, kb * 64, row ^ 64, f, pol); }
                    else if (!skip) e_tma2d_mc(a, tm, kb * amul, row, f, pol);
                } else {
                    const uint32_t b = sb + P_B + p.st * 8192;
                    e_expect(f, bytes);
                    e_tma2d(b, tm, n0, kb * 64, f, pol);
                    e_tma2d(b + P_PLANE, tm, n0 + 64, kb * 64, f, pol);
                    if (ph == 3 && both) mbar_wait_w(empty + 8 * p.st - 16, p.ph);
                    if (ph == 3) e_tma2d(b + 2 * P_PLANE, tm, n0 + 128, kb * 64, f, pol);
                }
                PH_(PPH == 0 && ph == 0 && q == 0 && kb + GS == e + E0, 0, 20 + A) PH_(PPH == 0 && ph == 0 && q == 0 && kb + GS == e + E0, 1, 20 + A)
                adv(p);
            }
        }
    }
    if (A) {
#pragma unroll 1
        for (int i = 0; i < P_ST; i++) mbar_wait_w(empty + 8 * i, p.ph ^ (i >= p.st));
    }
}

#define I4(d, i) "f"(d[i]), "f"(d[i + 1]), "f"(d[i + 2]), "f"(d[i + 3])
#define I16(d, i) I4(d, i), I4(d, i + 4), I4(d, i + 8), I4(d, i + 12)
__device__ __forceinline__ void pick16(float* v, int n, const float* c1, float2 a, float2 b, const float* old) {
    asm volatile("{PKT: .branchtargets PK0, PK1, PK2, PK3, PK4, PK5, PK6, PK7, PK8, PK9, PK10, PK11; brx.idx.uni %8, PKT;\n"
                 "PK0: fma.rn.f32 %0, %9, %11, %15; fma.rn.f32 %1, %9, %12, %16; fma.rn.f32 %2, %10, %11, %17; fma.rn.f32 %3, %10, %12, %18; fma.rn.f32 %4, %9, %13, %19; fma.rn.f32 %5, %9, %14, %20; fma.rn.f32 %6, %10, %13, %21; fma.rn.f32 %7, %10, %14, %22; bra.uni PKE;\n"
                 "PK1: fma.rn.f32 %0, %9, %11, %23; fma.rn.f32 %1, %9, %12, %24; fma.rn.f32 %2, %10, %11, %25; fma.rn.f32 %3, %10, %12, %26; fma.rn.f32 %4, %9, %13, %27; fma.rn.f32 %5, %9, %14, %28; fma.rn.f32 %6, %10, %13, %29; fma.rn.f32 %7, %10, %14, %30; bra.uni PKE;\n"
                 "PK2: fma.rn.f32 %0, %9, %11, %31; fma.rn.f32 %1, %9, %12, %32; fma.rn.f32 %2, %10, %11, %33; fma.rn.f32 %3, %10, %12, %34; fma.rn.f32 %4, %9, %13, %35; fma.rn.f32 %5, %9, %14, %36; fma.rn.f32 %6, %10, %13, %37; fma.rn.f32 %7, %10, %14, %38; bra.uni PKE;\n"
                 "PK3: fma.rn.f32 %0, %9, %11, %39; fma.rn.f32 %1, %9, %12, %40; fma.rn.f32 %2, %10, %11, %41; fma.rn.f32 %3, %10, %12, %42; fma.rn.f32 %4, %9, %13, %43; fma.rn.f32 %5, %9, %14, %44; fma.rn.f32 %6, %10, %13, %45; fma.rn.f32 %7, %10, %14, %46; bra.uni PKE;\n"
                 "PK4: fma.rn.f32 %0, %9, %11, %47; fma.rn.f32 %1, %9, %12, %48; fma.rn.f32 %2, %10, %11, %49; fma.rn.f32 %3, %10, %12, %50; fma.rn.f32 %4, %9, %13, %51; fma.rn.f32 %5, %9, %14, %52; fma.rn.f32 %6, %10, %13, %53; fma.rn.f32 %7, %10, %14, %54; bra.uni PKE;\n"
                 "PK5: fma.rn.f32 %0, %9, %11, %55; fma.rn.f32 %1, %9, %12, %56; fma.rn.f32 %2, %10, %11, %57; fma.rn.f32 %3, %10, %12, %58; fma.rn.f32 %4, %9, %13, %59; fma.rn.f32 %5, %9, %14, %60; fma.rn.f32 %6, %10, %13, %61; fma.rn.f32 %7, %10, %14, %62; bra.uni PKE;\n"
                 "PK6: fma.rn.f32 %0, %9, %11, %63; fma.rn.f32 %1, %9, %12, %64; fma.rn.f32 %2, %10, %11, %65; fma.rn.f32 %3, %10, %12, %66; fma.rn.f32 %4, %9, %13, %67; fma.rn.f32 %5, %9, %14, %68; fma.rn.f32 %6, %10, %13, %69; fma.rn.f32 %7, %10, %14, %70; bra.uni PKE;\n"
                 "PK7: fma.rn.f32 %0, %9, %11, %71; fma.rn.f32 %1, %9, %12, %72; fma.rn.f32 %2, %10, %11, %73; fma.rn.f32 %3, %10, %12, %74; fma.rn.f32 %4, %9, %13, %75; fma.rn.f32 %5, %9, %14, %76; fma.rn.f32 %6, %10, %13, %77; fma.rn.f32 %7, %10, %14, %78; bra.uni PKE;\n"
                 "PK8: fma.rn.f32 %0, %9, %11, %79; fma.rn.f32 %1, %9, %12, %80; fma.rn.f32 %2, %10, %11, %81; fma.rn.f32 %3, %10, %12, %82; fma.rn.f32 %4, %9, %13, %83; fma.rn.f32 %5, %9, %14, %84; fma.rn.f32 %6, %10, %13, %85; fma.rn.f32 %7, %10, %14, %86; bra.uni PKE;\n"
                 "PK9: fma.rn.f32 %0, %9, %11, %87; fma.rn.f32 %1, %9, %12, %88; fma.rn.f32 %2, %10, %11, %89; fma.rn.f32 %3, %10, %12, %90; fma.rn.f32 %4, %9, %13, %91; fma.rn.f32 %5, %9, %14, %92; fma.rn.f32 %6, %10, %13, %93; fma.rn.f32 %7, %10, %14, %94; bra.uni PKE;\n"
                 "PK10: fma.rn.f32 %0, %9, %11, %95; fma.rn.f32 %1, %9, %12, %96; fma.rn.f32 %2, %10, %11, %97; fma.rn.f32 %3, %10, %12, %98; fma.rn.f32 %4, %9, %13, %99; fma.rn.f32 %5, %9, %14, %100; fma.rn.f32 %6, %10, %13, %101; fma.rn.f32 %7, %10, %14, %102; bra.uni PKE;\n"
                 "PK11: fma.rn.f32 %0, %9, %11, %103; fma.rn.f32 %1, %9, %12, %104; fma.rn.f32 %2, %10, %11, %105; fma.rn.f32 %3, %10, %12, %106; fma.rn.f32 %4, %9, %13, %107; fma.rn.f32 %5, %9, %14, %108; fma.rn.f32 %6, %10, %13, %109; fma.rn.f32 %7, %10, %14, %110;\n"
                 "PKE: }"
                 : "=f"(v[0]), "=f"(v[1]), "=f"(v[2]), "=f"(v[3]), "=f"(v[4]), "=f"(v[5]), "=f"(v[6]), "=f"(v[7])
                 : "r"(n), "f"(c1[0]), "f"(c1[1]), "f"(a.x), "f"(a.y), "f"(b.x), "f"(b.y), I16(old, 0), I16(old, 16), I16(old, 32), I16(old, 48), I16(old, 64), I16(old, 80));
}
template <int PH, class F>
__device__ __forceinline__ void post_mma(uint32_t sb, float* acc, Pipe& p, int NK, int wg, uint32_t rel, bool lead, int pi, F hook) {
    const uint32_t full = sb + P_BAR + 8 * PB_F;
    constexpr uint64_t DA = PH == 0 ? mkdesc(SB0, 128, 1024, 0) : mkdesc(SB0, 16, 1024, 1);
    constexpr uint64_t DB = mkdesc(SB0 + P_B, P_PLANE, 1024, 1);
    auto release = [&](uint32_t a) { asm volatile("{.reg .pred p; setp.gt.u32 p, %0, 63; @p mbarrier.arrive.shared::cluster.b64 _, [%0];}" ::"r"(a) : "memory"); };
    uint32_t prev = 0;
    if (OWN && (PH & 1)) { if (HFENCE == 2) fence_async_smem(); bar_sync(12 + wg, 128); }
    bool ok = false;
#pragma unroll 1
    for (int kb = 0; kb < NK; kb++) {
        if (!ok) mbar_wait_w(full + 8 * p.st, p.ph);
        const uint32_t a = (uint32_t)DA + (OWN && (PH & 1) && kb < 2 ? P_OUT / 16 + wg * 1024 + kb * 512 : p.st * 1024 + wg * 512), b = (uint32_t)DB + p.st * 512;
        wg_fence();
#pragma unroll
        for (int k = 0; k < 4; k++) {
            const uint64_t da = (DA & 0xffffffff00000000ull) | (a + k * (PH == 0 ? 16 : 2)), db = (DB & 0xffffffff00000000ull) | (b + k * 128);
            if (PH == 3) wgmma_ss192(acc, da, db, (kb | k) != 0);
            else wgmma_ss128<PH == 0>(acc, da, db, (kb | k) != 0);
        }
        wg_commit();
        if (kb == 0) { PP(pi) if (PH == 0 && wg == 0) TL(11) }
        const uint32_t cur = rel + 8 * p.st;
        adv(p);
        hook(-1);
        uint32_t t;
        asm volatile("{.reg .pred p; mbarrier.test_wait.parity.shared.b64 p, [%1], %2; selp.u32 %0, 1, 0, p;}" : "=r"(t) : "r"(full + 8 * p.st), "r"(p.ph) : "memory");
        wg_wait<1>();
        release(prev);
        ok = __all_sync(~0u, t);
        prev = cur;
        hook(kb);
    }
    wg_wait<0>();
    release(prev);
    PP(pi + 1)
}

__global__ void __cluster_dims__(2, 1, 1) __launch_bounds__(384, 1)
k_post(const __grid_constant__ PostMaps mp) {
    extern __shared__ uint8_t smraw[];
    const uint32_t sb = smem_u32(smraw);
    if ((sb & 0x3FFFF) != SB0) __trap();
    const int tid = threadIdx.x, lane = tid & 31;
    const int rank = blockIdx.x & 1, c = blockIdx.x >> 1;
    int d, pi;
    pair_place(c, d, pi);
    const int mb = MAP == 0 ? c >> 2 : MAP == 1 ? (d >> 2) * 8 + pi : MAP == 2 ? (d >> 1) * 4 + (pi >> 1) : d * 2 + (pi >> 2);
    const int nb = rank + 2 * (MAP == 0 ? c & 3 : MAP == 1 ? d & 3 : MAP == 2 ? (d & 1) * 2 + (pi & 1) : pi & 3);
    const uint32_t bars = sb + P_BAR;
    PH_(PPH == 0 && tid == 0, 0, 22) PH_(PPH == 0 && tid == 0, 1, 22)
    const int w = __reduce_max_sync(~0u, (tid >> 5) - 8);
    if (w == 1) {
        if (lane == 0) {
#pragma unroll
            for (int i = 0; i < PB_OUT; i++) mbar_init(bars + 8 * i, i >= PB_E && i < PB_X ? 4 : 1);
            mbar_arrive(bars + 8 * (PB_F + P_ST0));
            asm volatile("mbarrier.arrive.shared.b64 _, [%0], 4;" ::"r"(bars + 8 * (PB_E + P_ST0)) : "memory");
            sts4(bars + 8 * PB_OUT, 0, 0, 0, 0);
            asm volatile("fence.mbarrier_init.release.cluster; fence.proxy.async.shared::cta;" ::: "memory");
        }
        __syncwarp();
    }
    asm volatile("barrier.cluster.arrive.relaxed.aligned;" ::: "memory");
    if (w == 1) {
#pragma unroll
        for (int i = 0; i < E0; i++) {
            const int st = (P_ST0 + i) % P_ST, kb = (ROT & 1 ? nb & 6 : 0) * 8 + i;
            const uint32_t f = bars + 8 * (PB_F + st);
            e_expect(f, 32768);
#pragma unroll
            for (int h = 0; h < 2; h++) {
                e_tma2d(sb + st * 16384 + h * 8192, &mp.o, kb * 256, mb * 16 + h * 8, f, evict_first());
                e_tma2d(sb + P_B + st * 8192 + h * P_PLANE, &mp.wo, nb * 128 + h * 64, kb * 64, f, evict_first());
            }
        }
    }
    if (w != 0 && w != 3) asm volatile("barrier.cluster.wait.aligned;" ::: "memory");
    if (w >= 0) {
        asm volatile("setmaxnreg.dec.sync.aligned.u32 40;");
        if (w == 0) {
            post_produce<false>(sb, mp, mb, nb, rank);
        } else if (w < 3) {
            const int wg = w - 1, rh = 2 * mb + wg;
            float* rowc = (float*)(smraw + P_ROW) + (wg * 64 + lane * 2) * 8;
            int nout = 0, sig = 0;
            if (X_DLY) __nanosleep(X_DLY);
            if (wg && lane < 9) asm volatile("prefetch.tensormap [%0];" ::"l"(&mp.y + lane) : "memory");
            e_expect(bars + 8 * (PB_X + wg), 16384);
            e_tma2d(sb + P_OUT + wg * 16384, &mp.x, nb * 128, rh * 64, bars + 8 * (PB_X + wg), evict_first());
            e_tma2d(sb + P_OUT + wg * 16384 + 8192, &mp.x, nb * 128 + 64, rh * 64, bars + 8 * (PB_X + wg), evict_first());
            if (wg == 0) {
#pragma unroll 1
                for (int i = 0; i < 11; i++) {
                    const float* src = i < 4 ? g_mod + ((0x5342 >> (4 * i)) & 15) * DM + nb * 128 : g_vec + (i < 7 ? (i - 4) * DM + nb * 128 : 3 * DM + u_col(max(i - 8, 0), nb) + (i == 8) * 128);
                    if (i != 8 || lane < 16) cp_async16(sb + P_VEC + i * 512 - (i > 8) * 256 + lane * 16, src + lane * 4);
                }
                *(uint4*)&g_modp[blockIdx.x * 128 + lane * 4] = make_uint4(0, 0, 0, 0);
                if (blockIdx.x == 64) *(uint2*)&g_tick[lane * 2] = make_uint2(0, 0);
                asm volatile("cp.async.wait_all;" ::: "memory");
                const float4 a = lds4f(sb + P_VEC + V_A * 512 + lane * 16);
                sts4f(sb + P_VEC + V_A * 512 + lane * 16, 1.0f + a.x, 1.0f + a.y, 1.0f + a.z, 1.0f + a.w);
                bar_arrive(3, 288);
            }
#pragma unroll 1
            for (int i = 0; i < 9; i++) {
                const int cnt = i == 8 ? 6 : (0x54392180u >> (4 * i)) & 15;
                if (cnt < C_S1) {
                    const bool isu = cnt >= C_U && cnt < 6;
                    const int ng = cnt == C_U ? 3 : 2, c0 = isu ? u_col(cnt - C_U, nb) : nb * 128;
                    const uint32_t src = sb + (cnt == C_U ? P_OUT3 : P_OUT) + wg * ng * 8192;
#pragma unroll 1
                    for (int j = 0; j < ng; j++) {
                        bar_sync(4 + 4 * wg + (sig++ & 3), 160);
                        if (lane == 0) {
                            if (HFENCE) fence_async_smem();
                            PH_(cnt == PPH - 1, wg, 20)
                            asm volatile("cp.async.bulk.tensor.2d.global.shared::cta.bulk_group [%0, {%2, %3}], [%1]; cp.async.bulk.commit_group;"
                                         ::"l"(&mp.y + 2 * (isu ? 3 : min(cnt, 4))), "r"(src + j * 8192), "r"(c0 + j * 64), "r"(rh * 64) : "memory");
                        }
                        __syncwarp();
                    }
                    if (lane == 0) {
                        asm volatile("cp.async.bulk.wait_group 0; fence.proxy.async.global;" ::: "memory");
                        PH_(cnt == PPH - 1, wg, 21)
                        asm volatile("st.release.cta.shared.u32 [%0], %1;" ::"r"(bars + 8 * (PB_OUT + wg)), "r"(nout + 1) : "memory");
                        if (cnt < 6) asm volatile(FLAG_ST " [%0], %1;" ::"l"(&g_pflag[cnt * 256 + rh * 8 + nb]), "r"(1) : "memory");
                        PH_(cnt == PPH - 1, wg, 22)
                    }
                    nout++;
                    __syncwarp();
                    continue;
                }
                bar_sync(4 + 4 * wg + (sig++ & 3), 160);
#pragma unroll 1
                for (int q = 0; q < (cnt == C_S1 ? 3 : 1); q++) {
                    const float4 v = lds4f(sb + P_ROW + wg * 2048 + q * 512 + lane * 16);
                    asm volatile("red.relaxed.gpu.global.add.v4.f32 [%0], {%1, %2, %3, %4};"
                                 ::"l"((float4*)g_st + (cnt == C_S1 ? q : 3) * (S_ / 2) + rh * 32 + lane), "f"(v.x), "f"(v.y), "f"(v.z), "f"(v.w) : "memory");
                }
                __syncwarp();
                uint32_t* c = &g_pcnt[(cnt - C_S1) * 256 + rh * 8];
                if (lane == 0) { signal_count(c); wait_count1(c, 8); }
                __syncwarp();
                const float4* sp = (const float4*)g_st + rh * 32 + lane;
                float4 u[3] = {__ldcg(sp + (cnt == C_S1 ? 0 : 3) * (S_ / 2)), __ldcg(sp + S_ / 2), __ldcg(sp + S_)};
#pragma unroll 1
                for (int h = 0; h < 2; h++) {
                    const float id = 1.0f / DM;
                    const float m = u[0].x * id, var = fmaxf(u[0].y * id - m * m, 0.f) + 1e-5f, r = rsqrtf(var);
                    float sc = r, m2 = 0.f;
                    if (cnt == C_S1) {
                        m2 = r * (u[1].x * id - m * g_cst[0]) + g_cst[3];
                        const float e2 = r * r * (u[2].x * id - 2.0f * m * u[1].y * id + m * m * g_cst[1]) + 2.0f * r * (u[2].y * id - m * g_cst[2]) + g_cst[4];
                        sc = r * rsqrtf(fmaxf(e2 - m2 * m2, 0.f) + 1e-5f);
                    }
                    const GeluK k = gelu_k(sc);
                    *(float4*)(rowc + h * 8) = make_float4(k.k0, k.k1, k.kh, -m);
                    *(float4*)(rowc + h * 8 + 4) = make_float4(var * r, -m2 * var * r, r, -m * r);
#pragma unroll
                    for (int q = 0; q < 3; q++) { u[q].x = u[q].z; u[q].y = u[q].w; }
                }
                bar_arrive(1 + wg, 160);
            }
        } else {
            post_produce<true>(sb, mp, mb, nb, rank);
        }
    } else {
        asm volatile("setmaxnreg.inc.sync.aligned.u32 232;");
        const int wg = __reduce_max_sync(~0u, tid >> 7), wi = (tid >> 5) & 3, g = lane >> 2, tq = lane & 3;
        const bool lead = (tid & 127) == 0;
        uint32_t rel = 0;
        if ((tid & 127) < 2) asm("mapa.shared::cluster.u32 %0, %1, %2;" : "=r"(rel) : "r"(bars + 8 * PB_E), "r"(tid & 1));
        PP(0)
        if (tid == 0) TL(10)
        uint32_t vec = sb + P_VEC + tq * 8;
        const uint32_t stw = sb + (wi * 16 + ((lane >> 3) & 1) * 8 + (lane & 7)) * 128 + (((lane >> 4) ^ (lane & 7)) << 4);
        int sig = 0;
        auto signal = [&]() { bar_arrive(4 + 4 * wg + (sig++ & 3), 160); };
        auto put64 = [&](uint32_t o, const float* v) {
#pragma unroll
            for (int jj = 0; jj < 4; jj++, v += 8) stsm4((stw + o) ^ (jj << 5), pack2(v[0], v[1]), pack2(v[2], v[3]), pack2(v[4], v[5]), pack2(v[6], v[7]));
            if (HFENCE < 2) fence_async_smem();
            signal();
        };
        auto out_free = [&](int n) { wait_smem(bars + 8 * (PB_OUT + (lane & 1)), n); };
        const uint32_t rowc = sb + P_ROW + (wg * 64 + wi * 16 + g) * 32, o128 = P_OUT + wg * 16384;
        const uint32_t rsum = sb + P_ROW + wg * 2048 + (wi * 16 + g) * 8;
        Pipe pa = {P_ST0, 1};
        auto none = [](int) {};
        uint32_t keep[32];
#define KEEP(jn, e) (((e) & 1) ? bfhi(keep[2 * (jn) + ((e) >> 1)]) : bflo(keep[2 * (jn) + ((e) >> 1)]))
        float mu1[2], r1[2];
        {
            float acc[64];
            post_mma<0>(sb, acc, pa, 64, wg, rel, lead, 1, [&](int kb) {
                if (kb != 40) return;
                bar_sync(3, 288);
                mbar_wait_w(bars + 8 * (PB_X + wg), 0);
#pragma unroll
                for (int jj = 0; jj < 8; jj++) ldsm4(keep + jj * 4, (stw + o128 + (jj >> 2) * 8192) ^ ((jj & 3) << 5));
            });
            asm volatile("" : "+r"(vec) :: "memory");
            float st[2][6];
#pragma unroll
            for (int q = 0; q < 6; q++) st[0][q] = st[1][q] = 0.f;
#pragma unroll
            for (int jn = 0; jn < 16; jn++) {
                const float2 ga = ldsv(vec + V_GA * 512 + jn * 32), a = ldsv(vec + V_A * 512 + jn * 32);
                float xa[4];
#pragma unroll
                for (int e = 0; e < 4; e++) {
                    xa[e] = fmaf((e & 1) ? ga.y : ga.x, acc[4 * jn + e], KEEP(jn, e));
                    st[e >> 1][0] += xa[e]; st[e >> 1][1] = fmaf(xa[e], xa[e], st[e >> 1][1]);
                    acc[4 * jn + e] = ((e & 1) ? a.y : a.x) * xa[e];
                }
                keep[2 * jn] = pack2(xa[0], xa[1]); keep[2 * jn + 1] = pack2(xa[2], xa[3]);
                if ((jn & 7) == 7) put64(o128 + (jn >> 3) * 8192, acc + 4 * jn - 28);
            }
            PP(3)
#pragma unroll
            for (int jn = 0; jn < 16; jn++) {
                const float2 a = ldsv(vec + V_A * 512 + jn * 32), b = ldsv(vec + V_B * 512 + jn * 32);
#pragma unroll
                for (int e = 0; e < 4; e++) {
                    const float y = acc[4 * jn + e], aa = (e & 1) ? a.y : a.x, bb = (e & 1) ? b.y : b.x;
                    float* s = st[e >> 1];
                    s[2] += y; s[3] = fmaf(aa, y, s[3]); s[4] = fmaf(y, y, s[4]); s[5] = fmaf(bb, y, s[5]);
                }
            }
#pragma unroll
            for (int h = 0; h < 2; h++)
#pragma unroll
                for (int q = 0; q < 6; q++) { st[h][q] += __shfl_xor_sync(~0u, st[h][q], 1); st[h][q] += __shfl_xor_sync(~0u, st[h][q], 2); }
            if (tq < 3) {
#pragma unroll
                for (int h = 0; h < 2; h++)
                    sts2(rsum + tq * 512 + h * 64, tq == 0 ? st[h][0] : tq == 1 ? st[h][2] : st[h][4], tq == 0 ? st[h][1] : tq == 1 ? st[h][3] : st[h][5]);
            }
            signal();
            PP(29)
        }
        {
            float acc[64];
            post_mma<1>(sb, acc, pa, 16, wg, rel, lead, 4, none);
            float c1[2], c2[2], c3[2];
            GeluK gk[2];
            bar_sync(1 + wg, 160);
#pragma unroll
            for (int h = 0; h < 2; h++) {
                const float4 a = lds4f(rowc + h * 256), b = lds4f(rowc + h * 256 + 16);
                gk[h] = {a.x, a.y, a.z}; c1[h] = a.w; c2[h] = b.x; c3[h] = b.y; mu1[h] = b.w; r1[h] = b.z;
            }
#pragma unroll
            for (int jn = 0; jn < 16; jn++) {
                const float2 va = ldsv(vec + V_VA * 512 + jn * 32), vb = ldsv(vec + V_VB * 512 + jn * 32), vc = ldsv(vec + V_VC * 512 + jn * 32);
#pragma unroll
                for (int e = 0; e < 4; e++) {
                    const int h = e >> 1;
                    const float t = fmaf(c1[h], (e & 1) ? va.y : va.x, fmaf(c2[h], (e & 1) ? vb.y : vb.x, fmaf(c3[h], (e & 1) ? vc.y : vc.x, acc[4 * jn + e])));
                    acc[4 * jn + e] = gelu_s(t, gk[h]);
                }
                if ((jn & 7) == 7) put64(o128 + (jn >> 3) * 8192, acc + 4 * jn - 28);
            }
            PP(6)
        }
        {
            float acc[64];
            post_mma<2>(sb, acc, pa, 16, wg, rel, lead, 7, none);
#pragma unroll
            for (int jn = 0; jn < 16; jn++) {
                const float2 a = ldsv(vec + V_A * 512 + jn * 32), b = ldsv(vec + V_B * 512 + jn * 32);
#pragma unroll
                for (int e = 0; e < 4; e++) {
                    const int h = e >> 1;
                    acc[4 * jn + e] += fmaf(fmaf(KEEP(jn, e), r1[h], mu1[h]), (e & 1) ? a.y : a.x, (e & 1) ? b.y : b.x);
                }
                if ((jn & 7) == 7) put64(o128 + (jn >> 3) * 8192, acc + 4 * jn - 28);
            }
            PP(9)
            float st[2][2] = {{0.f, 0.f}, {0.f, 0.f}};
#pragma unroll
            for (int jn = 0; jn < 16; jn++) {
                const float2 gb = ldsv(vec + V_GB * 512 + jn * 32);
                float z[4];
#pragma unroll
                for (int e = 0; e < 4; e++) {
                    const float x1 = acc[4 * jn + e];
                    st[e >> 1][0] += x1; st[e >> 1][1] = fmaf(x1, x1, st[e >> 1][1]);
                    z[e] = fmaf((e & 1) ? gb.y : gb.x, x1, KEEP(jn, e));
                }
                keep[2 * jn] = pack2(z[0], z[1]); keep[2 * jn + 1] = pack2(z[2], z[3]);
            }
#pragma unroll
            for (int h = 0; h < 2; h++)
#pragma unroll
                for (int q = 0; q < 2; q++) { st[h][q] += __shfl_xor_sync(~0u, st[h][q], 1); st[h][q] += __shfl_xor_sync(~0u, st[h][q], 2); }
            if (tq < 2) sts2(rsum + tq * 64, tq ? st[1][0] : st[0][0], tq ? st[1][1] : st[0][1]);
            signal();
            PP(30)
        }
        {
            float old[96], acc[64];
            post_mma<3>(sb, old, pa, 16, wg, rel, lead, 10, none);
            uint32_t v3 = vec + V_C3 * 512;
            float c1[2];
            GeluK gk[2];
            bar_sync(1 + wg, 160);
#pragma unroll
            for (int h = 0; h < 2; h++) { const float4 a = lds4f(rowc + h * 256); gk[h] = {a.x, a.y, a.z}; c1[h] = a.w; }
            bar_sync(3, 256);
#pragma unroll 1
            for (int r = 0; r < 3; r++) {
                const uint32_t o = stw + (r ? o128 : P_OUT3 + wg * 24576);
                uint32_t when = r == 0 ? (wg ? SL_A1 : SL_A0) : r == 1 ? (wg ? SL_B1 : SL_B0) : SL_C << wg, n = 0;
                float2 va, vb;
                post_mma<2>(sb, acc, pa, r < 2 ? 16 : 56, wg, rel, lead, 12 + 2 * r, [&](int kb) {
                    if (kb < 0) { va = lds2f(v3); vb = lds2f(v3 + 32); return; }
                    const bool now = when & 1;
                    when >>= 1;
                    if (!now) return;
                    if (n == 0) out_free(3 + r);
                    float v[8];
                    pick16(v, n, c1, va, vb, old);
#pragma unroll
                    for (int e = 0; e < 8; e++) v[e] = gelu_s(v[e], gk[(e >> 1) & 1]);
                    stsm4((o + (n >> 2) * 8192) ^ ((n & 3) << 5), pack2(v[0], v[1]), pack2(v[2], v[3]), pack2(v[4], v[5]), pack2(v[6], v[7]));
                    v3 += 64;
                    if ((++n & 3) == 0) { if (!HFENCE) fence_async_smem(); signal(); }
                });
                if (r == 2) break;
#pragma unroll
                for (int i = 0; i < 64; i++) old[i] = acc[i];
            }
#pragma unroll
            for (int jn = 0; jn < 16; jn++) {
                const float2 gb = ldsv(vec + V_GB * 512 + jn * 32);
#pragma unroll
                for (int e = 0; e < 4; e++) acc[4 * jn + e] = fmaf((e & 1) ? gb.y : gb.x, acc[4 * jn + e], KEEP(jn, e));
                if ((jn & 7) == 7) put64(o128 + (jn >> 3) * 8192, acc + 4 * jn - 28);
            }
            PP(18)
            if (tid == 0) TL(12)
        }
    }
}

typedef CUresult (*EncFn)(CUtensorMap*, CUtensorMapDataType, cuuint32_t, void*, const cuuint64_t*, const cuuint64_t*, const cuuint32_t*,
                          const cuuint32_t*, CUtensorMapInterleave, CUtensorMapSwizzle, CUtensorMapL2promotion, CUtensorMapFloatOOBfill);

static CUtensorMap make_map(EncFn enc, const void* p, uint64_t inner, uint64_t outer, uint64_t pitch = 0) {
    const uint32_t bi = 64;
    CUtensorMap m;
    cuuint64_t dims[2] = {inner, outer};
    cuuint64_t str[1] = {(pitch ? pitch : inner) * 2};
    cuuint32_t box[2] = {bi, 64};
    cuuint32_t es[2] = {1, 1};
    enc(&m, CU_TENSOR_MAP_DATA_TYPE_BFLOAT16, 2, (void*)p, dims, str, box, es, CU_TENSOR_MAP_INTERLEAVE_NONE,
        bi == 64 ? CU_TENSOR_MAP_SWIZZLE_128B : CU_TENSOR_MAP_SWIZZLE_64B, CU_TENSOR_MAP_L2_PROMOTION_L2_256B, CU_TENSOR_MAP_FLOAT_OOB_FILL_NONE);
    return m;
}
static CUtensorMap make_map_o(EncFn enc, const void* p) {
    CUtensorMap m;
    cuuint64_t dims[2] = {16384, 256};
    cuuint64_t str[1] = {65536};
    cuuint32_t box[2] = {256, 8};
    cuuint32_t es[2] = {1, 1};
    enc(&m, CU_TENSOR_MAP_DATA_TYPE_UINT32, 2, (void*)p, dims, str, box, es, CU_TENSOR_MAP_INTERLEAVE_NONE, CU_TENSOR_MAP_SWIZZLE_NONE,
        CU_TENSOR_MAP_L2_PROMOTION_L2_256B, CU_TENSOR_MAP_FLOAT_OOB_FILL_NONE);
    return m;
}
template <class T> static T* sym(T& s) { void* p = nullptr; cudaGetSymbolAddress(&p, s); return (T*)p; }

constexpr RecTime g_time = {T_GO, T_X2, T_V, D_X2, H_D};
extern "C" void kernel_launch(void* const* d_in, const int* in_sizes, int n_in, void* d_out, int out_size) {
    const bf16* x = (const bf16*)d_in[0];
    const bf16* mem0 = (const bf16*)d_in[1];
    const bf16 *Wq = (const bf16*)d_in[2], *Wk = (const bf16*)d_in[3], *Wv = (const bf16*)d_in[4], *Wo = (const bf16*)d_in[5];
    const bf16 *w1 = (const bf16*)d_in[8], *w2 = (const bf16*)d_in[9], *w3 = (const bf16*)d_in[10], *w4 = (const bf16*)d_in[11];
    const bf16 *c = (const bf16*)d_in[12], *wmod = (const bf16*)d_in[13];
    bf16* out = (bf16*)d_out;

    EncFn enc = nullptr;
    cudaDriverEntryPointQueryResult qr;
    cudaGetDriverEntryPoint("cuTensorMapEncodeTiled", (void**)&enc, cudaEnableDefault, &qr);
    CUtensorMap tWq = make_map(enc, Wq, NH * DH, DM), tWk = make_map(enc, Wk, NH * DH, DM), tWv = make_map(enc, Wv, NH * DH, DM);
    PostMaps mp;
    mp.o = make_map_o(enc, sym(g_O)); mp.wo = make_map(enc, Wo, DM, NH * DH);
    mp.y = make_map(enc, sym(g_y), DM, S_); mp.w1 = make_map(enc, w1, DM, DM);
    mp.g = make_map(enc, sym(g_g), DM, S_); mp.w2 = make_map(enc, w2, DM, DM);
    mp.x1 = make_map(enc, ALIAS & 2 ? sym(g_y) : sym(g_x1), DM, S_); mp.w3 = make_map(enc, w3, FF, DM);
    mp.u = ALIAS & 1 ? make_map(enc, sym(g_O), FF, S_, NH * DH) : make_map(enc, sym(g_u), FF, S_); mp.w4 = make_map(enc, w4, DM, FF);
    mp.out = make_map(enc, out, DM, S_); mp.x = make_map(enc, x, DM, S_);
    cudaFuncSetAttribute(k_rec, cudaFuncAttributeMaxDynamicSharedMemorySize, SM_REC_TOTAL);
    cudaFuncSetAttribute(k_post, cudaFuncAttributeMaxDynamicSharedMemorySize, P_SMEM);

    uint8_t* arena = (uint8_t*)(((uintptr_t)sym(g_arena) + (2u << 20) - 1) & ~(uintptr_t)((2u << 20) - 1));
    const RecPtrs rp = {x, mem0, c, wmod, w1, w3, arena, 0u, g_time};
    const RecMaps rm = {tWq, tWk, tWv, mp.wo};
    k_rec<<<132, 384, SM_REC_TOTAL>>>(rm, rp);
    k_post<<<128, 384, P_SMEM>>>(mp);
}
```

```cpp
#include <cuda_runtime.h>
#include <cuda.h>
#include <cuda_bf16.h>
#include <stdint.h>
#include <limits.h>

typedef __nv_bfloat16 bf16;

constexpr int S_ = 2048, DM = 1024, NH = 32, DH = 128, NSEG = 64, FF = 3584;
constexpr int SPIN_LIMIT = 1 << 22;
#define W_INFL 2
#define NPROBE 3

__device__ uint8_t g_arena[10 << 20];
__device__ __align__(16) uint32_t g_tick[64];
__device__ __align__(16) uint32_t g_modp[8 * 2 * DM];
__host__ __device__ constexpr uint32_t blk(uint32_t lb, uint32_t par) {
    return (lb << 13) | ((((lb) ^ (lb >> 3) ^ (lb >> 4) ^ (lb >> 6) ^ par) & 1) << 12);
}
__host__ __device__ constexpr uint32_t lb_x2(uint32_t h) { return (h & 1) | ((h >> 1) << 3); }
__host__ __device__ constexpr uint32_t acc_slot(uint32_t s) { return (1u << 20) + (s & 1) * 32768 + (s & 2) * 131072; }
__host__ __device__ constexpr uint32_t acc_piece(uint32_t half, uint32_t qd, uint32_t mt) { return mt * 1024 + (qd & 1) * 4096 + half * 8192 + (qd >> 1) * 16384; }
constexpr uint32_t LB_STAMP = 6;
__host__ __device__ constexpr uint32_t stamp_line(uint32_t w, uint32_t q) { return ((w & 1) * 2 + (q >> 1)) * 1024 + (q & 1) * 256; }
constexpr uint32_t ACC_ONE = 0x3c000000u, ACC_ALL = 0x50000000u;
constexpr uint32_t LB_PROBE = 6 | 64;
__host__ __device__ constexpr uint32_t lb_tok(uint32_t h) { return (h & 1) | ((h >> 1) << 3); }
__device__ __align__(16) float g_mod[6 * DM];
__device__ __align__(1024) bf16 g_himg[(S_ + 32) * DM];
__device__ __align__(1024) bf16 g_O[S_ * NH * DH];
__device__ __align__(1024) bf16 g_y[S_ * DM];
__device__ __align__(1024) bf16 g_g[S_ * DM];
__device__ __align__(1024) bf16 g_x1[S_ * DM];
__device__ __align__(16) float g_st[4 * S_ * 2];
__device__ __align__(16) float g_vec[3 * DM + FF];
__device__ float g_cst[8];
__device__ uint32_t g_pcnt[2 * 32 * 8], g_pflag[6 * 32 * 8];
__device__ __align__(1024) bf16 g_u[S_ * FF];

#define TL(i) {}
#define TX(i) {}
#define TLC(i) {}
__device__ __forceinline__ uint32_t smem_u32(const void* p) { return (uint32_t)__cvta_generic_to_shared(p); }
__device__ __forceinline__ void spin_guard(int it) {
    asm volatile("{.reg .pred p; setp.gt.s32 p, %0, %1; @p st.global.u32 [%2], %0;}" ::"r"(it), "n"(SPIN_LIMIT), "l"(1ull));
}
__device__ __forceinline__ void wg_fence() { asm volatile("wgmma.fence.sync.aligned;" ::: "memory"); }
__device__ __forceinline__ void wg_commit() { asm volatile("wgmma.commit_group.sync.aligned;" ::: "memory"); }
template <int N> __device__ __forceinline__ void wg_wait() { asm volatile("wgmma.wait_group.sync.aligned %0;" ::"n"(N) : "memory"); }
__host__ __device__ constexpr uint64_t mkdesc(uint32_t addr, uint32_t lbo, uint32_t sbo, uint32_t swz) {
    return (uint64_t)((addr & 0x3FFFF) >> 4) | ((uint64_t)(lbo >> 4) << 16) | ((uint64_t)(sbo >> 4) << 32) | ((uint64_t)swz << 62);
}
__device__ __forceinline__ uint64_t dadd(uint64_t d, uint32_t o) { return (d & 0xffffffff00000000ull) | (uint32_t)((uint32_t)d + o); }
__device__ __forceinline__ void mbar_init(uint32_t b, uint32_t c) { asm volatile("mbarrier.init.shared.b64 [%0], %1;" ::"r"(b), "r"(c) : "memory"); }
__device__ __forceinline__ void mbar_expect(uint32_t b, uint32_t tx) { asm volatile("mbarrier.arrive.expect_tx.shared.b64 _, [%0], %1;" ::"r"(b), "r"(tx) : "memory"); }
__device__ __forceinline__ void mbar_arrive(uint32_t b) { asm volatile("mbarrier.arrive.shared.b64 _, [%0];" ::"r"(b) : "memory"); }
__device__ __forceinline__ void mbar_arrive_cluster(uint32_t b, uint32_t cta) {
    asm volatile("{.reg .b32 r; mapa.shared::cluster.u32 r, %0, %1; mbarrier.arrive.shared::cluster.b64 _, [r];}" ::"r"(b), "r"(cta) : "memory");
}
__device__ __forceinline__ void mbar_arrive_cluster_if(bool c, uint32_t b, uint32_t cta) {
    asm volatile("{.reg .pred p; .reg .b32 r; setp.ne.u32 p, %2, 0; mapa.shared::cluster.u32 r, %0, %1; @p mbarrier.arrive.shared::cluster.b64 _, [r];}" ::"r"(b), "r"(cta), "r"((uint32_t)c) : "memory");
}
__device__ __forceinline__ bool mbar_try(uint32_t b, uint32_t par) {
    uint32_t ok;
    asm volatile("{.reg .pred p; mbarrier.try_wait.parity.shared.b64 p, [%1], %2; selp.u32 %0, 1, 0, p;}" : "=r"(ok) : "r"(b), "r"(par) : "memory");
    return ok;
}
__device__ __forceinline__ void mbar_wait(uint32_t b, uint32_t par) {
    int it = 0;
#pragma unroll 1
    while (!mbar_try(b, par)) { spin_guard(++it); }
}
__device__ __forceinline__ void mbar_wait_w(uint32_t b, uint32_t par) {
    int it = 0;
    bool ok;
#pragma unroll 1
    do { ok = __all_sync(~0u, mbar_try(b, par)); spin_guard(++it); } while (!ok);
}
__device__ __forceinline__ void mbar_wait_cluster(uint32_t b, uint32_t par) {
    int it = 0;
    while (true) {
        uint32_t ok;
        asm volatile("{.reg .pred p; mbarrier.try_wait.parity.acquire.cluster.shared::cta.b64 p, [%1], %2; selp.u32 %0, 1, 0, p;}" : "=r"(ok) : "r"(b), "r"(par) : "memory");
        if (ok) break;
        spin_guard(++it);
    }
}
__device__ __forceinline__ void tma2d(uint32_t dst, const CUtensorMap* m, int c0, int c1, uint32_t bar) {
    asm volatile("cp.async.bulk.tensor.2d.shared::cluster.global.mbarrier::complete_tx::bytes [%0], [%1, {%3, %4}], [%2];" ::"r"(dst), "l"(m), "r"(bar), "r"(c0), "r"(c1) : "memory");
}
__device__ __forceinline__ void tma2d_mc(uint32_t dst, const CUtensorMap* m, int c0, int c1, uint32_t bar, uint16_t mask) {
    asm volatile("cp.async.bulk.tensor.2d.shared::cluster.global.mbarrier::complete_tx::bytes.multicast::cluster [%0], [%1, {%3, %4}], [%2], %5;" ::"r"(dst), "l"(m), "r"(bar), "r"(c0), "r"(c1), "h"(mask) : "memory");
}
__device__ __forceinline__ void bulk_g2s(uint32_t dst, const void* src, uint32_t bytes, uint32_t bar) {
    asm volatile("cp.async.bulk.shared::cluster.global.mbarrier::complete_tx::bytes [%0], [%1], %2, [%3];" ::"r"(dst), "l"(src), "r"(bytes), "r"(bar) : "memory");
}
__device__ __forceinline__ void bar_sync(int id, int n) { asm volatile("bar.sync %0, %1;" ::"r"(id), "r"(n) : "memory"); }
__device__ __forceinline__ void bar_arrive(int id, int n) { asm volatile("bar.arrive %0, %1;" ::"r"(id), "r"(n) : "memory"); }
__device__ __forceinline__ void cluster_sync_all() { asm volatile("barrier.cluster.arrive.aligned; barrier.cluster.wait.aligned;" ::: "memory"); }
__device__ __forceinline__ void fence_async_smem() { asm volatile("fence.proxy.async.shared::cta;" ::: "memory"); }
__device__ __forceinline__ void ldsm4t(uint32_t* r, uint32_t a) {
    asm volatile("ldmatrix.sync.aligned.m8n8.x4.trans.shared.b16 {%0,%1,%2,%3}, [%4];" : "=r"(r[0]), "=r"(r[1]), "=r"(r[2]), "=r"(r[3]) : "r"(a) : "memory");
}
__device__ __forceinline__ void ldsm4(uint32_t* r, uint32_t a) {
    asm volatile("ldmatrix.sync.aligned.m8n8.x4.shared.b16 {%0,%1,%2,%3}, [%4];" : "=r"(r[0]), "=r"(r[1]), "=r"(r[2]), "=r"(r[3]) : "r"(a) : "memory");
}
__device__ __forceinline__ uint32_t movm(uint32_t a) {
    uint32_t d; asm volatile("movmatrix.sync.aligned.m8n8.trans.b16 %0, %1;" : "=r"(d) : "r"(a)); return d;
}
__device__ __forceinline__ void mma16816(float* d, uint32_t a0, uint32_t a1, uint32_t a2, uint32_t a3, uint32_t b0, uint32_t b1) {
    asm volatile("mma.sync.aligned.m16n8k16.row.col.f32.bf16.bf16.f32 {%0,%1,%2,%3},{%4,%5,%6,%7},{%8,%9},{%0,%1,%2,%3};"
                 : "+f"(d[0]), "+f"(d[1]), "+f"(d[2]), "+f"(d[3]) : "r"(a0), "r"(a1), "r"(a2), "r"(a3), "r"(b0), "r"(b1));
}
__device__ __forceinline__ void mma16816z(float* d, const uint32_t* a, uint32_t b0, uint32_t b1) {
    asm volatile("mma.sync.aligned.m16n8k16.row.col.f32.bf16.bf16.f32 {%0,%1,%2,%3},{%4,%5,%6,%7},{%8,%9},{%10,%10,%10,%10};"
                 : "=f"(d[0]), "=f"(d[1]), "=f"(d[2]), "=f"(d[3]) : "r"(a[0]), "r"(a[1]), "r"(a[2]), "r"(a[3]), "r"(b0), "r"(b1), "f"(0.f));
}
__device__ __forceinline__ void mma1688(float* d, uint32_t a0, uint32_t a1, uint32_t b0) {
    asm volatile("mma.sync.aligned.m16n8k8.row.col.f32.bf16.bf16.f32 {%0,%1,%2,%3},{%4,%5},{%6},{%0,%1,%2,%3};"
                 : "+f"(d[0]), "+f"(d[1]), "+f"(d[2]), "+f"(d[3]) : "r"(a0), "r"(a1), "r"(b0));
}
__device__ __forceinline__ uint32_t pack2(float lo, float hi) {
    uint32_t r; asm("cvt.rn.bf16x2.f32 %0, %1, %2;" : "=r"(r) : "f"(hi), "f"(lo)); return r;
}
__device__ __forceinline__ uint32_t hadd2(uint32_t a, uint32_t b) {
    uint32_t r; asm("add.rn.bf16x2 %0, %1, %2;" : "=r"(r) : "r"(a), "r"(b)); return r;
}
__device__ __forceinline__ uint32_t hadd2v(uint32_t a, uint32_t b) {
    uint32_t r; asm volatile("add.rn.bf16x2 %0, %1, %2;" : "=r"(r) : "r"(a), "r"(b)); return r;
}
__device__ __forceinline__ float bflo(uint32_t u) { return __uint_as_float(u << 16); }
__device__ __forceinline__ float bfhi(uint32_t u) { return __uint_as_float(u & 0xffff0000u); }
__device__ __forceinline__ float ex2(float x) { float r; asm("ex2.approx.ftz.f32 %0, %1;" : "=f"(r) : "f"(x)); return r; }
__device__ __forceinline__ uint4 ldg_rlx4(const void* p) {
    uint4 v; asm volatile("ld.relaxed.gpu.global.v4.u32 {%0,%1,%2,%3}, [%4];" : "=r"(v.x), "=r"(v.y), "=r"(v.z), "=r"(v.w) : "l"(p) : "memory"); return v;
}
__device__ __forceinline__ uint2 ldg_rlx2(const void* p) {
    unsigned long long v; asm volatile("ld.relaxed.gpu.global.b64 %0, [%1];" : "=l"(v) : "l"(p) : "memory");
    return make_uint2((uint32_t)v, (uint32_t)(v >> 32));
}
__device__ __forceinline__ uint32_t ldg_rlx1(const void* p) {
    uint32_t v; asm volatile("ld.relaxed.gpu.global.u32 %0, [%1];" : "=r"(v) : "l"(p) : "memory"); return v;
}
__device__ __forceinline__ void stg_rlx1(void* p, uint32_t v) { asm volatile("st.relaxed.gpu.global.u32 [%0], %1;" ::"l"(p), "r"(v) : "memory"); }
__device__ __forceinline__ void stg_rlx2(void* p, uint32_t x, uint32_t y) {
    unsigned long long v = (unsigned long long)x | ((unsigned long long)y << 32);
    asm volatile("st.relaxed.gpu.global.b64 [%0], %1;" ::"l"(p), "l"(v) : "memory");
}
__device__ __forceinline__ void stg_rlx4(void* p, uint32_t x, uint32_t y, uint32_t z, uint32_t w) {
    asm volatile("st.relaxed.gpu.global.v4.u32 [%0], {%1,%2,%3,%4};" ::"l"(p), "r"(x), "r"(y), "r"(z), "r"(w) : "memory");
}
__device__ __forceinline__ void sts4(uint32_t a, uint32_t x, uint32_t y, uint32_t z, uint32_t w) {
    asm volatile("st.shared.v4.u32 [%0], {%1,%2,%3,%4};" ::"r"(a), "r"(x), "r"(y), "r"(z), "r"(w) : "memory");
}
__device__ __forceinline__ uint4 lds4(uint32_t a) {
    uint4 v; asm volatile("ld.shared.v4.u32 {%0,%1,%2,%3}, [%4];" : "=r"(v.x), "=r"(v.y), "=r"(v.z), "=r"(v.w) : "r"(a) : "memory"); return v;
}
__device__ __forceinline__ void st_async4(uint32_t a, float x, float y, float z, float w, uint32_t bar) {
    asm volatile("st.async.shared::cluster.mbarrier::complete_tx::bytes.v4.f32 [%0], {%1,%2,%3,%4}, [%5];" ::"r"(a), "f"(x), "f"(y), "f"(z), "f"(w), "r"(bar) : "memory");
}
#define F4(d, i) "+f"(d[i]), "+f"(d[i + 1]), "+f"(d[i + 2]), "+f"(d[i + 3])
template <bool V> __device__ __forceinline__ void wgmma_tok_rs(float* d, const uint32_t* a, uint64_t b, int sc) {
    if (V) asm volatile("{.reg .pred p; setp.ne.b32 p, %25, 0;\n wgmma.mma_async.sync.aligned.m64n40k16.f32.bf16.bf16 {%0,%1,%2,%3,%4,%5,%6,%7,%8,%9,%10,%11,%12,%13,%14,%15,%16,%17,%18,%19}, {%20,%21,%22,%23}, %24, p, 1, 1, 0;}"
                        : F4(d, 0), F4(d, 4), F4(d, 8), F4(d, 12), F4(d, 16) : "r"(a[0]), "r"(a[1]), "r"(a[2]), "r"(a[3]), "l"(b), "r"(sc));
    else asm volatile("{.reg .pred p; setp.ne.b32 p, %21, 0;\n wgmma.mma_async.sync.aligned.m64n32k16.f32.bf16.bf16 {%0,%1,%2,%3,%4,%5,%6,%7,%8,%9,%10,%11,%12,%13,%14,%15}, {%16,%17,%18,%19}, %20, p, 1, 1, 0;}"
                      : F4(d, 0), F4(d, 4), F4(d, 8), F4(d, 12) : "r"(a[0]), "r"(a[1]), "r"(a[2]), "r"(a[3]), "l"(b), "r"(sc));
}
template <bool V> __device__ __forceinline__ void wgmma_tok_ss(float* d, uint64_t a, uint64_t b) {
    if (V) asm volatile("wgmma.mma_async.sync.aligned.m64n40k16.f32.bf16.bf16 {%0,%1,%2,%3,%4,%5,%6,%7,%8,%9,%10,%11,%12,%13,%14,%15,%16,%17,%18,%19}, %20, %21, 1, 1, 1, 1, 0;"
                        : F4(d, 0), F4(d, 4), F4(d, 8), F4(d, 12), F4(d, 16) : "l"(a), "l"(b));
    else asm volatile("wgmma.mma_async.sync.aligned.m64n32k16.f32.bf16.bf16 {%0,%1,%2,%3,%4,%5,%6,%7,%8,%9,%10,%11,%12,%13,%14,%15}, %16, %17, 1, 1, 1, 1, 0;"
                      : F4(d, 0), F4(d, 4), F4(d, 8), F4(d, 12) : "l"(a), "l"(b));
}
#define F16(d, i) F4(d, i), F4(d, i + 4), F4(d, i + 8), F4(d, i + 12)
template <int TA>
__device__ __forceinline__ void wgmma_ss128(float* d, uint64_t a, uint64_t b, int sc) {
    asm volatile("{.reg .pred p; setp.ne.b32 p, %66, 0;\n wgmma.mma_async.sync.aligned.m64n128k16.f32.bf16.bf16 "
                 "{%0,%1,%2,%3,%4,%5,%6,%7,%8,%9,%10,%11,%12,%13,%14,%15,%16,%17,%18,%19,%20,%21,%22,%23,%24,%25,%26,%27,%28,%29,%30,%31,"
                 "%32,%33,%34,%35,%36,%37,%38,%39,%40,%41,%42,%43,%44,%45,%46,%47,%48,%49,%50,%51,%52,%53,%54,%55,%56,%57,%58,%59,%60,%61,%62,%63}, %64, %65, p, 1, 1, %67, 1;}"
                 : F16(d, 0), F16(d, 16), F16(d, 32), F16(d, 48) : "l"(a), "l"(b), "r"(sc), "n"(TA));
}

__device__ __forceinline__ float warp_sum(float v) {
#pragma unroll
    for (int o = 16; o; o >>= 1) v += __shfl_xor_sync(~0u, v, o);
    return v;
}
__device__ __forceinline__ float bfround(float x) { return __bfloat162float(__float2bfloat16(x)); }

__device__ __forceinline__ void wait_count1(const uint32_t* p, uint32_t target) {
    int it = 0;
#pragma unroll 1
    while (true) {
        uint32_t v;
        asm volatile("ld.acquire.gpu.global.u32 %0, [%1];" : "=r"(v) : "l"(p) : "memory");
        if (v >= target) break;
        spin_guard(++it);
    }
}
__device__ __forceinline__ void red2(float* p, float a, float b) {
    asm volatile("red.relaxed.gpu.global.add.v2.f32 [%0], {%1, %2};" ::"l"(p), "f"(a), "f"(b) : "memory");
}
__device__ __forceinline__ void l2_prefetch(const void* p, uint32_t bytes) {
    asm volatile("cp.async.bulk.prefetch.L2.global [%0], %1;" ::"l"(p), "r"(bytes) : "memory");
}
__device__ __forceinline__ void signal_count(uint32_t* p) { asm volatile("red.release.gpu.global.add.u32 [%0], 1;" ::"l"(p) : "memory"); }
__device__ __forceinline__ void e_expect(uint32_t b, uint32_t tx) {
    asm volatile("{.reg .pred p; elect.sync _|p, 0xffffffff; @p mbarrier.arrive.expect_tx.shared.b64 _, [%0], %1;}" ::"r"(b), "r"(tx) : "memory");
}
__device__ __forceinline__ uint64_t evict_first() { uint64_t p; asm("createpolicy.fractional.L2::evict_first.b64 %0, 1.0;" : "=l"(p)); return p; }
__device__ __forceinline__ uint64_t evict_normal() { uint64_t p; asm("createpolicy.fractional.L2::evict_unchanged.b64 %0, 1.0;" : "=l"(p)); return p; }
__device__ __forceinline__ void e_tma2d(uint32_t dst, const CUtensorMap* m, int c0, int c1, uint32_t bar, uint64_t pol) {
    asm volatile("{.reg .pred p; elect.sync _|p, 0xffffffff;\n @p cp.async.bulk.tensor.2d.shared::cluster.global.mbarrier::complete_tx::bytes.L2::cache_hint [%0], [%1, {%3, %4}], [%2], %5;}"
                 ::"r"(dst), "l"(m), "r"(bar), "r"(c0), "r"(c1), "l"(pol) : "memory");
}
__device__ __forceinline__ void e_tma2d_mc(uint32_t dst, const CUtensorMap* m, int c0, int c1, uint32_t bar, uint64_t pol) {
    asm volatile("{.reg .pred p; elect.sync _|p, 0xffffffff;\n @p cp.async.bulk.tensor.2d.shared::cluster.global.mbarrier::complete_tx::bytes.multicast::cluster.L2::cache_hint [%0], [%1, {%3, %4}], [%2], %5, %6;}"
                 ::"r"(dst), "l"(m), "r"(bar), "r"(c0), "r"(c1), "h"((uint16_t)3), "l"(pol) : "memory");
}
__device__ __forceinline__ void e_prefetch(const void* p, uint32_t bytes) {
    asm volatile("{.reg .pred p; elect.sync _|p, 0xffffffff; @p cp.async.bulk.prefetch.L2.global [%0], %1;}" ::"l"(p), "r"(bytes) : "memory");
}
__device__ __forceinline__ uint32_t wait_count_w(const uint32_t* p, uint32_t target) {
    int it = 0;
#pragma unroll 1
    while (true) {
        uint32_t v;
        asm volatile("ld.acquire.gpu.global.u32 %0, [%1];" : "=r"(v) : "l"(p) : "memory");
        if (__all_sync(~0u, v >= target)) return v;
        spin_guard(++it);
    }
}

__device__ __forceinline__ uint4 pack8(const float* x) {
    return make_uint4(pack2(x[0], x[1]), pack2(x[2], x[3]), pack2(x[4], x[5]), pack2(x[6], x[7]));
}
#define NL 6
constexpr uint32_t HCH = 5120, HBUF = 8 * HCH;
constexpr uint32_t SM_SX = 0, SM_ST = 2560, SM_OX = 8192, SM_LX = 10240, SM_PX = 11392, SM_PA = 12288, SM_VF = 18432, SM_TAB = 26624, SM_WL2 = 41984, SM_HB = 49152, SM_WO = 131072,
                   SM_WL = 196608, SM_PRE = SM_WL, SM_BAR = 227328, SM_TRC = SM_BAR + 256, SM_REC_TOTAL = SM_TRC + 2688;
__host__ __device__ constexpr uint32_t sm_wl(int i) { return i < 5 ? SM_WL + i * 6144 : SM_WL2; }
constexpr uint32_t SB0 = 1024;
constexpr int B_WO = 0, B_HE = 1, B_ROLE = 2, B_HB = 3, B_W = 5;
constexpr int NB_MEM = 1, NB_QK = 2, NB_X1 = 3, NB_X2 = 4, NB_WIN = 5, NB_WG = 6, NB_KDONE = 7, NB_FIN0 = 8, NB_LN = 9, NB_MEM2 = 10, NB_H = 11, NB_A = 12, NB_B = 13, NB_C = 14, NB_F = 15;
#define TPV_DLY 4
#define L_AT 1
#define D_X2 300
#define NPF1 6
#define NPF 11
#define T_GO 29
#define GATE_AT 25
#define T_X2 1875
#define T_V 300
#define VP_AT 1
#define PD 4
#define PV_FENCE 0
#define SSG 4
#define SSG_V 5
#define SS0_K 4
#define SS0_V 6
#define NPF0 4
#define STG_FENCE 1
#define WO_AT 0x1100
#define W_SPEC 6
#define NO_GUESS 0
#define NPF2 9
#define PF_DLY 6
#define H_D 225
#define PIN_EPI 1

#define PROF_INIT
#define PROF(i)
#define PROFV(i, v)
#define PROF_OUT

__device__ __forceinline__ uint32_t clk32() { uint32_t t; asm volatile("mov.u32 %0, %%clock;" : "=r"(t) :: "memory"); return t; }
__device__ __forceinline__ uint32_t gtime32() { uint32_t t; asm volatile("mov.u32 %0, %%globaltimer_lo;" : "=r"(t) :: "memory"); return t; }
__device__ __forceinline__ void spin_until(uint32_t t0, uint32_t d) { while (clk32() - t0 < d) {} }
template <int N> __device__ __forceinline__ uint32_t delay(uint32_t zero) {
    float x = __uint_as_float(clk32());
#pragma unroll
    for (int i = 0; i < N; i++) asm volatile("ex2.approx.ftz.f32 %0, %0;" : "+f"(x));
    return __float_as_uint(x) & zero;
}
__device__ __forceinline__ uint32_t clk_after(uint32_t x, uint32_t zero) {
    unsigned long long c = 0;
    asm volatile("{.reg .pred p; setp.eq.u32 p, %1, 0; @p mov.u64 %0, %%clock64;}" : "+l"(c) : "r"(x & zero) : "memory");
    return (uint32_t)c;
}
__device__ __forceinline__ uint32_t later(uint32_t a, uint32_t b) { return a + max((int)(b - a), 0); }
__device__ __forceinline__ void wait_clk(uint32_t t) {
#pragma unroll 1
    while (true) {
        unsigned long long c;
        asm volatile("mov.u64 %0, %%clock64;" : "=l"(c) :: "memory");
        if ((int)((uint32_t)c - t) >= 0) break;
    }
}
__device__ __forceinline__ uint32_t opaque(uint32_t v) { return __shfl_sync(~0u, v, threadIdx.x & 31); }
__device__ __forceinline__ uint32_t xor_or(uint32_t a, uint32_t b, uint32_t t) {
    uint32_t r; asm volatile("lop3.b32 %0, %1, %2, %3, 0x7E;" : "=r"(r) : "r"(a), "r"(b), "r"(t)); return r;
}
__device__ __forceinline__ uint32_t or3(uint32_t a, uint32_t b, uint32_t c) {
    uint32_t r; asm volatile("lop3.b32 %0, %1, %2, %3, 0xFE;" : "=r"(r) : "r"(a), "r"(b), "r"(c)); return r;
}
__device__ __forceinline__ uint32_t settag(uint32_t v, uint32_t tag) {
    uint32_t r; asm("lop3.b32 %0, %1, 1, %2, 0xB8;" : "=r"(r) : "r"(v), "r"(tag)); return r;
}
__device__ __forceinline__ void ldg4_if(uint4& v, const void* p, bool c) {
    asm volatile("{.reg .pred p; setp.ne.u32 p, %5, 0; @p ld.relaxed.gpu.global.v4.u32 {%0,%1,%2,%3}, [%4];}"
                 : "+r"(v.x), "+r"(v.y), "+r"(v.z), "+r"(v.w) : "l"(p), "r"((uint32_t)c) : "memory");
}
__device__ __forceinline__ uint4 ldg_rlx2x2(const void* p) {
    unsigned long long a, b;
    asm volatile("ld.relaxed.gpu.global.v2.b64 {%0,%1}, [%2];" : "=l"(a), "=l"(b) : "l"(p) : "memory");
    return make_uint4((uint32_t)a, (uint32_t)(a >> 32), (uint32_t)b, (uint32_t)(b >> 32));
}
__device__ __forceinline__ void stg_rlx2x2(void* p, uint32_t x, uint32_t y, uint32_t z, uint32_t w) {
    asm volatile("{.reg .b64 a, b; mov.b64 a, {%1,%2}; mov.b64 b, {%3,%4}; st.relaxed.gpu.global.v2.b64 [%0], {a, b};}" ::"l"(p), "r"(x), "r"(y), "r"(z), "r"(w) : "memory");
}
__device__ __forceinline__ void ldg1_if(uint32_t& v, const void* p, bool c) {
    asm volatile("{.reg .pred p; setp.ne.u32 p, %2, 0; @p ld.relaxed.gpu.global.u32 %0, [%1];}" : "+r"(v) : "l"(p), "r"((uint32_t)c) : "memory");
}
__device__ __forceinline__ void sts2(uint32_t a, float x, float y) { asm volatile("st.shared.v2.f32 [%0], {%1,%2};" ::"r"(a), "f"(x), "f"(y) : "memory"); }
__device__ __forceinline__ void sts4f(uint32_t a, float x, float y, float z, float w) {
    asm volatile("st.shared.v4.f32 [%0], {%1,%2,%3,%4};" ::"r"(a), "f"(x), "f"(y), "f"(z), "f"(w) : "memory");
}
__device__ __forceinline__ void sts1(uint32_t a, uint32_t x) { asm volatile("st.shared.u32 [%0], %1;" ::"r"(a), "r"(x) : "memory"); }
__device__ __forceinline__ uint32_t lds1(uint32_t a) { uint32_t v; asm volatile("ld.shared.u32 %0, [%1];" : "=r"(v) : "r"(a) : "memory"); return v; }
__device__ __forceinline__ float4 lds4f(uint32_t a) {
    float4 v; asm volatile("ld.shared.v4.f32 {%0,%1,%2,%3}, [%4];" : "=f"(v.x), "=f"(v.y), "=f"(v.z), "=f"(v.w) : "r"(a) : "memory"); return v;
}
__device__ __forceinline__ float2 lds2f(uint32_t a) {
    float2 v; asm volatile("ld.shared.v2.f32 {%0,%1}, [%2];" : "=f"(v.x), "=f"(v.y) : "r"(a) : "memory"); return v;
}
__device__ __forceinline__ bool any_bit0(uint32_t x) {
    uint32_t r;
    asm volatile("{.reg .pred p, q; .reg .b32 t; and.b32 t, %1, 1; setp.ne.u32 p, t, 0; vote.sync.any.pred q, p, 0xffffffff; selp.u32 %0, 1, 0, q;}" : "=r"(r) : "r"(x));
    return r;
}
__device__ __forceinline__ float rcp_fast(float x) { float r; asm("rcp.approx.ftz.f32 %0, %1;" : "=f"(r) : "f"(x)); return r; }
__device__ __forceinline__ void stsm4(uint32_t a, uint32_t r0, uint32_t r1, uint32_t r2, uint32_t r3) {
    asm volatile("stmatrix.sync.aligned.m8n8.x4.shared.b16 [%0], {%1,%2,%3,%4};" ::"r"(a), "r"(r0), "r"(r1), "r"(r2), "r"(r3) : "memory");
}
__device__ __forceinline__ void stsm4t(uint32_t a, uint32_t r0, uint32_t r1, uint32_t r2, uint32_t r3) {
    asm volatile("stmatrix.sync.aligned.m8n8.x4.trans.shared.b16 [%0], {%1,%2,%3,%4};" ::"r"(a), "r"(r0), "r"(r1), "r"(r2), "r"(r3) : "memory");
}
__device__ __forceinline__ void stg_b64_if(bool c, void* p, uint32_t x, uint32_t y) {
    asm volatile("{.reg .pred p; .reg .b64 a; setp.ne.u32 p, %3, 0; mov.b64 a, {%1,%2}; @p st.relaxed.gpu.global.b64 [%0], a;}" ::"l"(p), "r"(x), "r"(y), "r"((uint32_t)c) : "memory");
}
__device__ __forceinline__ void cp_async16(uint32_t dst, const void* src) { asm volatile("cp.async.cg.shared.global [%0], [%1], 16;" ::"r"(dst), "l"(src) : "memory"); }
__device__ __forceinline__ void cp_async16_ef(uint32_t dst, const void* src) {
    asm volatile("cp.async.cg.shared.global.L2::cache_hint [%0], [%1], 16, %2;" ::"r"(dst), "l"(src), "l"(evict_first()) : "memory");
}
__device__ __forceinline__ uint32_t prmt(uint32_t a, uint32_t b, uint32_t c) { uint32_t r; asm("prmt.b32 %0, %1, %2, %3;" : "=r"(r) : "r"(a), "r"(b), "r"(c)); return r; }
__device__ __forceinline__ uint32_t hadd2h(uint32_t a, uint32_t b) { uint32_t r; asm("add.rn.f16x2 %0, %1, %2;" : "=r"(r) : "r"(a), "r"(b)); return r; }
__device__ __forceinline__ uint32_t hmin2h(uint32_t a, uint32_t b) { uint32_t r; asm("min.f16x2 %0, %1, %2;" : "=r"(r) : "r"(a), "r"(b)); return r; }
__device__ __forceinline__ uint32_t hmax2h(uint32_t a, uint32_t b) { uint32_t r; asm("max.f16x2 %0, %1, %2;" : "=r"(r) : "r"(a), "r"(b)); return r; }
__device__ __forceinline__ uint32_t max3u(uint32_t a, uint32_t b, uint32_t c) { return __vimax3_u32(a, b, c); }
__device__ __forceinline__ void fence_gpu() { asm volatile("fence.acq_rel.gpu;" ::: "memory"); }

__device__ __forceinline__ void h_load(uint32_t sb, const uint8_t* hsrc, int pass, uint32_t rank, uint32_t rot, uint32_t wq, bool arm = true, uint32_t skip = 0) {
    const uint32_t bar = sb + SM_BAR + 8 * (B_HB + (pass & 1)), c = (wq + rot) & 3, dst = sb + SM_HB + (pass & 1) * HBUF + (rank * 4 + c) * HCH + skip;
    const uint8_t* src = hsrc + ((size_t)pass * 65536 + c * 4096 + skip);
    if (arm && wq == 0) e_expect(bar, 32768 - 8 * skip);
    asm volatile("{.reg .pred p; elect.sync _|p, 0xffffffff;\n"
                 " @p cp.async.bulk.shared::cluster.global.mbarrier::complete_tx::bytes.multicast::cluster.L2::cache_hint [%0], [%1], %4, [%2], %3, %5;}"
                 ::"r"(dst), "l"(src), "r"(bar), "h"((uint16_t)3), "r"(4096 - skip), "l"(evict_first()) : "memory");
}
__device__ __forceinline__ uint4 ldg_b128(const void* p) {
    uint4 v;
    asm volatile("{.reg .b128 t; .reg .b64 a, b; ld.relaxed.gpu.global.b128 t, [%4]; mov.b128 {a, b}, t; mov.b64 {%0,%1}, a; mov.b64 {%2,%3}, b;}"
                 : "=r"(v.x), "=r"(v.y), "=r"(v.z), "=r"(v.w) : "l"(p) : "memory");
    return v;
}
__device__ __forceinline__ void stg_b128_if(bool c, void* p, uint32_t x, uint32_t y, uint32_t z, uint32_t w) {
    asm volatile("{.reg .pred p; .reg .b128 t; .reg .b64 a, b; setp.ne.u32 p, %5, 0; mov.b64 a, {%1,%2}; mov.b64 b, {%3,%4}; mov.b128 t, {a, b}; @p st.relaxed.gpu.global.b128 [%0], t;}"
                 ::"l"(p), "r"(x), "r"(y), "r"(z), "r"(w), "r"((uint32_t)c) : "memory");
}
__device__ __forceinline__ float pretag(float x, uint32_t add, uint32_t keep) { return __uint_as_float((__float_as_uint(x) + add) & keep); }

template <bool MASK, class F>
__device__ __forceinline__ void softmax_rows(uint32_t src, uint32_t dst, uint32_t g16, int row0, F mid) {
    const uint32_t u = (g16 >> 7) & 3, e = ((g16 >> 9) << 3) | ((g16 >> 4) & 7);
    const uint32_t se = src + e * 8, su = se + u * 1088;
    const float2 p0 = lds2f(su), p1 = lds2f(su + 256), p2 = lds2f(su + 512), p3 = lds2f(su + 768);
    const float2 m0 = lds2f(se + 4352), m1 = lds2f(se + 4352 + 256), m2 = lds2f(se + 4352 + 512), m3 = lds2f(se + 4352 + 768);
    float a0 = (p0.x + p1.x) + (p2.x + p3.x), a1 = (p0.y + p1.y) + (p2.y + p3.y);
    const float a2 = (m0.x + m1.x) + (m2.x + m3.x), a3 = (m0.y + m1.y) + (m2.y + m3.y);
    mid(__float_as_uint(a3));
    if (MASK) {
        const int vis = row0 + (e >> 2) - 2 * (e & 3) - 8 * u;
        if (vis < 0) a0 = -1e9f / 0.08838834764831845f;
        if (vis < 1) a1 = -1e9f / 0.08838834764831845f;
    }
    int k = __float_as_int(fmaxf(fmaxf(a0, a1), fmaxf(a2, a3)));
    k ^= (k >> 31) & 0x7fffffff;
    const bool hi = g16 & 64;
    const int k0 = __reduce_max_sync(~0u, hi ? INT_MIN : k), k1 = __reduce_max_sync(~0u, hi ? k : INT_MIN);
    k = hi ? k1 : k0;
    const float m = __int_as_float(k ^ ((k >> 31) & 0x7fffffff));
    const float sl2 = 0.08838834764831845f * 1.4426950408889634f, mb = -m * sl2;
    sts1(dst + e * 16 + u * 4, pack2(ex2(fmaf(a0, sl2, mb)), ex2(fmaf(a1, sl2, mb))));
    sts1(dst + 512 + e * 4, pack2(ex2(fmaf(a2, sl2, mb)), ex2(fmaf(a3, sl2, mb))));
}

__device__ __forceinline__ uint32_t pack_h2(float lo, float hi) {
    uint32_t r; asm("cvt.rn.satfinite.f16x2.f32 %0, %1, %2;" : "=r"(r) : "f"(hi), "f"(lo)); return r;
}
__device__ __forceinline__ float2 unpack_h2(uint32_t u) {
    float2 r; asm("{.reg .b16 l, h; mov.b32 {l, h}, %2; cvt.f32.f16 %0, l; cvt.f32.f16 %1, h;}" : "=f"(r.x), "=f"(r.y) : "r"(u)); return r;
}
__device__ __forceinline__ uint32_t h2bf(uint32_t u) {
    uint32_t r;
    asm volatile("{.reg .b16 l, h; .reg .f32 a, b; mov.b32 {l, h}, %1; cvt.f32.f16 a, l; cvt.f32.f16 b, h; cvt.rn.bf16x2.f32 %0, b, a;}" : "=r"(r) : "r"(u));
    return r;
}
__device__ __forceinline__ void red_h8(void* p, uint32_t x, uint32_t y, uint32_t z, uint32_t w) {
    asm volatile("red.relaxed.gpu.global.add.noftz.v4.f16x2 [%0], {%1,%2,%3,%4};" ::"l"(p), "r"(x), "r"(y), "r"(z), "r"(w) : "memory");
}
__device__ __forceinline__ void red_h2_if(bool c, void* p, uint32_t x) {
    asm volatile("{.reg .pred p; setp.ne.u32 p, %2, 0; @p red.relaxed.gpu.global.add.noftz.f16x2 [%0], %1;}" ::"l"(p), "r"(x), "r"((uint32_t)c) : "memory");
}
__device__ __forceinline__ void red_h10(bool c, void* p, void* q, uint32_t x, uint32_t y, uint32_t z, uint32_t w, uint32_t e) {
    asm volatile("{.reg .pred p; setp.ne.u32 p, %7, 0; red.relaxed.gpu.global.add.noftz.v4.f16x2 [%0], {%2,%3,%4,%5};\n"
                 " @p red.relaxed.gpu.global.add.noftz.f16x2 [%1], %6;}" ::"l"(p), "l"(q), "r"(x), "r"(y), "r"(z), "r"(w), "r"(e), "r"((uint32_t)c) : "memory");
}
constexpr float Q_SCALE = 1024.0f;
constexpr float SM_L2E = 0.08838834764831845f * 1.4426950408889634f * Q_SCALE;
template <int V> struct IC { static constexpr int value = V; };
typedef unsigned long long u64;
__device__ __forceinline__ uint32_t lo32(u64 v) { return (uint32_t)v; }
__device__ __forceinline__ uint32_t hi32(u64 v) { return (uint32_t)(v >> 32); }
__device__ __forceinline__ u64 ldg_u64(const void* p) { u64 v; asm volatile("ld.relaxed.gpu.global.b64 %0, [%1];" : "=l"(v) : "l"(p) : "memory"); return v; }
__device__ __forceinline__ void ldg_u64_if(u64& v, const void* p, bool c) {
    asm volatile("{.reg .pred p; setp.ne.u32 p, %2, 0; @p ld.relaxed.gpu.global.b64 %0, [%1];}" : "+l"(v) : "l"(p), "r"((uint32_t)c) : "memory");
}
struct RecTime { uint32_t go, x2, v, dx2, h; };
__device__ __forceinline__ void rec_main(uint32_t sb, const CUtensorMap* tWo, uint8_t* arena, int role, int hinfo, int wg, uint32_t zero, const RecTime& tm) {
    const int hA = hinfo & 255;
    const int tid = threadIdx.x, t = tid & 127, lane = tid & 31, wi = t >> 5;
    const uint32_t bars = sb + SM_BAR;
    const int head = role >> 2, qd = role & 3, j = blockIdx.x & 1, kh = role & 1;
    const uint32_t mypar = head >= hA;
    const uint32_t wiu = __reduce_max_sync(~0u, wi);
    const bool warp0 = wiu == 0;
    const uint8_t* hsrc = (const uint8_t*)g_himg + kh * 32768 + j * 16384;
    auto tokbase = [&](int ty) { return ((ty + 1) << 21) + blk(lb_tok(head), mypar ^ ((hinfo >> (8 + ty)) & 1)); };
    const uint32_t tbw = tokbase(wg), tbq = tokbase(0) + (qd >> 1) * 2048 + (qd & 1) * 8;
#define KS(p) (4 * (((p) >> 1) & 7) + ((p) >> 4) + 2 * ((p) & 1))
    uint32_t w[32 - NL][4];
    uint4 wl5;
    if (wg == 2) bar_arrive(NB_WIN, 384);
    const uint32_t po = (1 << 20) + j * 16384 + kh * 2048;
    const uint32_t c16 = kh * 2048 + ((2 * j + (wi >> 1)) * 32 + lane) * 16, xso = blk(lb_x2(head), mypar);
    const uint32_t x2o = xso + wg * 16384 + (wi & 1) * 2048 + (c16 >> 1), tko = tbw + (wi & 1) * 16384 + c16;
    {
        stg_rlx2(arena + x2o, 0, 0);
#pragma unroll
        for (int i = 0; i < 4; i++) stg_rlx4(arena + ((i & 1 ? tko : tbw + (po ^ 2048) + t * 16) + (i >> 1) * 32768), 0, 0, 0, 0);
    }
    const uint32_t frow = ((lane >> 4) * 8 + (lane & 7)) * 128, fx = ((lane >> 3) & 1) ^ (lane & 7);
    {
#pragma unroll 1
        for (int i = 0; i < 4; i++) mbar_wait_w(bars + 8 * (B_W + (wg == 2 ? 8 + i : 2 * i + wg)), 0);
        const uint32_t stg = sb + wg * 65536;
#pragma unroll
        for (int p = NL; p < 32; p++) ldsm4t(w[p - NL], stg + KS(p) * 2048 + frow + ((fx ^ (2 * wi)) << 4));
#pragma unroll
        for (int i = 0; i < NL; i++) {
            wl5 = lds4(stg + KS(i) * 2048 + t * 16);
            if (i < 5) sts4(sb + sm_wl(i) + tid * 16, wl5.x, wl5.y, wl5.z, wl5.w);
        }
        fence_async_smem();
        if (wg < 2) bar_sync(NB_WG, 256);
        if (wg > 0) wait_count_w(&g_tick[32 + (lane & 3) * 8], wg);
        if (wg == 1) {
            mbar_arrive_cluster_if(t == 0, bars + 8 * B_HE, j ^ 1);
            asm volatile("fence.proxy.async.global;" ::: "memory");
            mbar_wait_w(bars + 8 * B_HE, 0);
#pragma unroll 1
            for (int i = 0; i < 2; i++) h_load(sb, hsrc, i, j, head, wiu, true, i ? 0 : 2048);
        }
        TL(3 + wg)
    }
    uint32_t g16 = opaque(t * 16);
    {
        const uint32_t wr = ((wg * 4 + wi) ^ head) & 7;
        const uint32_t pc = wg < 2 ? acc_piece(wr >> 2, qd, wr & 3) : acc_piece(kh, wi, 0);
        const uint32_t lm = sb + SM_HB + 4096 + (lane & 7) * 128;
        const uint32_t a0 = wg < 2 ? sb + SM_WL + wg * 2048 + frow + ((fx ^ (2 * wi)) << 4) : blk(LB_STAMP + (wi >> 1), mypar) + stamp_line(wi, lane >> 3) + (lane & 7) * 16;
        const uint32_t a1 = pc + lane * 16;
        const uint32_t a2 = wg < 2 ? pc + 512 + (lane >> 3) * 4 : (role >> 2) * 1024 + (lane < 8 ? (role & 3) * 128 : 384) + lane * 16;
        const uint32_t a3 = wg < 2 ? sb + SM_WO + (wr >> 2) * 32768 + frow + ((fx ^ (2 * (wr & 3))) << 4) : qd * 65536 + head * 2048 + wi * 512 + lane * 4;
        const uint32_t a4 = wg < 2 ? lm + ((fx ^ ((lane >> 4) * 4)) << 4) : lm + (fx << 4) + ((lane >> 4) + 2 * wi) * HCH;
        if (wg < 2) bar_arrive(NB_X2, 384);
        else bar_sync(NB_X2, 384);
        if (NL > 5) {
            sts4(sb + SM_WL2 + tid * 16, wl5.x, wl5.y, wl5.z, wl5.w);
            fence_async_smem();
            bar_sync(NB_WG + 1 + wg, 128);
        }
        sts4(sb + SM_TAB + wg * 5120 + g16, a0, x2o,
             wg ? xso + (wg == 2 ? 32768 : 0) + t * 8 : blk(LB_STAMP + ((lane >> 1) & 1), (lane >> 2) & 1) + stamp_line(lane, qd) + head * 4, tko);
        sts4(sb + SM_TAB + wg * 5120 + 2048 + g16, a1, a2, a3, a4);
        sts2(sb + SM_TAB + wg * 5120 + 4096 + t * 8, __uint_as_float(tbw + t * 16), __uint_as_float((wg ? tbq : tokbase(1)) + t * 16));
    }
    const uint32_t ONES = 0x3f803f80u, tabw = sb + SM_TAB + wg * 5120;
#define LAST ((g16 & 0x70) == 0x70)
    PROF_INIT

    auto pa_ptr = [&](int p) { return arena + (((p & 1) ^ 1) * 32768 + po + lds1(tabw + 4096 + (g16 >> 1))); };
    auto pa_request = [&](int p) { cp_async16(sb + SM_PA + wg * 2048 + g16, pa_ptr(p)); };
    auto pa_get = [&](int p) {
        asm volatile("cp.async.wait_all;" ::: "memory");
        uint4 pa = lds4(sb + SM_PA + wg * 2048 + g16);
        int it = 0;
#pragma unroll 1
        while (any_bit0(pa.x ^ ((p - 1) >> 1) ^ 1) && p > 0 && p <= NSEG) { pa = ldg_b128(pa_ptr(p)); spin_guard(++it); }
        return pa;
    };
    auto pass_init = [&](float* acc, int n, uint4 pa) {
#pragma unroll
        for (int i = 0; i < 4; i++) { acc[2 * i] = bflo((&pa.x)[i]); acc[2 * i + 1] = bfhi((&pa.x)[i]); }
#pragma unroll
        for (int i = 8; i < n; i++) acc[i] = 0.f;
    };
    auto pass_run = [&](auto vc, int p, float* acc, auto mid) {
        constexpr bool V = decltype(vc)::value;
#define HB(ks) dadd(mkdesc(SB0 + SM_HB + ((ks) >> 2) * HCH + ((ks) & 3) * 32, 16, 1024, 1), (p & 1) * (HBUF / 16))
        wg_fence();
#pragma unroll
        for (int i = 0; i < 32; i++) {
            constexpr int GAP = V ? SSG_V : SSG, SS0 = V ? SS0_V : SS0_K;
            const int u = i < SS0 ? 0 : (i - SS0 + GAP - 1) / GAP, q = i - (u < NL ? u : NL);
            if (i >= SS0 && (i - SS0) % GAP == 0 && u < NL) wgmma_tok_ss<V>(acc, dadd(mkdesc(SB0 + sm_wl(u), 8192, 1024, 1), (V ? 2 : wg) * 128), HB(KS(u)));
            else wgmma_tok_rs<V>(acc, w[q], HB(KS(NL + q)), 1);
            mid(i);
        }
        wg_commit();
    };
    auto pass_out = [&](auto tc, int p, float* acc, auto mid) {
        constexpr int TY = decltype(tc)::value;
        const bool V = TY == 2 || (TY == 4 && wg == 2), Q = TY >= 3 && wg == 0;
        const int b = p & 1, s = p - 2;
        (void)s;
        const uint32_t ftag = (((p - 1) >> 1) & 1) ^ 1, ptag = ((p >> 1) & 1) ^ 1;
        const bool tg = V || !(g16 & 64);
        const uint32_t add = tg ? (ftag ^ 1) << 16 : 0u, keep = tg ? 0xfffe0000u : ~0u;
        const uint32_t add1 = V ? 0u : add, keep1 = V ? ~0u : keep;
        const uint32_t add2 = Q ? add : 0u, keep2 = Q ? keep : ~0u;
        uint8_t* pdst = arena + (b * 32768 + (po ^ 2048) + lds1(tabw + 4096 + (g16 >> 1)));
        uint8_t* fdst = arena + ((b ^ 1) * 32768 + lds1(tabw + 12 + g16));
        if (PIN_EPI) asm volatile("" : "+l"(pdst), "+l"(fdst));
        mid(0);
        uint32_t r0 = pack2(pretag(acc[0], add, keep), pretag(acc[1], add1, keep1));
        uint32_t r1 = pack2(acc[2], acc[3]), r3 = pack2(acc[6], acc[7]);
        uint32_t r2 = pack2(pretag(acc[4], add2, keep2), pretag(acc[5], add2, keep2));
        if (!V) { r0 = movm(r0); r1 = movm(r1); r2 = movm(r2); r3 = movm(r3); }
        mid(1);
        stg_b128_if(p < NSEG, pdst, settag(pack2(pretag(acc[8], (ptag ^ 1) << 16, 0xfffe0000u), acc[9]), ptag), pack2(acc[10], acc[11]), pack2(acc[12], acc[13]), pack2(acc[14], acc[15]));
        stg_b128_if(p > 0 && p <= NSEG, fdst, settag(r0, ftag), r1, Q ? settag(r2, ftag) : r2, r3);
        PROF(10)
    };
    auto nop = [](int) {};
    auto wait0 = [](int i) { if (i == 0) wg_wait<0>(); };
    uint4 tf[2][2];
    auto load_tok = [&](int s, uint32_t o) {
        const uint8_t* ts = arena + ((s & 1) * 32768 + o);
#pragma unroll
        for (int a = 0; a < 2; a++)
#pragma unroll
            for (int b = 0; b < 2; b++) tf[a][b] = ldg_b128(ts + a * 16384 + b * 2048);
    };

    auto wo_load = [&](int stage) {
        if (wg == 2 && ((WO_AT >> (4 * wiu)) & 15) == stage) {
            const int c0 = (wiu >> 1) * 512 + qd * 128 + (wiu & 1) * 64;
            e_expect(bars + 8 * B_WO, 16384);
            e_tma2d(sb + SM_WO + wiu * 16384, tWo, c0, head * DH, bars + 8 * B_WO, evict_normal());
            e_tma2d(sb + SM_WO + wiu * 16384 + 8192, tWo, c0, head * DH + 64, bars + 8 * B_WO, evict_normal());
        }
    };
#pragma unroll 1
    for (int p = 0; p <= (wg >> 1); p++) {
        mbar_wait_w(bars + 8 * (B_HB + p), 0);
        float acc[16];
        pass_init(acc, 16, pa_get(p));
        if (wg == 2) TX(2 + 3 * p)
        wo_load(p);
        pass_run(IC<0>(), p, acc, nop);
        if (p) {
            mbar_wait_w(bars + 8 * B_HE, 1);
            asm volatile("fence.proxy.async.global;" ::: "memory");
            h_load(sb, hsrc, 2, j, head, wiu);
        }
        pass_out(IC<4>(), p, acc, wait0);
        if (wg < 2) {
            bar_arrive(NB_C, 384);
            if (wg == 0) bar_arrive(NB_WIN, 384);
        } else if (p == 0) {
            TX(3)
            bar_sync(NB_C, 384);
            mbar_arrive_cluster_if(g16 == 0, bars + 8 * B_HE, j ^ 1);
        }
        pa_request(p + 1);
    }
    if (wg < 2) {
        mbar_wait_w(bars + 8 * (B_HB + 1), 0);
        uint4 pa = pa_get(1);
        uint32_t wl = lds1(tabw + g16);
#pragma unroll 1
        for (int s = 0; s < NSEG; s++) {
            uint32_t w0[NL][4], xo, lm, fz = 0;
            float acc[16];
#pragma unroll
            for (int i = 0; i < 4; i++)
                asm volatile("shl.b32 %0, %4, 16; and.b32 %1, %4, 0xffff0000; mov.b32 %2, %5; mov.b32 %3, %5;"
                             : "=&f"(acc[2 * i]), "=f"(acc[2 * i + 1]), "=f"(acc[8 + 2 * i]), "=f"(acc[9 + 2 * i]) : "r"((&pa.x)[i]), "r"(zero));
#pragma unroll
            for (int i = 0; i < NL; i++) ldsm4t(w0[i], wl + (sm_wl(i) - SM_WL));
            if (wg == 0) bar_sync(NB_B, 256);
            else bar_sync(NB_WIN, 384);
            pass_run(IC<0>(), s + 1, acc, [&](int i) { if (i == GATE_AT && wg) bar_arrive(NB_B, 256); });
            xo = lds1(tabw + 4 + g16);
            lm = lds1(tabw + 2060 + g16) + (s & 1) * HBUF;
            pass_out(IC<3>(), s + 1, acc, [&](int i) {
                if (i == 0) {
                    wg_wait<0>();
                    if (wg == 0) bar_arrive(NB_MEM, 384);
                    fz |= clk32();
                    { const int s_ = s; { const int s = s_ - 1; (void)s; PROF(9) } }
                }
                if (i == 1 && wg) bar_sync(NB_F, 256);
            });
            asm volatile("" : "+r"(lm));
            if (wg == 0) bar_sync(NB_MEM2, 256);
            else bar_sync(NB_MEM, 384);
            PROF(1)
            float c[4][4];
            uint32_t bq[PD][4];
#define MEMF(it) ((lm ^ (((it) >> 3) * 32)) + ((it) & 7) * HCH)
#pragma unroll
            for (int it = 0; it < PD; it++) ldsm4(bq[it], MEMF(it));
#pragma unroll
            for (int it = 0; it < 16; it++) {
                uint32_t* bfr = bq[it % PD];
                const uint32_t* wa = 2 * it < NL ? w0[2 * it < NL ? 2 * it : 0] : w[2 * it < NL ? 0 : 2 * it - NL];
                const uint32_t* wb = 2 * it + 1 < NL ? w0[2 * it + 1 < NL ? 2 * it + 1 : 0] : w[2 * it + 1 < NL ? 0 : 2 * it + 1 - NL];
                float *ca = c[(2 * it) & 3], *cb = c[(2 * it + 1) & 3];
                if (it < 2) { mma16816z(ca, wa, bfr[0], bfr[1]); mma16816z(cb, wb, bfr[2], bfr[3]); }
                else { mma16816(ca, wa[0], wa[1], wa[2], wa[3], bfr[0], bfr[1]); mma16816(cb, wb[0], wb[1], wb[2], wb[3], bfr[2], bfr[3]); }
                if (it + PD < 16) ldsm4(bfr, MEMF(it + PD));
            }
            const float qs = wg ? 1.0f : 1.0f / Q_SCALE;
#define CSUM(e) fmaf(c[2][e] + c[3][e], qs, (c[0][e] + c[1][e]) * qs)
            const uint32_t r0 = pack2(CSUM(0), CSUM(1)), r1 = pack2(CSUM(2), CSUM(3));
            bar_arrive(NB_QK + (r0 & zero), 384);
            stg_rlx2(arena + xo, settag(movm(r0), (s & 1) ^ 1), movm(r1));
            const uint32_t tx = later(lds1(sb + SM_LX + 1040) + tm.x2, clk_after(r0, zero) + tm.dx2);
            g16 |= (fz | tx) & zero;
            PROF(2)
            {
                const uint32_t l16 = sb + (g16 & 0x1f0), g8 = g16 >> 1;
                const uint32_t tag = (s & 1) ^ 1, ttag = ((s >> 1) & 1) ^ 1;
                uint32_t wf[NPF][4], a3;
#define WF(f) (a3 + ((f) & 1) * 16384 + ((f) >> 1) * 2048)
                if (wg == 1) {
                    float sc[5][4];
                    uint4 (&kf)[2][2] = tf;
                    uint32_t qa[2][4], km[4], fz;
                    const uint32_t sd = lds1(sb + SM_TAB + 8 + g16);
                    int it = 0;
                    bool bad;
#pragma unroll 1
                    do {
                        u64 qf[2], x[8];
                        const float2 u = lds2f(tabw + 4096 + g8);
                        load_tok(s, __float_as_uint(u.x));
                        const uint8_t *xp = arena + lds1(tabw + 8 + g16), *tq = arena + ((s & 1) * 32768 + __float_as_uint(u.y));
                        asm volatile("" : "+l"(xp));
                        asm volatile("" : "+l"(tq));
#pragma unroll
                        for (int a = 0; a < 2; a++) qf[a] = ldg_u64(tq + a * 16384);
                        spin_guard(++it);
                        wait_clk(tx);
                        PROF(8)
#pragma unroll
                        for (int i = 0; i < 8; i++) x[i] = ldg_u64(xp + (i >> 2) * 16384 + (i & 3) * 1024);
                        fz = clk32();
                        const uint32_t bt = or3(xor_or(lo32(qf[0]), lo32(qf[1]), ttag), xor_or(kf[0][0].x, kf[0][1].x, ttag), xor_or(kf[1][0].x, kf[1][1].x, ttag));
#pragma unroll
                        for (int a = 0; a < 2; a++) { qa[a][1] = or3(lo32(qf[a]), zero, 0); qa[a][3] = or3(hi32(qf[a]), zero, 0); }
                        fz |= clk32();
#pragma unroll
                        for (int a = 0; a < 2; a++) { qa[a][0] = hadd2v(lo32(x[2 * a]), lo32(x[2 * a + 1])); qa[a][2] = hadd2v(hi32(x[2 * a]), hi32(x[2 * a + 1])); }
#pragma unroll
                        for (int a = 0; a < 2; a++) { km[2 * a] = hadd2v(lo32(x[4 + 2 * a]), lo32(x[5 + 2 * a])); km[2 * a + 1] = hadd2v(hi32(x[4 + 2 * a]), hi32(x[5 + 2 * a])); }
                        bad = any_bit0(or3(or3(bt, xor_or(lo32(x[0]), lo32(x[1]), tag), xor_or(lo32(x[2]), lo32(x[3]), tag)), xor_or(lo32(x[4]), lo32(x[5]), tag), xor_or(lo32(x[6]), lo32(x[7]), tag)));
                    } while (bad);
                    PROFV(13, it - 1)
                    PROF(7)
                    mma16816z(sc[0], qa[0], kf[0][0].x, kf[0][0].y);
                    mma16816z(sc[1], qa[0], kf[0][0].z, kf[0][0].w);
                    mma16816z(sc[2], qa[0], kf[0][1].x, kf[0][1].y);
                    mma16816z(sc[3], qa[0], kf[0][1].z, kf[0][1].w);
                    mma16816z(sc[4], qa[0], km[0], km[1]);
                    mma16816(sc[0], qa[1][0], qa[1][1], qa[1][2], qa[1][3], kf[1][0].x, kf[1][0].y);
                    mma16816(sc[1], qa[1][0], qa[1][1], qa[1][2], qa[1][3], kf[1][0].z, kf[1][0].w);
                    mma16816(sc[2], qa[1][0], qa[1][1], qa[1][2], qa[1][3], kf[1][1].x, kf[1][1].y);
                    mma16816(sc[3], qa[1][0], qa[1][1], qa[1][2], qa[1][3], kf[1][1].z, kf[1][1].w);
                    mma16816(sc[4], qa[1][0], qa[1][1], qa[1][2], qa[1][3], km[2], km[3]);
                    const uint32_t sx = sb + SM_SX + (g16 & 0x1f0) * 5;
                    sts4(sx + (g16 >> 5 & 0x30), pack_h2(sc[0][0], sc[0][1]), pack_h2(sc[1][0], sc[1][1]),
                         pack_h2(sc[2][0], sc[2][1]), pack_h2(sc[3][0], sc[3][1]));
                    sts1(sx + 64 + (g16 >> 7 & 0xc), pack_h2(sc[4][0], sc[4][1]));
                    bar_arrive(NB_X1, 256);
                    if (s == 0) TX(15)
                    const uint32_t now = gtime32();
#pragma unroll
                    for (int n = 0; n < 5; n++) sts2(sb + SM_ST + g8 + n * 1088, sc[n][2], sc[n][3]);
                    bar_arrive(NB_H, 256);
                    PROF(3)
                    a3 = lds1(tabw + 2056 + g16) | (fz & zero);
                    asm volatile("{.reg .pred p; setp.lt.u32 p, %2, 128; @p red.relaxed.gpu.global.max.u32 [%0], %1;}"
                                 ::"l"(arena + sd), "r"(__funnelshift_r(now * 8, s + 1, 8)), "r"(g16) : "memory");
                    if (s == 0) mbar_wait_w(bars + 8 * B_WO, 0);
                    a3 += delay<PF_DLY>(zero);
#pragma unroll
                    for (int f = 0; f < NPF; f++) ldsm4t(wf[f], WF(f));
                } else {
                    if (s == 0) { TL(9) mbar_wait_w(bars + 8 * B_WO, 0); TL(6) }
                    if (warp0 && !(s & 3)) {
                        const uint32_t need = min((s + 4) / 4 + 2, 17), a = sb + SM_LX + 1024 + ((g16 >> 2) & 12);
                        if (s == 0 || __any_sync(~0u, lds1(a) < need)) sts1(a, wait_count_w(&g_tick[32 + ((g16 >> 4) & 3) * 8], need));
                    }
                    a3 = lds1(tabw + 2056 + g16);
#pragma unroll
                    for (int f = 0; f < NPF0; f++) ldsm4t(wf[f], WF(f));
                    const float2 u = lds2f(tabw + 4096 + g8);
                    const uint8_t *q0 = arena + (tag * 32768 + po + __float_as_uint(u.x)), *q1 = arena + (tag * 32768 + po + __float_as_uint(u.y));
                    wait_clk(tx + tm.h);
                    int it = 0;
                    bool bad;
#pragma unroll 1
                    do {
                        const uint4 p0 = ldg_b128(q0), p1 = ldg_b128(q1);
                        spin_guard(++it);
                        wait_clk(tx + tm.v);
#pragma unroll
                        for (int f = NPF0; f < NPF1; f++) ldsm4t(wf[f], WF(f));
                        sts4(sb + SM_PA + g16, p0.x, p0.y, p0.z, p0.w);
                        sts4(sb + SM_PA + 2048 + g16, p1.x, p1.y, p1.z, p1.w);
                        bad = any_bit0(xor_or(p0.x, p1.x, ((s + 1) >> 1) ^ 1)) && s + 2 <= NSEG;
                    } while (bad);
                    bar_sync(NB_H, 256);
                    PROF(3)
                    softmax_rows<true>(sb + SM_ST, sb + SM_PX, g16, qd * 8, [&](uint32_t v) {
                        a3 += v & zero;
#pragma unroll
                        for (int f = NPF1; f < NPF2; f++) ldsm4t(wf[f], WF(f));
                    });
#pragma unroll
                    for (int f = NPF2; f < NPF; f++) ldsm4t(wf[f], WF(f));
                }
                PROF(5)
                float2 ls, a12;
                uint8_t *d0, *d1;
                bar_sync(NB_X2, 384);
                float c[4][4];
#pragma unroll
                for (int q = 0; q < 4; q++) {
                    uint32_t ob[4];
                    ldsm4t(ob, l16 + SM_OX + q * 512);
                    if (q == L_AT) ls = lds2f(sb + SM_LX + g8);
                    if (q == 2) { pa = lds4(sb + SM_PA + wg * 2048 + g16); wl = lds1(tabw + g16); }
                    if (q == 2) { a12 = lds2f(tabw + 2048 + g16); d0 = arena + (acc_slot(s + 1) + __float_as_uint(a12.x)); d1 = arena + (acc_slot(s + 1) + __float_as_uint(a12.y)); }
#pragma unroll
                    for (int f = 4 * q; f < 4 * q + 4; f++) {
                        const uint32_t* a = wf[f % NPF];
                        if (f < 4) mma16816z(c[f], a, ob[f & 2], ob[(f & 2) + 1]);
                        else mma16816(c[f & 3], a[0], a[1], a[2], a[3], ob[f & 2], ob[(f & 2) + 1]);
                        if (f + NPF < 16) ldsm4t(wf[f % NPF], WF(f + NPF));
                    }
                }
                if (wg == 0) bar_arrive(NB_WIN, 384);
                const float i0 = rcp_fast(ls.x), i1 = rcp_fast(ls.y);
                uint32_t v[4];
#pragma unroll
                for (int m = 0; m < 4; m++) v[m] = pack_h2((c[m >> 1][(m & 1) * 2] + c[(m >> 1) + 2][(m & 1) * 2]) * i0, (c[m >> 1][(m & 1) * 2 + 1] + c[(m >> 1) + 2][(m & 1) * 2 + 1]) * i1);
                red_h10(LAST, d0, d1, v[0], v[1], v[2], prmt(v[3], ACC_ONE, LAST ? 0x7610 : 0x3210), prmt(v[3], ACC_ONE, 0x7632));
                g16 |= v[0] & zero;
                PROF(6)
            }
        }
        if (wg) bar_sync(NB_WIN, 384);
    } else {
        TLC(0)
        auto request = [&](int s, uint32_t o) {
            cp_async16(sb + SM_PA + 4096 + g16, arena + (((s & 1) ^ 1) * 32768 + po + o));
            const uint8_t* ts = arena + ((s & 1) * 32768 + o);
#pragma unroll
            for (int i = 0; i < 4; i++) cp_async16(sb + SM_VF + i * 2048 + g16, ts + (i >> 1) * 16384 + (i & 1) * 2048);
        };
        auto fetch = [&](int s, uint4 t1, auto wait, auto after) {
            const uint32_t mo = acc_slot(s) + t1.x, eo = mo - (g16 & 0x1f0) + 512 + ((g16 >> 5) & 12);
            const uint8_t *ms = arena + mo, *es = arena + eo;
            uint32_t e[4] = {0, 0, 0, 0}, sel = LAST ? 0x5410 : 0x3210, dst[4];
#pragma unroll
            for (int i = 0; i < 4; i++) dst[i] = (t1.w + (s & 1) * HBUF) ^ (i * 32);
            asm volatile("" : "+l"(ms), "+l"(es), "+r"(e[0]), "+r"(e[1]), "+r"(e[2]), "+r"(e[3]), "+r"(sel), "+r"(dst[0]), "+r"(dst[1]), "+r"(dst[2]), "+r"(dst[3]));
            uint32_t late = wait(), fz;
            PROF(11) PROFV(0, gtime32())
            int it = 0;
            bool bad;
#pragma unroll 1
            do {
                uint4 m[4];
                uint32_t b = 0;
#pragma unroll
                for (int i = 0; i < 4; i++) {
                    m[i] = ldg_rlx4(ms + i * 1024);
                    ldg1_if(e[i], es + i * 1024, LAST);
                }
                if (it == 0) bar_arrive(NB_F, 256);
                const uint32_t now = clk32();
                fz = now;
                after(now & zero);
                sts1(sb + SM_LX + 1040, now - min(late >> 8, 8u) * 57);
                late = 0;
                spin_guard(++it);
#pragma unroll
                for (int i = 0; i < 4; i++) {
                    if (STG_FENCE >> i & 1) fz |= clk32();
                    b |= xor_or(m[i].w, e[i], ACC_ALL);
                    stsm4t(dst[i], h2bf(m[i].x), h2bf(m[i].y), h2bf(m[i].z), h2bf(prmt(m[i].w, e[i], sel)));
                }
                bad = __any_sync(~0u, LAST && b > 0xffffu);
            } while (bad);
            bar_arrive(NB_MEM, 384);
            bar_arrive(NB_MEM2, 256);
            g16 |= fz & zero;
            PROFV(12, it - 1) PROF(1)
        };
        TX(6)
        fetch(0, lds4(tabw + 2048 + g16), []() { return 0u; }, [&](uint32_t z) { request(0, lds1(tabw + 4096 + (g16 >> 1)) + z); });
        wo_load(2);
        TX(7)
#pragma unroll 1
        for (int s = 0;; s++) {
            const uint32_t tag = (s & 1) ^ 1, ttag = ((s >> 1) & 1) ^ 1, l16 = sb + (g16 & 0x1f0), g8 = g16 >> 1;
            const int p = s + 2;
            if (s == 1) TL(7)
            if (s == 0) TL(13)
            fence_async_smem();
            stg_b128_if(g16 < ((role & 3) ? 128 : 160), arena + (acc_slot(s + 3) + lds1(tabw + 2052 + g16)), 0, 0, 0, 0);
            const uint4 pa = pa_get(p);
            if (p <= NSEG) mbar_wait_w(bars + 8 * (B_HB + (p & 1)), (p >> 1) & 1);
            asm volatile("fence.proxy.async.global;" ::: "memory");
            if (warp0 && s + 3 <= NSEG) e_expect(bars + 8 * (B_HB + ((s + 3) & 1)), 32768);
            uint8_t* xd = arena + lds1(tabw + 4 + g16);
            uint32_t tx;
            float acc[20];
            pass_init(acc, 20, pa);
            if (s == 0) TX(10)
            bar_sync(NB_QK, 384);
            pass_run(IC<1>(), p, acc, nop);
            pass_out(IC<2>(), p, acc, [&](int i) {
                if (i) return;
                wg_wait<0>();
                const uint32_t r0 = pack2(acc[16], acc[17]);
                stg_rlx2(xd, settag(r0, tag), pack2(acc[18], acc[19]));
                tx = clk_after(r0, zero) + 100;
                PROF(2)
            });
            uint4 (&vf)[2][2] = tf;
#pragma unroll
            for (int i = 0; i < 4; i++) vf[i >> 1][i & 1] = lds4(sb + SM_VF + i * 2048 + g16);
            uint32_t xv[4] = {0, 0, 0, 0};
            float oc[2][4], lc[4];
            auto pv = [&](uint32_t p0, uint32_t p1, uint32_t p2, uint32_t p3, uint32_t p4, auto mid) {
                lc[0] = lc[1] = lc[2] = lc[3] = 0.f;
                mma16816z(oc[0], &vf[0][0].x, p0, p1);
                mma16816z(oc[1], &vf[1][0].x, p0, p1);
                mma16816(lc, ONES, ONES, ONES, ONES, p0, p1);
                mma16816(oc[0], vf[0][1].x, vf[0][1].y, vf[0][1].z, vf[0][1].w, p2, p3);
                mma16816(oc[1], vf[1][1].x, vf[1][1].y, vf[1][1].z, vf[1][1].w, p2, p3);
                mma16816(lc, ONES, ONES, ONES, ONES, p2, p3);
                mid();
                mma1688(oc[0], xv[0], xv[1], p4);
                mma1688(oc[1], xv[2], xv[3], p4);
                mma1688(lc, ONES, ONES, p4);
            };
            uint32_t so, to, fz = 0;
            uint4 t1;
            int it = 0;
            bool bad;
#pragma unroll 1
            do {
#pragma unroll 1
                for (int i = it; i > 0; i &= zero) load_tok(s, lds1(tabw + 4096 + g8));
                u64 xr[4];
                const uint8_t* xp = arena + lds1(tabw + 8 + g16);
                asm volatile("" : "+l"(xp));
                const uint32_t bt = or3(xor_or(vf[0][0].x, vf[0][1].x, ttag), xor_or(vf[1][0].x, vf[1][1].x, ttag), 0);
                uint32_t sa = sb + SM_SX + (g16 & 0x1f0) * 5;
                asm volatile("" : "+r"(sa));
                spin_guard(it);
                wait_clk(tx);
                PROF(3)
                if (s == 0 && it == 0) TX(11)
                if (it++ == 0) bar_sync(NB_X1, 256);
                uint4 sx[5];
#pragma unroll
                for (int i = 0; i < 5; i++) sx[i] = lds4(sa + i * 16);
                __syncwarp();
#pragma unroll
                for (int i = 0; i < 4; i++) xr[i] = ldg_u64(xp + (VP_AT == 2 ? sx[0].x & zero : 0) + i * 1024);
                uint32_t a[5], pm[5];
#pragma unroll
                for (int n = 0; n < 5; n++) {
                    uint32_t u[4];
#pragma unroll
                    for (int w = 0; w < 4; w++) u[w] = n < 4 ? (&sx[w].x)[n] : (&sx[4].x)[w];
                    a[n] = hadd2h(hadd2h(u[0], u[1]), hadd2h(u[2], u[3]));
                }
                uint32_t m = hmax2h(hmax2h(hmax2h(a[0], a[1]), hmax2h(a[2], a[3])), a[4]);
                const uint32_t m1 = __shfl_xor_sync(~0u, m, 1), m2 = __shfl_xor_sync(~0u, m, 2), m3 = __shfl_xor_sync(~0u, m, 3);
                m = hmax2h(hmax2h(m, m1), hmax2h(m2, m3));
                so = lds1(tabw + g16); t1 = lds4(tabw + 2048 + g16); to = lds1(tabw + 4096 + g8);
                const float2 mm = unpack_h2(m);
                const float mf = -SM_L2E * fmaxf(mm.x, mm.y);
#pragma unroll
                for (int n = 0; n < 5; n++) { const float2 u = unpack_h2(a[n]); pm[n] = pack2(ex2(fmaf(u.x, SM_L2E, mf)), ex2(fmaf(u.y, SM_L2E, mf))); }
                PROF(4)
                pv(pm[0], pm[1], pm[2], pm[3], pm[4], [&]() {
                    if (PV_FENCE & 1) fz = clk32();
#pragma unroll
                    for (int i = 0; i < 2; i++) { xv[2 * i] = hadd2v(lo32(xr[2 * i]), lo32(xr[2 * i + 1])); xv[2 * i + 1] = hadd2v(hi32(xr[2 * i]), hi32(xr[2 * i + 1])); }
                });
                bad = any_bit0(or3(bt, xor_or(lo32(xr[0]), lo32(xr[1]), tag), xor_or(lo32(xr[2]), lo32(xr[3]), tag)));
                if (PV_FENCE & 2) fz |= clk32();
                stsm4(sb + SM_OX + g16, pack2(oc[0][0], oc[0][1]), pack2(oc[0][2], oc[0][3]), pack2(oc[1][0], oc[1][1]), pack2(oc[1][2], oc[1][3]));
                sts2(sb + SM_LX + g8, lc[0], lc[1]);
            } while (bad);
            if (s == 0) TX(12)
            PROFV(14, it - 1)
            PROF(5)
            bar_sync(NB_X2, 384);
            const uint8_t* sp = arena + so;
            uint4 sv = ldg_rlx4(sp);
            if (s == 0) TX(13)
            if (s + 3 <= NSEG) h_load(sb, hsrc, s + 3, j, head, wiu, false);
            const uint4 pp = lds4(l16 + SM_PX + delay<TPV_DLY>(zero));
            pv(pp.x, pp.y, pp.z, pp.w, lds1(sb + SM_PX + 512 + ((g16 >> 2) & 0x7c)), []() {});
            const float i0 = rcp_fast(lc[0]), i1 = rcp_fast(lc[1]);
            bar_arrive(NB_WIN + ((__float_as_uint(i0) | fz) & zero), 384);
            uint8_t* od = (uint8_t*)g_O + ((size_t)s * (32 * NH * DH * 2) + t1.z);
            const uint32_t ov[4] = {pack2(oc[0][0] * i0, oc[0][1] * i1), pack2(oc[0][2] * i0, oc[0][3] * i1), pack2(oc[1][0] * i0, oc[1][1] * i1), pack2(oc[1][2] * i0, oc[1][3] * i1)};
#pragma unroll
            for (int a = 0; a < 4; a++) if (s + 1 == NSEG) stg_rlx1(od + a * 128, ov[a]);
            PROF(6)
            if (s + 1 == NSEG) break;
            fetch(s + 1, t1, [&]() {
                int it = 0;
#pragma unroll 1
                while (__any_sync(~0u, (int)(min(__vimin3_u32(sv.x, sv.y, sv.z), sv.w) >> 24) <= s)) {
                    sv = ldg_rlx4(sp);
                    spin_guard(++it);
                }
                if (s == 0) TX(14)
                PROFV(15, it)
                const uint32_t tgo = (__reduce_max_sync(~0u, max(max3u(sv.x, sv.y, sv.z), sv.w)) + tm.go + (sv.x & zero)) << 8;
                PROF(7)
                int late;
#pragma unroll 1
                do { late = gtime32() * 8 - tgo; } while (late < 0);
                __syncwarp();
                return (uint32_t)late;
            }, [&](uint32_t z) {
#pragma unroll
                for (int a = 0; a < 4; a++) stg_rlx1(od + a * 128, ov[a]);
                request(s + 1, to + z);
            });
        }
        TL(8) TLC(1)
    }
    asm volatile("cp.async.wait_all;" ::: "memory");
    PROF_OUT
}

struct RecMaps { CUtensorMap wq, wk, wv, wo; };
struct RecPtrs { const bf16 *x, *mem0, *c, *wmod, *w1, *w3; uint8_t* arena; uint32_t zero; RecTime tm; };

__device__ __forceinline__ float silu_bf(const bf16* c, int i) {
    const float v = __bfloat162float(c[i]);
    return bfround(__fdividef(v, 1.0f + __expf(-v)));
}
__device__ __noinline__ void rec_ln(float* coef, const RecPtrs& p, int id, int r0) {
    int r1 = 32;
    const int tid = threadIdx.x;
    const int lane = tid & 31, wid = tid >> 5;
    const uint32_t ring = smem_u32(coef) - SM_PRE + wid * 8192 + lane * 16;
    auto fetch = [&](int r) {
        if (r < r1) {
            const bf16* src = p.x + (size_t)(r * 64 + (id * 8 + wid) * 2) * DM + lane * 8;
#pragma unroll
            for (int i = 0; i < 8; i++) cp_async16(ring + (r & 1) * 4096 + i * 512, src + i * 256);
        }
        asm volatile("cp.async.commit_group;" ::: "memory");
    };
    auto row8 = [&](uint32_t a, float* f) {
        const uint4 v = lds4(a);
        f[0] = bflo(v.x); f[1] = bfhi(v.x); f[2] = bflo(v.y); f[3] = bfhi(v.y); f[4] = bflo(v.z); f[5] = bfhi(v.z); f[6] = bflo(v.w); f[7] = bfhi(v.w);
    };
#pragma unroll 1
    for (int r = r0 - 2; r < r1; r++) {
        if (r >= r0) {
            asm volatile("cp.async.wait_group 1;" ::: "memory");
            const uint32_t a = ring + (r & 1) * 4096;
            float m[2] = {0.f, 0.f}, t[2];
#pragma unroll 1
            for (int ps = 0; ps < 2; ps++) {
                t[0] = t[1] = 0.f;
#pragma unroll 1
                for (int i = 0; i < 4; i++)
#pragma unroll
                    for (int h = 0; h < 2; h++) {
                        float f[8];
                        row8(a + h * 2048 + i * 512, f);
#pragma unroll
                        for (int e = 0; e < 8; e++) { const float d = f[e] - m[h]; t[h] = fmaf(d, ps ? d : 1.0f, t[h]); }
                    }
#pragma unroll
                for (int o = 16; o; o >>= 1) { t[0] += __shfl_xor_sync(~0u, t[0], o); t[1] += __shfl_xor_sync(~0u, t[1], o); }
                if (ps == 0) { m[0] = t[0] * (1.0f / DM); m[1] = t[1] * (1.0f / DM); }
            }
            t[0] = rsqrtf(t[0] * (1.0f / DM) + 1e-5f); t[1] = rsqrtf(t[1] * (1.0f / DM) + 1e-5f);
            if (r == r0) {
#pragma unroll 1
                for (int i = tid; i < 2 * DM / 4; i += 256) {
                    float4 u;
                    int it = 0;
                    uint32_t ok;
#pragma unroll 1
                    do {
                        uint4 v[8];
#pragma unroll
                        for (int k = 0; k < 8; k++) v[k] = ldg_rlx4(g_modp + k * 2 * DM + i * 4);
                        ok = 1;
                        u = make_float4(0.f, 0.f, 0.f, 0.f);
#pragma unroll
                        for (int k = 0; k < 8; k++) {
                            ok &= v[k].x & v[k].y & v[k].z & v[k].w;
                            u.x += __uint_as_float(v[k].x); u.y += __uint_as_float(v[k].y); u.z += __uint_as_float(v[k].z); u.w += __uint_as_float(v[k].w);
                        }
                        spin_guard(++it);
                    } while (!ok);
                    const uint32_t lo = pack2(u.x, u.y), hi = pack2(u.z, u.w);
                    const float one = i >= DM / 4 ? 1.0f : 0.0f;
                    *(float4*)(coef + i * 4) = make_float4(bflo(lo) + one, bfhi(lo) + one, bflo(hi) + one, bfhi(hi) + one);
                }
                bar_sync(NB_FIN0, 256);
                if (tid == 0 && r0 == 0) TL(2)
            }
            const int row = r * 64 + (id * 8 + wid) * 2;
#pragma unroll 1
            for (int i = 0; i < 4; i++) {
                const float4* cf = (const float4*)(coef + i * 256 + lane * 8);
                const float4 s0 = cf[0], s1 = cf[1], c0 = cf[256], c1 = cf[257];
                const float sh[8] = {s0.x, s0.y, s0.z, s0.w, s1.x, s1.y, s1.z, s1.w}, sc[8] = {c0.x, c0.y, c0.z, c0.w, c1.x, c1.y, c1.z, c1.w};
                const int own = ((row >> 4) & 1) == (i >> 1), rr = row & 15;
                const uint32_t off = ((row >> 5) + own) * 65536 + (i * 4 + (lane >> 3)) * 4096 + (rr + (own ? 0 : 16)) * 128 + (((lane & 7) ^ (rr & 7)) << 4);
#pragma unroll
                for (int h = 0; h < 2; h++) {
                    float y[8];
                    row8(a + h * 2048 + i * 512, y);
#pragma unroll
                    for (int e = 0; e < 8; e++) y[e] = fmaf((y[e] - m[h]) * t[h], sc[e], sh[e]);
                    *(uint4*)((uint8_t*)g_himg + (off ^ (h * 144))) = pack8(y);
                }
            }
            if (r == 0) {
                int v, it = 0;
#pragma unroll 1
                do { v = *(volatile int*)((uint8_t*)coef - SM_PRE + SM_BAR + 192); spin_guard(++it); } while (v == INT_MIN);
                if (v >= 0) r1 = 2;
            }
        }
        fetch(r + 2);
        if (r < r0 || (r > 0 && !(r & 1))) continue;
        bar_sync(r == 0 ? NB_C : r == 1 ? NB_FIN0 : NB_LN, r == 0 ? 320 : r == 1 ? 256 : 288);
        if (r < 2 && wid == r) {
            if (r == 1) bar_arrive(NB_B, 64);
            if (lane == 0) { signal_count(&g_tick[32 + id * 8]); TL(13) }
            __syncwarp();
        }
    }
}
template <int NQ, int CG>
__device__ __forceinline__ void side_gemv(const bf16* w, int ld, int ncol, const float* coef, float* red, float* out, int ostride, bool round) {
    constexpr int KG = 384 / CG, W = CG * 8;
    const int tid = threadIdx.x, cg = tid % CG, kg = tid / CG;
    float acc[NQ][8];
#pragma unroll
    for (int q = 0; q < NQ; q++)
#pragma unroll
        for (int j = 0; j < 8; j++) acc[q][j] = 0.f;
    if (cg * 8 < ncol) {
        const bf16* src = w + cg * 8;
        const uint32_t ring = smem_u32(red) + 36864 + tid * 16;
        auto fetch = [&](int k0, int slot) {
#pragma unroll
            for (int i = 0; i < 4; i++)
                if (k0 + i * KG < DM) cp_async16_ef(ring + (slot * 4 + i) * 6144, src + (size_t)(k0 + i * KG) * ld);
            asm volatile("cp.async.commit_group;" ::: "memory");
        };
#pragma unroll 1
        for (int g = 0; g < 5; g++) fetch(kg + g * 4 * KG, g);
#pragma unroll 1
        for (int k0 = kg, slot = 0; k0 < DM; k0 += 4 * KG) {
            fetch(k0 + 20 * KG, slot ? slot - 1 : 5);
            asm volatile("cp.async.wait_group 5;" ::: "memory");
#pragma unroll
            for (int i = 0; i < 4; i++) {
                const int k = k0 + i * KG;
                if (k < DM) {
                    const uint4 v = lds4(ring + (slot * 4 + i) * 6144);
                    const float f[8] = {bflo(v.x), bfhi(v.x), bflo(v.y), bfhi(v.y), bflo(v.z), bfhi(v.z), bflo(v.w), bfhi(v.w)};
#pragma unroll
                    for (int q = 0; q < NQ; q++) {
                        const float cf = coef[q * DM + k];
#pragma unroll
                        for (int j = 0; j < 8; j++) acc[q][j] = fmaf(cf, f[j], acc[q][j]);
                    }
                }
            }
            slot = slot == 5 ? 0 : slot + 1;
        }
    }
    __syncthreads();
#pragma unroll
    for (int q = 0; q < NQ; q++)
#pragma unroll
        for (int j = 0; j < 8; j++) red[(kg * NQ + q) * W + cg * 8 + j] = acc[q][j];
    __syncthreads();
#pragma unroll 1
    for (int i = tid; i < NQ * W; i += 384) {
        const int q = i / W, cidx = i % W;
        float t = 0.f;
#pragma unroll
        for (int k = 0; k < KG; k++) t += red[k * NQ * W + i];
        if (cidx < ncol) out[q * ostride + cidx] = round ? bfround(t) : t;
    }
}
__device__ __noinline__ void rec_side(float* sm, const RecPtrs& p, int id) {
    const int tid = threadIdx.x;
    float *coef = sm, *red = sm + 3 * DM;
    if (tid < 256 && blockIdx.x < 128) rec_ln(sm + SM_PRE / 4, p, id, 2);
    if (tid >> 5 == 8) {
#pragma unroll 1
        for (int n = 1; n < 16; n++) {
            bar_sync(NB_LN, 288);
            if (tid == 256) { if (n == 1) wait_count1(&g_tick[32 + id * 8], 2); signal_count(&g_tick[32 + id * 8]); }
            __syncwarp();
        }
    }
    __syncthreads();
    for (int i = tid; i < 2 * S_; i += 384) g_st[id * 2 * S_ + i] = 0.f;
    if (id == 0) for (int i = tid; i < 2 * 32; i += 384) g_pcnt[i * 8] = 0;
    if (id == 1) for (int i = tid; i < 6 * 256; i += 384) g_pflag[i] = 0;
    for (int i = tid; i < DM; i += 384) { coef[i] = silu_bf(p.c, i); coef[2 * DM + i] = 1.0f; }
    __syncthreads();
    if (tid == 0) TL(3)
    side_gemv<1, 128>(p.wmod + (2 + id) * DM, 6 * DM, DM, coef, red, g_mod + (2 + id) * DM, 0, true);
    __syncthreads();
    if (tid == 0) signal_count(&g_tick[8]);
    if (tid == 0) TL(4)
    side_gemv<1, 128>(p.w3 + id * (FF / 4), FF, FF / 4, coef + 2 * DM, red, g_vec + 3 * DM + id * (FF / 4), 0, false);
    if (tid == 0) wait_count1(&g_tick[8], 4);
    __syncthreads();
    for (int i = tid; i < DM; i += 384) { coef[i] = 1.0f + __ldcg(g_mod + 4 * DM + i); coef[DM + i] = __ldcg(g_mod + 3 * DM + i); }
    __syncthreads();
    if (id == 1 && tid < 32) {
        float t[5] = {0, 0, 0, 0, 0};
        for (int i = tid; i < DM; i += 32) {
            const float a = coef[i], b = coef[DM + i];
            t[0] += a; t[1] += a * a; t[2] += a * b; t[3] += b; t[4] += b * b;
        }
#pragma unroll
        for (int q = 0; q < 5; q++) { const float r = warp_sum(t[q]); if (tid == 0) g_cst[q] = r * (1.0f / DM); }
    }
    side_gemv<3, 32>(p.w1 + id * 256, DM, 256, coef, red, g_vec + id * 256, DM, false);
    if (tid == 0) TL(9)
}

__device__ __forceinline__ void pair_place(int c, int& d, int& pi) {
    const int c7 = ((c - 36) * 37) >> 8;
    d = c < 4 ? 0 : c < 36 ? (c - 4) & 7 : c - 35 - 7 * c7;
    pi = c < 4 ? c : c < 36 ? ((c - 4) >> 3) + (d ? 0 : 4) : 4 + c7;
}
__global__ void __cluster_dims__(2, 1, 1) __launch_bounds__(384, 1)
k_rec(const __grid_constant__ RecMaps mp, const __grid_constant__ RecPtrs p) {
    extern __shared__ uint8_t smraw[];
    const uint32_t sb = smem_u32(smraw);
    if ((sb & 0x3FFFF) != SB0) __trap();
    const uint32_t bars = sb + SM_BAR;
    const int tid = threadIdx.x, lane = tid & 31, b = blockIdx.x;
    const int wid = __reduce_max_sync(~0u, tid >> 5);
    const uint32_t rank = b & 1;
    uint8_t* arena = p.arena;
    volatile int* sinfo = (volatile int*)(smraw + SM_BAR + 192);
    if (tid == 0) TL(0)
    if (tid == 0) sinfo[0] = INT_MIN;
    uint32_t smid;
    asm("mov.u32 %0, %%smid;" : "=r"(smid));
    smid = __reduce_max_sync(~0u, smid);
    int d, pi;
    pair_place(smid >= 124 ? (smid >> 1) - 62 : (smid >> 1) + 4, d, pi);
    const int guess = b < 128 && smid < 132 && (smid & ~3u) != 120 && (NO_GUESS == 0 || (NO_GUESS == 2 && b != 20)) ? d * 8 + pi : -9;
    if (wid == 8) {
        if (lane == 0) {
#pragma unroll
            for (int i = 0; i < 17; i++) mbar_init(bars + 8 * i, i == B_WO ? 4 : 1);
            asm volatile("fence.mbarrier_init.release.cluster; fence.proxy.async.shared::cta;" ::: "memory");
            mbar_expect(bars + 8 * B_ROLE, 8);
        }
        __syncwarp();
    }
    asm volatile("barrier.cluster.arrive.relaxed.aligned;" ::: "memory");
    int pr = 0, hA = 0;
    if (wid < 8) {
        if (b < 128) {
            const int cb = (b & 15) * 128, k0 = (b >> 4) * 128 + (tid >> 4);
            uint4 v[8];
#pragma unroll
            for (int i = 0; i < 8; i++) v[i] = __ldg((const uint4*)(p.wmod + (size_t)(k0 + 16 * i) * (6 * DM) + cb + (tid & 15) * 8));
            float acc[8] = {0, 0, 0, 0, 0, 0, 0, 0};
            const float sl = silu_bf(p.c, k0 + 16 * (lane & 7));
#pragma unroll
            for (int i = 0; i < 8; i++) {
                const float sv = __shfl_sync(~0u, sl, i, 16);
                acc[0] += sv * bflo(v[i].x); acc[1] += sv * bfhi(v[i].x); acc[2] += sv * bflo(v[i].y); acc[3] += sv * bfhi(v[i].y);
                acc[4] += sv * bflo(v[i].z); acc[5] += sv * bfhi(v[i].z); acc[6] += sv * bflo(v[i].w); acc[7] += sv * bfhi(v[i].w);
            }
            float* red = (float*)(smraw + SM_PRE);
            *(float4*)(red + (tid >> 4) * 128 + (tid & 15) * 8) = make_float4(acc[0], acc[1], acc[2], acc[3]);
            *(float4*)(red + (tid >> 4) * 128 + (tid & 15) * 8 + 4) = make_float4(acc[4], acc[5], acc[6], acc[7]);
            bar_sync(NB_FIN0, 256);
            if (wid < 4) {
                float t = 0;
#pragma unroll
                for (int i = 0; i < 16; i++) t += red[i * 128 + tid];
                stg_rlx1(&g_modp[(b >> 4) * 2 * DM + cb + tid], __float_as_uint(t) | 1u);
                if (rank) TL(2)
            }
        } else {
            rec_ln((float*)(smraw + SM_PRE), p, b - 128, 0);
        }
    } else if (wid >= 10 && b >= 128) {
        {
            const int u = (b - 128) * 2 + wid - 10;
            const uint16_t* src = (const uint16_t*)p.mem0 + (lane & 3) * 2 * DM + (u >> 1) * 128 + (u & 1) * 32 + (lane >> 2);
            stg_rlx4(arena + (LB_STAMP << 13) + u * 2048 + (lane >> 4) * 1024 + ((lane >> 3) & 1) * 256 + (lane & 7) * 16, 0, 0, 0, 0);
#pragma unroll 1
            for (int r = 0; r < 4; r++) {
                uint32_t w[5];
#pragma unroll
                for (int e = 0; e < 4; e++) {
                    const uint16_t* q = src + (r >> 1) * 512 + (r & 1) * 16 + (e & 2) * 32 + (e & 1) * 8;
                    w[e] = pack_h2(bflo(q[0]), bflo(q[DM]));
                }
                w[4] = __shfl_sync(~0u, __byte_perm(w[3], ACC_ALL, 0x7632), lane * 8 + 7);
                w[3] = __byte_perm(w[3], ACC_ALL, (lane & 7) == 7 ? 0x7610 : 0x3210);
#pragma unroll 1
                for (int i = 0; i < 3; i++) {
                    uint8_t* d = arena + acc_slot(i) + acc_piece(r >> 1, u >> 1, (u & 1) * 2 + (r & 1));
                    stg_rlx4(d + lane * 16, w[0], w[1], w[2], w[3]);
                    if (lane < 8) stg_rlx1(d + 512 + lane * 4, w[4]);
                    w[0] = w[1] = w[2] = w[3] = w[4] = 0;
                }
            }
            bar_arrive(NB_C, 320);
        }
    } else if (rank == 0 && (wid > 8 || b >= 128)) {
        uint32_t best = ~0u;
        const int pg = wid < 11 ? 0 : 1 + (b >> 1) % 3;
        uint32_t* q = (uint32_t*)(arena + (pg << 21) + (pg ? blk(b >> 1, 1) : blk(LB_PROBE, wid & 1) + b * 16));
        if (lane < 8) stg_rlx1(q + lane, 0);
        u64 tk2 = ldg_u64(&g_tick[0]);
        __syncwarp();
        if (lane == 0) {
            q += 3;
            uint32_t v = atomicAdd(q, 1u);
#pragma unroll 1
            for (int r = 0; r < NPROBE; r++) {
                const uint32_t t0 = clk32() + (v >> 8);
                v = atomicAdd(q + (v >> 8), 1u);
                uint32_t t1;
                asm volatile("{.reg .pred p; setp.eq.u32 p, %1, 0xffffffff; @p exit; mov.u32 %0, %%clock;}" : "=r"(t1) : "r"(v) : "memory");
                best = min(best, t1 - t0);
            }
            sinfo[pg ? 4 : 2 + (wid & 1)] = best;
        }
        bar_sync(NB_KDONE, b < 128 ? 96 : 64);
        if (wid == 9) {
            const int par = sinfo[2] > sinfo[3], ncl = gridDim.x >> 1;
            u64 add = (1u << (8 * par)) + 65536;
            if (b < 128) add += ((u64)((2 * sinfo[4] < sinfo[2] + sinfo[3]) != par) << (32 + 8 * ((b >> 1) % 3))) + (guess < 0 || (smid & 1) ? 1 << 24 : 0);
            int tk = 0, it = 0;
            if (b >= 128) {
#pragma unroll 1
                while (!__all_sync(~0u, (int)((lo32(tk2) >> 16) & 255) >= ncl - 2)) { tk2 = ldg_u64(&g_tick[0]); spin_guard(++it); }
            }
            if (lane == 0) {
                if (guess >= 0) add += atomicXor(&g_tick[2], par << (guess >> 1)) & p.zero;
                tk = (atomicAdd((u64*)&g_tick[0], add) >> (8 * par)) & 255;
            }
#pragma unroll 1
            while (!__all_sync(~0u, (int)((lo32(tk2) >> 16) & 255) >= ncl)) { tk2 = ldg_u64(&g_tick[0]); spin_guard(++it); }
            tk = __shfl_sync(~0u, tk, 0);
            const int n0 = tk2 & 255, n1 = (tk2 >> 8) & 255;
            hA = min(n0 >> 1, NH);
            const int q0 = 2 * hA, q1 = 2 * NH - q0;
            const int over = tk - (par ? q1 : q0), lack = max(par ? q0 - n0 : q1 - n1, 0);
            if (over < 0) pr = par ? q0 + tk : tk;
            else if (over < lack) pr = (par ? n0 : q0 + n1) + over;
            else pr = -1 - (over - lack + (par ? max(n0 - q0, 0) : 0));
            if (!(lo32(tk2) >> 24) && !ldg_rlx1(&g_tick[2])) { pr = guess; hA = par ? 0 : NH; }
#pragma unroll
            for (int i = 0; i < 3; i++) hA |= ((hi32(tk2) >> (8 * i)) & 255) > 10 ? 256 << i : 0;
        }
    }
    asm volatile("barrier.cluster.wait.aligned;" ::: "memory");
    if (wid == 9 && rank == 0) {
        asm volatile("{.reg .pred p; .reg .b32 a; setp.lt.u32 p, %3, 2; @p mapa.shared::cluster.u32 a, %0, %3;\n"
                     " @p st.async.shared::cluster.mbarrier::complete_tx::bytes.v2.u32 [a + 192], {%1, %2}, [a + %4];}"
                     ::"r"(bars), "r"(pr), "r"(hA), "r"(lane), "n"(8 * B_ROLE) : "memory");
        if (b >= 128) atomicOr(&g_tick[4], (pr < 0 ? 4u : 1u) << ((b - 128) >> 1));
    }
    if (wid == 8) {
        int pu = guess;
        bool fast = false, known = false;
#pragma unroll 1
        for (int n = 0; n < 12; n++) {
            if (!known && (n == W_SPEC || pu < 0)) {
                mbar_wait_w(bars + 8 * B_ROLE, 0);
                TL(1)
                known = true;
                const int r = __reduce_max_sync(~0u, sinfo[0]);
                if (r != pu) {
#pragma unroll 1
                    for (; n > 0; n--) {
                        mbar_wait_w(bars + 8 * (B_W + n - 1), 0);
                        asm volatile("{.reg .pred p; elect.sync _|p, 0xffffffff; @p mbarrier.arrive.shared.b64 _, [%0];}" ::"r"(bars + 8 * (B_W + n - 1)) : "memory");
                    }
                    pu = r;
                }
                bar_arrive(NB_A, 384);
                if (b >= 128 && pu < 0) bar_sync(NB_B, 64);
                if (pu < 0) break;
            }
            const int rot = b >= 128 ? 8 : 0, i = (n + rot) % 12;
            if (rot && n == 4) bar_sync(NB_B, 64);
            if (n >= W_INFL && !fast) {
                const uint32_t v = ldg_rlx1(&g_tick[32 + (lane & 3) * 8]);
                mbar_wait_w(bars + 8 * (B_W + (n - W_INFL + rot) % 12), 0);
                fast = __all_sync(~0u, v != 0);
            }
            const int m = i < 8 ? i & 1 : 2, k = i < 8 ? i >> 1 : i - 8, c0 = (pu >> 1) * 128 + rank * 64, r0 = (pu & 1) * 512;
            const uint32_t dst = sb + m * 65536 + k * 16384, br = bars + 8 * (B_W + i);
            e_expect(br, 16384);
            e_tma2d(dst, &mp.wq + m, c0, r0 + k * 128, br, evict_first());
            e_tma2d(dst + 8192, &mp.wq + m, c0, r0 + k * 128 + 64, br, evict_first());
        }
    } else {
        bar_sync(NB_A, 384);
    }
    const int prr = __reduce_max_sync(~0u, sinfo[0]);
    hA = __reduce_max_sync(~0u, sinfo[1]);
    if (prr < 0) {
        int j = (b - 128) >> 1;
        if (b < 128) {
            uint32_t v;
            int it = 0;
#pragma unroll 1
            do { v = __reduce_max_sync(~0u, ldg_rlx1(&g_tick[4])); spin_guard(++it); } while (__popc(v) < 2);
            j = v == 3 ? -1 - prr : (v & 1) ^ 1;
        }
        rec_side((float*)smraw, p, j * 2 + rank);
        return;
    }
    const int role = (prr >> 1) * 4 + rank * 2 + (prr & 1);
    rec_main(sb, &mp.wo, arena, role, hA, wid >> 2, p.zero, p.tm);
}

__device__ __forceinline__ void wgmma_ss192(float* d, uint64_t a, uint64_t b, int sc) {
    asm volatile("{.reg .pred p; setp.ne.b32 p, %98, 0;\n wgmma.mma_async.sync.aligned.m64n192k16.f32.bf16.bf16 "
                 "{%0,%1,%2,%3,%4,%5,%6,%7,%8,%9,%10,%11,%12,%13,%14,%15,%16,%17,%18,%19,%20,%21,%22,%23,%24,%25,%26,%27,%28,%29,%30,%31,%32,%33,%34,%35,%36,%37,%38,%39,%40,%41,%42,%43,%44,%45,%46,%47,%48,%49,%50,%51,%52,%53,%54,%55,%56,%57,%58,%59,%60,%61,%62,%63,%64,%65,%66,%67,%68,%69,%70,%71,%72,%73,%74,%75,%76,%77,%78,%79,%80,%81,%82,%83,%84,%85,%86,%87,%88,%89,%90,%91,%92,%93,%94,%95}, %96, %97, p, 1, 1, 0, 1;}"
                 : F16(d, 0), F16(d, 16), F16(d, 32), F16(d, 48), F16(d, 64), F16(d, 80) : "l"(a), "l"(b), "r"(sc));
}

constexpr uint32_t P_B = 81920, P_PLANE = 40960, P_VEC = 212992, P_ROW = P_VEC + 6144, P_BAR = P_ROW + 4096, P_SMEM = P_BAR + 256;
constexpr uint32_t P_OUT = 180224, P_OUT3 = P_B + 2 * P_PLANE;
#define PPH 1
#define FLAG_ST "st.release.gpu.global.u32"
#define FLAG_LD "ld.acquire.gpu.global.u32"
#define EFA 0x1e7
#define EFB 0x1ff
#define E0 3
#define SL_B0 0x5555
#define SL_B1 0xaaaa
#define SL_C 0x2492490
#define SL_A0 0x7777
#define SL_A1 0x77dd
#define HFENCE 2
#define X_DLY 4000
#define ROT 0x00e
#define OWN 1
constexpr int P_ST = 5, P_ST0 = 4;
constexpr int PB_F = 0, PB_E = 5, PB_X = 10, PB_OUT = 12;
enum { C_Y = 0, C_G = 1, C_X1 = 2, C_U = 3, C_S1 = 8, C_S3 = 9 };
enum { V_GA = 0, V_A = 1, V_B = 2, V_GB = 3, V_VA = 4, V_VB = 5, V_VC = 6, V_C3 = 7 };
struct PostMaps { CUtensorMap o, wo, y, w1, g, w2, x1, w3, u, w4, out, x; };

struct GeluK { float k0, k1, kh; };
__device__ __forceinline__ GeluK gelu_k(float c) { return {0.7978845608028654f * c, 0.7978845608028654f * 0.044715f * c * c * c, 0.5f * c}; }
__device__ __forceinline__ float gelu_s(float t, const GeluK& k) {
    const float u = t * fmaf(t * t, k.k1, k.k0);
    float th; asm("tanh.approx.f32 %0, %1;" : "=f"(th) : "f"(u));
    const float hx = k.kh * t;
    return fmaf(hx, th, hx);
}
__device__ __forceinline__ float2 ldsv(uint32_t a) {
    float2 v; asm("ld.shared.v2.f32 {%0,%1}, [%2];" : "=f"(v.x), "=f"(v.y) : "r"(a)); return v;
}
__device__ __forceinline__ void wait_smem(uint32_t a, int target) {
    int it = 0;
#pragma unroll 1
    while (true) {
        int v;
        asm volatile("ld.acquire.cta.shared.u32 %0, [%1];" : "=r"(v) : "r"(a) : "memory");
        if (__all_sync(~0u, v >= target)) break;
        spin_guard(++it);
    }
}

#define PP(i)
#define PH_(c, w, i)
struct Pipe { int st, ph; };
__device__ __forceinline__ void adv(Pipe& p) { if (++p.st == P_ST) { p.st = 0; p.ph ^= 1; } }
__device__ __forceinline__ int u_col(int r, int nb) { return r ? 512 + r * 1024 + nb * 128 : nb * 192; }

template <bool A>
__device__ __forceinline__ void post_produce(uint32_t sb, const PostMaps& mp, int mb, int nb, int rank) {
    const int rh = 2 * mb + rank, lane = threadIdx.x & 31;
    const uint32_t full = sb + P_BAR + 8 * PB_F, empty = sb + P_BAR + 8 * PB_E;
    Pipe p = {(P_ST0 + E0) % P_ST, !E0};
#pragma unroll 1
    for (int ph = 0; ph < 9; ph++) {
        const int GS = ph == 0 ? 8 : ph == 6 ? 3 : 2, kb0 = ph < 7 ? 0 : ph * 16 - 88;
        const CUtensorMap* tm = &mp.o + 2 * (ph < 3 ? ph : ph < 6 ? 3 : 4) + !A;
        const uint64_t pol = ((A ? EFA : EFB) >> ph) & 1 ? evict_first() : evict_normal();
        const bool own = OWN && (ph == 1 || ph == 3);
        const int n0 = ph >= 3 && ph < 6 ? u_col(ph - 3, nb) : nb * 128;
        const int amul = ph == 0 ? 256 : 64, arow = ph == 0 ? rh * 8 : rh * 64;
        const int wr = ph == 2 ? min(max(rh + min(lane >> 3, 2) - 1, 0), 31) : rh ^ ((lane >> 3) & 1);
        const uint32_t* fl = &g_pflag[(ph < 3 ? ph - 1 : ph < 6 ? C_X1 : ph - 3) * 256 + wr * 8 + (lane & 7)];
        uint32_t have = ph == 0 || ph == 5 ? ~0u : 0u;
        PH_(A && ph == PPH, 0, 26) PH_(A && ph == PPH, 1, 26)
#pragma unroll 1
        for (int q = 0; q < 8; q++) {
            const int src = own && q < 2 ? nb ^ q : (q + ((ROT >> ph) & 1 ? nb & 6 : 0)) & 7;
            const bool skip = own && q == 0, both = own && q == 1;
            const uint32_t need = skip ? 0 : (ph == 2 ? 0x10101 : both ? 0x101 : 1) << src;
            if (A && (have & need) != need) {
                int it = 0;
#pragma unroll 1
                do {
                    uint32_t v;
                    asm volatile(FLAG_LD " %0, [%1];" : "=r"(v) : "l"(fl) : "memory");
                    have = __ballot_sync(~0u, v != 0);
                    spin_guard(++it);
                } while ((have & need) != need);
                PH_(ph == PPH && q == own, 0, 23) PH_(ph == PPH, 0, 24) PH_(ph == PPH && q == own, 1, 23) PH_(ph == PPH, 1, 24)
                asm volatile("fence.proxy.async.global;" ::: "memory");
            }
            if (!A && ph == 3 && q == 1) wait_smem(sb + P_BAR + 8 * (PB_OUT + (lane & 1)), 3);
            const int row = arow + (ph == 2 ? (int)((0x04000301u >> ((src & 6) * 4)) & 7) - 2 : 0);
            const uint32_t bytes = (skip ? 16384 : 32768) + (ph == 3 ? 8192 : 0);
            if ((ph | q) == 0) asm volatile("barrier.cluster.wait.aligned;" ::: "memory");
#pragma unroll 1
            for (int e = kb0 + (src + 1) * GS, kb = e - GS + (ph | q ? 0 : E0); kb < e; kb++) {
                const uint32_t f = full + 8 * p.st;
                mbar_wait_w(empty + 8 * p.st, p.ph ^ 1);
                if (A) {
                    const uint32_t a = sb + p.st * 16384 + rank * 8192;
                    if (both) { e_tma2d(a, tm, kb * 64, row, f, pol); e_tma2d(a + 8192 - rank * 16384, tm, kb * 64, row ^ 64, f, pol); }
                    else if (!skip) e_tma2d_mc(a, tm, kb * amul, row, f, pol);
                } else {
                    const uint32_t b = sb + P_B + p.st * 8192;
                    e_expect(f, bytes);
                    e_tma2d(b, tm, n0, kb * 64, f, pol);
                    e_tma2d(b + P_PLANE, tm, n0 + 64, kb * 64, f, pol);
                    if (ph == 3 && both) mbar_wait_w(empty + 8 * p.st - 16, p.ph);
                    if (ph == 3) e_tma2d(b + 2 * P_PLANE, tm, n0 + 128, kb * 64, f, pol);
                }
                PH_(PPH == 0 && ph == 0 && q == 0 && kb + GS == e + E0, 0, 20 + A) PH_(PPH == 0 && ph == 0 && q == 0 && kb + GS == e + E0, 1, 20 + A)
                adv(p);
            }
        }
    }
    if (A) {
#pragma unroll 1
        for (int i = 0; i < P_ST; i++) mbar_wait_w(empty + 8 * i, p.ph ^ (i >= p.st));
    }
}

#define I4(d, i) "f"(d[i]), "f"(d[i + 1]), "f"(d[i + 2]), "f"(d[i + 3])
#define I16(d, i) I4(d, i), I4(d, i + 4), I4(d, i + 8), I4(d, i + 12)
__device__ __forceinline__ void pick16(float* v, int n, const float* c1, float2 a, float2 b, const float* old) {
    asm volatile("{PKT: .branchtargets PK0, PK1, PK2, PK3, PK4, PK5, PK6, PK7, PK8, PK9, PK10, PK11; brx.idx.uni %8, PKT;\n"
                 "PK0: fma.rn.f32 %0, %9, %11, %15; fma.rn.f32 %1, %9, %12, %16; fma.rn.f32 %2, %10, %11, %17; fma.rn.f32 %3, %10, %12, %18; fma.rn.f32 %4, %9, %13, %19; fma.rn.f32 %5, %9, %14, %20; fma.rn.f32 %6, %10, %13, %21; fma.rn.f32 %7, %10, %14, %22; bra.uni PKE;\n"
                 "PK1: fma.rn.f32 %0, %9, %11, %23; fma.rn.f32 %1, %9, %12, %24; fma.rn.f32 %2, %10, %11, %25; fma.rn.f32 %3, %10, %12, %26; fma.rn.f32 %4, %9, %13, %27; fma.rn.f32 %5, %9, %14, %28; fma.rn.f32 %6, %10, %13, %29; fma.rn.f32 %7, %10, %14, %30; bra.uni PKE;\n"
                 "PK2: fma.rn.f32 %0, %9, %11, %31; fma.rn.f32 %1, %9, %12, %32; fma.rn.f32 %2, %10, %11, %33; fma.rn.f32 %3, %10, %12, %34; fma.rn.f32 %4, %9, %13, %35; fma.rn.f32 %5, %9, %14, %36; fma.rn.f32 %6, %10, %13, %37; fma.rn.f32 %7, %10, %14, %38; bra.uni PKE;\n"
                 "PK3: fma.rn.f32 %0, %9, %11, %39; fma.rn.f32 %1, %9, %12, %40; fma.rn.f32 %2, %10, %11, %41; fma.rn.f32 %3, %10, %12, %42; fma.rn.f32 %4, %9, %13, %43; fma.rn.f32 %5, %9, %14, %44; fma.rn.f32 %6, %10, %13, %45; fma.rn.f32 %7, %10, %14, %46; bra.uni PKE;\n"
                 "PK4: fma.rn.f32 %0, %9, %11, %47; fma.rn.f32 %1, %9, %12, %48; fma.rn.f32 %2, %10, %11, %49; fma.rn.f32 %3, %10, %12, %50; fma.rn.f32 %4, %9, %13, %51; fma.rn.f32 %5, %9, %14, %52; fma.rn.f32 %6, %10, %13, %53; fma.rn.f32 %7, %10, %14, %54; bra.uni PKE;\n"
                 "PK5: fma.rn.f32 %0, %9, %11, %55; fma.rn.f32 %1, %9, %12, %56; fma.rn.f32 %2, %10, %11, %57; fma.rn.f32 %3, %10, %12, %58; fma.rn.f32 %4, %9, %13, %59; fma.rn.f32 %5, %9, %14, %60; fma.rn.f32 %6, %10, %13, %61; fma.rn.f32 %7, %10, %14, %62; bra.uni PKE;\n"
                 "PK6: fma.rn.f32 %0, %9, %11, %63; fma.rn.f32 %1, %9, %12, %64; fma.rn.f32 %2, %10, %11, %65; fma.rn.f32 %3, %10, %12, %66; fma.rn.f32 %4, %9, %13, %67; fma.rn.f32 %5, %9, %14, %68; fma.rn.f32 %6, %10, %13, %69; fma.rn.f32 %7, %10, %14, %70; bra.uni PKE;\n"
                 "PK7: fma.rn.f32 %0, %9, %11, %71; fma.rn.f32 %1, %9, %12, %72; fma.rn.f32 %2, %10, %11, %73; fma.rn.f32 %3, %10, %12, %74; fma.rn.f32 %4, %9, %13, %75; fma.rn.f32 %5, %9, %14, %76; fma.rn.f32 %6, %10, %13, %77; fma.rn.f32 %7, %10, %14, %78; bra.uni PKE;\n"
                 "PK8: fma.rn.f32 %0, %9, %11, %79; fma.rn.f32 %1, %9, %12, %80; fma.rn.f32 %2, %10, %11, %81; fma.rn.f32 %3, %10, %12, %82; fma.rn.f32 %4, %9, %13, %83; fma.rn.f32 %5, %9, %14, %84; fma.rn.f32 %6, %10, %13, %85; fma.rn.f32 %7, %10, %14, %86; bra.uni PKE;\n"
                 "PK9: fma.rn.f32 %0, %9, %11, %87; fma.rn.f32 %1, %9, %12, %88; fma.rn.f32 %2, %10, %11, %89; fma.rn.f32 %3, %10, %12, %90; fma.rn.f32 %4, %9, %13, %91; fma.rn.f32 %5, %9, %14, %92; fma.rn.f32 %6, %10, %13, %93; fma.rn.f32 %7, %10, %14, %94; bra.uni PKE;\n"
                 "PK10: fma.rn.f32 %0, %9, %11, %95; fma.rn.f32 %1, %9, %12, %96; fma.rn.f32 %2, %10, %11, %97; fma.rn.f32 %3, %10, %12, %98; fma.rn.f32 %4, %9, %13, %99; fma.rn.f32 %5, %9, %14, %100; fma.rn.f32 %6, %10, %13, %101; fma.rn.f32 %7, %10, %14, %102; bra.uni PKE;\n"
                 "PK11: fma.rn.f32 %0, %9, %11, %103; fma.rn.f32 %1, %9, %12, %104; fma.rn.f32 %2, %10, %11, %105; fma.rn.f32 %3, %10, %12, %106; fma.rn.f32 %4, %9, %13, %107; fma.rn.f32 %5, %9, %14, %108; fma.rn.f32 %6, %10, %13, %109; fma.rn.f32 %7, %10, %14, %110;\n"
                 "PKE: }"
                 : "=f"(v[0]), "=f"(v[1]), "=f"(v[2]), "=f"(v[3]), "=f"(v[4]), "=f"(v[5]), "=f"(v[6]), "=f"(v[7])
                 : "r"(n), "f"(c1[0]), "f"(c1[1]), "f"(a.x), "f"(a.y), "f"(b.x), "f"(b.y), I16(old, 0), I16(old, 16), I16(old, 32), I16(old, 48), I16(old, 64), I16(old, 80));
}
template <int PH, class F>
__device__ __forceinline__ void post_mma(uint32_t sb, float* acc, Pipe& p, int NK, int wg, uint32_t rel, bool lead, int pi, F hook) {
    const uint32_t full = sb + P_BAR + 8 * PB_F;
    constexpr uint64_t DA = PH == 0 ? mkdesc(SB0, 128, 1024, 0) : mkdesc(SB0, 16, 1024, 1);
    constexpr uint64_t DB = mkdesc(SB0 + P_B, P_PLANE, 1024, 1);
    auto release = [&](uint32_t a) { asm volatile("{.reg .pred p; setp.gt.u32 p, %0, 63; @p mbarrier.arrive.shared::cluster.b64 _, [%0];}" ::"r"(a) : "memory"); };
    uint32_t prev = 0;
    if (OWN && (PH & 1)) { if (HFENCE == 2) fence_async_smem(); bar_sync(12 + wg, 128); }
    bool ok = false;
#pragma unroll 1
    for (int kb = 0; kb < NK; kb++) {
        if (!ok) mbar_wait_w(full + 8 * p.st, p.ph);
        const uint32_t a = (uint32_t)DA + (OWN && (PH & 1) && kb < 2 ? P_OUT / 16 + wg * 1024 + kb * 512 : p.st * 1024 + wg * 512), b = (uint32_t)DB + p.st * 512;
        wg_fence();
#pragma unroll
        for (int k = 0; k < 4; k++) {
            const uint64_t da = (DA & 0xffffffff00000000ull) | (a + k * (PH == 0 ? 16 : 2)), db = (DB & 0xffffffff00000000ull) | (b + k * 128);
            if (PH == 3) wgmma_ss192(acc, da, db, (kb | k) != 0);
            else wgmma_ss128<PH == 0>(acc, da, db, (kb | k) != 0);
        }
        wg_commit();
        if (kb == 0) { PP(pi) if (PH == 0 && wg == 0) TL(11) }
        const uint32_t cur = rel + 8 * p.st;
        adv(p);
        hook(-1);
        uint32_t t;
        asm volatile("{.reg .pred p; mbarrier.test_wait.parity.shared.b64 p, [%1], %2; selp.u32 %0, 1, 0, p;}" : "=r"(t) : "r"(full + 8 * p.st), "r"(p.ph) : "memory");
        wg_wait<1>();
        release(prev);
        ok = __all_sync(~0u, t);
        prev = cur;
        hook(kb);
    }
    wg_wait<0>();
    release(prev);
    PP(pi + 1)
}

__global__ void __cluster_dims__(2, 1, 1) __launch_bounds__(384, 1)
k_post(const __grid_constant__ PostMaps mp) {
    extern __shared__ uint8_t smraw[];
    const uint32_t sb = smem_u32(smraw);
    if ((sb & 0x3FFFF) != SB0) __trap();
    const int tid = threadIdx.x, lane = tid & 31;
    int d, pi;
    pair_place(blockIdx.x >> 1, d, pi);
    const int rank = blockIdx.x & 1, mb = (d >> 2) * 8 + pi, nb = (d & 3) * 2 + rank;
    const uint32_t bars = sb + P_BAR;
    PH_(PPH == 0 && tid == 0, 0, 22) PH_(PPH == 0 && tid == 0, 1, 22)
    const int w = __reduce_max_sync(~0u, (tid >> 5) - 8);
    if (w == 1) {
        if (lane == 0) {
#pragma unroll
            for (int i = 0; i < PB_OUT; i++) mbar_init(bars + 8 * i, i >= PB_E && i < PB_X ? 4 : 1);
            mbar_arrive(bars + 8 * (PB_F + P_ST0));
            asm volatile("mbarrier.arrive.shared.b64 _, [%0], 4;" ::"r"(bars + 8 * (PB_E + P_ST0)) : "memory");
            sts4(bars + 8 * PB_OUT, 0, 0, 0, 0);
            asm volatile("fence.mbarrier_init.release.cluster; fence.proxy.async.shared::cta;" ::: "memory");
        }
        __syncwarp();
    }
    asm volatile("barrier.cluster.arrive.relaxed.aligned;" ::: "memory");
    if (w == 1) {
#pragma unroll
        for (int i = 0; i < E0; i++) {
            const int st = (P_ST0 + i) % P_ST, kb = (ROT & 1 ? nb & 6 : 0) * 8 + i;
            const uint32_t f = bars + 8 * (PB_F + st);
            e_expect(f, 32768);
#pragma unroll
            for (int h = 0; h < 2; h++) {
                e_tma2d(sb + st * 16384 + h * 8192, &mp.o, kb * 256, mb * 16 + h * 8, f, evict_first());
                e_tma2d(sb + P_B + st * 8192 + h * P_PLANE, &mp.wo, nb * 128 + h * 64, kb * 64, f, evict_first());
            }
        }
    }
    if (w != 0 && w != 3) asm volatile("barrier.cluster.wait.aligned;" ::: "memory");
    if (w >= 0) {
        asm volatile("setmaxnreg.dec.sync.aligned.u32 40;");
        if (w == 0) {
            post_produce<false>(sb, mp, mb, nb, rank);
        } else if (w < 3) {
            const int wg = w - 1, rh = 2 * mb + wg;
            float* rowc = (float*)(smraw + P_ROW) + (wg * 64 + lane * 2) * 8;
            int nout = 0, sig = 0;
            if (X_DLY) __nanosleep(X_DLY);
            if (wg && lane < 9) asm volatile("prefetch.tensormap [%0];" ::"l"(&mp.y + lane) : "memory");
            e_expect(bars + 8 * (PB_X + wg), 16384);
            e_tma2d(sb + P_OUT + wg * 16384, &mp.x, nb * 128, rh * 64, bars + 8 * (PB_X + wg), evict_first());
            e_tma2d(sb + P_OUT + wg * 16384 + 8192, &mp.x, nb * 128 + 64, rh * 64, bars + 8 * (PB_X + wg), evict_first());
            if (wg == 0) {
#pragma unroll 1
                for (int i = 0; i < 11; i++) {
                    const float* src = i < 4 ? g_mod + ((0x5342 >> (4 * i)) & 15) * DM + nb * 128 : g_vec + (i < 7 ? (i - 4) * DM + nb * 128 : 3 * DM + u_col(max(i - 8, 0), nb) + (i == 8) * 128);
                    if (i != 8 || lane < 16) cp_async16(sb + P_VEC + i * 512 - (i > 8) * 256 + lane * 16, src + lane * 4);
                }
                *(uint4*)&g_modp[blockIdx.x * 128 + lane * 4] = make_uint4(0, 0, 0, 0);
                if (blockIdx.x == 64) *(uint2*)&g_tick[lane * 2] = make_uint2(0, 0);
                asm volatile("cp.async.wait_all;" ::: "memory");
                const float4 a = lds4f(sb + P_VEC + V_A * 512 + lane * 16);
                sts4f(sb + P_VEC + V_A * 512 + lane * 16, 1.0f + a.x, 1.0f + a.y, 1.0f + a.z, 1.0f + a.w);
                bar_arrive(3, 288);
            }
#pragma unroll 1
            for (int i = 0; i < 9; i++) {
                const int cnt = i == 8 ? 6 : (0x54392180u >> (4 * i)) & 15;
                if (cnt < C_S1) {
                    const bool isu = cnt >= C_U && cnt < 6;
                    const int ng = cnt == C_U ? 3 : 2, c0 = isu ? u_col(cnt - C_U, nb) : nb * 128;
                    const uint32_t src = sb + (cnt == C_U ? P_OUT3 : P_OUT) + wg * ng * 8192;
#pragma unroll 1
                    for (int j = 0; j < ng; j++) {
                        bar_sync(4 + 4 * wg + (sig++ & 3), 160);
                        if (lane == 0) {
                            if (HFENCE) fence_async_smem();
                            PH_(cnt == PPH - 1, wg, 20)
                            asm volatile("cp.async.bulk.tensor.2d.global.shared::cta.bulk_group [%0, {%2, %3}], [%1]; cp.async.bulk.commit_group;"
                                         ::"l"(&mp.y + 2 * (isu ? 3 : min(cnt, 4))), "r"(src + j * 8192), "r"(c0 + j * 64), "r"(rh * 64) : "memory");
                        }
                        __syncwarp();
                    }
                    if (lane == 0) {
                        asm volatile("cp.async.bulk.wait_group 0; fence.proxy.async.global;" ::: "memory");
                        PH_(cnt == PPH - 1, wg, 21)
                        asm volatile("st.release.cta.shared.u32 [%0], %1;" ::"r"(bars + 8 * (PB_OUT + wg)), "r"(nout + 1) : "memory");
                        if (cnt < 6) asm volatile(FLAG_ST " [%0], %1;" ::"l"(&g_pflag[cnt * 256 + rh * 8 + nb]), "r"(1) : "memory");
                        PH_(cnt == PPH - 1, wg, 22)
                    }
                    nout++;
                    __syncwarp();
                    continue;
                }
                bar_sync(4 + 4 * wg + (sig++ & 3), 160);
#pragma unroll 1
                for (int q = 0; q < (cnt == C_S1 ? 3 : 1); q++) {
                    const float4 v = lds4f(sb + P_ROW + wg * 2048 + q * 512 + lane * 16);
                    asm volatile("red.relaxed.gpu.global.add.v4.f32 [%0], {%1, %2, %3, %4};"
                                 ::"l"((float4*)g_st + (cnt == C_S1 ? q : 3) * (S_ / 2) + rh * 32 + lane), "f"(v.x), "f"(v.y), "f"(v.z), "f"(v.w) : "memory");
                }
                __syncwarp();
                uint32_t* c = &g_pcnt[(cnt - C_S1) * 256 + rh * 8];
                if (lane == 0) { signal_count(c); wait_count1(c, 8); }
                __syncwarp();
                const float4* sp = (const float4*)g_st + rh * 32 + lane;
                float4 u[3] = {__ldcg(sp + (cnt == C_S1 ? 0 : 3) * (S_ / 2)), __ldcg(sp + S_ / 2), __ldcg(sp + S_)};
#pragma unroll 1
                for (int h = 0; h < 2; h++) {
                    const float id = 1.0f / DM;
                    const float m = u[0].x * id, var = fmaxf(u[0].y * id - m * m, 0.f) + 1e-5f, r = rsqrtf(var);
                    float sc = r, m2 = 0.f;
                    if (cnt == C_S1) {
                        m2 = r * (u[1].x * id - m * g_cst[0]) + g_cst[3];
                        const float e2 = r * r * (u[2].x * id - 2.0f * m * u[1].y * id + m * m * g_cst[1]) + 2.0f * r * (u[2].y * id - m * g_cst[2]) + g_cst[4];
                        sc = r * rsqrtf(fmaxf(e2 - m2 * m2, 0.f) + 1e-5f);
                    }
                    const GeluK k = gelu_k(sc);
                    *(float4*)(rowc + h * 8) = make_float4(k.k0, k.k1, k.kh, -m);
                    *(float4*)(rowc + h * 8 + 4) = make_float4(var * r, -m2 * var * r, r, -m * r);
#pragma unroll
                    for (int q = 0; q < 3; q++) { u[q].x = u[q].z; u[q].y = u[q].w; }
                }
                bar_arrive(1 + wg, 160);
            }
        } else {
            post_produce<true>(sb, mp, mb, nb, rank);
        }
    } else {
        asm volatile("setmaxnreg.inc.sync.aligned.u32 232;");
        const int wg = __reduce_max_sync(~0u, tid >> 7), wi = (tid >> 5) & 3, g = lane >> 2, tq = lane & 3;
        const bool lead = (tid & 127) == 0;
        uint32_t rel = 0;
        if ((tid & 127) < 2) asm("mapa.shared::cluster.u32 %0, %1, %2;" : "=r"(rel) : "r"(bars + 8 * PB_E), "r"(tid & 1));
        PP(0)
        if (tid == 0) TL(10)
        uint32_t vec = sb + P_VEC + tq * 8;
        const uint32_t stw = sb + (wi * 16 + ((lane >> 3) & 1) * 8 + (lane & 7)) * 128 + (((lane >> 4) ^ (lane & 7)) << 4);
        int sig = 0;
        auto signal = [&]() { bar_arrive(4 + 4 * wg + (sig++ & 3), 160); };
        auto put64 = [&](uint32_t o, const float* v) {
#pragma unroll
            for (int jj = 0; jj < 4; jj++, v += 8) stsm4((stw + o) ^ (jj << 5), pack2(v[0], v[1]), pack2(v[2], v[3]), pack2(v[4], v[5]), pack2(v[6], v[7]));
            if (HFENCE < 2) fence_async_smem();
            signal();
        };
        auto out_free = [&](int n) { wait_smem(bars + 8 * (PB_OUT + (lane & 1)), n); };
        const uint32_t rowc = sb + P_ROW + (wg * 64 + wi * 16 + g) * 32, o128 = P_OUT + wg * 16384;
        const uint32_t rsum = sb + P_ROW + wg * 2048 + (wi * 16 + g) * 8;
        Pipe pa = {P_ST0, 1};
        auto none = [](int) {};
        uint32_t keep[32];
#define KEEP(jn, e) (((e) & 1) ? bfhi(keep[2 * (jn) + ((e) >> 1)]) : bflo(keep[2 * (jn) + ((e) >> 1)]))
        float mu1[2], r1[2];
        {
            float acc[64];
            post_mma<0>(sb, acc, pa, 64, wg, rel, lead, 1, [&](int kb) {
                if (kb != 40) return;
                bar_sync(3, 288);
                mbar_wait_w(bars + 8 * (PB_X + wg), 0);
#pragma unroll
                for (int jj = 0; jj < 8; jj++) ldsm4(keep + jj * 4, (stw + o128 + (jj >> 2) * 8192) ^ ((jj & 3) << 5));
            });
            asm volatile("" : "+r"(vec) :: "memory");
            float st[2][6];
#pragma unroll
            for (int q = 0; q < 6; q++) st[0][q] = st[1][q] = 0.f;
#pragma unroll
            for (int jn = 0; jn < 16; jn++) {
                const float2 ga = ldsv(vec + V_GA * 512 + jn * 32), a = ldsv(vec + V_A * 512 + jn * 32);
                float xa[4];
#pragma unroll
                for (int e = 0; e < 4; e++) {
                    xa[e] = fmaf((e & 1) ? ga.y : ga.x, acc[4 * jn + e], KEEP(jn, e));
                    st[e >> 1][0] += xa[e]; st[e >> 1][1] = fmaf(xa[e], xa[e], st[e >> 1][1]);
                    acc[4 * jn + e] = ((e & 1) ? a.y : a.x) * xa[e];
                }
                keep[2 * jn] = pack2(xa[0], xa[1]); keep[2 * jn + 1] = pack2(xa[2], xa[3]);
                if ((jn & 7) == 7) put64(o128 + (jn >> 3) * 8192, acc + 4 * jn - 28);
            }
            PP(3)
#pragma unroll
            for (int jn = 0; jn < 16; jn++) {
                const float2 a = ldsv(vec + V_A * 512 + jn * 32), b = ldsv(vec + V_B * 512 + jn * 32);
#pragma unroll
                for (int e = 0; e < 4; e++) {
                    const float y = acc[4 * jn + e], aa = (e & 1) ? a.y : a.x, bb = (e & 1) ? b.y : b.x;
                    float* s = st[e >> 1];
                    s[2] += y; s[3] = fmaf(aa, y, s[3]); s[4] = fmaf(y, y, s[4]); s[5] = fmaf(bb, y, s[5]);
                }
            }
#pragma unroll
            for (int h = 0; h < 2; h++)
#pragma unroll
                for (int q = 0; q < 6; q++) { st[h][q] += __shfl_xor_sync(~0u, st[h][q], 1); st[h][q] += __shfl_xor_sync(~0u, st[h][q], 2); }
            if (tq < 3) {
#pragma unroll
                for (int h = 0; h < 2; h++)
                    sts2(rsum + tq * 512 + h * 64, tq == 0 ? st[h][0] : tq == 1 ? st[h][2] : st[h][4], tq == 0 ? st[h][1] : tq == 1 ? st[h][3] : st[h][5]);
            }
            signal();
            PP(29)
        }
        {
            float acc[64];
            post_mma<1>(sb, acc, pa, 16, wg, rel, lead, 4, none);
            float c1[2], c2[2], c3[2];
            GeluK gk[2];
            bar_sync(1 + wg, 160);
#pragma unroll
            for (int h = 0; h < 2; h++) {
                const float4 a = lds4f(rowc + h * 256), b = lds4f(rowc + h * 256 + 16);
                gk[h] = {a.x, a.y, a.z}; c1[h] = a.w; c2[h] = b.x; c3[h] = b.y; mu1[h] = b.w; r1[h] = b.z;
            }
#pragma unroll
            for (int jn = 0; jn < 16; jn++) {
                const float2 va = ldsv(vec + V_VA * 512 + jn * 32), vb = ldsv(vec + V_VB * 512 + jn * 32), vc = ldsv(vec + V_VC * 512 + jn * 32);
#pragma unroll
                for (int e = 0; e < 4; e++) {
                    const int h = e >> 1;
                    const float t = fmaf(c1[h], (e & 1) ? va.y : va.x, fmaf(c2[h], (e & 1) ? vb.y : vb.x, fmaf(c3[h], (e & 1) ? vc.y : vc.x, acc[4 * jn + e])));
                    acc[4 * jn + e] = gelu_s(t, gk[h]);
                }
                if ((jn & 7) == 7) put64(o128 + (jn >> 3) * 8192, acc + 4 * jn - 28);
            }
            PP(6)
        }
        {
            float acc[64];
            post_mma<2>(sb, acc, pa, 16, wg, rel, lead, 7, none);
#pragma unroll
            for (int jn = 0; jn < 16; jn++) {
                const float2 a = ldsv(vec + V_A * 512 + jn * 32), b = ldsv(vec + V_B * 512 + jn * 32);
#pragma unroll
                for (int e = 0; e < 4; e++) {
                    const int h = e >> 1;
                    acc[4 * jn + e] += fmaf(fmaf(KEEP(jn, e), r1[h], mu1[h]), (e & 1) ? a.y : a.x, (e & 1) ? b.y : b.x);
                }
                if ((jn & 7) == 7) put64(o128 + (jn >> 3) * 8192, acc + 4 * jn - 28);
            }
            PP(9)
            float st[2][2] = {{0.f, 0.f}, {0.f, 0.f}};
#pragma unroll
            for (int jn = 0; jn < 16; jn++) {
                const float2 gb = ldsv(vec + V_GB * 512 + jn * 32);
                float z[4];
#pragma unroll
                for (int e = 0; e < 4; e++) {
                    const float x1 = acc[4 * jn + e];
                    st[e >> 1][0] += x1; st[e >> 1][1] = fmaf(x1, x1, st[e >> 1][1]);
                    z[e] = fmaf((e & 1) ? gb.y : gb.x, x1, KEEP(jn, e));
                }
                keep[2 * jn] = pack2(z[0], z[1]); keep[2 * jn + 1] = pack2(z[2], z[3]);
            }
#pragma unroll
            for (int h = 0; h < 2; h++)
#pragma unroll
                for (int q = 0; q < 2; q++) { st[h][q] += __shfl_xor_sync(~0u, st[h][q], 1); st[h][q] += __shfl_xor_sync(~0u, st[h][q], 2); }
            if (tq < 2) sts2(rsum + tq * 64, tq ? st[1][0] : st[0][0], tq ? st[1][1] : st[0][1]);
            signal();
            PP(30)
        }
        {
            float old[96], acc[64];
            post_mma<3>(sb, old, pa, 16, wg, rel, lead, 10, none);
            uint32_t v3 = vec + V_C3 * 512;
            float c1[2];
            GeluK gk[2];
            bar_sync(1 + wg, 160);
#pragma unroll
            for (int h = 0; h < 2; h++) { const float4 a = lds4f(rowc + h * 256); gk[h] = {a.x, a.y, a.z}; c1[h] = a.w; }
            bar_sync(3, 256);
#pragma unroll 1
            for (int r = 0; r < 3; r++) {
                const uint32_t o = stw + (r ? o128 : P_OUT3 + wg * 24576);
                uint32_t when = r == 0 ? (wg ? SL_A1 : SL_A0) : r == 1 ? (wg ? SL_B1 : SL_B0) : SL_C << wg, n = 0;
                float2 va, vb;
                post_mma<2>(sb, acc, pa, r < 2 ? 16 : 56, wg, rel, lead, 12 + 2 * r, [&](int kb) {
                    if (kb < 0) { va = lds2f(v3); vb = lds2f(v3 + 32); return; }
                    const bool now = when & 1;
                    when >>= 1;
                    if (!now) return;
                    if (n == 0) out_free(3 + r);
                    float v[8];
                    pick16(v, n, c1, va, vb, old);
#pragma unroll
                    for (int e = 0; e < 8; e++) v[e] = gelu_s(v[e], gk[(e >> 1) & 1]);
                    stsm4((o + (n >> 2) * 8192) ^ ((n & 3) << 5), pack2(v[0], v[1]), pack2(v[2], v[3]), pack2(v[4], v[5]), pack2(v[6], v[7]));
                    v3 += 64;
                    if ((++n & 3) == 0) { if (!HFENCE) fence_async_smem(); signal(); }
                });
                if (r == 2) break;
#pragma unroll
                for (int i = 0; i < 64; i++) old[i] = acc[i];
            }
#pragma unroll
            for (int jn = 0; jn < 16; jn++) {
                const float2 gb = ldsv(vec + V_GB * 512 + jn * 32);
#pragma unroll
                for (int e = 0; e < 4; e++) acc[4 * jn + e] = fmaf((e & 1) ? gb.y : gb.x, acc[4 * jn + e], KEEP(jn, e));
                if ((jn & 7) == 7) put64(o128 + (jn >> 3) * 8192, acc + 4 * jn - 28);
            }
            PP(18)
            if (tid == 0) TL(12)
        }
    }
}

typedef CUresult (*EncFn)(CUtensorMap*, CUtensorMapDataType, cuuint32_t, void*, const cuuint64_t*, const cuuint64_t*, const cuuint32_t*,
                          const cuuint32_t*, CUtensorMapInterleave, CUtensorMapSwizzle, CUtensorMapL2promotion, CUtensorMapFloatOOBfill);

static CUtensorMap make_map(EncFn enc, const void* p, uint64_t inner, uint64_t outer) {
    CUtensorMap m;
    cuuint64_t dims[2] = {inner, outer};
    cuuint64_t str[1] = {inner * 2};
    cuuint32_t box[2] = {64, 64};
    cuuint32_t es[2] = {1, 1};
    enc(&m, CU_TENSOR_MAP_DATA_TYPE_BFLOAT16, 2, (void*)p, dims, str, box, es, CU_TENSOR_MAP_INTERLEAVE_NONE,
        CU_TENSOR_MAP_SWIZZLE_128B, CU_TENSOR_MAP_L2_PROMOTION_L2_256B, CU_TENSOR_MAP_FLOAT_OOB_FILL_NONE);
    return m;
}
static CUtensorMap make_map_o(EncFn enc, const void* p) {
    CUtensorMap m;
    cuuint64_t dims[2] = {16384, 256};
    cuuint64_t str[1] = {65536};
    cuuint32_t box[2] = {256, 8};
    cuuint32_t es[2] = {1, 1};
    enc(&m, CU_TENSOR_MAP_DATA_TYPE_UINT32, 2, (void*)p, dims, str, box, es, CU_TENSOR_MAP_INTERLEAVE_NONE, CU_TENSOR_MAP_SWIZZLE_NONE,
        CU_TENSOR_MAP_L2_PROMOTION_L2_256B, CU_TENSOR_MAP_FLOAT_OOB_FILL_NONE);
    return m;
}
template <class T> static T* sym(T& s) { void* p = nullptr; cudaGetSymbolAddress(&p, s); return (T*)p; }

constexpr RecTime g_time = {T_GO, T_X2, T_V, D_X2, H_D};
extern "C" void kernel_launch(void* const* d_in, const int* in_sizes, int n_in, void* d_out, int out_size) {
    const bf16* x = (const bf16*)d_in[0];
    const bf16* mem0 = (const bf16*)d_in[1];
    const bf16 *Wq = (const bf16*)d_in[2], *Wk = (const bf16*)d_in[3], *Wv = (const bf16*)d_in[4], *Wo = (const bf16*)d_in[5];
    const bf16 *w1 = (const bf16*)d_in[8], *w2 = (const bf16*)d_in[9], *w3 = (const bf16*)d_in[10], *w4 = (const bf16*)d_in[11];
    const bf16 *c = (const bf16*)d_in[12], *wmod = (const bf16*)d_in[13];
    bf16* out = (bf16*)d_out;

    EncFn enc = nullptr;
    cudaDriverEntryPointQueryResult qr;
    cudaGetDriverEntryPoint("cuTensorMapEncodeTiled", (void**)&enc, cudaEnableDefault, &qr);
    CUtensorMap tWq = make_map(enc, Wq, NH * DH, DM), tWk = make_map(enc, Wk, NH * DH, DM), tWv = make_map(enc, Wv, NH * DH, DM);
    PostMaps mp;
    mp.o = make_map_o(enc, sym(g_O)); mp.wo = make_map(enc, Wo, DM, NH * DH);
    mp.y = make_map(enc, sym(g_y), DM, S_); mp.w1 = make_map(enc, w1, DM, DM);
    mp.g = make_map(enc, sym(g_g), DM, S_); mp.w2 = make_map(enc, w2, DM, DM);
    mp.x1 = make_map(enc, sym(g_x1), DM, S_); mp.w3 = make_map(enc, w3, FF, DM);
    mp.u = make_map(enc, sym(g_u), FF, S_); mp.w4 = make_map(enc, w4, DM, FF);
    mp.out = make_map(enc, out, DM, S_); mp.x = make_map(enc, x, DM, S_);
    cudaFuncSetAttribute(k_rec, cudaFuncAttributeMaxDynamicSharedMemorySize, SM_REC_TOTAL);
    cudaFuncSetAttribute(k_post, cudaFuncAttributeMaxDynamicSharedMemorySize, P_SMEM);

    uint8_t* arena = (uint8_t*)(((uintptr_t)sym(g_arena) + (2u << 20) - 1) & ~(uintptr_t)((2u << 20) - 1));
    const RecPtrs rp = {x, mem0, c, wmod, w1, w3, arena, 0u, g_time};
    const RecMaps rm = {tWq, tWk, tWv, mp.wo};
    k_rec<<<132, 384, SM_REC_TOTAL>>>(rm, rp);
    k_post<<<128, 384, P_SMEM>>>(mp);
}
```

```cpp
#include <cuda_runtime.h>
#include <cuda.h>
#include <cuda_bf16.h>
#include <stdint.h>
#include <limits.h>

typedef __nv_bfloat16 bf16;

constexpr int S_ = 2048, DM = 1024, NH = 32, DH = 128, NSEG = 64, FF = 3584;
constexpr int SPIN_LIMIT = 1 << 22;
#define W_INFL 2
#define NPROBE 3

__device__ uint8_t g_arena[10 << 20];
__device__ __align__(16) uint32_t g_tick[64];
__device__ __align__(16) uint32_t g_modp[8 * 2 * DM];
__host__ __device__ constexpr uint32_t blk(uint32_t lb, uint32_t par) {
    return (lb << 13) | ((((lb) ^ (lb >> 3) ^ (lb >> 4) ^ (lb >> 6) ^ par) & 1) << 12);
}
__host__ __device__ constexpr uint32_t lb_x2(uint32_t h) { return (h & 1) | ((h >> 1) << 3); }
__host__ __device__ constexpr uint32_t acc_slot(uint32_t s) { return (1u << 20) + (s & 1) * 32768 + (s & 2) * 131072; }
__host__ __device__ constexpr uint32_t acc_piece(uint32_t half, uint32_t qd, uint32_t mt) { return mt * 1024 + (qd & 1) * 4096 + half * 8192 + (qd >> 1) * 16384; }
constexpr uint32_t LB_STAMP = 6;
__host__ __device__ constexpr uint32_t stamp_line(uint32_t w, uint32_t q) { return ((w & 1) * 2 + (q >> 1)) * 1024 + (q & 1) * 256; }
constexpr uint32_t ACC_ONE = 0x3c000000u, ACC_ALL = 0x50000000u;
constexpr uint32_t LB_PROBE = 6 | 64;
__host__ __device__ constexpr uint32_t lb_tok(uint32_t h) { return (h & 1) | ((h >> 1) << 3); }
__device__ __align__(16) float g_mod[6 * DM];
__device__ __align__(1024) bf16 g_himg[(S_ + 32) * DM];
__device__ __align__(1024) bf16 g_O[S_ * NH * DH];
__device__ __align__(1024) bf16 g_y[S_ * DM];
__device__ __align__(1024) bf16 g_g[S_ * DM];
__device__ __align__(1024) bf16 g_x1[S_ * DM];
__device__ __align__(16) float g_st[4 * S_ * 2];
__device__ __align__(16) float g_vec[3 * DM + FF];
__device__ float g_cst[8];
__device__ uint32_t g_pcnt[2 * 32 * 8], g_pflag[6 * 32 * 8];
__device__ __align__(1024) bf16 g_u[S_ * FF];

#define TL(i) {}
#define TX(i) {}
#define TLC(i) {}
__device__ __forceinline__ uint32_t smem_u32(const void* p) { return (uint32_t)__cvta_generic_to_shared(p); }
__device__ __forceinline__ void spin_guard(int it) {
    asm volatile("{.reg .pred p; setp.gt.s32 p, %0, %1; @p st.global.u32 [%2], %0;}" ::"r"(it), "n"(SPIN_LIMIT), "l"(1ull));
}
__device__ __forceinline__ void wg_fence() { asm volatile("wgmma.fence.sync.aligned;" ::: "memory"); }
__device__ __forceinline__ void wg_commit() { asm volatile("wgmma.commit_group.sync.aligned;" ::: "memory"); }
template <int N> __device__ __forceinline__ void wg_wait() { asm volatile("wgmma.wait_group.sync.aligned %0;" ::"n"(N) : "memory"); }
__host__ __device__ constexpr uint64_t mkdesc(uint32_t addr, uint32_t lbo, uint32_t sbo, uint32_t swz) {
    return (uint64_t)((addr & 0x3FFFF) >> 4) | ((uint64_t)(lbo >> 4) << 16) | ((uint64_t)(sbo >> 4) << 32) | ((uint64_t)swz << 62);
}
__device__ __forceinline__ uint64_t dadd(uint64_t d, uint32_t o) { return (d & 0xffffffff00000000ull) | (uint32_t)((uint32_t)d + o); }
__device__ __forceinline__ void mbar_init(uint32_t b, uint32_t c) { asm volatile("mbarrier.init.shared.b64 [%0], %1;" ::"r"(b), "r"(c) : "memory"); }
__device__ __forceinline__ void mbar_expect(uint32_t b, uint32_t tx) { asm volatile("mbarrier.arrive.expect_tx.shared.b64 _, [%0], %1;" ::"r"(b), "r"(tx) : "memory"); }
__device__ __forceinline__ void mbar_arrive(uint32_t b) { asm volatile("mbarrier.arrive.shared.b64 _, [%0];" ::"r"(b) : "memory"); }
__device__ __forceinline__ void mbar_arrive_cluster(uint32_t b, uint32_t cta) {
    asm volatile("{.reg .b32 r; mapa.shared::cluster.u32 r, %0, %1; mbarrier.arrive.shared::cluster.b64 _, [r];}" ::"r"(b), "r"(cta) : "memory");
}
__device__ __forceinline__ void mbar_arrive_cluster_if(bool c, uint32_t b, uint32_t cta) {
    asm volatile("{.reg .pred p; .reg .b32 r; setp.ne.u32 p, %2, 0; mapa.shared::cluster.u32 r, %0, %1; @p mbarrier.arrive.shared::cluster.b64 _, [r];}" ::"r"(b), "r"(cta), "r"((uint32_t)c) : "memory");
}
__device__ __forceinline__ bool mbar_try(uint32_t b, uint32_t par) {
    uint32_t ok;
    asm volatile("{.reg .pred p; mbarrier.try_wait.parity.shared.b64 p, [%1], %2; selp.u32 %0, 1, 0, p;}" : "=r"(ok) : "r"(b), "r"(par) : "memory");
    return ok;
}
__device__ __forceinline__ void mbar_wait(uint32_t b, uint32_t par) {
    int it = 0;
#pragma unroll 1
    while (!mbar_try(b, par)) { spin_guard(++it); }
}
__device__ __forceinline__ void mbar_wait_w(uint32_t b, uint32_t par) {
    int it = 0;
    bool ok;
#pragma unroll 1
    do { ok = __all_sync(~0u, mbar_try(b, par)); spin_guard(++it); } while (!ok);
}
__device__ __forceinline__ void mbar_wait_cluster(uint32_t b, uint32_t par) {
    int it = 0;
    while (true) {
        uint32_t ok;
        asm volatile("{.reg .pred p; mbarrier.try_wait.parity.acquire.cluster.shared::cta.b64 p, [%1], %2; selp.u32 %0, 1, 0, p;}" : "=r"(ok) : "r"(b), "r"(par) : "memory");
        if (ok) break;
        spin_guard(++it);
    }
}
__device__ __forceinline__ void tma2d(uint32_t dst, const CUtensorMap* m, int c0, int c1, uint32_t bar) {
    asm volatile("cp.async.bulk.tensor.2d.shared::cluster.global.mbarrier::complete_tx::bytes [%0], [%1, {%3, %4}], [%2];" ::"r"(dst), "l"(m), "r"(bar), "r"(c0), "r"(c1) : "memory");
}
__device__ __forceinline__ void tma2d_mc(uint32_t dst, const CUtensorMap* m, int c0, int c1, uint32_t bar, uint16_t mask) {
    asm volatile("cp.async.bulk.tensor.2d.shared::cluster.global.mbarrier::complete_tx::bytes.multicast::cluster [%0], [%1, {%3, %4}], [%2], %5;" ::"r"(dst), "l"(m), "r"(bar), "r"(c0), "r"(c1), "h"(mask) : "memory");
}
__device__ __forceinline__ void bulk_g2s(uint32_t dst, const void* src, uint32_t bytes, uint32_t bar) {
    asm volatile("cp.async.bulk.shared::cluster.global.mbarrier::complete_tx::bytes [%0], [%1], %2, [%3];" ::"r"(dst), "l"(src), "r"(bytes), "r"(bar) : "memory");
}
__device__ __forceinline__ void bar_sync(int id, int n) { asm volatile("bar.sync %0, %1;" ::"r"(id), "r"(n) : "memory"); }
__device__ __forceinline__ void bar_arrive(int id, int n) { asm volatile("bar.arrive %0, %1;" ::"r"(id), "r"(n) : "memory"); }
__device__ __forceinline__ void cluster_sync_all() { asm volatile("barrier.cluster.arrive.aligned; barrier.cluster.wait.aligned;" ::: "memory"); }
__device__ __forceinline__ void fence_async_smem() { asm volatile("fence.proxy.async.shared::cta;" ::: "memory"); }
__device__ __forceinline__ void ldsm4t(uint32_t* r, uint32_t a) {
    asm volatile("ldmatrix.sync.aligned.m8n8.x4.trans.shared.b16 {%0,%1,%2,%3}, [%4];" : "=r"(r[0]), "=r"(r[1]), "=r"(r[2]), "=r"(r[3]) : "r"(a) : "memory");
}
__device__ __forceinline__ void ldsm4(uint32_t* r, uint32_t a) {
    asm volatile("ldmatrix.sync.aligned.m8n8.x4.shared.b16 {%0,%1,%2,%3}, [%4];" : "=r"(r[0]), "=r"(r[1]), "=r"(r[2]), "=r"(r[3]) : "r"(a) : "memory");
}
__device__ __forceinline__ uint32_t movm(uint32_t a) {
    uint32_t d; asm volatile("movmatrix.sync.aligned.m8n8.trans.b16 %0, %1;" : "=r"(d) : "r"(a)); return d;
}
__device__ __forceinline__ void mma16816(float* d, uint32_t a0, uint32_t a1, uint32_t a2, uint32_t a3, uint32_t b0, uint32_t b1) {
    asm volatile("mma.sync.aligned.m16n8k16.row.col.f32.bf16.bf16.f32 {%0,%1,%2,%3},{%4,%5,%6,%7},{%8,%9},{%0,%1,%2,%3};"
                 : "+f"(d[0]), "+f"(d[1]), "+f"(d[2]), "+f"(d[3]) : "r"(a0), "r"(a1), "r"(a2), "r"(a3), "r"(b0), "r"(b1));
}
__device__ __forceinline__ void mma16816z(float* d, const uint32_t* a, uint32_t b0, uint32_t b1) {
    asm volatile("mma.sync.aligned.m16n8k16.row.col.f32.bf16.bf16.f32 {%0,%1,%2,%3},{%4,%5,%6,%7},{%8,%9},{%10,%10,%10,%10};"
                 : "=f"(d[0]), "=f"(d[1]), "=f"(d[2]), "=f"(d[3]) : "r"(a[0]), "r"(a[1]), "r"(a[2]), "r"(a[3]), "r"(b0), "r"(b1), "f"(0.f));
}
__device__ __forceinline__ void mma1688(float* d, uint32_t a0, uint32_t a1, uint32_t b0) {
    asm volatile("mma.sync.aligned.m16n8k8.row.col.f32.bf16.bf16.f32 {%0,%1,%2,%3},{%4,%5},{%6},{%0,%1,%2,%3};"
                 : "+f"(d[0]), "+f"(d[1]), "+f"(d[2]), "+f"(d[3]) : "r"(a0), "r"(a1), "r"(b0));
}
__device__ __forceinline__ uint32_t pack2(float lo, float hi) {
    uint32_t r; asm("cvt.rn.bf16x2.f32 %0, %1, %2;" : "=r"(r) : "f"(hi), "f"(lo)); return r;
}
__device__ __forceinline__ uint32_t hadd2(uint32_t a, uint32_t b) {
    uint32_t r; asm("add.rn.bf16x2 %0, %1, %2;" : "=r"(r) : "r"(a), "r"(b)); return r;
}
__device__ __forceinline__ uint32_t hadd2v(uint32_t a, uint32_t b) {
    uint32_t r; asm volatile("add.rn.bf16x2 %0, %1, %2;" : "=r"(r) : "r"(a), "r"(b)); return r;
}
__device__ __forceinline__ float bflo(uint32_t u) { return __uint_as_float(u << 16); }
__device__ __forceinline__ float bfhi(uint32_t u) { return __uint_as_float(u & 0xffff0000u); }
__device__ __forceinline__ float ex2(float x) { float r; asm("ex2.approx.ftz.f32 %0, %1;" : "=f"(r) : "f"(x)); return r; }
__device__ __forceinline__ uint4 ldg_rlx4(const void* p) {
    uint4 v; asm volatile("ld.relaxed.gpu.global.v4.u32 {%0,%1,%2,%3}, [%4];" : "=r"(v.x), "=r"(v.y), "=r"(v.z), "=r"(v.w) : "l"(p) : "memory"); return v;
}
__device__ __forceinline__ uint2 ldg_rlx2(const void* p) {
    unsigned long long v; asm volatile("ld.relaxed.gpu.global.b64 %0, [%1];" : "=l"(v) : "l"(p) : "memory");
    return make_uint2((uint32_t)v, (uint32_t)(v >> 32));
}
__device__ __forceinline__ uint32_t ldg_rlx1(const void* p) {
    uint32_t v; asm volatile("ld.relaxed.gpu.global.u32 %0, [%1];" : "=r"(v) : "l"(p) : "memory"); return v;
}
__device__ __forceinline__ void stg_rlx1(void* p, uint32_t v) { asm volatile("st.relaxed.gpu.global.u32 [%0], %1;" ::"l"(p), "r"(v) : "memory"); }
__device__ __forceinline__ void stg_rlx2(void* p, uint32_t x, uint32_t y) {
    unsigned long long v = (unsigned long long)x | ((unsigned long long)y << 32);
    asm volatile("st.relaxed.gpu.global.b64 [%0], %1;" ::"l"(p), "l"(v) : "memory");
}
__device__ __forceinline__ void stg_rlx4(void* p, uint32_t x, uint32_t y, uint32_t z, uint32_t w) {
    asm volatile("st.relaxed.gpu.global.v4.u32 [%0], {%1,%2,%3,%4};" ::"l"(p), "r"(x), "r"(y), "r"(z), "r"(w) : "memory");
}
__device__ __forceinline__ void sts4(uint32_t a, uint32_t x, uint32_t y, uint32_t z, uint32_t w) {
    asm volatile("st.shared.v4.u32 [%0], {%1,%2,%3,%4};" ::"r"(a), "r"(x), "r"(y), "r"(z), "r"(w) : "memory");
}
__device__ __forceinline__ uint4 lds4(uint32_t a) {
    uint4 v; asm volatile("ld.shared.v4.u32 {%0,%1,%2,%3}, [%4];" : "=r"(v.x), "=r"(v.y), "=r"(v.z), "=r"(v.w) : "r"(a) : "memory"); return v;
}
__device__ __forceinline__ void st_async4(uint32_t a, float x, float y, float z, float w, uint32_t bar) {
    asm volatile("st.async.shared::cluster.mbarrier::complete_tx::bytes.v4.f32 [%0], {%1,%2,%3,%4}, [%5];" ::"r"(a), "f"(x), "f"(y), "f"(z), "f"(w), "r"(bar) : "memory");
}
#define F4(d, i) "+f"(d[i]), "+f"(d[i + 1]), "+f"(d[i + 2]), "+f"(d[i + 3])
template <bool V> __device__ __forceinline__ void wgmma_tok_rs(float* d, const uint32_t* a, uint64_t b, int sc) {
    if (V) asm volatile("{.reg .pred p; setp.ne.b32 p, %25, 0;\n wgmma.mma_async.sync.aligned.m64n40k16.f32.bf16.bf16 {%0,%1,%2,%3,%4,%5,%6,%7,%8,%9,%10,%11,%12,%13,%14,%15,%16,%17,%18,%19}, {%20,%21,%22,%23}, %24, p, 1, 1, 0;}"
                        : F4(d, 0), F4(d, 4), F4(d, 8), F4(d, 12), F4(d, 16) : "r"(a[0]), "r"(a[1]), "r"(a[2]), "r"(a[3]), "l"(b), "r"(sc));
    else asm volatile("{.reg .pred p; setp.ne.b32 p, %21, 0;\n wgmma.mma_async.sync.aligned.m64n32k16.f32.bf16.bf16 {%0,%1,%2,%3,%4,%5,%6,%7,%8,%9,%10,%11,%12,%13,%14,%15}, {%16,%17,%18,%19}, %20, p, 1, 1, 0;}"
                      : F4(d, 0), F4(d, 4), F4(d, 8), F4(d, 12) : "r"(a[0]), "r"(a[1]), "r"(a[2]), "r"(a[3]), "l"(b), "r"(sc));
}
template <bool V> __device__ __forceinline__ void wgmma_tok_ss(float* d, uint64_t a, uint64_t b) {
    if (V) asm volatile("wgmma.mma_async.sync.aligned.m64n40k16.f32.bf16.bf16 {%0,%1,%2,%3,%4,%5,%6,%7,%8,%9,%10,%11,%12,%13,%14,%15,%16,%17,%18,%19}, %20, %21, 1, 1, 1, 1, 0;"
                        : F4(d, 0), F4(d, 4), F4(d, 8), F4(d, 12), F4(d, 16) : "l"(a), "l"(b));
    else asm volatile("wgmma.mma_async.sync.aligned.m64n32k16.f32.bf16.bf16 {%0,%1,%2,%3,%4,%5,%6,%7,%8,%9,%10,%11,%12,%13,%14,%15}, %16, %17, 1, 1, 1, 1, 0;"
                      : F4(d, 0), F4(d, 4), F4(d, 8), F4(d, 12) : "l"(a), "l"(b));
}
#define F16(d, i) F4(d, i), F4(d, i + 4), F4(d, i + 8), F4(d, i + 12)
template <int TA>
__device__ __forceinline__ void wgmma_ss128(float* d, uint64_t a, uint64_t b, int sc) {
    asm volatile("{.reg .pred p; setp.ne.b32 p, %66, 0;\n wgmma.mma_async.sync.aligned.m64n128k16.f32.bf16.bf16 "
                 "{%0,%1,%2,%3,%4,%5,%6,%7,%8,%9,%10,%11,%12,%13,%14,%15,%16,%17,%18,%19,%20,%21,%22,%23,%24,%25,%26,%27,%28,%29,%30,%31,"
                 "%32,%33,%34,%35,%36,%37,%38,%39,%40,%41,%42,%43,%44,%45,%46,%47,%48,%49,%50,%51,%52,%53,%54,%55,%56,%57,%58,%59,%60,%61,%62,%63}, %64, %65, p, 1, 1, %67, 1;}"
                 : F16(d, 0), F16(d, 16), F16(d, 32), F16(d, 48) : "l"(a), "l"(b), "r"(sc), "n"(TA));
}

__device__ __forceinline__ float warp_sum(float v) {
#pragma unroll
    for (int o = 16; o; o >>= 1) v += __shfl_xor_sync(~0u, v, o);
    return v;
}
__device__ __forceinline__ float bfround(float x) { return __bfloat162float(__float2bfloat16(x)); }

__device__ __forceinline__ void wait_count1(const uint32_t* p, uint32_t target) {
    int it = 0;
#pragma unroll 1
    while (true) {
        uint32_t v;
        asm volatile("ld.acquire.gpu.global.u32 %0, [%1];" : "=r"(v) : "l"(p) : "memory");
        if (v >= target) break;
        spin_guard(++it);
    }
}
__device__ __forceinline__ void red2(float* p, float a, float b) {
    asm volatile("red.relaxed.gpu.global.add.v2.f32 [%0], {%1, %2};" ::"l"(p), "f"(a), "f"(b) : "memory");
}
__device__ __forceinline__ void l2_prefetch(const void* p, uint32_t bytes) {
    asm volatile("cp.async.bulk.prefetch.L2.global [%0], %1;" ::"l"(p), "r"(bytes) : "memory");
}
__device__ __forceinline__ void signal_count(uint32_t* p) { asm volatile("red.release.gpu.global.add.u32 [%0], 1;" ::"l"(p) : "memory"); }
__device__ __forceinline__ void e_expect(uint32_t b, uint32_t tx) {
    asm volatile("{.reg .pred p; elect.sync _|p, 0xffffffff; @p mbarrier.arrive.expect_tx.shared.b64 _, [%0], %1;}" ::"r"(b), "r"(tx) : "memory");
}
__device__ __forceinline__ uint64_t evict_first() { uint64_t p; asm("createpolicy.fractional.L2::evict_first.b64 %0, 1.0;" : "=l"(p)); return p; }
__device__ __forceinline__ uint64_t evict_normal() { uint64_t p; asm("createpolicy.fractional.L2::evict_unchanged.b64 %0, 1.0;" : "=l"(p)); return p; }
__device__ __forceinline__ void e_tma2d(uint32_t dst, const CUtensorMap* m, int c0, int c1, uint32_t bar, uint64_t pol) {
    asm volatile("{.reg .pred p; elect.sync _|p, 0xffffffff;\n @p cp.async.bulk.tensor.2d.shared::cluster.global.mbarrier::complete_tx::bytes.L2::cache_hint [%0], [%1, {%3, %4}], [%2], %5;}"
                 ::"r"(dst), "l"(m), "r"(bar), "r"(c0), "r"(c1), "l"(pol) : "memory");
}
__device__ __forceinline__ void e_tma2d_mc(uint32_t dst, const CUtensorMap* m, int c0, int c1, uint32_t bar, uint64_t pol) {
    asm volatile("{.reg .pred p; elect.sync _|p, 0xffffffff;\n @p cp.async.bulk.tensor.2d.shared::cluster.global.mbarrier::complete_tx::bytes.multicast::cluster.L2::cache_hint [%0], [%1, {%3, %4}], [%2], %5, %6;}"
                 ::"r"(dst), "l"(m), "r"(bar), "r"(c0), "r"(c1), "h"((uint16_t)3), "l"(pol) : "memory");
}
__device__ __forceinline__ void e_prefetch(const void* p, uint32_t bytes) {
    asm volatile("{.reg .pred p; elect.sync _|p, 0xffffffff; @p cp.async.bulk.prefetch.L2.global [%0], %1;}" ::"l"(p), "r"(bytes) : "memory");
}
__device__ __forceinline__ uint32_t wait_count_w(const uint32_t* p, uint32_t target) {
    int it = 0;
#pragma unroll 1
    while (true) {
        uint32_t v;
        asm volatile("ld.acquire.gpu.global.u32 %0, [%1];" : "=r"(v) : "l"(p) : "memory");
        if (__all_sync(~0u, v >= target)) return v;
        spin_guard(++it);
    }
}

__device__ __forceinline__ uint4 pack8(const float* x) {
    return make_uint4(pack2(x[0], x[1]), pack2(x[2], x[3]), pack2(x[4], x[5]), pack2(x[6], x[7]));
}
#define NL 6
constexpr uint32_t HCH = 5120, HBUF = 8 * HCH;
constexpr uint32_t SM_SX = 0, SM_ST = 2560, SM_OX = 8192, SM_LX = 10240, SM_PX = 11392, SM_PA = 12288, SM_VF = 18432, SM_TAB = 26624, SM_WL2 = 41984, SM_HB = 49152, SM_WO = 131072,
                   SM_WL = 196608, SM_PRE = SM_WL, SM_BAR = 227328, SM_TRC = SM_BAR + 256, SM_REC_TOTAL = SM_TRC + 2688;
__host__ __device__ constexpr uint32_t sm_wl(int i) { return i < 5 ? SM_WL + i * 6144 : SM_WL2; }
constexpr uint32_t SB0 = 1024;
constexpr int B_WO = 0, B_HE = 1, B_ROLE = 2, B_HB = 3, B_W = 5;
constexpr int NB_MEM = 1, NB_QK = 2, NB_X1 = 3, NB_X2 = 4, NB_WIN = 5, NB_WG = 6, NB_KDONE = 7, NB_FIN0 = 8, NB_LN = 9, NB_MEM2 = 10, NB_H = 11, NB_A = 12, NB_B = 13, NB_C = 14, NB_F = 15;
#define TPV_DLY 3
#define L_AT 0
#define D_X2 340
#define NPF1 6
#define NPF 11
#define T_GO 29
#define GATE_AT 25
#define T_X2 1875
#define T_V 300
#define VP_AT 1
#define PD 4
#define PV_FENCE 0
#define SSG 4
#define SSG_V 5
#define SS0_K 4
#define SS0_V 6
#define NPF0 4
#define STG_FENCE 1
#define WO_AT 0x1100
#define W_SPEC 6
#define NO_GUESS 0
#define NPF2 9
#define PF_DLY 6
#define H_D 210
#define PIN_EPI 1

#define PROF_INIT
#define PROF(i)
#define PROFV(i, v)
#define PROF_OUT

__device__ __forceinline__ uint32_t clk32() { uint32_t t; asm volatile("mov.u32 %0, %%clock;" : "=r"(t) :: "memory"); return t; }
__device__ __forceinline__ uint32_t gtime32() { uint32_t t; asm volatile("mov.u32 %0, %%globaltimer_lo;" : "=r"(t) :: "memory"); return t; }
__device__ __forceinline__ void spin_until(uint32_t t0, uint32_t d) { while (clk32() - t0 < d) {} }
template <int N> __device__ __forceinline__ uint32_t delay(uint32_t zero) {
    float x = __uint_as_float(clk32());
#pragma unroll
    for (int i = 0; i < N; i++) asm volatile("ex2.approx.ftz.f32 %0, %0;" : "+f"(x));
    return __float_as_uint(x) & zero;
}
__device__ __forceinline__ uint32_t clk_after(uint32_t x, uint32_t zero) {
    unsigned long long c = 0;
    asm volatile("{.reg .pred p; setp.eq.u32 p, %1, 0; @p mov.u64 %0, %%clock64;}" : "+l"(c) : "r"(x & zero) : "memory");
    return (uint32_t)c;
}
__device__ __forceinline__ uint32_t later(uint32_t a, uint32_t b) { return a + max((int)(b - a), 0); }
__device__ __forceinline__ void wait_clk(uint32_t t) {
#pragma unroll 1
    while (true) {
        unsigned long long c;
        asm volatile("mov.u64 %0, %%clock64;" : "=l"(c) :: "memory");
        if ((int)((uint32_t)c - t) >= 0) break;
    }
}
__device__ __forceinline__ uint32_t opaque(uint32_t v) { return __shfl_sync(~0u, v, threadIdx.x & 31); }
__device__ __forceinline__ uint32_t xor_or(uint32_t a, uint32_t b, uint32_t t) {
    uint32_t r; asm volatile("lop3.b32 %0, %1, %2, %3, 0x7E;" : "=r"(r) : "r"(a), "r"(b), "r"(t)); return r;
}
__device__ __forceinline__ uint32_t or3(uint32_t a, uint32_t b, uint32_t c) {
    uint32_t r; asm volatile("lop3.b32 %0, %1, %2, %3, 0xFE;" : "=r"(r) : "r"(a), "r"(b), "r"(c)); return r;
}
__device__ __forceinline__ uint32_t settag(uint32_t v, uint32_t tag) {
    uint32_t r; asm("lop3.b32 %0, %1, 1, %2, 0xB8;" : "=r"(r) : "r"(v), "r"(tag)); return r;
}
__device__ __forceinline__ void ldg4_if(uint4& v, const void* p, bool c) {
    asm volatile("{.reg .pred p; setp.ne.u32 p, %5, 0; @p ld.relaxed.gpu.global.v4.u32 {%0,%1,%2,%3}, [%4];}"
                 : "+r"(v.x), "+r"(v.y), "+r"(v.z), "+r"(v.w) : "l"(p), "r"((uint32_t)c) : "memory");
}
__device__ __forceinline__ uint4 ldg_rlx2x2(const void* p) {
    unsigned long long a, b;
    asm volatile("ld.relaxed.gpu.global.v2.b64 {%0,%1}, [%2];" : "=l"(a), "=l"(b) : "l"(p) : "memory");
    return make_uint4((uint32_t)a, (uint32_t)(a >> 32), (uint32_t)b, (uint32_t)(b >> 32));
}
__device__ __forceinline__ void stg_rlx2x2(void* p, uint32_t x, uint32_t y, uint32_t z, uint32_t w) {
    asm volatile("{.reg .b64 a, b; mov.b64 a, {%1,%2}; mov.b64 b, {%3,%4}; st.relaxed.gpu.global.v2.b64 [%0], {a, b};}" ::"l"(p), "r"(x), "r"(y), "r"(z), "r"(w) : "memory");
}
__device__ __forceinline__ void ldg1_if(uint32_t& v, const void* p, bool c) {
    asm volatile("{.reg .pred p; setp.ne.u32 p, %2, 0; @p ld.relaxed.gpu.global.u32 %0, [%1];}" : "+r"(v) : "l"(p), "r"((uint32_t)c) : "memory");
}
__device__ __forceinline__ void sts2(uint32_t a, float x, float y) { asm volatile("st.shared.v2.f32 [%0], {%1,%2};" ::"r"(a), "f"(x), "f"(y) : "memory"); }
__device__ __forceinline__ void sts4f(uint32_t a, float x, float y, float z, float w) {
    asm volatile("st.shared.v4.f32 [%0], {%1,%2,%3,%4};" ::"r"(a), "f"(x), "f"(y), "f"(z), "f"(w) : "memory");
}
__device__ __forceinline__ void sts1(uint32_t a, uint32_t x) { asm volatile("st.shared.u32 [%0], %1;" ::"r"(a), "r"(x) : "memory"); }
__device__ __forceinline__ uint32_t lds1(uint32_t a) { uint32_t v; asm volatile("ld.shared.u32 %0, [%1];" : "=r"(v) : "r"(a) : "memory"); return v; }
__device__ __forceinline__ float4 lds4f(uint32_t a) {
    float4 v; asm volatile("ld.shared.v4.f32 {%0,%1,%2,%3}, [%4];" : "=f"(v.x), "=f"(v.y), "=f"(v.z), "=f"(v.w) : "r"(a) : "memory"); return v;
}
__device__ __forceinline__ float2 lds2f(uint32_t a) {
    float2 v; asm volatile("ld.shared.v2.f32 {%0,%1}, [%2];" : "=f"(v.x), "=f"(v.y) : "r"(a) : "memory"); return v;
}
__device__ __forceinline__ bool any_bit0(uint32_t x) {
    uint32_t r;
    asm volatile("{.reg .pred p, q; .reg .b32 t; and.b32 t, %1, 1; setp.ne.u32 p, t, 0; vote.sync.any.pred q, p, 0xffffffff; selp.u32 %0, 1, 0, q;}" : "=r"(r) : "r"(x));
    return r;
}
__device__ __forceinline__ float rcp_fast(float x) { float r; asm("rcp.approx.ftz.f32 %0, %1;" : "=f"(r) : "f"(x)); return r; }
__device__ __forceinline__ void stsm4(uint32_t a, uint32_t r0, uint32_t r1, uint32_t r2, uint32_t r3) {
    asm volatile("stmatrix.sync.aligned.m8n8.x4.shared.b16 [%0], {%1,%2,%3,%4};" ::"r"(a), "r"(r0), "r"(r1), "r"(r2), "r"(r3) : "memory");
}
__device__ __forceinline__ void stsm4t(uint32_t a, uint32_t r0, uint32_t r1, uint32_t r2, uint32_t r3) {
    asm volatile("stmatrix.sync.aligned.m8n8.x4.trans.shared.b16 [%0], {%1,%2,%3,%4};" ::"r"(a), "r"(r0), "r"(r1), "r"(r2), "r"(r3) : "memory");
}
__device__ __forceinline__ void stg_b64_if(bool c, void* p, uint32_t x, uint32_t y) {
    asm volatile("{.reg .pred p; .reg .b64 a; setp.ne.u32 p, %3, 0; mov.b64 a, {%1,%2}; @p st.relaxed.gpu.global.b64 [%0], a;}" ::"l"(p), "r"(x), "r"(y), "r"((uint32_t)c) : "memory");
}
__device__ __forceinline__ void cp_async16(uint32_t dst, const void* src) { asm volatile("cp.async.cg.shared.global [%0], [%1], 16;" ::"r"(dst), "l"(src) : "memory"); }
__device__ __forceinline__ void cp_async16_ef(uint32_t dst, const void* src) {
    asm volatile("cp.async.cg.shared.global.L2::cache_hint [%0], [%1], 16, %2;" ::"r"(dst), "l"(src), "l"(evict_first()) : "memory");
}
__device__ __forceinline__ uint32_t prmt(uint32_t a, uint32_t b, uint32_t c) { uint32_t r; asm("prmt.b32 %0, %1, %2, %3;" : "=r"(r) : "r"(a), "r"(b), "r"(c)); return r; }
__device__ __forceinline__ uint32_t hadd2h(uint32_t a, uint32_t b) { uint32_t r; asm("add.rn.f16x2 %0, %1, %2;" : "=r"(r) : "r"(a), "r"(b)); return r; }
__device__ __forceinline__ uint32_t hmin2h(uint32_t a, uint32_t b) { uint32_t r; asm("min.f16x2 %0, %1, %2;" : "=r"(r) : "r"(a), "r"(b)); return r; }
__device__ __forceinline__ uint32_t hmax2h(uint32_t a, uint32_t b) { uint32_t r; asm("max.f16x2 %0, %1, %2;" : "=r"(r) : "r"(a), "r"(b)); return r; }
__device__ __forceinline__ uint32_t max3u(uint32_t a, uint32_t b, uint32_t c) { return __vimax3_u32(a, b, c); }
__device__ __forceinline__ void fence_gpu() { asm volatile("fence.acq_rel.gpu;" ::: "memory"); }

__device__ __forceinline__ void h_load(uint32_t sb, const uint8_t* hsrc, int pass, uint32_t rank, uint32_t rot, uint32_t wq, bool arm = true, uint32_t skip = 0) {
    const uint32_t bar = sb + SM_BAR + 8 * (B_HB + (pass & 1)), c = (wq + rot) & 3, dst = sb + SM_HB + (pass & 1) * HBUF + (rank * 4 + c) * HCH + skip;
    const uint8_t* src = hsrc + ((size_t)pass * 65536 + c * 4096 + skip);
    if (arm && wq == 0) e_expect(bar, 32768 - 8 * skip);
    asm volatile("{.reg .pred p; elect.sync _|p, 0xffffffff;\n"
                 " @p cp.async.bulk.shared::cluster.global.mbarrier::complete_tx::bytes.multicast::cluster.L2::cache_hint [%0], [%1], %4, [%2], %3, %5;}"
                 ::"r"(dst), "l"(src), "r"(bar), "h"((uint16_t)3), "r"(4096 - skip), "l"(evict_first()) : "memory");
}
__device__ __forceinline__ uint4 ldg_b128(const void* p) {
    uint4 v;
    asm volatile("{.reg .b128 t; .reg .b64 a, b; ld.relaxed.gpu.global.b128 t, [%4]; mov.b128 {a, b}, t; mov.b64 {%0,%1}, a; mov.b64 {%2,%3}, b;}"
                 : "=r"(v.x), "=r"(v.y), "=r"(v.z), "=r"(v.w) : "l"(p) : "memory");
    return v;
}
__device__ __forceinline__ void stg_b128_if(bool c, void* p, uint32_t x, uint32_t y, uint32_t z, uint32_t w) {
    asm volatile("{.reg .pred p; .reg .b128 t; .reg .b64 a, b; setp.ne.u32 p, %5, 0; mov.b64 a, {%1,%2}; mov.b64 b, {%3,%4}; mov.b128 t, {a, b}; @p st.relaxed.gpu.global.b128 [%0], t;}"
                 ::"l"(p), "r"(x), "r"(y), "r"(z), "r"(w), "r"((uint32_t)c) : "memory");
}
__device__ __forceinline__ float pretag(float x, uint32_t add, uint32_t keep) { return __uint_as_float((__float_as_uint(x) + add) & keep); }

template <bool MASK, class F>
__device__ __forceinline__ void softmax_rows(uint32_t src, uint32_t dst, uint32_t g16, int row0, F mid) {
    const uint32_t u = (g16 >> 7) & 3, e = ((g16 >> 9) << 3) | ((g16 >> 4) & 7);
    const uint32_t se = src + e * 8, su = se + u * 1088;
    const float2 p0 = lds2f(su), p1 = lds2f(su + 256), p2 = lds2f(su + 512), p3 = lds2f(su + 768);
    const float2 m0 = lds2f(se + 4352), m1 = lds2f(se + 4352 + 256), m2 = lds2f(se + 4352 + 512), m3 = lds2f(se + 4352 + 768);
    float a0 = (p0.x + p1.x) + (p2.x + p3.x), a1 = (p0.y + p1.y) + (p2.y + p3.y);
    const float a2 = (m0.x + m1.x) + (m2.x + m3.x), a3 = (m0.y + m1.y) + (m2.y + m3.y);
    mid(__float_as_uint(a3));
    if (MASK) {
        const int vis = row0 + (e >> 2) - 2 * (e & 3) - 8 * u;
        if (vis < 0) a0 = -1e9f / 0.08838834764831845f;
        if (vis < 1) a1 = -1e9f / 0.08838834764831845f;
    }
    int k = __float_as_int(fmaxf(fmaxf(a0, a1), fmaxf(a2, a3)));
    k ^= (k >> 31) & 0x7fffffff;
    const bool hi = g16 & 64;
    const int k0 = __reduce_max_sync(~0u, hi ? INT_MIN : k), k1 = __reduce_max_sync(~0u, hi ? k : INT_MIN);
    k = hi ? k1 : k0;
    const float m = __int_as_float(k ^ ((k >> 31) & 0x7fffffff));
    const float sl2 = 0.08838834764831845f * 1.4426950408889634f, mb = -m * sl2;
    sts1(dst + e * 16 + u * 4, pack2(ex2(fmaf(a0, sl2, mb)), ex2(fmaf(a1, sl2, mb))));
    sts1(dst + 512 + e * 4, pack2(ex2(fmaf(a2, sl2, mb)), ex2(fmaf(a3, sl2, mb))));
}

__device__ __forceinline__ uint32_t pack_h2(float lo, float hi) {
    uint32_t r; asm("cvt.rn.satfinite.f16x2.f32 %0, %1, %2;" : "=r"(r) : "f"(hi), "f"(lo)); return r;
}
__device__ __forceinline__ float2 unpack_h2(uint32_t u) {
    float2 r; asm("{.reg .b16 l, h; mov.b32 {l, h}, %2; cvt.f32.f16 %0, l; cvt.f32.f16 %1, h;}" : "=f"(r.x), "=f"(r.y) : "r"(u)); return r;
}
__device__ __forceinline__ uint32_t h2bf(uint32_t u) {
    uint32_t r;
    asm volatile("{.reg .b16 l, h; .reg .f32 a, b; mov.b32 {l, h}, %1; cvt.f32.f16 a, l; cvt.f32.f16 b, h; cvt.rn.bf16x2.f32 %0, b, a;}" : "=r"(r) : "r"(u));
    return r;
}
__device__ __forceinline__ void red_h8(void* p, uint32_t x, uint32_t y, uint32_t z, uint32_t w) {
    asm volatile("red.relaxed.gpu.global.add.noftz.v4.f16x2 [%0], {%1,%2,%3,%4};" ::"l"(p), "r"(x), "r"(y), "r"(z), "r"(w) : "memory");
}
__device__ __forceinline__ void red_h2_if(bool c, void* p, uint32_t x) {
    asm volatile("{.reg .pred p; setp.ne.u32 p, %2, 0; @p red.relaxed.gpu.global.add.noftz.f16x2 [%0], %1;}" ::"l"(p), "r"(x), "r"((uint32_t)c) : "memory");
}
__device__ __forceinline__ void red_h10(bool c, void* p, void* q, uint32_t x, uint32_t y, uint32_t z, uint32_t w, uint32_t e) {
    asm volatile("{.reg .pred p; setp.ne.u32 p, %7, 0; red.relaxed.gpu.global.add.noftz.v4.f16x2 [%0], {%2,%3,%4,%5};\n"
                 " @p red.relaxed.gpu.global.add.noftz.f16x2 [%1], %6;}" ::"l"(p), "l"(q), "r"(x), "r"(y), "r"(z), "r"(w), "r"(e), "r"((uint32_t)c) : "memory");
}
constexpr float Q_SCALE = 1024.0f;
constexpr float SM_L2E = 0.08838834764831845f * 1.4426950408889634f * Q_SCALE;
template <int V> struct IC { static constexpr int value = V; };
typedef unsigned long long u64;
__device__ __forceinline__ uint32_t lo32(u64 v) { return (uint32_t)v; }
__device__ __forceinline__ uint32_t hi32(u64 v) { return (uint32_t)(v >> 32); }
__device__ __forceinline__ u64 ldg_u64(const void* p) { u64 v; asm volatile("ld.relaxed.gpu.global.b64 %0, [%1];" : "=l"(v) : "l"(p) : "memory"); return v; }
__device__ __forceinline__ void ldg_u64_if(u64& v, const void* p, bool c) {
    asm volatile("{.reg .pred p; setp.ne.u32 p, %2, 0; @p ld.relaxed.gpu.global.b64 %0, [%1];}" : "+l"(v) : "l"(p), "r"((uint32_t)c) : "memory");
}
struct RecTime { uint32_t go, x2, v, dx2, h; };
__device__ __forceinline__ void rec_main(uint32_t sb, const CUtensorMap* tWo, uint8_t* arena, int role, int hinfo, int wg, uint32_t zero, const RecTime& tm) {
    const int hA = hinfo & 255;
    const int tid = threadIdx.x, t = tid & 127, lane = tid & 31, wi = t >> 5;
    const uint32_t bars = sb + SM_BAR;
    const int head = role >> 2, qd = role & 3, j = blockIdx.x & 1, kh = role & 1;
    const uint32_t mypar = head >= hA;
    const uint32_t wiu = __reduce_max_sync(~0u, wi);
    const bool warp0 = wiu == 0;
    const uint8_t* hsrc = (const uint8_t*)g_himg + kh * 32768 + j * 16384;
    auto tokbase = [&](int ty) { return ((ty + 1) << 21) + blk(lb_tok(head), mypar ^ ((hinfo >> (8 + ty)) & 1)); };
    const uint32_t tbw = tokbase(wg), tbq = tokbase(0) + (qd >> 1) * 2048 + (qd & 1) * 8;
#define KS(p) (4 * (((p) >> 1) & 7) + ((p) >> 4) + 2 * ((p) & 1))
    uint32_t w[32 - NL][4];
    uint4 wl5;
    if (wg == 2) bar_arrive(NB_WIN, 384);
    const uint32_t po = (1 << 20) + j * 16384 + kh * 2048;
    const uint32_t c16 = kh * 2048 + ((2 * j + (wi >> 1)) * 32 + lane) * 16, xso = blk(lb_x2(head), mypar);
    const uint32_t x2o = xso + wg * 16384 + (wi & 1) * 2048 + (c16 >> 1), tko = tbw + (wi & 1) * 16384 + c16;
    {
        stg_rlx2(arena + x2o, 0, 0);
#pragma unroll
        for (int i = 0; i < 4; i++) stg_rlx4(arena + ((i & 1 ? tko : tbw + (po ^ 2048) + t * 16) + (i >> 1) * 32768), 0, 0, 0, 0);
    }
    const uint32_t frow = ((lane >> 4) * 8 + (lane & 7)) * 128, fx = ((lane >> 3) & 1) ^ (lane & 7);
    {
#pragma unroll 1
        for (int i = 0; i < 4; i++) mbar_wait_w(bars + 8 * (B_W + (wg == 2 ? 8 + i : 2 * i + wg)), 0);
        const uint32_t stg = sb + wg * 65536;
#pragma unroll
        for (int p = NL; p < 32; p++) ldsm4t(w[p - NL], stg + KS(p) * 2048 + frow + ((fx ^ (2 * wi)) << 4));
#pragma unroll
        for (int i = 0; i < NL; i++) {
            wl5 = lds4(stg + KS(i) * 2048 + t * 16);
            if (i < 5) sts4(sb + sm_wl(i) + tid * 16, wl5.x, wl5.y, wl5.z, wl5.w);
        }
        fence_async_smem();
        if (wg < 2) bar_sync(NB_WG, 256);
        if (wg > 0) wait_count_w(&g_tick[32 + (lane & 3) * 8], wg);
        if (wg == 1) {
            mbar_arrive_cluster_if(t == 0, bars + 8 * B_HE, j ^ 1);
            asm volatile("fence.proxy.async.global;" ::: "memory");
            mbar_wait_w(bars + 8 * B_HE, 0);
#pragma unroll 1
            for (int i = 0; i < 2; i++) h_load(sb, hsrc, i, j, head, wiu, true, i ? 0 : 2048);
        }
        TL(3 + wg)
    }
    uint32_t g16 = opaque(t * 16);
    {
        const uint32_t wr = ((wg * 4 + wi) ^ head) & 7;
        const uint32_t pc = wg < 2 ? acc_piece(wr >> 2, qd, wr & 3) : acc_piece(kh, wi, 0);
        const uint32_t lm = sb + SM_HB + 4096 + (lane & 7) * 128;
        const uint32_t a0 = wg < 2 ? sb + SM_WL + wg * 2048 + frow + ((fx ^ (2 * wi)) << 4) : blk(LB_STAMP + (wi >> 1), mypar) + stamp_line(wi, lane >> 3) + (lane & 7) * 16;
        const uint32_t a1 = pc + lane * 16;
        const uint32_t a2 = wg < 2 ? pc + 512 + (lane >> 3) * 4 : (role >> 2) * 1024 + (lane < 8 ? (role & 3) * 128 : 384) + lane * 16;
        const uint32_t a3 = wg < 2 ? sb + SM_WO + (wr >> 2) * 32768 + frow + ((fx ^ (2 * (wr & 3))) << 4) : qd * 65536 + head * 2048 + wi * 512 + lane * 4;
        const uint32_t a4 = wg < 2 ? lm + ((fx ^ ((lane >> 4) * 4)) << 4) : lm + (fx << 4) + ((lane >> 4) + 2 * wi) * HCH;
        if (wg < 2) bar_arrive(NB_X2, 384);
        else bar_sync(NB_X2, 384);
        if (NL > 5) {
            sts4(sb + SM_WL2 + tid * 16, wl5.x, wl5.y, wl5.z, wl5.w);
            fence_async_smem();
            bar_sync(NB_WG + 1 + wg, 128);
        }
        sts4(sb + SM_TAB + wg * 5120 + g16, a0, x2o,
             wg ? xso + (wg == 2 ? 32768 : 0) + t * 8 : blk(LB_STAMP + ((lane >> 1) & 1), (lane >> 2) & 1) + stamp_line(lane, qd) + head * 4, tko);
        sts4(sb + SM_TAB + wg * 5120 + 2048 + g16, a1, a2, a3, a4);
        sts2(sb + SM_TAB + wg * 5120 + 4096 + t * 8, __uint_as_float(tbw + t * 16), __uint_as_float((wg ? tbq : tokbase(1)) + t * 16));
    }
    const uint32_t ONES = 0x3f803f80u, tabw = sb + SM_TAB + wg * 5120;
#define LAST ((g16 & 0x70) == 0x70)
    PROF_INIT

    auto pa_ptr = [&](int p) { return arena + (((p & 1) ^ 1) * 32768 + po + lds1(tabw + 4096 + (g16 >> 1))); };
    auto pa_request = [&](int p) { cp_async16(sb + SM_PA + wg * 2048 + g16, pa_ptr(p)); };
    auto pa_get = [&](int p) {
        asm volatile("cp.async.wait_all;" ::: "memory");
        uint4 pa = lds4(sb + SM_PA + wg * 2048 + g16);
        int it = 0;
#pragma unroll 1
        while (any_bit0(pa.x ^ ((p - 1) >> 1) ^ 1) && p > 0 && p <= NSEG) { pa = ldg_b128(pa_ptr(p)); spin_guard(++it); }
        return pa;
    };
    auto pass_init = [&](float* acc, int n, uint4 pa) {
#pragma unroll
        for (int i = 0; i < 4; i++) { acc[2 * i] = bflo((&pa.x)[i]); acc[2 * i + 1] = bfhi((&pa.x)[i]); }
#pragma unroll
        for (int i = 8; i < n; i++) acc[i] = 0.f;
    };
    auto pass_run = [&](auto vc, int p, float* acc, auto mid) {
        constexpr bool V = decltype(vc)::value;
#define HB(ks) dadd(mkdesc(SB0 + SM_HB + ((ks) >> 2) * HCH + ((ks) & 3) * 32, 16, 1024, 1), (p & 1) * (HBUF / 16))
        wg_fence();
#pragma unroll
        for (int i = 0; i < 32; i++) {
            constexpr int GAP = V ? SSG_V : SSG, SS0 = V ? SS0_V : SS0_K;
            const int u = i < SS0 ? 0 : (i - SS0 + GAP - 1) / GAP, q = i - (u < NL ? u : NL);
            if (i >= SS0 && (i - SS0) % GAP == 0 && u < NL) wgmma_tok_ss<V>(acc, dadd(mkdesc(SB0 + sm_wl(u), 8192, 1024, 1), (V ? 2 : wg) * 128), HB(KS(u)));
            else wgmma_tok_rs<V>(acc, w[q], HB(KS(NL + q)), 1);
            mid(i);
        }
        wg_commit();
    };
    auto pass_out = [&](auto tc, int p, float* acc, auto mid) {
        constexpr int TY = decltype(tc)::value;
        const bool V = TY == 2 || (TY == 4 && wg == 2), Q = TY >= 3 && wg == 0;
        const int b = p & 1, s = p - 2;
        (void)s;
        const uint32_t ftag = (((p - 1) >> 1) & 1) ^ 1, ptag = ((p >> 1) & 1) ^ 1;
        const bool tg = V || !(g16 & 64);
        const uint32_t add = tg ? (ftag ^ 1) << 16 : 0u, keep = tg ? 0xfffe0000u : ~0u;
        const uint32_t add1 = V ? 0u : add, keep1 = V ? ~0u : keep;
        const uint32_t add2 = Q ? add : 0u, keep2 = Q ? keep : ~0u;
        uint8_t* pdst = arena + (b * 32768 + (po ^ 2048) + lds1(tabw + 4096 + (g16 >> 1)));
        uint8_t* fdst = arena + ((b ^ 1) * 32768 + lds1(tabw + 12 + g16));
        if (PIN_EPI) asm volatile("" : "+l"(pdst), "+l"(fdst));
        mid(0);
        uint32_t r0 = pack2(pretag(acc[0], add, keep), pretag(acc[1], add1, keep1));
        uint32_t r1 = pack2(acc[2], acc[3]), r3 = pack2(acc[6], acc[7]);
        uint32_t r2 = pack2(pretag(acc[4], add2, keep2), pretag(acc[5], add2, keep2));
        if (!V) { r0 = movm(r0); r1 = movm(r1); r2 = movm(r2); r3 = movm(r3); }
        mid(1);
        stg_b128_if(p < NSEG, pdst, settag(pack2(pretag(acc[8], (ptag ^ 1) << 16, 0xfffe0000u), acc[9]), ptag), pack2(acc[10], acc[11]), pack2(acc[12], acc[13]), pack2(acc[14], acc[15]));
        stg_b128_if(p > 0 && p <= NSEG, fdst, settag(r0, ftag), r1, Q ? settag(r2, ftag) : r2, r3);
        PROF(10)
    };
    auto nop = [](int) {};
    auto wait0 = [](int i) { if (i == 0) wg_wait<0>(); };
    uint4 tf[2][2];
    auto load_tok = [&](int s, uint32_t o) {
        const uint8_t* ts = arena + ((s & 1) * 32768 + o);
#pragma unroll
        for (int a = 0; a < 2; a++)
#pragma unroll
            for (int b = 0; b < 2; b++) tf[a][b] = ldg_b128(ts + a * 16384 + b * 2048);
    };

    auto wo_load = [&](int stage) {
        if (wg == 2 && ((WO_AT >> (4 * wiu)) & 15) == stage) {
            const int c0 = (wiu >> 1) * 512 + qd * 128 + (wiu & 1) * 64;
            e_expect(bars + 8 * B_WO, 16384);
            e_tma2d(sb + SM_WO + wiu * 16384, tWo, c0, head * DH, bars + 8 * B_WO, evict_normal());
            e_tma2d(sb + SM_WO + wiu * 16384 + 8192, tWo, c0, head * DH + 64, bars + 8 * B_WO, evict_normal());
        }
    };
#pragma unroll 1
    for (int p = 0; p <= (wg >> 1); p++) {
        mbar_wait_w(bars + 8 * (B_HB + p), 0);
        float acc[16];
        pass_init(acc, 16, pa_get(p));
        if (wg == 2) TX(2 + 3 * p)
        wo_load(p);
        pass_run(IC<0>(), p, acc, nop);
        if (p) {
            mbar_wait_w(bars + 8 * B_HE, 1);
            asm volatile("fence.proxy.async.global;" ::: "memory");
            h_load(sb, hsrc, 2, j, head, wiu);
        }
        pass_out(IC<4>(), p, acc, wait0);
        if (wg < 2) {
            bar_arrive(NB_C, 384);
            if (wg == 0) bar_arrive(NB_WIN, 384);
        } else if (p == 0) {
            TX(3)
            bar_sync(NB_C, 384);
            mbar_arrive_cluster_if(g16 == 0, bars + 8 * B_HE, j ^ 1);
        }
        pa_request(p + 1);
    }
    if (wg < 2) {
        mbar_wait_w(bars + 8 * (B_HB + 1), 0);
        uint4 pa = pa_get(1);
        uint32_t wl = lds1(tabw + g16);
#pragma unroll 1
        for (int s = 0; s < NSEG; s++) {
            uint32_t w0[NL][4], xo, lm, fz = 0;
            float acc[16];
#pragma unroll
            for (int i = 0; i < 4; i++)
                asm volatile("shl.b32 %0, %4, 16; and.b32 %1, %4, 0xffff0000; mov.b32 %2, %5; mov.b32 %3, %5;"
                             : "=&f"(acc[2 * i]), "=f"(acc[2 * i + 1]), "=f"(acc[8 + 2 * i]), "=f"(acc[9 + 2 * i]) : "r"((&pa.x)[i]), "r"(zero));
#pragma unroll
            for (int i = 0; i < NL; i++) ldsm4t(w0[i], wl + (sm_wl(i) - SM_WL));
            if (wg == 0) bar_sync(NB_B, 256);
            else bar_sync(NB_WIN, 384);
            pass_run(IC<0>(), s + 1, acc, [&](int i) { if (i == GATE_AT && wg) bar_arrive(NB_B, 256); });
            xo = lds1(tabw + 4 + g16);
            lm = lds1(tabw + 2060 + g16) + (s & 1) * HBUF;
            pass_out(IC<3>(), s + 1, acc, [&](int i) {
                if (i == 0) {
                    wg_wait<0>();
                    if (wg == 0) bar_arrive(NB_MEM, 384);
                    fz |= clk32();
                    { const int s_ = s; { const int s = s_ - 1; (void)s; PROF(9) } }
                }
                if (i == 1 && wg) bar_sync(NB_F, 256);
            });
            asm volatile("" : "+r"(lm));
            if (wg == 0) bar_sync(NB_MEM2, 256);
            else bar_sync(NB_MEM, 384);
            PROF(1)
            float c[4][4];
            uint32_t bq[PD][4];
#define MEMF(it) ((lm ^ (((it) >> 3) * 32)) + ((it) & 7) * HCH)
#pragma unroll
            for (int it = 0; it < PD; it++) ldsm4(bq[it], MEMF(it));
#pragma unroll
            for (int it = 0; it < 16; it++) {
                uint32_t* bfr = bq[it % PD];
                const uint32_t* wa = 2 * it < NL ? w0[2 * it < NL ? 2 * it : 0] : w[2 * it < NL ? 0 : 2 * it - NL];
                const uint32_t* wb = 2 * it + 1 < NL ? w0[2 * it + 1 < NL ? 2 * it + 1 : 0] : w[2 * it + 1 < NL ? 0 : 2 * it + 1 - NL];
                float *ca = c[(2 * it) & 3], *cb = c[(2 * it + 1) & 3];
                if (it < 2) { mma16816z(ca, wa, bfr[0], bfr[1]); mma16816z(cb, wb, bfr[2], bfr[3]); }
                else { mma16816(ca, wa[0], wa[1], wa[2], wa[3], bfr[0], bfr[1]); mma16816(cb, wb[0], wb[1], wb[2], wb[3], bfr[2], bfr[3]); }
                if (it + PD < 16) ldsm4(bfr, MEMF(it + PD));
            }
            const float qs = wg ? 1.0f : 1.0f / Q_SCALE;
#define CSUM(e) fmaf(c[2][e] + c[3][e], qs, (c[0][e] + c[1][e]) * qs)
            const uint32_t r0 = pack2(CSUM(0), CSUM(1)), r1 = pack2(CSUM(2), CSUM(3));
            bar_arrive(NB_QK + (r0 & zero), 384);
            stg_rlx2(arena + xo, settag(movm(r0), (s & 1) ^ 1), movm(r1));
            const uint32_t tx = later(lds1(sb + SM_LX + 1040) + tm.x2, clk_after(r0, zero) + tm.dx2);
            g16 |= (fz | tx) & zero;
            PROF(2)
            {
                const uint32_t l16 = sb + (g16 & 0x1f0), g8 = g16 >> 1;
                const uint32_t tag = (s & 1) ^ 1, ttag = ((s >> 1) & 1) ^ 1;
                uint32_t wf[NPF][4], a3;
#define WF(f) (a3 + ((f) & 1) * 16384 + ((f) >> 1) * 2048)
                if (wg == 1) {
                    float sc[5][4];
                    uint4 (&kf)[2][2] = tf;
                    uint32_t qa[2][4], km[4], fz;
                    const uint32_t sd = lds1(sb + SM_TAB + 8 + g16);
                    int it = 0;
                    bool bad;
#pragma unroll 1
                    do {
                        u64 qf[2], x[8];
                        const float2 u = lds2f(tabw + 4096 + g8);
                        load_tok(s, __float_as_uint(u.x));
                        const uint8_t *xp = arena + lds1(tabw + 8 + g16), *tq = arena + ((s & 1) * 32768 + __float_as_uint(u.y));
                        asm volatile("" : "+l"(xp));
                        asm volatile("" : "+l"(tq));
#pragma unroll
                        for (int a = 0; a < 2; a++) qf[a] = ldg_u64(tq + a * 16384);
                        spin_guard(++it);
                        wait_clk(tx);
                        PROF(8)
#pragma unroll
                        for (int i = 0; i < 8; i++) x[i] = ldg_u64(xp + (i >> 2) * 16384 + (i & 3) * 1024);
                        fz = clk32();
                        const uint32_t bt = or3(xor_or(lo32(qf[0]), lo32(qf[1]), ttag), xor_or(kf[0][0].x, kf[0][1].x, ttag), xor_or(kf[1][0].x, kf[1][1].x, ttag));
#pragma unroll
                        for (int a = 0; a < 2; a++) { qa[a][1] = or3(lo32(qf[a]), zero, 0); qa[a][3] = or3(hi32(qf[a]), zero, 0); }
                        fz |= clk32();
#pragma unroll
                        for (int a = 0; a < 2; a++) { qa[a][0] = hadd2v(lo32(x[2 * a]), lo32(x[2 * a + 1])); qa[a][2] = hadd2v(hi32(x[2 * a]), hi32(x[2 * a + 1])); }
#pragma unroll
                        for (int a = 0; a < 2; a++) { km[2 * a] = hadd2v(lo32(x[4 + 2 * a]), lo32(x[5 + 2 * a])); km[2 * a + 1] = hadd2v(hi32(x[4 + 2 * a]), hi32(x[5 + 2 * a])); }
                        bad = any_bit0(or3(or3(bt, xor_or(lo32(x[0]), lo32(x[1]), tag), xor_or(lo32(x[2]), lo32(x[3]), tag)), xor_or(lo32(x[4]), lo32(x[5]), tag), xor_or(lo32(x[6]), lo32(x[7]), tag)));
                    } while (bad);
                    PROFV(13, it - 1)
                    PROF(7)
                    mma16816z(sc[0], qa[0], kf[0][0].x, kf[0][0].y);
                    mma16816z(sc[1], qa[0], kf[0][0].z, kf[0][0].w);
                    mma16816z(sc[2], qa[0], kf[0][1].x, kf[0][1].y);
                    mma16816z(sc[3], qa[0], kf[0][1].z, kf[0][1].w);
                    mma16816z(sc[4], qa[0], km[0], km[1]);
                    mma16816(sc[0], qa[1][0], qa[1][1], qa[1][2], qa[1][3], kf[1][0].x, kf[1][0].y);
                    mma16816(sc[1], qa[1][0], qa[1][1], qa[1][2], qa[1][3], kf[1][0].z, kf[1][0].w);
                    mma16816(sc[2], qa[1][0], qa[1][1], qa[1][2], qa[1][3], kf[1][1].x, kf[1][1].y);
                    mma16816(sc[3], qa[1][0], qa[1][1], qa[1][2], qa[1][3], kf[1][1].z, kf[1][1].w);
                    mma16816(sc[4], qa[1][0], qa[1][1], qa[1][2], qa[1][3], km[2], km[3]);
                    const uint32_t sx = sb + SM_SX + (g16 & 0x1f0) * 5;
                    sts4(sx + (g16 >> 5 & 0x30), pack_h2(sc[0][0], sc[0][1]), pack_h2(sc[1][0], sc[1][1]),
                         pack_h2(sc[2][0], sc[2][1]), pack_h2(sc[3][0], sc[3][1]));
                    sts1(sx + 64 + (g16 >> 7 & 0xc), pack_h2(sc[4][0], sc[4][1]));
                    bar_arrive(NB_X1, 256);
                    if (s == 0) TX(15)
                    const uint32_t now = gtime32();
#pragma unroll
                    for (int n = 0; n < 5; n++) sts2(sb + SM_ST + g8 + n * 1088, sc[n][2], sc[n][3]);
                    bar_arrive(NB_H, 256);
                    PROF(3)
                    a3 = lds1(tabw + 2056 + g16) | (fz & zero);
                    asm volatile("{.reg .pred p; setp.lt.u32 p, %2, 128; @p red.relaxed.gpu.global.max.u32 [%0], %1;}"
                                 ::"l"(arena + sd), "r"(__funnelshift_r(now * 8, s + 1, 8)), "r"(g16) : "memory");
                    if (s == 0) mbar_wait_w(bars + 8 * B_WO, 0);
                    a3 += delay<PF_DLY>(zero);
#pragma unroll
                    for (int f = 0; f < NPF; f++) ldsm4t(wf[f], WF(f));
                } else {
                    if (s == 0) { TL(9) mbar_wait_w(bars + 8 * B_WO, 0); TL(6) }
                    if (warp0 && !(s & 3)) {
                        const uint32_t need = min((s + 4) / 4 + 2, 17), a = sb + SM_LX + 1024 + ((g16 >> 2) & 12);
                        if (s == 0 || __any_sync(~0u, lds1(a) < need)) sts1(a, wait_count_w(&g_tick[32 + ((g16 >> 4) & 3) * 8], need));
                    }
                    a3 = lds1(tabw + 2056 + g16);
#pragma unroll
                    for (int f = 0; f < NPF0; f++) ldsm4t(wf[f], WF(f));
                    const float2 u = lds2f(tabw + 4096 + g8);
                    const uint8_t *q0 = arena + (tag * 32768 + po + __float_as_uint(u.x)), *q1 = arena + (tag * 32768 + po + __float_as_uint(u.y));
                    wait_clk(tx + tm.h);
                    int it = 0;
                    bool bad;
#pragma unroll 1
                    do {
                        const uint4 p0 = ldg_b128(q0), p1 = ldg_b128(q1);
                        spin_guard(++it);
                        wait_clk(tx + tm.v);
#pragma unroll
                        for (int f = NPF0; f < NPF1; f++) ldsm4t(wf[f], WF(f));
                        sts4(sb + SM_PA + g16, p0.x, p0.y, p0.z, p0.w);
                        sts4(sb + SM_PA + 2048 + g16, p1.x, p1.y, p1.z, p1.w);
                        bad = any_bit0(xor_or(p0.x, p1.x, ((s + 1) >> 1) ^ 1)) && s + 2 <= NSEG;
                    } while (bad);
                    bar_sync(NB_H, 256);
                    PROF(3)
                    softmax_rows<true>(sb + SM_ST, sb + SM_PX, g16, qd * 8, [&](uint32_t v) {
                        a3 += v & zero;
#pragma unroll
                        for (int f = NPF1; f < NPF2; f++) ldsm4t(wf[f], WF(f));
                    });
#pragma unroll
                    for (int f = NPF2; f < NPF; f++) ldsm4t(wf[f], WF(f));
                }
                PROF(5)
                float2 ls, a12;
                uint8_t *d0, *d1;
                bar_sync(NB_X2, 384);
                float c[4][4];
#pragma unroll
                for (int q = 0; q < 4; q++) {
                    uint32_t ob[4];
                    ldsm4t(ob, l16 + SM_OX + q * 512);
                    if (q == L_AT) ls = lds2f(sb + SM_LX + g8);
                    if (q == 2) { pa = lds4(sb + SM_PA + wg * 2048 + g16); wl = lds1(tabw + g16); }
                    if (q == 2) { a12 = lds2f(tabw + 2048 + g16); d0 = arena + (acc_slot(s + 1) + __float_as_uint(a12.x)); d1 = arena + (acc_slot(s + 1) + __float_as_uint(a12.y)); }
#pragma unroll
                    for (int f = 4 * q; f < 4 * q + 4; f++) {
                        const uint32_t* a = wf[f % NPF];
                        if (f < 4) mma16816z(c[f], a, ob[f & 2], ob[(f & 2) + 1]);
                        else mma16816(c[f & 3], a[0], a[1], a[2], a[3], ob[f & 2], ob[(f & 2) + 1]);
                        if (f + NPF < 16) ldsm4t(wf[f % NPF], WF(f + NPF));
                    }
                }
                if (wg == 0) bar_arrive(NB_WIN, 384);
                const float i0 = rcp_fast(ls.x), i1 = rcp_fast(ls.y);
                uint32_t v[4];
#pragma unroll
                for (int m = 0; m < 4; m++) v[m] = pack_h2((c[m >> 1][(m & 1) * 2] + c[(m >> 1) + 2][(m & 1) * 2]) * i0, (c[m >> 1][(m & 1) * 2 + 1] + c[(m >> 1) + 2][(m & 1) * 2 + 1]) * i1);
                red_h10(LAST, d0, d1, v[0], v[1], v[2], prmt(v[3], ACC_ONE, LAST ? 0x7610 : 0x3210), prmt(v[3], ACC_ONE, 0x7632));
                g16 |= v[0] & zero;
                PROF(6)
            }
        }
        if (wg) bar_sync(NB_WIN, 384);
    } else {
        TLC(0)
        auto request = [&](int s, uint32_t o) {
            cp_async16(sb + SM_PA + 4096 + g16, arena + (((s & 1) ^ 1) * 32768 + po + o));
            const uint8_t* ts = arena + ((s & 1) * 32768 + o);
#pragma unroll
            for (int i = 0; i < 4; i++) cp_async16(sb + SM_VF + i * 2048 + g16, ts + (i >> 1) * 16384 + (i & 1) * 2048);
        };
        auto fetch = [&](int s, uint4 t1, auto wait, auto after) {
            const uint32_t mo = acc_slot(s) + t1.x, eo = mo - (g16 & 0x1f0) + 512 + ((g16 >> 5) & 12);
            const uint8_t *ms = arena + mo, *es = arena + eo;
            uint32_t e[4] = {0, 0, 0, 0}, sel = LAST ? 0x5410 : 0x3210, dst[4];
#pragma unroll
            for (int i = 0; i < 4; i++) dst[i] = (t1.w + (s & 1) * HBUF) ^ (i * 32);
            asm volatile("" : "+l"(ms), "+l"(es), "+r"(e[0]), "+r"(e[1]), "+r"(e[2]), "+r"(e[3]), "+r"(sel), "+r"(dst[0]), "+r"(dst[1]), "+r"(dst[2]), "+r"(dst[3]));
            uint32_t late = wait(), fz;
            PROF(11) PROFV(0, gtime32())
            int it = 0;
            bool bad;
#pragma unroll 1
            do {
                uint4 m[4];
                uint32_t b = 0;
#pragma unroll
                for (int i = 0; i < 4; i++) {
                    m[i] = ldg_rlx4(ms + i * 1024);
                    ldg1_if(e[i], es + i * 1024, LAST);
                }
                if (it == 0) bar_arrive(NB_F, 256);
                const uint32_t now = clk32();
                fz = now;
                after(now & zero);
                sts1(sb + SM_LX + 1040, now - min(late >> 8, 8u) * 57);
                late = 0;
                spin_guard(++it);
#pragma unroll
                for (int i = 0; i < 4; i++) {
                    if (STG_FENCE >> i & 1) fz |= clk32();
                    b |= xor_or(m[i].w, e[i], ACC_ALL);
                    stsm4t(dst[i], h2bf(m[i].x), h2bf(m[i].y), h2bf(m[i].z), h2bf(prmt(m[i].w, e[i], sel)));
                }
                bad = __any_sync(~0u, LAST && b > 0xffffu);
            } while (bad);
            bar_arrive(NB_MEM, 384);
            bar_arrive(NB_MEM2, 256);
            g16 |= fz & zero;
            PROFV(12, it - 1) PROF(1)
        };
        TX(6)
        fetch(0, lds4(tabw + 2048 + g16), []() { return 0u; }, [&](uint32_t z) { request(0, lds1(tabw + 4096 + (g16 >> 1)) + z); });
        wo_load(2);
        TX(7)
#pragma unroll 1
        for (int s = 0;; s++) {
            const uint32_t tag = (s & 1) ^ 1, ttag = ((s >> 1) & 1) ^ 1, l16 = sb + (g16 & 0x1f0), g8 = g16 >> 1;
            const int p = s + 2;
            if (s == 1) TL(7)
            if (s == 0) TL(13)
            fence_async_smem();
            stg_b128_if(g16 < ((role & 3) ? 128 : 160), arena + (acc_slot(s + 3) + lds1(tabw + 2052 + g16)), 0, 0, 0, 0);
            const uint4 pa = pa_get(p);
            if (p <= NSEG) mbar_wait_w(bars + 8 * (B_HB + (p & 1)), (p >> 1) & 1);
            asm volatile("fence.proxy.async.global;" ::: "memory");
            if (warp0 && s + 3 <= NSEG) e_expect(bars + 8 * (B_HB + ((s + 3) & 1)), 32768);
            uint8_t* xd = arena + lds1(tabw + 4 + g16);
            uint32_t tx;
            float acc[20];
            pass_init(acc, 20, pa);
            if (s == 0) TX(10)
            bar_sync(NB_QK, 384);
            pass_run(IC<1>(), p, acc, nop);
            pass_out(IC<2>(), p, acc, [&](int i) {
                if (i) return;
                wg_wait<0>();
                const uint32_t r0 = pack2(acc[16], acc[17]);
                stg_rlx2(xd, settag(r0, tag), pack2(acc[18], acc[19]));
                tx = clk_after(r0, zero) + 100;
                PROF(2)
            });
            uint4 (&vf)[2][2] = tf;
#pragma unroll
            for (int i = 0; i < 4; i++) vf[i >> 1][i & 1] = lds4(sb + SM_VF + i * 2048 + g16);
            uint32_t xv[4] = {0, 0, 0, 0};
            float oc[2][4], lc[4];
            auto pv = [&](uint32_t p0, uint32_t p1, uint32_t p2, uint32_t p3, uint32_t p4, auto mid) {
                lc[0] = lc[1] = lc[2] = lc[3] = 0.f;
                mma16816z(oc[0], &vf[0][0].x, p0, p1);
                mma16816z(oc[1], &vf[1][0].x, p0, p1);
                mma16816(lc, ONES, ONES, ONES, ONES, p0, p1);
                mma16816(oc[0], vf[0][1].x, vf[0][1].y, vf[0][1].z, vf[0][1].w, p2, p3);
                mma16816(oc[1], vf[1][1].x, vf[1][1].y, vf[1][1].z, vf[1][1].w, p2, p3);
                mma16816(lc, ONES, ONES, ONES, ONES, p2, p3);
                mid();
                mma1688(oc[0], xv[0], xv[1], p4);
                mma1688(oc[1], xv[2], xv[3], p4);
                mma1688(lc, ONES, ONES, p4);
            };
            uint32_t so, to, fz = 0;
            uint4 t1;
            int it = 0;
            bool bad;
#pragma unroll 1
            do {
#pragma unroll 1
                for (int i = it; i > 0; i &= zero) load_tok(s, lds1(tabw + 4096 + g8));
                u64 xr[4];
                const uint8_t* xp = arena + lds1(tabw + 8 + g16);
                asm volatile("" : "+l"(xp));
                const uint32_t bt = or3(xor_or(vf[0][0].x, vf[0][1].x, ttag), xor_or(vf[1][0].x, vf[1][1].x, ttag), 0);
                uint32_t sa = sb + SM_SX + (g16 & 0x1f0) * 5;
                asm volatile("" : "+r"(sa));
                spin_guard(it);
                wait_clk(tx);
                PROF(3)
                if (s == 0 && it == 0) TX(11)
                if (it++ == 0) bar_sync(NB_X1, 256);
                uint4 sx[5];
#pragma unroll
                for (int i = 0; i < 5; i++) sx[i] = lds4(sa + i * 16);
                __syncwarp();
#pragma unroll
                for (int i = 0; i < 4; i++) xr[i] = ldg_u64(xp + (VP_AT == 2 ? sx[0].x & zero : 0) + i * 1024);
                uint32_t a[5], pm[5];
#pragma unroll
                for (int n = 0; n < 5; n++) {
                    uint32_t u[4];
#pragma unroll
                    for (int w = 0; w < 4; w++) u[w] = n < 4 ? (&sx[w].x)[n] : (&sx[4].x)[w];
                    a[n] = hadd2h(hadd2h(u[0], u[1]), hadd2h(u[2], u[3]));
                }
                uint32_t m = hmax2h(hmax2h(hmax2h(a[0], a[1]), hmax2h(a[2], a[3])), a[4]);
                const uint32_t m1 = __shfl_xor_sync(~0u, m, 1), m2 = __shfl_xor_sync(~0u, m, 2), m3 = __shfl_xor_sync(~0u, m, 3);
                m = hmax2h(hmax2h(m, m1), hmax2h(m2, m3));
                so = lds1(tabw + g16); t1 = lds4(tabw + 2048 + g16); to = lds1(tabw + 4096 + g8);
                const float2 mm = unpack_h2(m);
                const float mf = -SM_L2E * fmaxf(mm.x, mm.y);
#pragma unroll
                for (int n = 0; n < 5; n++) { const float2 u = unpack_h2(a[n]); pm[n] = pack2(ex2(fmaf(u.x, SM_L2E, mf)), ex2(fmaf(u.y, SM_L2E, mf))); }
                PROF(4)
                pv(pm[0], pm[1], pm[2], pm[3], pm[4], [&]() {
                    if (PV_FENCE & 1) fz = clk32();
#pragma unroll
                    for (int i = 0; i < 2; i++) { xv[2 * i] = hadd2v(lo32(xr[2 * i]), lo32(xr[2 * i + 1])); xv[2 * i + 1] = hadd2v(hi32(xr[2 * i]), hi32(xr[2 * i + 1])); }
                });
                bad = any_bit0(or3(bt, xor_or(lo32(xr[0]), lo32(xr[1]), tag), xor_or(lo32(xr[2]), lo32(xr[3]), tag)));
                if (PV_FENCE & 2) fz |= clk32();
                stsm4(sb + SM_OX + g16, pack2(oc[0][0], oc[0][1]), pack2(oc[0][2], oc[0][3]), pack2(oc[1][0], oc[1][1]), pack2(oc[1][2], oc[1][3]));
                sts2(sb + SM_LX + g8, lc[0], lc[1]);
            } while (bad);
            if (s == 0) TX(12)
            PROFV(14, it - 1)
            PROF(5)
            bar_sync(NB_X2, 384);
            const uint8_t* sp = arena + so;
            uint4 sv = ldg_rlx4(sp);
            if (s == 0) TX(13)
            if (s + 3 <= NSEG) h_load(sb, hsrc, s + 3, j, head, wiu, false);
            const uint4 pp = lds4(l16 + SM_PX + delay<TPV_DLY>(zero));
            pv(pp.x, pp.y, pp.z, pp.w, lds1(sb + SM_PX + 512 + ((g16 >> 2) & 0x7c)), []() {});
            const float i0 = rcp_fast(lc[0]), i1 = rcp_fast(lc[1]);
            bar_arrive(NB_WIN + ((__float_as_uint(i0) | fz) & zero), 384);
            uint8_t* od = (uint8_t*)g_O + ((size_t)s * (32 * NH * DH * 2) + t1.z);
            const uint32_t ov[4] = {pack2(oc[0][0] * i0, oc[0][1] * i1), pack2(oc[0][2] * i0, oc[0][3] * i1), pack2(oc[1][0] * i0, oc[1][1] * i1), pack2(oc[1][2] * i0, oc[1][3] * i1)};
#pragma unroll
            for (int a = 0; a < 4; a++) if (s + 1 == NSEG) stg_rlx1(od + a * 128, ov[a]);
            PROF(6)
            if (s + 1 == NSEG) break;
            fetch(s + 1, t1, [&]() {
                int it = 0;
#pragma unroll 1
                while (__any_sync(~0u, (int)(min(__vimin3_u32(sv.x, sv.y, sv.z), sv.w) >> 24) <= s)) {
                    sv = ldg_rlx4(sp);
                    spin_guard(++it);
                }
                if (s == 0) TX(14)
                PROFV(15, it)
                const uint32_t tgo = (__reduce_max_sync(~0u, max(max3u(sv.x, sv.y, sv.z), sv.w)) + tm.go + (sv.x & zero)) << 8;
                PROF(7)
                int late;
#pragma unroll 1
                do { late = gtime32() * 8 - tgo; } while (late < 0);
                __syncwarp();
                return (uint32_t)late;
            }, [&](uint32_t z) {
#pragma unroll
                for (int a = 0; a < 4; a++) stg_rlx1(od + a * 128, ov[a]);
                request(s + 1, to + z);
            });
        }
        TL(8) TLC(1)
    }
    asm volatile("cp.async.wait_all;" ::: "memory");
    PROF_OUT
}

struct RecMaps { CUtensorMap wq, wk, wv, wo; };
struct RecPtrs { const bf16 *x, *mem0, *c, *wmod, *w1, *w3; uint8_t* arena; uint32_t zero; RecTime tm; };

__device__ __forceinline__ float silu_bf(const bf16* c, int i) {
    const float v = __bfloat162float(c[i]);
    return bfround(__fdividef(v, 1.0f + __expf(-v)));
}
__device__ __noinline__ void rec_ln(float* coef, const RecPtrs& p, int id, int r0) {
    int r1 = 32;
    const int tid = threadIdx.x;
    const int lane = tid & 31, wid = tid >> 5;
    const uint32_t ring = smem_u32(coef) - SM_PRE + wid * 8192 + lane * 16;
    auto fetch = [&](int r) {
        if (r < r1) {
            const bf16* src = p.x + (size_t)(r * 64 + (id * 8 + wid) * 2) * DM + lane * 8;
#pragma unroll
            for (int i = 0; i < 8; i++) cp_async16(ring + (r & 1) * 4096 + i * 512, src + i * 256);
        }
        asm volatile("cp.async.commit_group;" ::: "memory");
    };
    auto row8 = [&](uint32_t a, float* f) {
        const uint4 v = lds4(a);
        f[0] = bflo(v.x); f[1] = bfhi(v.x); f[2] = bflo(v.y); f[3] = bfhi(v.y); f[4] = bflo(v.z); f[5] = bfhi(v.z); f[6] = bflo(v.w); f[7] = bfhi(v.w);
    };
#pragma unroll 1
    for (int r = r0 - 2; r < r1; r++) {
        if (r >= r0) {
            asm volatile("cp.async.wait_group 1;" ::: "memory");
            const uint32_t a = ring + (r & 1) * 4096;
            float m[2] = {0.f, 0.f}, t[2];
#pragma unroll 1
            for (int ps = 0; ps < 2; ps++) {
                t[0] = t[1] = 0.f;
#pragma unroll 1
                for (int i = 0; i < 4; i++)
#pragma unroll
                    for (int h = 0; h < 2; h++) {
                        float f[8];
                        row8(a + h * 2048 + i * 512, f);
#pragma unroll
                        for (int e = 0; e < 8; e++) { const float d = f[e] - m[h]; t[h] = fmaf(d, ps ? d : 1.0f, t[h]); }
                    }
#pragma unroll
                for (int o = 16; o; o >>= 1) { t[0] += __shfl_xor_sync(~0u, t[0], o); t[1] += __shfl_xor_sync(~0u, t[1], o); }
                if (ps == 0) { m[0] = t[0] * (1.0f / DM); m[1] = t[1] * (1.0f / DM); }
            }
            t[0] = rsqrtf(t[0] * (1.0f / DM) + 1e-5f); t[1] = rsqrtf(t[1] * (1.0f / DM) + 1e-5f);
            if (r == r0) {
#pragma unroll 1
                for (int i = tid; i < 2 * DM / 4; i += 256) {
                    float4 u;
                    int it = 0;
                    uint32_t ok;
#pragma unroll 1
                    do {
                        uint4 v[8];
#pragma unroll
                        for (int k = 0; k < 8; k++) v[k] = ldg_rlx4(g_modp + k * 2 * DM + i * 4);
                        ok = 1;
                        u = make_float4(0.f, 0.f, 0.f, 0.f);
#pragma unroll
                        for (int k = 0; k < 8; k++) {
                            ok &= v[k].x & v[k].y & v[k].z & v[k].w;
                            u.x += __uint_as_float(v[k].x); u.y += __uint_as_float(v[k].y); u.z += __uint_as_float(v[k].z); u.w += __uint_as_float(v[k].w);
                        }
                        spin_guard(++it);
                    } while (!ok);
                    const uint32_t lo = pack2(u.x, u.y), hi = pack2(u.z, u.w);
                    const float one = i >= DM / 4 ? 1.0f : 0.0f;
                    *(float4*)(coef + i * 4) = make_float4(bflo(lo) + one, bfhi(lo) + one, bflo(hi) + one, bfhi(hi) + one);
                }
                bar_sync(NB_FIN0, 256);
                if (tid == 0 && r0 == 0) TL(2)
            }
            const int row = r * 64 + (id * 8 + wid) * 2;
#pragma unroll 1
            for (int i = 0; i < 4; i++) {
                const float4* cf = (const float4*)(coef + i * 256 + lane * 8);
                const float4 s0 = cf[0], s1 = cf[1], c0 = cf[256], c1 = cf[257];
                const float sh[8] = {s0.x, s0.y, s0.z, s0.w, s1.x, s1.y, s1.z, s1.w}, sc[8] = {c0.x, c0.y, c0.z, c0.w, c1.x, c1.y, c1.z, c1.w};
                const int own = ((row >> 4) & 1) == (i >> 1), rr = row & 15;
                const uint32_t off = ((row >> 5) + own) * 65536 + (i * 4 + (lane >> 3)) * 4096 + (rr + (own ? 0 : 16)) * 128 + (((lane & 7) ^ (rr & 7)) << 4);
#pragma unroll
                for (int h = 0; h < 2; h++) {
                    float y[8];
                    row8(a + h * 2048 + i * 512, y);
#pragma unroll
                    for (int e = 0; e < 8; e++) y[e] = fmaf((y[e] - m[h]) * t[h], sc[e], sh[e]);
                    *(uint4*)((uint8_t*)g_himg + (off ^ (h * 144))) = pack8(y);
                }
            }
            if (r == 0) {
                int v, it = 0;
#pragma unroll 1
                do { v = *(volatile int*)((uint8_t*)coef - SM_PRE + SM_BAR + 192); spin_guard(++it); } while (v == INT_MIN);
                if (v >= 0) r1 = 2;
            }
        }
        fetch(r + 2);
        if (r < r0 || (r > 0 && !(r & 1))) continue;
        bar_sync(r == 0 ? NB_C : r == 1 ? NB_FIN0 : NB_LN, r == 0 ? 320 : r == 1 ? 256 : 288);
        if (r < 2 && wid == r) {
            if (r == 1) bar_arrive(NB_B, 64);
            if (lane == 0) { signal_count(&g_tick[32 + id * 8]); TL(13) }
            __syncwarp();
        }
    }
}
template <int NQ, int CG>
__device__ __forceinline__ void side_gemv(const bf16* w, int ld, int ncol, const float* coef, float* red, float* out, int ostride, bool round) {
    constexpr int KG = 384 / CG, W = CG * 8;
    const int tid = threadIdx.x, cg = tid % CG, kg = tid / CG;
    float acc[NQ][8];
#pragma unroll
    for (int q = 0; q < NQ; q++)
#pragma unroll
        for (int j = 0; j < 8; j++) acc[q][j] = 0.f;
    if (cg * 8 < ncol) {
        const bf16* src = w + cg * 8;
        const uint32_t ring = smem_u32(red) + 36864 + tid * 16;
        auto fetch = [&](int k0, int slot) {
#pragma unroll
            for (int i = 0; i < 4; i++)
                if (k0 + i * KG < DM) cp_async16_ef(ring + (slot * 4 + i) * 6144, src + (size_t)(k0 + i * KG) * ld);
            asm volatile("cp.async.commit_group;" ::: "memory");
        };
#pragma unroll 1
        for (int g = 0; g < 5; g++) fetch(kg + g * 4 * KG, g);
#pragma unroll 1
        for (int k0 = kg, slot = 0; k0 < DM; k0 += 4 * KG) {
            fetch(k0 + 20 * KG, slot ? slot - 1 : 5);
            asm volatile("cp.async.wait_group 5;" ::: "memory");
#pragma unroll
            for (int i = 0; i < 4; i++) {
                const int k = k0 + i * KG;
                if (k < DM) {
                    const uint4 v = lds4(ring + (slot * 4 + i) * 6144);
                    const float f[8] = {bflo(v.x), bfhi(v.x), bflo(v.y), bfhi(v.y), bflo(v.z), bfhi(v.z), bflo(v.w), bfhi(v.w)};
#pragma unroll
                    for (int q = 0; q < NQ; q++) {
                        const float cf = coef[q * DM + k];
#pragma unroll
                        for (int j = 0; j < 8; j++) acc[q][j] = fmaf(cf, f[j], acc[q][j]);
                    }
                }
            }
            slot = slot == 5 ? 0 : slot + 1;
        }
    }
    __syncthreads();
#pragma unroll
    for (int q = 0; q < NQ; q++)
#pragma unroll
        for (int j = 0; j < 8; j++) red[(kg * NQ + q) * W + cg * 8 + j] = acc[q][j];
    __syncthreads();
#pragma unroll 1
    for (int i = tid; i < NQ * W; i += 384) {
        const int q = i / W, cidx = i % W;
        float t = 0.f;
#pragma unroll
        for (int k = 0; k < KG; k++) t += red[k * NQ * W + i];
        if (cidx < ncol) out[q * ostride + cidx] = round ? bfround(t) : t;
    }
}
__device__ __noinline__ void rec_side(float* sm, const RecPtrs& p, int id) {
    const int tid = threadIdx.x;
    float *coef = sm, *red = sm + 3 * DM;
    if (tid < 256 && blockIdx.x < 128) rec_ln(sm + SM_PRE / 4, p, id, 2);
    if (tid >> 5 == 8) {
#pragma unroll 1
        for (int n = 1; n < 16; n++) {
            bar_sync(NB_LN, 288);
            if (tid == 256) { if (n == 1) wait_count1(&g_tick[32 + id * 8], 2); signal_count(&g_tick[32 + id * 8]); }
            __syncwarp();
        }
    }
    __syncthreads();
    for (int i = tid; i < 2 * S_; i += 384) g_st[id * 2 * S_ + i] = 0.f;
    if (id == 0) for (int i = tid; i < 2 * 32; i += 384) g_pcnt[i * 8] = 0;
    if (id == 1) for (int i = tid; i < 6 * 256; i += 384) g_pflag[i] = 0;
    for (int i = tid; i < DM; i += 384) { coef[i] = silu_bf(p.c, i); coef[2 * DM + i] = 1.0f; }
    __syncthreads();
    if (tid == 0) TL(3)
    side_gemv<1, 128>(p.wmod + (2 + id) * DM, 6 * DM, DM, coef, red, g_mod + (2 + id) * DM, 0, true);
    __syncthreads();
    if (tid == 0) signal_count(&g_tick[8]);
    if (tid == 0) TL(4)
    side_gemv<1, 128>(p.w3 + id * (FF / 4), FF, FF / 4, coef + 2 * DM, red, g_vec + 3 * DM + id * (FF / 4), 0, false);
    if (tid == 0) wait_count1(&g_tick[8], 4);
    __syncthreads();
    for (int i = tid; i < DM; i += 384) { coef[i] = 1.0f + __ldcg(g_mod + 4 * DM + i); coef[DM + i] = __ldcg(g_mod + 3 * DM + i); }
    __syncthreads();
    if (id == 1 && tid < 32) {
        float t[5] = {0, 0, 0, 0, 0};
        for (int i = tid; i < DM; i += 32) {
            const float a = coef[i], b = coef[DM + i];
            t[0] += a; t[1] += a * a; t[2] += a * b; t[3] += b; t[4] += b * b;
        }
#pragma unroll
        for (int q = 0; q < 5; q++) { const float r = warp_sum(t[q]); if (tid == 0) g_cst[q] = r * (1.0f / DM); }
    }
    side_gemv<3, 32>(p.w1 + id * 256, DM, 256, coef, red, g_vec + id * 256, DM, false);
    if (tid == 0) TL(9)
}

__device__ __forceinline__ void pair_place(int c, int& d, int& pi) {
    const int c7 = ((c - 36) * 37) >> 8;
    d = c < 4 ? 0 : c < 36 ? (c - 4) & 7 : c - 35 - 7 * c7;
    pi = c < 4 ? c : c < 36 ? ((c - 4) >> 3) + (d ? 0 : 4) : 4 + c7;
}
__global__ void __cluster_dims__(2, 1, 1) __launch_bounds__(384, 1)
k_rec(const __grid_constant__ RecMaps mp, const __grid_constant__ RecPtrs p) {
    extern __shared__ uint8_t smraw[];
    const uint32_t sb = smem_u32(smraw);
    if ((sb & 0x3FFFF) != SB0) __trap();
    const uint32_t bars = sb + SM_BAR;
    const int tid = threadIdx.x, lane = tid & 31, b = blockIdx.x;
    const int wid = __reduce_max_sync(~0u, tid >> 5);
    const uint32_t rank = b & 1;
    uint8_t* arena = p.arena;
    volatile int* sinfo = (volatile int*)(smraw + SM_BAR + 192);
    if (tid == 0) TL(0)
    if (tid == 0) sinfo[0] = INT_MIN;
    uint32_t smid;
    asm("mov.u32 %0, %%smid;" : "=r"(smid));
    smid = __reduce_max_sync(~0u, smid);
    int d, pi;
    pair_place(smid >= 124 ? (smid >> 1) - 62 : (smid >> 1) + 4, d, pi);
    const int guess = b < 128 && smid < 132 && (smid & ~3u) != 120 && (NO_GUESS == 0 || (NO_GUESS == 2 && b != 20)) ? d * 8 + pi : -9;
    if (wid == 8) {
        if (lane == 0) {
#pragma unroll
            for (int i = 0; i < 17; i++) mbar_init(bars + 8 * i, i == B_WO ? 4 : 1);
            asm volatile("fence.mbarrier_init.release.cluster; fence.proxy.async.shared::cta;" ::: "memory");
            mbar_expect(bars + 8 * B_ROLE, 8);
        }
        __syncwarp();
    }
    asm volatile("barrier.cluster.arrive.relaxed.aligned;" ::: "memory");
    int pr = 0, hA = 0;
    if (wid < 8) {
        if (b < 128) {
            const int cb = (b & 15) * 128, k0 = (b >> 4) * 128 + (tid >> 4);
            uint4 v[8];
#pragma unroll
            for (int i = 0; i < 8; i++) v[i] = __ldg((const uint4*)(p.wmod + (size_t)(k0 + 16 * i) * (6 * DM) + cb + (tid & 15) * 8));
            float acc[8] = {0, 0, 0, 0, 0, 0, 0, 0};
            const float sl = silu_bf(p.c, k0 + 16 * (lane & 7));
#pragma unroll
            for (int i = 0; i < 8; i++) {
                const float sv = __shfl_sync(~0u, sl, i, 16);
                acc[0] += sv * bflo(v[i].x); acc[1] += sv * bfhi(v[i].x); acc[2] += sv * bflo(v[i].y); acc[3] += sv * bfhi(v[i].y);
                acc[4] += sv * bflo(v[i].z); acc[5] += sv * bfhi(v[i].z); acc[6] += sv * bflo(v[i].w); acc[7] += sv * bfhi(v[i].w);
            }
            float* red = (float*)(smraw + SM_PRE);
            *(float4*)(red + (tid >> 4) * 128 + (tid & 15) * 8) = make_float4(acc[0], acc[1], acc[2], acc[3]);
            *(float4*)(red + (tid >> 4) * 128 + (tid & 15) * 8 + 4) = make_float4(acc[4], acc[5], acc[6], acc[7]);
            bar_sync(NB_FIN0, 256);
            if (wid < 4) {
                float t = 0;
#pragma unroll
                for (int i = 0; i < 16; i++) t += red[i * 128 + tid];
                stg_rlx1(&g_modp[(b >> 4) * 2 * DM + cb + tid], __float_as_uint(t) | 1u);
                if (rank) TL(2)
            }
        } else {
            rec_ln((float*)(smraw + SM_PRE), p, b - 128, 0);
        }
    } else if (wid >= 10 && b >= 128) {
        {
            const int u = (b - 128) * 2 + wid - 10;
            const uint16_t* src = (const uint16_t*)p.mem0 + (lane & 3) * 2 * DM + (u >> 1) * 128 + (u & 1) * 32 + (lane >> 2);
            stg_rlx4(arena + (LB_STAMP << 13) + u * 2048 + (lane >> 4) * 1024 + ((lane >> 3) & 1) * 256 + (lane & 7) * 16, 0, 0, 0, 0);
#pragma unroll 1
            for (int r = 0; r < 4; r++) {
                uint32_t w[5];
#pragma unroll
                for (int e = 0; e < 4; e++) {
                    const uint16_t* q = src + (r >> 1) * 512 + (r & 1) * 16 + (e & 2) * 32 + (e & 1) * 8;
                    w[e] = pack_h2(bflo(q[0]), bflo(q[DM]));
                }
                w[4] = __shfl_sync(~0u, __byte_perm(w[3], ACC_ALL, 0x7632), lane * 8 + 7);
                w[3] = __byte_perm(w[3], ACC_ALL, (lane & 7) == 7 ? 0x7610 : 0x3210);
#pragma unroll 1
                for (int i = 0; i < 3; i++) {
                    uint8_t* d = arena + acc_slot(i) + acc_piece(r >> 1, u >> 1, (u & 1) * 2 + (r & 1));
                    stg_rlx4(d + lane * 16, w[0], w[1], w[2], w[3]);
                    if (lane < 8) stg_rlx1(d + 512 + lane * 4, w[4]);
                    w[0] = w[1] = w[2] = w[3] = w[4] = 0;
                }
            }
            bar_arrive(NB_C, 320);
        }
    } else if (rank == 0 && (wid > 8 || b >= 128)) {
        uint32_t best = ~0u;
        const int pg = wid < 11 ? 0 : 1 + (b >> 1) % 3;
        uint32_t* q = (uint32_t*)(arena + (pg << 21) + (pg ? blk(b >> 1, 1) : blk(LB_PROBE, wid & 1) + b * 16));
        if (lane < 8) stg_rlx1(q + lane, 0);
        u64 tk2 = ldg_u64(&g_tick[0]);
        __syncwarp();
        if (lane == 0) {
            q += 3;
            uint32_t v = atomicAdd(q, 1u);
#pragma unroll 1
            for (int r = 0; r < NPROBE; r++) {
                const uint32_t t0 = clk32() + (v >> 8);
                v = atomicAdd(q + (v >> 8), 1u);
                uint32_t t1;
                asm volatile("{.reg .pred p; setp.eq.u32 p, %1, 0xffffffff; @p exit; mov.u32 %0, %%clock;}" : "=r"(t1) : "r"(v) : "memory");
                best = min(best, t1 - t0);
            }
            sinfo[pg ? 4 : 2 + (wid & 1)] = best;
        }
        bar_sync(NB_KDONE, b < 128 ? 96 : 64);
        if (wid == 9) {
            const int par = sinfo[2] > sinfo[3], ncl = gridDim.x >> 1;
            u64 add = (1u << (8 * par)) + 65536;
            if (b < 128) add += ((u64)((2 * sinfo[4] < sinfo[2] + sinfo[3]) != par) << (32 + 8 * ((b >> 1) % 3))) + (guess < 0 || (smid & 1) ? 1 << 24 : 0);
            int tk = 0, it = 0;
            if (b >= 128) {
#pragma unroll 1
                while (!__all_sync(~0u, (int)((lo32(tk2) >> 16) & 255) >= ncl - 2)) { tk2 = ldg_u64(&g_tick[0]); spin_guard(++it); }
            }
            if (lane == 0) {
                if (guess >= 0) add += atomicXor(&g_tick[2], par << (guess >> 1)) & p.zero;
                tk = (atomicAdd((u64*)&g_tick[0], add) >> (8 * par)) & 255;
            }
#pragma unroll 1
            while (!__all_sync(~0u, (int)((lo32(tk2) >> 16) & 255) >= ncl)) { tk2 = ldg_u64(&g_tick[0]); spin_guard(++it); }
            tk = __shfl_sync(~0u, tk, 0);
            const int n0 = tk2 & 255, n1 = (tk2 >> 8) & 255;
            hA = min(n0 >> 1, NH);
            const int q0 = 2 * hA, q1 = 2 * NH - q0;
            const int over = tk - (par ? q1 : q0), lack = max(par ? q0 - n0 : q1 - n1, 0);
            if (over < 0) pr = par ? q0 + tk : tk;
            else if (over < lack) pr = (par ? n0 : q0 + n1) + over;
            else pr = -1 - (over - lack + (par ? max(n0 - q0, 0) : 0));
            if (!(lo32(tk2) >> 24) && !ldg_rlx1(&g_tick[2])) { pr = guess; hA = par ? 0 : NH; }
#pragma unroll
            for (int i = 0; i < 3; i++) hA |= ((hi32(tk2) >> (8 * i)) & 255) > 10 ? 256 << i : 0;
        }
    }
    asm volatile("barrier.cluster.wait.aligned;" ::: "memory");
    if (wid == 9 && rank == 0) {
        asm volatile("{.reg .pred p; .reg .b32 a; setp.lt.u32 p, %3, 2; @p mapa.shared::cluster.u32 a, %0, %3;\n"
                     " @p st.async.shared::cluster.mbarrier::complete_tx::bytes.v2.u32 [a + 192], {%1, %2}, [a + %4];}"
                     ::"r"(bars), "r"(pr), "r"(hA), "r"(lane), "n"(8 * B_ROLE) : "memory");
        if (b >= 128) atomicOr(&g_tick[4], (pr < 0 ? 4u : 1u) << ((b - 128) >> 1));
    }
    if (wid == 8) {
        int pu = guess;
        bool fast = false, known = false;
#pragma unroll 1
        for (int n = 0; n < 12; n++) {
            if (!known && (n == W_SPEC || pu < 0)) {
                mbar_wait_w(bars + 8 * B_ROLE, 0);
                TL(1)
                known = true;
                const int r = __reduce_max_sync(~0u, sinfo[0]);
                if (r != pu) {
#pragma unroll 1
                    for (; n > 0; n--) {
                        mbar_wait_w(bars + 8 * (B_W + n - 1), 0);
                        asm volatile("{.reg .pred p; elect.sync _|p, 0xffffffff; @p mbarrier.arrive.shared.b64 _, [%0];}" ::"r"(bars + 8 * (B_W + n - 1)) : "memory");
                    }
                    pu = r;
                }
                bar_arrive(NB_A, 384);
                if (b >= 128 && pu < 0) bar_sync(NB_B, 64);
                if (pu < 0) break;
            }
            const int rot = b >= 128 ? 8 : 0, i = (n + rot) % 12;
            if (rot && n == 4) bar_sync(NB_B, 64);
            if (n >= W_INFL && !fast) {
                const uint32_t v = ldg_rlx1(&g_tick[32 + (lane & 3) * 8]);
                mbar_wait_w(bars + 8 * (B_W + (n - W_INFL + rot) % 12), 0);
                fast = __all_sync(~0u, v != 0);
            }
            const int m = i < 8 ? i & 1 : 2, k = i < 8 ? i >> 1 : i - 8, c0 = (pu >> 1) * 128 + rank * 64, r0 = (pu & 1) * 512;
            const uint32_t dst = sb + m * 65536 + k * 16384, br = bars + 8 * (B_W + i);
            e_expect(br, 16384);
            e_tma2d(dst, &mp.wq + m, c0, r0 + k * 128, br, evict_first());
            e_tma2d(dst + 8192, &mp.wq + m, c0, r0 + k * 128 + 64, br, evict_first());
        }
    } else {
        bar_sync(NB_A, 384);
    }
    const int prr = __reduce_max_sync(~0u, sinfo[0]);
    hA = __reduce_max_sync(~0u, sinfo[1]);
    if (prr < 0) {
        int j = (b - 128) >> 1;
        if (b < 128) {
            uint32_t v;
            int it = 0;
#pragma unroll 1
            do { v = __reduce_max_sync(~0u, ldg_rlx1(&g_tick[4])); spin_guard(++it); } while (__popc(v) < 2);
            j = v == 3 ? -1 - prr : (v & 1) ^ 1;
        }
        rec_side((float*)smraw, p, j * 2 + rank);
        return;
    }
    const int role = (prr >> 1) * 4 + rank * 2 + (prr & 1);
    rec_main(sb, &mp.wo, arena, role, hA, wid >> 2, p.zero, p.tm);
}

__device__ __forceinline__ void wgmma_ss192(float* d, uint64_t a, uint64_t b, int sc) {
    asm volatile("{.reg .pred p; setp.ne.b32 p, %98, 0;\n wgmma.mma_async.sync.aligned.m64n192k16.f32.bf16.bf16 "
                 "{%0,%1,%2,%3,%4,%5,%6,%7,%8,%9,%10,%11,%12,%13,%14,%15,%16,%17,%18,%19,%20,%21,%22,%23,%24,%25,%26,%27,%28,%29,%30,%31,%32,%33,%34,%35,%36,%37,%38,%39,%40,%41,%42,%43,%44,%45,%46,%47,%48,%49,%50,%51,%52,%53,%54,%55,%56,%57,%58,%59,%60,%61,%62,%63,%64,%65,%66,%67,%68,%69,%70,%71,%72,%73,%74,%75,%76,%77,%78,%79,%80,%81,%82,%83,%84,%85,%86,%87,%88,%89,%90,%91,%92,%93,%94,%95}, %96, %97, p, 1, 1, 0, 1;}"
                 : F16(d, 0), F16(d, 16), F16(d, 32), F16(d, 48), F16(d, 64), F16(d, 80) : "l"(a), "l"(b), "r"(sc));
}

constexpr uint32_t P_B = 81920, P_PLANE = 40960, P_VEC = 212992, P_ROW = P_VEC + 6144, P_BAR = P_ROW + 4096, P_SMEM = P_BAR + 256;
constexpr uint32_t P_OUT = 180224, P_OUT3 = P_B + 2 * P_PLANE;
#define PPH 1
#define FLAG_LD "ld.acquire.gpu.global.u32"
#define EFA 0x1e7
#define EFB 0x1ff
#define E0 2
#define SL_B0 0x2222
#define SL_B1 0x8888
#define SL_C 0x11110
#define SL_A0 0x5494
#define SL_A1 0x2929
#define HFENCE 2
#define X_DLY 4000
#define ROT 0x00e
#define BPF 6
#define BPF_Q 1
#define PEER 1
#define OWN 1
constexpr int P_ST = 5, P_ST0 = 4;
constexpr int PB_F = 0, PB_E = 5, PB_X = 10, PB_P = 12, PB_OUT = 14;
enum { C_Y = 0, C_G = 1, C_X1 = 2, C_U = 3, C_S1 = 8, C_S3 = 9 };
enum { V_GA = 0, V_A = 1, V_B = 2, V_GB = 3, V_VA = 4, V_VB = 5, V_VC = 6, V_C3 = 7 };
struct PostMaps { CUtensorMap o, wo, y, w1, g, w2, x1, w3, u, w4, out, x; };

struct GeluK { float k0, k1, kh; };
__device__ __forceinline__ GeluK gelu_k(float c) { return {0.7978845608028654f * c, 0.7978845608028654f * 0.044715f * c * c * c, 0.5f * c}; }
__device__ __forceinline__ float gelu_s(float t, const GeluK& k) {
    const float u = t * fmaf(t * t, k.k1, k.k0);
    float th; asm("tanh.approx.f32 %0, %1;" : "=f"(th) : "f"(u));
    const float hx = k.kh * t;
    return fmaf(hx, th, hx);
}
__device__ __forceinline__ float2 ldsv(uint32_t a) {
    float2 v; asm("ld.shared.v2.f32 {%0,%1}, [%2];" : "=f"(v.x), "=f"(v.y) : "r"(a)); return v;
}
__device__ __forceinline__ void wait_smem(uint32_t a, int target) {
    int it = 0;
#pragma unroll 1
    while (true) {
        int v;
        asm volatile("ld.acquire.cta.shared.u32 %0, [%1];" : "=r"(v) : "r"(a) : "memory");
        if (__all_sync(~0u, v >= target)) break;
        spin_guard(++it);
    }
}

#define PP(i)
#define PH_(c, w, i)
struct Pipe { int st, ph; };
__device__ __forceinline__ void adv(Pipe& p) { if (++p.st == P_ST) { p.st = 0; p.ph ^= 1; } }
__device__ __forceinline__ int u_col(int r, int nb) { return r ? 512 + r * 1024 + nb * 128 : nb * 192; }

template <bool A>
__device__ __forceinline__ void post_produce(uint32_t sb, const PostMaps& mp, int mb, int nb, int rank) {
    const int rh = 2 * mb + rank, lane = threadIdx.x & 31;
    const uint32_t full = sb + P_BAR + 8 * PB_F, empty = sb + P_BAR + 8 * PB_E;
    Pipe p = {(P_ST0 + E0) % P_ST, !E0};
#pragma unroll 1
    for (int ph = 0; ph < 9; ph++) {
        const int GS = ph == 0 ? 8 : ph == 6 ? 3 : 2, kb0 = ph < 7 ? 0 : ph * 16 - 88;
        const CUtensorMap* tm = &mp.o + 2 * (ph < 3 ? ph : ph < 6 ? 3 : 4) + !A;
        const uint64_t pol = ((A ? EFA : EFB) >> ph) & 1 ? evict_first() : evict_normal();
        const bool own = OWN && (ph == 1 || ph == 3);
        const int n0 = ph >= 3 && ph < 6 ? u_col(ph - 3, nb) : nb * 128;
        const int amul = ph == 0 ? 256 : 64, arow = ph == 0 ? rh * 8 : rh * 64;
        const int wr = ph == 2 ? min(max(rh + min(lane >> 3, 2) - 1, 0), 31) : rh ^ ((lane >> 3) & 1);
        const uint32_t* fl = &g_pflag[(ph < 3 ? ph - 1 : ph < 6 ? C_X1 : ph - 3) * 256 + wr * 8 + (lane & 7)];
        uint32_t have = ph == 0 || ph == 5 ? ~0u : 0u;
        PH_(A && ph == PPH, 0, 26) PH_(A && ph == PPH, 1, 26)
#pragma unroll 1
        for (int q = 0; q < 8; q++) {
            const int src = own && q < 2 ? nb ^ q : (q + ((ROT >> ph) & 1 ? nb & 6 : 0)) & 7;
            const bool skip = own && q == 0, both = own && q == 1;
            const uint32_t need = skip || (PEER && both) ? 0 : (ph == 2 ? 0x10101 : both ? 0x101 : 1) << src;
            if (A && PEER && both) {
                int it = 0;
                uint32_t ok;
#pragma unroll 1
                do {
                    asm volatile("{.reg .pred p; mbarrier.try_wait.parity.acquire.cluster.shared::cta.b64 p, [%1], %2; selp.u32 %0, 1, 0, p;}" : "=r"(ok) : "r"(sb + P_BAR + 8 * PB_P), "r"(ph >> 1) : "memory");
                    spin_guard(++it);
                } while (!__all_sync(~0u, ok));
                asm volatile("fence.proxy.async.global;" ::: "memory");
            }
            if (A && (have & need) != need) {
                int it = 0;
#pragma unroll 1
                do {
                    uint32_t v;
                    asm volatile(FLAG_LD " %0, [%1];" : "=r"(v) : "l"(fl) : "memory");
                    have = __ballot_sync(~0u, v != 0);
                    spin_guard(++it);
                } while ((have & need) != need);
                PH_(ph == PPH && q == own * (1 + PEER), 0, 23) PH_(ph == PPH, 0, 24) PH_(ph == PPH && q == own * (1 + PEER), 1, 23) PH_(ph == PPH, 1, 24)
                asm volatile("fence.proxy.async.global;" ::: "memory");
            }
            if (!A && q == BPF_Q && ((BPF >> ph) & 1)) {
                const int np = ph + 1, nn = np >= 3 && np < 6 ? u_col(np - 3, nb) : nb * 128;
                const CUtensorMap* nm = &mp.wo + 2 * (np < 3 ? np : np < 6 ? 3 : 4);
#pragma unroll 1
                for (int i = 0; i < (np == 3 || np == 6 ? 3 : 2); i++) {
                    const int u = np == 6 ? mb * 3 + i : 0;
                    asm volatile("{.reg .pred p; elect.sync _|p, 0xffffffff; @p cp.async.bulk.prefetch.tensor.2d.L2.global [%0, {%1, %2}];}"
                                 ::"l"(nm), "r"(nn + (np == 6 ? u & 1 : i) * 64), "r"((np == 6 ? u >> 1 : mb + (np < 7 ? 0 : np * 16 - 88)) * 64) : "memory");
                }
            }
            if (!A && ph == 3 && q == 1) wait_smem(sb + P_BAR + 8 * (PB_OUT + (lane & 1)), 3);
            const int row = arow + (ph == 2 ? (int)((0x04000301u >> ((src & 6) * 4)) & 7) - 2 : 0);
            const uint32_t bytes = (skip ? 16384 : 32768) + (ph == 3 ? 8192 : 0);
            if ((ph | q) == 0) asm volatile("barrier.cluster.wait.aligned;" ::: "memory");
#pragma unroll 1
            for (int e = kb0 + (src + 1) * GS, kb = e - GS + (ph | q ? 0 : E0); kb < e; kb++) {
                const uint32_t f = full + 8 * p.st;
                mbar_wait_w(empty + 8 * p.st, p.ph ^ 1);
                if (A) {
                    const uint32_t a = sb + p.st * 16384 + rank * 8192;
                    if (both) { e_tma2d(a, tm, kb * 64, row, f, pol); e_tma2d(a + 8192 - rank * 16384, tm, kb * 64, row ^ 64, f, pol); }
                    else if (!skip) e_tma2d_mc(a, tm, kb * amul, row, f, pol);
                } else {
                    const uint32_t b = sb + P_B + p.st * 8192;
                    e_expect(f, bytes);
                    e_tma2d(b, tm, n0, kb * 64, f, pol);
                    e_tma2d(b + P_PLANE, tm, n0 + 64, kb * 64, f, pol);
                    if (ph == 3 && both) mbar_wait_w(empty + 8 * p.st - 16, p.ph);
                    if (ph == 3) e_tma2d(b + 2 * P_PLANE, tm, n0 + 128, kb * 64, f, pol);
                }
                PH_(PPH == 0 && ph == 0 && q == 0 && kb + GS == e + E0, 0, 20 + A) PH_(PPH == 0 && ph == 0 && q == 0 && kb + GS == e + E0, 1, 20 + A)
                adv(p);
            }
        }
    }
    if (A) {
#pragma unroll 1
        for (int i = 0; i < P_ST; i++) mbar_wait_w(empty + 8 * i, p.ph ^ (i >= p.st));
    }
}

#define I4(d, i) "f"(d[i]), "f"(d[i + 1]), "f"(d[i + 2]), "f"(d[i + 3])
#define I16(d, i) I4(d, i), I4(d, i + 4), I4(d, i + 8), I4(d, i + 12)
#define O4(d, i) "=f"(d[i]), "=f"(d[i + 1]), "=f"(d[i + 2]), "=f"(d[i + 3])
__device__ __forceinline__ void pick32(float* v, int n, const float* c1, const float* vc, const float* old) {
    asm volatile("{PKT: .branchtargets PK0, PK1, PK2, PK3, PK4, PK5; brx.idx.uni %16, PKT;\n"
                 "PK0: fma.rn.f32 %0, %17, %19, %27; fma.rn.f32 %1, %17, %20, %28; fma.rn.f32 %2, %18, %19, %29; fma.rn.f32 %3, %18, %20, %30; fma.rn.f32 %4, %17, %21, %31; fma.rn.f32 %5, %17, %22, %32; fma.rn.f32 %6, %18, %21, %33; fma.rn.f32 %7, %18, %22, %34; fma.rn.f32 %8, %17, %23, %35; fma.rn.f32 %9, %17, %24, %36; fma.rn.f32 %10, %18, %23, %37; fma.rn.f32 %11, %18, %24, %38; fma.rn.f32 %12, %17, %25, %39; fma.rn.f32 %13, %17, %26, %40; fma.rn.f32 %14, %18, %25, %41; fma.rn.f32 %15, %18, %26, %42; bra.uni PKE;\n"
                 "PK1: fma.rn.f32 %0, %17, %19, %43; fma.rn.f32 %1, %17, %20, %44; fma.rn.f32 %2, %18, %19, %45; fma.rn.f32 %3, %18, %20, %46; fma.rn.f32 %4, %17, %21, %47; fma.rn.f32 %5, %17, %22, %48; fma.rn.f32 %6, %18, %21, %49; fma.rn.f32 %7, %18, %22, %50; fma.rn.f32 %8, %17, %23, %51; fma.rn.f32 %9, %17, %24, %52; fma.rn.f32 %10, %18, %23, %53; fma.rn.f32 %11, %18, %24, %54; fma.rn.f32 %12, %17, %25, %55; fma.rn.f32 %13, %17, %26, %56; fma.rn.f32 %14, %18, %25, %57; fma.rn.f32 %15, %18, %26, %58; bra.uni PKE;\n"
                 "PK2: fma.rn.f32 %0, %17, %19, %59; fma.rn.f32 %1, %17, %20, %60; fma.rn.f32 %2, %18, %19, %61; fma.rn.f32 %3, %18, %20, %62; fma.rn.f32 %4, %17, %21, %63; fma.rn.f32 %5, %17, %22, %64; fma.rn.f32 %6, %18, %21, %65; fma.rn.f32 %7, %18, %22, %66; fma.rn.f32 %8, %17, %23, %67; fma.rn.f32 %9, %17, %24, %68; fma.rn.f32 %10, %18, %23, %69; fma.rn.f32 %11, %18, %24, %70; fma.rn.f32 %12, %17, %25, %71; fma.rn.f32 %13, %17, %26, %72; fma.rn.f32 %14, %18, %25, %73; fma.rn.f32 %15, %18, %26, %74; bra.uni PKE;\n"
                 "PK3: fma.rn.f32 %0, %17, %19, %75; fma.rn.f32 %1, %17, %20, %76; fma.rn.f32 %2, %18, %19, %77; fma.rn.f32 %3, %18, %20, %78; fma.rn.f32 %4, %17, %21, %79; fma.rn.f32 %5, %17, %22, %80; fma.rn.f32 %6, %18, %21, %81; fma.rn.f32 %7, %18, %22, %82; fma.rn.f32 %8, %17, %23, %83; fma.rn.f32 %9, %17, %24, %84; fma.rn.f32 %10, %18, %23, %85; fma.rn.f32 %11, %18, %24, %86; fma.rn.f32 %12, %17, %25, %87; fma.rn.f32 %13, %17, %26, %88; fma.rn.f32 %14, %18, %25, %89; fma.rn.f32 %15, %18, %26, %90; bra.uni PKE;\n"
                 "PK4: fma.rn.f32 %0, %17, %19, %91; fma.rn.f32 %1, %17, %20, %92; fma.rn.f32 %2, %18, %19, %93; fma.rn.f32 %3, %18, %20, %94; fma.rn.f32 %4, %17, %21, %95; fma.rn.f32 %5, %17, %22, %96; fma.rn.f32 %6, %18, %21, %97; fma.rn.f32 %7, %18, %22, %98; fma.rn.f32 %8, %17, %23, %99; fma.rn.f32 %9, %17, %24, %100; fma.rn.f32 %10, %18, %23, %101; fma.rn.f32 %11, %18, %24, %102; fma.rn.f32 %12, %17, %25, %103; fma.rn.f32 %13, %17, %26, %104; fma.rn.f32 %14, %18, %25, %105; fma.rn.f32 %15, %18, %26, %106; bra.uni PKE;\n"
                 "PK5: fma.rn.f32 %0, %17, %19, %107; fma.rn.f32 %1, %17, %20, %108; fma.rn.f32 %2, %18, %19, %109; fma.rn.f32 %3, %18, %20, %110; fma.rn.f32 %4, %17, %21, %111; fma.rn.f32 %5, %17, %22, %112; fma.rn.f32 %6, %18, %21, %113; fma.rn.f32 %7, %18, %22, %114; fma.rn.f32 %8, %17, %23, %115; fma.rn.f32 %9, %17, %24, %116; fma.rn.f32 %10, %18, %23, %117; fma.rn.f32 %11, %18, %24, %118; fma.rn.f32 %12, %17, %25, %119; fma.rn.f32 %13, %17, %26, %120; fma.rn.f32 %14, %18, %25, %121; fma.rn.f32 %15, %18, %26, %122;\n"
                 "PKE: }"
                 : O4(v, 0), O4(v, 4), O4(v, 8), O4(v, 12)
                 : "r"(n), "f"(c1[0]), "f"(c1[1]), I4(vc, 0), I4(vc, 4), I16(old, 0), I16(old, 16), I16(old, 32), I16(old, 48), I16(old, 64), I16(old, 80));
}
template <int PH, class F>
__device__ __forceinline__ void post_mma(uint32_t sb, float* acc, Pipe& p, int NK, int wg, uint32_t rel, bool lead, int pi, F hook) {
    const uint32_t full = sb + P_BAR + 8 * PB_F;
    constexpr uint64_t DA = PH == 0 ? mkdesc(SB0, 128, 1024, 0) : mkdesc(SB0, 16, 1024, 1);
    constexpr uint64_t DB = mkdesc(SB0 + P_B, P_PLANE, 1024, 1);
    auto release = [&](uint32_t a) { asm volatile("{.reg .pred p; setp.gt.u32 p, %0, 63; @p mbarrier.arrive.shared::cluster.b64 _, [%0];}" ::"r"(a) : "memory"); };
    uint32_t prev = 0;
    if (OWN && (PH & 1)) { if (HFENCE == 2) fence_async_smem(); bar_sync(12 + wg, 128); }
    bool ok = false;
#pragma unroll 1
    for (int kb = 0; kb < NK; kb++) {
        if (!ok) mbar_wait_w(full + 8 * p.st, p.ph);
        const uint32_t a = (uint32_t)DA + (OWN && (PH & 1) && kb < 2 ? P_OUT / 16 + wg * 1024 + kb * 512 : p.st * 1024 + wg * 512), b = (uint32_t)DB + p.st * 512;
        wg_fence();
#pragma unroll
        for (int k = 0; k < 4; k++) {
            const uint64_t da = (DA & 0xffffffff00000000ull) | (a + k * (PH == 0 ? 16 : 2)), db = (DB & 0xffffffff00000000ull) | (b + k * 128);
            if (PH == 3) wgmma_ss192(acc, da, db, (kb | k) != 0);
            else wgmma_ss128<PH == 0>(acc, da, db, (kb | k) != 0);
        }
        wg_commit();
        if (kb == 0) { PP(pi) if (PH == 0 && wg == 0) TL(11) }
        const uint32_t cur = rel + 8 * p.st;
        adv(p);
        uint32_t t;
        asm volatile("{.reg .pred p; mbarrier.test_wait.parity.shared.b64 p, [%1], %2; selp.u32 %0, 1, 0, p;}" : "=r"(t) : "r"(full + 8 * p.st), "r"(p.ph) : "memory");
        wg_wait<1>();
        release(prev);
        ok = __all_sync(~0u, t);
        prev = cur;
        hook(kb);
    }
    wg_wait<0>();
    release(prev);
    PP(pi + 1)
}

__global__ void __cluster_dims__(2, 1, 1) __launch_bounds__(384, 1)
k_post(const __grid_constant__ PostMaps mp) {
    extern __shared__ uint8_t smraw[];
    const uint32_t sb = smem_u32(smraw);
    if ((sb & 0x3FFFF) != SB0) __trap();
    const int tid = threadIdx.x, lane = tid & 31;
    int d, pi;
    pair_place(blockIdx.x >> 1, d, pi);
    const int rank = blockIdx.x & 1, mb = (d >> 2) * 8 + pi, nb = (d & 3) * 2 + rank;
    const uint32_t bars = sb + P_BAR;
    PH_(PPH == 0 && tid == 0, 0, 22) PH_(PPH == 0 && tid == 0, 1, 22)
    const int w = __reduce_max_sync(~0u, (tid >> 5) - 8);
    if (w == 1) {
        if (lane == 0) {
#pragma unroll
            for (int i = 0; i <= PB_P; i++) mbar_init(bars + 8 * i, i >= PB_E && i < PB_X ? 4 : i == PB_P ? 2 : 1);
            mbar_arrive(bars + 8 * (PB_F + P_ST0));
            asm volatile("mbarrier.arrive.shared.b64 _, [%0], 4;" ::"r"(bars + 8 * (PB_E + P_ST0)) : "memory");
            sts4(bars + 8 * PB_OUT, 0, 0, 0, 0);
            asm volatile("fence.mbarrier_init.release.cluster; fence.proxy.async.shared::cta;" ::: "memory");
        }
        __syncwarp();
    }
    asm volatile("barrier.cluster.arrive.relaxed.aligned;" ::: "memory");
    if (w == 1) {
#pragma unroll
        for (int i = 0; i < E0; i++) {
            const int st = (P_ST0 + i) % P_ST, kb = (ROT & 1 ? nb & 6 : 0) * 8 + i;
            const uint32_t f = bars + 8 * (PB_F + st);
            e_expect(f, 32768);
#pragma unroll
            for (int h = 0; h < 2; h++) {
                e_tma2d(sb + st * 16384 + h * 8192, &mp.o, kb * 256, mb * 16 + h * 8, f, evict_first());
                e_tma2d(sb + P_B + st * 8192 + h * P_PLANE, &mp.wo, nb * 128 + h * 64, kb * 64, f, evict_first());
            }
        }
    }
    if (w != 0 && w != 3) asm volatile("barrier.cluster.wait.aligned;" ::: "memory");
    if (w >= 0) {
        asm volatile("setmaxnreg.dec.sync.aligned.u32 40;");
        if (w == 0) {
            post_produce<false>(sb, mp, mb, nb, rank);
        } else if (w < 3) {
            const int wg = w - 1, rh = 2 * mb + wg;
            float* rowc = (float*)(smraw + P_ROW) + (wg * 64 + lane * 2) * 8;
            int nout = 0, sig = 0;
            if (X_DLY) __nanosleep(X_DLY);
            if (wg && lane < 9) asm volatile("prefetch.tensormap [%0];" ::"l"(&mp.y + lane) : "memory");
            e_expect(bars + 8 * (PB_X + wg), 16384);
            e_tma2d(sb + P_OUT + wg * 16384, &mp.x, nb * 128, rh * 64, bars + 8 * (PB_X + wg), evict_first());
            e_tma2d(sb + P_OUT + wg * 16384 + 8192, &mp.x, nb * 128 + 64, rh * 64, bars + 8 * (PB_X + wg), evict_first());
            if (wg == 0) {
#pragma unroll 1
                for (int i = 0; i < 11; i++) {
                    const float* src = i < 4 ? g_mod + ((0x5342 >> (4 * i)) & 15) * DM + nb * 128 : g_vec + (i < 7 ? (i - 4) * DM + nb * 128 : 3 * DM + u_col(max(i - 8, 0), nb) + (i == 8) * 128);
                    if (i != 8 || lane < 16) cp_async16(sb + P_VEC + i * 512 - (i > 8) * 256 + lane * 16, src + lane * 4);
                }
                *(uint4*)&g_modp[blockIdx.x * 128 + lane * 4] = make_uint4(0, 0, 0, 0);
                if (blockIdx.x == 64) *(uint2*)&g_tick[lane * 2] = make_uint2(0, 0);
                asm volatile("cp.async.wait_all;" ::: "memory");
                const float4 a = lds4f(sb + P_VEC + V_A * 512 + lane * 16);
                sts4f(sb + P_VEC + V_A * 512 + lane * 16, 1.0f + a.x, 1.0f + a.y, 1.0f + a.z, 1.0f + a.w);
                bar_arrive(3, 288);
            }
#pragma unroll 1
            for (int i = 0; i < 9; i++) {
                const int cnt = i == 8 ? 6 : (0x54392180u >> (4 * i)) & 15;
                if (cnt < C_S1) {
                    const bool isu = cnt >= C_U && cnt < 6;
                    const int ng = cnt == C_U ? 3 : 2, c0 = isu ? u_col(cnt - C_U, nb) : nb * 128;
                    const uint32_t src = sb + (cnt == C_U ? P_OUT3 : P_OUT) + wg * ng * 8192;
#pragma unroll 1
                    for (int j = 0; j < ng; j++) {
                        bar_sync(4 + 4 * wg + (sig++ & 3), 160);
                        if (lane == 0) {
                            if (HFENCE) fence_async_smem();
                            PH_(cnt == PPH - 1, wg, 20)
                            asm volatile("cp.async.bulk.tensor.2d.global.shared::cta.bulk_group [%0, {%2, %3}], [%1]; cp.async.bulk.commit_group;"
                                         ::"l"(&mp.y + 2 * (isu ? 3 : min(cnt, 4))), "r"(src + j * 8192), "r"(c0 + j * 64), "r"(rh * 64) : "memory");
                        }
                        __syncwarp();
                    }
                    if (lane == 0) {
                        asm volatile("cp.async.bulk.wait_group 0; fence.proxy.async.global;" ::: "memory");
                        PH_(cnt == PPH - 1, wg, 21)
                        asm volatile("st.release.cta.shared.u32 [%0], %1;" ::"r"(bars + 8 * (PB_OUT + wg)), "r"(nout + 1) : "memory");
                        if (cnt < 6) asm volatile("fence.acq_rel.gpu; st.relaxed.gpu.global.u32 [%0], %1;" ::"l"(&g_pflag[cnt * 256 + rh * 8 + nb]), "r"(1) : "memory");
                        if (PEER && (cnt == C_Y || cnt == C_X1))
                            asm volatile("{.reg .b32 r; mapa.shared::cluster.u32 r, %0, %1; mbarrier.arrive.relaxed.cluster.shared::cluster.b64 _, [r];}" ::"r"(bars + 8 * PB_P), "r"(rank ^ 1) : "memory");
                        PH_(cnt == PPH - 1, wg, 22)
                    }
                    nout++;
                    __syncwarp();
                    continue;
                }
                bar_sync(4 + 4 * wg + (sig++ & 3), 160);
#pragma unroll 1
                for (int q = 0; q < (cnt == C_S1 ? 3 : 1); q++) {
                    const float4 v = lds4f(sb + P_ROW + wg * 2048 + q * 512 + lane * 16);
                    asm volatile("red.relaxed.gpu.global.add.v4.f32 [%0], {%1, %2, %3, %4};"
                                 ::"l"((float4*)g_st + (cnt == C_S1 ? q : 3) * (S_ / 2) + rh * 32 + lane), "f"(v.x), "f"(v.y), "f"(v.z), "f"(v.w) : "memory");
                }
                __syncwarp();
                uint32_t* c = &g_pcnt[(cnt - C_S1) * 256 + rh * 8];
                if (lane == 0) { signal_count(c); wait_count1(c, 8); }
                __syncwarp();
                const float4* sp = (const float4*)g_st + rh * 32 + lane;
                float4 u[3] = {__ldcg(sp + (cnt == C_S1 ? 0 : 3) * (S_ / 2)), __ldcg(sp + S_ / 2), __ldcg(sp + S_)};
#pragma unroll 1
                for (int h = 0; h < 2; h++) {
                    const float id = 1.0f / DM;
                    const float m = u[0].x * id, var = fmaxf(u[0].y * id - m * m, 0.f) + 1e-5f, r = rsqrtf(var);
                    float sc = r, m2 = 0.f;
                    if (cnt == C_S1) {
                        m2 = r * (u[1].x * id - m * g_cst[0]) + g_cst[3];
                        const float e2 = r * r * (u[2].x * id - 2.0f * m * u[1].y * id + m * m * g_cst[1]) + 2.0f * r * (u[2].y * id - m * g_cst[2]) + g_cst[4];
                        sc = r * rsqrtf(fmaxf(e2 - m2 * m2, 0.f) + 1e-5f);
                    }
                    const GeluK k = gelu_k(sc);
                    *(float4*)(rowc + h * 8) = make_float4(k.k0, k.k1, k.kh, -m);
                    *(float4*)(rowc + h * 8 + 4) = make_float4(var * r, -m2 * var * r, r, -m * r);
#pragma unroll
                    for (int q = 0; q < 3; q++) { u[q].x = u[q].z; u[q].y = u[q].w; }
                }
                bar_arrive(1 + wg, 160);
            }
        } else {
            post_produce<true>(sb, mp, mb, nb, rank);
        }
    } else {
        asm volatile("setmaxnreg.inc.sync.aligned.u32 232;");
        const int wg = __reduce_max_sync(~0u, tid >> 7), wi = (tid >> 5) & 3, g = lane >> 2, tq = lane & 3;
        const bool lead = (tid & 127) == 0;
        uint32_t rel = 0;
        if ((tid & 127) < 2) asm("mapa.shared::cluster.u32 %0, %1, %2;" : "=r"(rel) : "r"(bars + 8 * PB_E), "r"(tid & 1));
        PP(0)
        if (tid == 0) TL(10)
        uint32_t vec = sb + P_VEC + tq * 8;
        const uint32_t stw = sb + (wi * 16 + ((lane >> 3) & 1) * 8 + (lane & 7)) * 128 + (((lane >> 4) ^ (lane & 7)) << 4);
        int sig = 0;
        auto signal = [&]() { bar_arrive(4 + 4 * wg + (sig++ & 3), 160); };
        auto put64 = [&](uint32_t o, const float* v) {
#pragma unroll
            for (int jj = 0; jj < 4; jj++, v += 8) stsm4((stw + o) ^ (jj << 5), pack2(v[0], v[1]), pack2(v[2], v[3]), pack2(v[4], v[5]), pack2(v[6], v[7]));
            if (HFENCE < 2) fence_async_smem();
            signal();
        };
        auto out_free = [&](int n) { wait_smem(bars + 8 * (PB_OUT + (lane & 1)), n); };
        const uint32_t rowc = sb + P_ROW + (wg * 64 + wi * 16 + g) * 32, o128 = P_OUT + wg * 16384;
        const uint32_t rsum = sb + P_ROW + wg * 2048 + (wi * 16 + g) * 8;
        Pipe pa = {P_ST0, 1};
        auto none = [](int) {};
        uint32_t keep[32];
#define KEEP(jn, e) (((e) & 1) ? bfhi(keep[2 * (jn) + ((e) >> 1)]) : bflo(keep[2 * (jn) + ((e) >> 1)]))
        float mu1[2], r1[2];
        {
            float acc[64];
            post_mma<0>(sb, acc, pa, 64, wg, rel, lead, 1, [&](int kb) {
                if (kb != 40) return;
                bar_sync(3, 288);
                mbar_wait_w(bars + 8 * (PB_X + wg), 0);
#pragma unroll
                for (int jj = 0; jj < 8; jj++) ldsm4(keep + jj * 4, (stw + o128 + (jj >> 2) * 8192) ^ ((jj & 3) << 5));
            });
            asm volatile("" : "+r"(vec) :: "memory");
            float st[2][6];
#pragma unroll
            for (int q = 0; q < 6; q++) st[0][q] = st[1][q] = 0.f;
#pragma unroll
            for (int jn = 0; jn < 16; jn++) {
                const float2 ga = ldsv(vec + V_GA * 512 + jn * 32), a = ldsv(vec + V_A * 512 + jn * 32);
                float xa[4];
#pragma unroll
                for (int e = 0; e < 4; e++) {
                    xa[e] = fmaf((e & 1) ? ga.y : ga.x, acc[4 * jn + e], KEEP(jn, e));
                    st[e >> 1][0] += xa[e]; st[e >> 1][1] = fmaf(xa[e], xa[e], st[e >> 1][1]);
                    acc[4 * jn + e] = ((e & 1) ? a.y : a.x) * xa[e];
                }
                keep[2 * jn] = pack2(xa[0], xa[1]); keep[2 * jn + 1] = pack2(xa[2], xa[3]);
                if ((jn & 7) == 7) put64(o128 + (jn >> 3) * 8192, acc + 4 * jn - 28);
            }
            PP(3)
#pragma unroll
            for (int jn = 0; jn < 16; jn++) {
                const float2 a = ldsv(vec + V_A * 512 + jn * 32), b = ldsv(vec + V_B * 512 + jn * 32);
#pragma unroll
                for (int e = 0; e < 4; e++) {
                    const float y = acc[4 * jn + e], aa = (e & 1) ? a.y : a.x, bb = (e & 1) ? b.y : b.x;
                    float* s = st[e >> 1];
                    s[2] += y; s[3] = fmaf(aa, y, s[3]); s[4] = fmaf(y, y, s[4]); s[5] = fmaf(bb, y, s[5]);
                }
            }
#pragma unroll
            for (int h = 0; h < 2; h++)
#pragma unroll
                for (int q = 0; q < 6; q++) { st[h][q] += __shfl_xor_sync(~0u, st[h][q], 1); st[h][q] += __shfl_xor_sync(~0u, st[h][q], 2); }
            if (tq < 3) {
#pragma unroll
                for (int h = 0; h < 2; h++)
                    sts2(rsum + tq * 512 + h * 64, tq == 0 ? st[h][0] : tq == 1 ? st[h][2] : st[h][4], tq == 0 ? st[h][1] : tq == 1 ? st[h][3] : st[h][5]);
            }
            signal();
            PP(29)
        }
        {
            float acc[64];
            post_mma<1>(sb, acc, pa, 16, wg, rel, lead, 4, none);
            float c1[2], c2[2], c3[2];
            GeluK gk[2];
            bar_sync(1 + wg, 160);
#pragma unroll
            for (int h = 0; h < 2; h++) {
                const float4 a = lds4f(rowc + h * 256), b = lds4f(rowc + h * 256 + 16);
                gk[h] = {a.x, a.y, a.z}; c1[h] = a.w; c2[h] = b.x; c3[h] = b.y; mu1[h] = b.w; r1[h] = b.z;
            }
#pragma unroll
            for (int jn = 0; jn < 16; jn++) {
                const float2 va = ldsv(vec + V_VA * 512 + jn * 32), vb = ldsv(vec + V_VB * 512 + jn * 32), vc = ldsv(vec + V_VC * 512 + jn * 32);
#pragma unroll
                for (int e = 0; e < 4; e++) {
                    const int h = e >> 1;
                    const float t = fmaf(c1[h], (e & 1) ? va.y : va.x, fmaf(c2[h], (e & 1) ? vb.y : vb.x, fmaf(c3[h], (e & 1) ? vc.y : vc.x, acc[4 * jn + e])));
                    acc[4 * jn + e] = gelu_s(t, gk[h]);
                }
                if ((jn & 7) == 7) put64(o128 + (jn >> 3) * 8192, acc + 4 * jn - 28);
            }
            PP(6)
        }
        {
            float acc[64];
            post_mma<2>(sb, acc, pa, 16, wg, rel, lead, 7, none);
#pragma unroll
            for (int jn = 0; jn < 16; jn++) {
                const float2 a = ldsv(vec + V_A * 512 + jn * 32), b = ldsv(vec + V_B * 512 + jn * 32);
#pragma unroll
                for (int e = 0; e < 4; e++) {
                    const int h = e >> 1;
                    acc[4 * jn + e] += fmaf(fmaf(KEEP(jn, e), r1[h], mu1[h]), (e & 1) ? a.y : a.x, (e & 1) ? b.y : b.x);
                }
                if ((jn & 7) == 7) put64(o128 + (jn >> 3) * 8192, acc + 4 * jn - 28);
            }
            PP(9)
            float st[2][2] = {{0.f, 0.f}, {0.f, 0.f}};
#pragma unroll
            for (int jn = 0; jn < 16; jn++) {
                const float2 gb = ldsv(vec + V_GB * 512 + jn * 32);
                float z[4];
#pragma unroll
                for (int e = 0; e < 4; e++) {
                    const float x1 = acc[4 * jn + e];
                    st[e >> 1][0] += x1; st[e >> 1][1] = fmaf(x1, x1, st[e >> 1][1]);
                    z[e] = fmaf((e & 1) ? gb.y : gb.x, x1, KEEP(jn, e));
                }
                keep[2 * jn] = pack2(z[0], z[1]); keep[2 * jn + 1] = pack2(z[2], z[3]);
            }
#pragma unroll
            for (int h = 0; h < 2; h++)
#pragma unroll
                for (int q = 0; q < 2; q++) { st[h][q] += __shfl_xor_sync(~0u, st[h][q], 1); st[h][q] += __shfl_xor_sync(~0u, st[h][q], 2); }
            if (tq < 2) sts2(rsum + tq * 64, tq ? st[1][0] : st[0][0], tq ? st[1][1] : st[0][1]);
            signal();
            PP(30)
        }
        {
            float old[96], acc[64];
            post_mma<3>(sb, old, pa, 16, wg, rel, lead, 10, none);
            uint32_t v3 = vec + V_C3 * 512;
            float c1[2], vc[8];
            auto next_vc = [&]() {
#pragma unroll
                for (int i = 0; i < 4; i++) { const float2 u = lds2f(v3 + i * 32); vc[2 * i] = u.x; vc[2 * i + 1] = u.y; }
                v3 += 128;
            };
            next_vc();
            GeluK gk[2];
            bar_sync(1 + wg, 160);
#pragma unroll
            for (int h = 0; h < 2; h++) { const float4 a = lds4f(rowc + h * 256); gk[h] = {a.x, a.y, a.z}; c1[h] = a.w; }
            bar_arrive(14 + wg, 256);
#pragma unroll 1
            for (int r = 0; r < 3; r++) {
                const uint32_t o = stw + (r ? o128 : P_OUT3 + wg * 24576);
                uint32_t when = r == 0 ? (wg ? SL_A1 : SL_A0) : r == 1 ? (wg ? SL_B1 : SL_B0) : SL_C << (2 * wg), n = 0;
                post_mma<2>(sb, acc, pa, r < 2 ? 16 : 56, wg, rel, lead, 12 + 2 * r, [&](int kb) {
                    const bool now = when & 1;
                    when >>= 1;
                    if (!now) return;
                    if (n == 0) { if (r == 0) bar_sync(15 - wg, 256); out_free(3 + r); }
                    float v[16];
                    pick32(v, n, c1, vc, old);
                    next_vc();
#pragma unroll
                    for (int e = 0; e < 16; e++) v[e] = gelu_s(v[e], gk[(e >> 1) & 1]);
                    const uint32_t a = (o + (n >> 1) * 8192) ^ ((n & 1) << 6);
                    stsm4(a, pack2(v[0], v[1]), pack2(v[2], v[3]), pack2(v[4], v[5]), pack2(v[6], v[7]));
                    stsm4(a ^ 32, pack2(v[8], v[9]), pack2(v[10], v[11]), pack2(v[12], v[13]), pack2(v[14], v[15]));
                    if ((++n & 1) == 0) signal();
                });
                if (r == 2) break;
#pragma unroll
                for (int i = 0; i < 64; i++) old[i] = acc[i];
            }
#pragma unroll
            for (int jn = 0; jn < 16; jn++) {
                const float2 gb = ldsv(vec + V_GB * 512 + jn * 32);
#pragma unroll
                for (int e = 0; e < 4; e++) acc[4 * jn + e] = fmaf((e & 1) ? gb.y : gb.x, acc[4 * jn + e], KEEP(jn, e));
                if ((jn & 7) == 7) put64(o128 + (jn >> 3) * 8192, acc + 4 * jn - 28);
            }
            PP(18)
            if (tid == 0) TL(12)
        }
    }
}

typedef CUresult (*EncFn)(CUtensorMap*, CUtensorMapDataType, cuuint32_t, void*, const cuuint64_t*, const cuuint64_t*, const cuuint32_t*,
                          const cuuint32_t*, CUtensorMapInterleave, CUtensorMapSwizzle, CUtensorMapL2promotion, CUtensorMapFloatOOBfill);

static CUtensorMap make_map(EncFn enc, const void* p, uint64_t inner, uint64_t outer) {
    CUtensorMap m;
    cuuint64_t dims[2] = {inner, outer};
    cuuint64_t str[1] = {inner * 2};
    cuuint32_t box[2] = {64, 64};
    cuuint32_t es[2] = {1, 1};
    enc(&m, CU_TENSOR_MAP_DATA_TYPE_BFLOAT16, 2, (void*)p, dims, str, box, es, CU_TENSOR_MAP_INTERLEAVE_NONE,
        CU_TENSOR_MAP_SWIZZLE_128B, CU_TENSOR_MAP_L2_PROMOTION_L2_256B, CU_TENSOR_MAP_FLOAT_OOB_FILL_NONE);
    return m;
}
static CUtensorMap make_map_o(EncFn enc, const void* p) {
    CUtensorMap m;
    cuuint64_t dims[2] = {16384, 256};
    cuuint64_t str[1] = {65536};
    cuuint32_t box[2] = {256, 8};
    cuuint32_t es[2] = {1, 1};
    enc(&m, CU_TENSOR_MAP_DATA_TYPE_UINT32, 2, (void*)p, dims, str, box, es, CU_TENSOR_MAP_INTERLEAVE_NONE, CU_TENSOR_MAP_SWIZZLE_NONE,
        CU_TENSOR_MAP_L2_PROMOTION_L2_256B, CU_TENSOR_MAP_FLOAT_OOB_FILL_NONE);
    return m;
}
template <class T> static T* sym(T& s) { void* p = nullptr; cudaGetSymbolAddress(&p, s); return (T*)p; }

constexpr RecTime g_time = {T_GO, T_X2, T_V, D_X2, H_D};
extern "C" void kernel_launch(void* const* d_in, const int* in_sizes, int n_in, void* d_out, int out_size) {
    const bf16* x = (const bf16*)d_in[0];
    const bf16* mem0 = (const bf16*)d_in[1];
    const bf16 *Wq = (const bf16*)d_in[2], *Wk = (const bf16*)d_in[3], *Wv = (const bf16*)d_in[4], *Wo = (const bf16*)d_in[5];
    const bf16 *w1 = (const bf16*)d_in[8], *w2 = (const bf16*)d_in[9], *w3 = (const bf16*)d_in[10], *w4 = (const bf16*)d_in[11];
    const bf16 *c = (const bf16*)d_in[12], *wmod = (const bf16*)d_in[13];
    bf16* out = (bf16*)d_out;

    EncFn enc = nullptr;
    cudaDriverEntryPointQueryResult qr;
    cudaGetDriverEntryPoint("cuTensorMapEncodeTiled", (void**)&enc, cudaEnableDefault, &qr);
    CUtensorMap tWq = make_map(enc, Wq, NH * DH, DM), tWk = make_map(enc, Wk, NH * DH, DM), tWv = make_map(enc, Wv, NH * DH, DM);
    PostMaps mp;
    mp.o = make_map_o(enc, sym(g_O)); mp.wo = make_map(enc, Wo, DM, NH * DH);
    mp.y = make_map(enc, sym(g_y), DM, S_); mp.w1 = make_map(enc, w1, DM, DM);
    mp.g = make_map(enc, sym(g_g), DM, S_); mp.w2 = make_map(enc, w2, DM, DM);
    mp.x1 = make_map(enc, sym(g_x1), DM, S_); mp.w3 = make_map(enc, w3, FF, DM);
    mp.u = make_map(enc, sym(g_u), FF, S_); mp.w4 = make_map(enc, w4, DM, FF);
    mp.out = make_map(enc, out, DM, S_); mp.x = make_map(enc, x, DM, S_);
    cudaFuncSetAttribute(k_rec, cudaFuncAttributeMaxDynamicSharedMemorySize, SM_REC_TOTAL);
    cudaFuncSetAttribute(k_post, cudaFuncAttributeMaxDynamicSharedMemorySize, P_SMEM);

    uint8_t* arena = (uint8_t*)(((uintptr_t)sym(g_arena) + (2u << 20) - 1) & ~(uintptr_t)((2u << 20) - 1));
    const RecPtrs rp = {x, mem0, c, wmod, w1, w3, arena, 0u, g_time};
    const RecMaps rm = {tWq, tWk, tWv, mp.wo};
    k_rec<<<132, 384, SM_REC_TOTAL>>>(rm, rp);
    k_post<<<128, 384, P_SMEM>>>(mp);
}
```

```cpp
#include <cuda_runtime.h>
#include <cuda.h>
#include <cuda_bf16.h>
#include <stdint.h>
#include <limits.h>

typedef __nv_bfloat16 bf16;

constexpr int S_ = 2048, DM = 1024, NH = 32, DH = 128, NSEG = 64, FF = 3584;
constexpr int SPIN_LIMIT = 1 << 22;
constexpr int W_INFL = 2;
constexpr int NPROBE = 4;

__device__ uint8_t g_arena[10 << 20];
__device__ __align__(16) uint32_t g_tick[64];
__device__ __align__(16) uint32_t g_modp[8 * 2 * DM];
__host__ __device__ constexpr uint32_t blk(uint32_t lb, uint32_t par) {
    return (lb << 13) | ((((lb) ^ (lb >> 3) ^ (lb >> 4) ^ (lb >> 6) ^ par) & 1) << 12);
}
__host__ __device__ constexpr uint32_t lb_x2(uint32_t h) { return (h & 1) | ((h >> 1) << 3); }
__host__ __device__ constexpr uint32_t acc_slot(uint32_t s) { return (1u << 20) + (s & 1) * 32768 + (s & 2) * 131072; }
__host__ __device__ constexpr uint32_t acc_piece(uint32_t half, uint32_t qd, uint32_t mt) { return mt * 1024 + (qd & 1) * 4096 + half * 8192 + (qd >> 1) * 16384; }
constexpr uint32_t LB_STAMP = 6;
__host__ __device__ constexpr uint32_t stamp_line(uint32_t w, uint32_t q) { return ((w & 1) * 2 + (q >> 1)) * 1024 + (q & 1) * 256; }
constexpr uint32_t ACC_ONE = 0x3c000000u, ACC_ALL = 0x50000000u;
constexpr uint32_t LB_PROBE = 6 | 64;
__host__ __device__ constexpr uint32_t lb_tok(uint32_t h) { return (h & 1) | ((h >> 1) << 3); }
__device__ __align__(16) float g_mod[6 * DM];
__device__ __align__(1024) bf16 g_himg[(S_ + 32) * DM];
__device__ __align__(1024) bf16 g_O[S_ * NH * DH];
__device__ __align__(1024) bf16 g_y[S_ * DM];
__device__ __align__(1024) bf16 g_g[S_ * DM];
__device__ __align__(1024) bf16 g_x1[S_ * DM];
__device__ __align__(16) float g_st[4 * S_ * 2];
__device__ __align__(16) float g_vec[3 * DM + FF];
__device__ float g_cst[8];
__device__ uint32_t g_pcnt[2 * 32 * 8], g_pflag[6 * 32 * 8];
__device__ __align__(1024) bf16 g_u[S_ * FF];

__device__ __forceinline__ uint32_t smem_u32(const void* p) { return (uint32_t)__cvta_generic_to_shared(p); }
__device__ __forceinline__ void spin_guard(int it) {
    asm volatile("{.reg .pred p; setp.gt.s32 p, %0, %1; @p st.global.u32 [%2], %0;}" ::"r"(it), "n"(SPIN_LIMIT), "l"(1ull));
}
__device__ __forceinline__ void wg_fence() { asm volatile("wgmma.fence.sync.aligned;" ::: "memory"); }
__device__ __forceinline__ void wg_commit() { asm volatile("wgmma.commit_group.sync.aligned;" ::: "memory"); }
template <int N> __device__ __forceinline__ void wg_wait() { asm volatile("wgmma.wait_group.sync.aligned %0;" ::"n"(N) : "memory"); }
__host__ __device__ constexpr uint64_t mkdesc(uint32_t addr, uint32_t lbo, uint32_t sbo, uint32_t swz) {
    return (uint64_t)((addr & 0x3FFFF) >> 4) | ((uint64_t)(lbo >> 4) << 16) | ((uint64_t)(sbo >> 4) << 32) | ((uint64_t)swz << 62);
}
__device__ __forceinline__ uint64_t dadd(uint64_t d, uint32_t o) { return (d & 0xffffffff00000000ull) | (uint32_t)((uint32_t)d + o); }
__device__ __forceinline__ void mbar_init(uint32_t b, uint32_t c) { asm volatile("mbarrier.init.shared.b64 [%0], %1;" ::"r"(b), "r"(c) : "memory"); }
__device__ __forceinline__ void mbar_expect(uint32_t b, uint32_t tx) { asm volatile("mbarrier.arrive.expect_tx.shared.b64 _, [%0], %1;" ::"r"(b), "r"(tx) : "memory"); }
__device__ __forceinline__ void mbar_arrive(uint32_t b) { asm volatile("mbarrier.arrive.shared.b64 _, [%0];" ::"r"(b) : "memory"); }
__device__ __forceinline__ void mbar_arrive_cluster_if(bool c, uint32_t b, uint32_t cta) {
    asm volatile("{.reg .pred p; .reg .b32 r; setp.ne.u32 p, %2, 0; mapa.shared::cluster.u32 r, %0, %1; @p mbarrier.arrive.shared::cluster.b64 _, [r];}" ::"r"(b), "r"(cta), "r"((uint32_t)c) : "memory");
}
__device__ __forceinline__ bool mbar_try(uint32_t b, uint32_t par) {
    uint32_t ok;
    asm volatile("{.reg .pred p; mbarrier.try_wait.parity.shared.b64 p, [%1], %2; selp.u32 %0, 1, 0, p;}" : "=r"(ok) : "r"(b), "r"(par) : "memory");
    return ok;
}
__device__ __forceinline__ void mbar_wait_w(uint32_t b, uint32_t par) {
    int it = 0;
    bool ok;
#pragma unroll 1
    do { ok = __all_sync(~0u, mbar_try(b, par)); spin_guard(++it); } while (!ok);
}
__device__ __forceinline__ void bar_sync(int id, int n) { asm volatile("bar.sync %0, %1;" ::"r"(id), "r"(n) : "memory"); }
__device__ __forceinline__ void bar_arrive(int id, int n) { asm volatile("bar.arrive %0, %1;" ::"r"(id), "r"(n) : "memory"); }
__device__ __forceinline__ void fence_async_smem() { asm volatile("fence.proxy.async.shared::cta;" ::: "memory"); }
__device__ __forceinline__ void ldsm4t(uint32_t* r, uint32_t a) {
    asm volatile("ldmatrix.sync.aligned.m8n8.x4.trans.shared.b16 {%0,%1,%2,%3}, [%4];" : "=r"(r[0]), "=r"(r[1]), "=r"(r[2]), "=r"(r[3]) : "r"(a) : "memory");
}
__device__ __forceinline__ void ldsm4(uint32_t* r, uint32_t a) {
    asm volatile("ldmatrix.sync.aligned.m8n8.x4.shared.b16 {%0,%1,%2,%3}, [%4];" : "=r"(r[0]), "=r"(r[1]), "=r"(r[2]), "=r"(r[3]) : "r"(a) : "memory");
}
__device__ __forceinline__ uint32_t movm(uint32_t a) {
    uint32_t d; asm volatile("movmatrix.sync.aligned.m8n8.trans.b16 %0, %1;" : "=r"(d) : "r"(a)); return d;
}
__device__ __forceinline__ void mma16816(float* d, uint32_t a0, uint32_t a1, uint32_t a2, uint32_t a3, uint32_t b0, uint32_t b1) {
    asm volatile("mma.sync.aligned.m16n8k16.row.col.f32.bf16.bf16.f32 {%0,%1,%2,%3},{%4,%5,%6,%7},{%8,%9},{%0,%1,%2,%3};"
                 : "+f"(d[0]), "+f"(d[1]), "+f"(d[2]), "+f"(d[3]) : "r"(a0), "r"(a1), "r"(a2), "r"(a3), "r"(b0), "r"(b1));
}
__device__ __forceinline__ void mma16816z(float* d, const uint32_t* a, uint32_t b0, uint32_t b1) {
    asm volatile("mma.sync.aligned.m16n8k16.row.col.f32.bf16.bf16.f32 {%0,%1,%2,%3},{%4,%5,%6,%7},{%8,%9},{%10,%10,%10,%10};"
                 : "=f"(d[0]), "=f"(d[1]), "=f"(d[2]), "=f"(d[3]) : "r"(a[0]), "r"(a[1]), "r"(a[2]), "r"(a[3]), "r"(b0), "r"(b1), "f"(0.f));
}
__device__ __forceinline__ void mma1688(float* d, uint32_t a0, uint32_t a1, uint32_t b0) {
    asm volatile("mma.sync.aligned.m16n8k8.row.col.f32.bf16.bf16.f32 {%0,%1,%2,%3},{%4,%5},{%6},{%0,%1,%2,%3};"
                 : "+f"(d[0]), "+f"(d[1]), "+f"(d[2]), "+f"(d[3]) : "r"(a0), "r"(a1), "r"(b0));
}
__device__ __forceinline__ uint32_t pack2(float lo, float hi) {
    uint32_t r; asm("cvt.rn.bf16x2.f32 %0, %1, %2;" : "=r"(r) : "f"(hi), "f"(lo)); return r;
}
__device__ __forceinline__ uint32_t hadd2v(uint32_t a, uint32_t b) {
    uint32_t r; asm volatile("add.rn.bf16x2 %0, %1, %2;" : "=r"(r) : "r"(a), "r"(b)); return r;
}
__device__ __forceinline__ float bflo(uint32_t u) { return __uint_as_float(u << 16); }
__device__ __forceinline__ float bfhi(uint32_t u) { return __uint_as_float(u & 0xffff0000u); }
__device__ __forceinline__ float ex2(float x) { float r; asm("ex2.approx.ftz.f32 %0, %1;" : "=f"(r) : "f"(x)); return r; }
__device__ __forceinline__ uint4 ldg_rlx4(const void* p) {
    uint4 v; asm volatile("ld.relaxed.gpu.global.v4.u32 {%0,%1,%2,%3}, [%4];" : "=r"(v.x), "=r"(v.y), "=r"(v.z), "=r"(v.w) : "l"(p) : "memory"); return v;
}
__device__ __forceinline__ uint32_t ldg_rlx1(const void* p) {
    uint32_t v; asm volatile("ld.relaxed.gpu.global.u32 %0, [%1];" : "=r"(v) : "l"(p) : "memory"); return v;
}
__device__ __forceinline__ void stg_rlx1(void* p, uint32_t v) { asm volatile("st.relaxed.gpu.global.u32 [%0], %1;" ::"l"(p), "r"(v) : "memory"); }
__device__ __forceinline__ void stg_rlx2(void* p, uint32_t x, uint32_t y) {
    unsigned long long v = (unsigned long long)x | ((unsigned long long)y << 32);
    asm volatile("st.relaxed.gpu.global.b64 [%0], %1;" ::"l"(p), "l"(v) : "memory");
}
__device__ __forceinline__ void stg_rlx4(void* p, uint32_t x, uint32_t y, uint32_t z, uint32_t w) {
    asm volatile("st.relaxed.gpu.global.v4.u32 [%0], {%1,%2,%3,%4};" ::"l"(p), "r"(x), "r"(y), "r"(z), "r"(w) : "memory");
}
__device__ __forceinline__ void sts4(uint32_t a, uint32_t x, uint32_t y, uint32_t z, uint32_t w) {
    asm volatile("st.shared.v4.u32 [%0], {%1,%2,%3,%4};" ::"r"(a), "r"(x), "r"(y), "r"(z), "r"(w) : "memory");
}
__device__ __forceinline__ uint4 lds4(uint32_t a) {
    uint4 v; asm volatile("ld.shared.v4.u32 {%0,%1,%2,%3}, [%4];" : "=r"(v.x), "=r"(v.y), "=r"(v.z), "=r"(v.w) : "r"(a) : "memory"); return v;
}
#define F4(d, i) "+f"(d[i]), "+f"(d[i + 1]), "+f"(d[i + 2]), "+f"(d[i + 3])
template <bool V> __device__ __forceinline__ void wgmma_tok_rs(float* d, const uint32_t* a, uint64_t b, int sc) {
    if (V) asm volatile("{.reg .pred p; setp.ne.b32 p, %25, 0;\n wgmma.mma_async.sync.aligned.m64n40k16.f32.bf16.bf16 {%0,%1,%2,%3,%4,%5,%6,%7,%8,%9,%10,%11,%12,%13,%14,%15,%16,%17,%18,%19}, {%20,%21,%22,%23}, %24, p, 1, 1, 0;}"
                        : F4(d, 0), F4(d, 4), F4(d, 8), F4(d, 12), F4(d, 16) : "r"(a[0]), "r"(a[1]), "r"(a[2]), "r"(a[3]), "l"(b), "r"(sc));
    else asm volatile("{.reg .pred p; setp.ne.b32 p, %21, 0;\n wgmma.mma_async.sync.aligned.m64n32k16.f32.bf16.bf16 {%0,%1,%2,%3,%4,%5,%6,%7,%8,%9,%10,%11,%12,%13,%14,%15}, {%16,%17,%18,%19}, %20, p, 1, 1, 0;}"
                      : F4(d, 0), F4(d, 4), F4(d, 8), F4(d, 12) : "r"(a[0]), "r"(a[1]), "r"(a[2]), "r"(a[3]), "l"(b), "r"(sc));
}
template <bool V> __device__ __forceinline__ void wgmma_tok_ss(float* d, uint64_t a, uint64_t b) {
    if (V) asm volatile("wgmma.mma_async.sync.aligned.m64n40k16.f32.bf16.bf16 {%0,%1,%2,%3,%4,%5,%6,%7,%8,%9,%10,%11,%12,%13,%14,%15,%16,%17,%18,%19}, %20, %21, 1, 1, 1, 1, 0;"
                        : F4(d, 0), F4(d, 4), F4(d, 8), F4(d, 12), F4(d, 16) : "l"(a), "l"(b));
    else asm volatile("wgmma.mma_async.sync.aligned.m64n32k16.f32.bf16.bf16 {%0,%1,%2,%3,%4,%5,%6,%7,%8,%9,%10,%11,%12,%13,%14,%15}, %16, %17, 1, 1, 1, 1, 0;"
                      : F4(d, 0), F4(d, 4), F4(d, 8), F4(d, 12) : "l"(a), "l"(b));
}
#define F16(d, i) F4(d, i), F4(d, i + 4), F4(d, i + 8), F4(d, i + 12)
template <int TA>
__device__ __forceinline__ void wgmma_ss128(float* d, uint64_t a, uint64_t b, int sc) {
    asm volatile("{.reg .pred p; setp.ne.b32 p, %66, 0;\n wgmma.mma_async.sync.aligned.m64n128k16.f32.bf16.bf16 "
                 "{%0,%1,%2,%3,%4,%5,%6,%7,%8,%9,%10,%11,%12,%13,%14,%15,%16,%17,%18,%19,%20,%21,%22,%23,%24,%25,%26,%27,%28,%29,%30,%31,"
                 "%32,%33,%34,%35,%36,%37,%38,%39,%40,%41,%42,%43,%44,%45,%46,%47,%48,%49,%50,%51,%52,%53,%54,%55,%56,%57,%58,%59,%60,%61,%62,%63}, %64, %65, p, 1, 1, %67, 1;}"
                 : F16(d, 0), F16(d, 16), F16(d, 32), F16(d, 48) : "l"(a), "l"(b), "r"(sc), "n"(TA));
}

__device__ __forceinline__ float warp_sum(float v) {
#pragma unroll
    for (int o = 16; o; o >>= 1) v += __shfl_xor_sync(~0u, v, o);
    return v;
}
__device__ __forceinline__ float bfround(float x) { return __bfloat162float(__float2bfloat16(x)); }

__device__ __forceinline__ void wait_count1(const uint32_t* p, uint32_t target) {
    int it = 0;
#pragma unroll 1
    while (true) {
        uint32_t v;
        asm volatile("ld.acquire.gpu.global.u32 %0, [%1];" : "=r"(v) : "l"(p) : "memory");
        if (v >= target) break;
        spin_guard(++it);
    }
}
__device__ __forceinline__ void signal_count(uint32_t* p) { asm volatile("red.release.gpu.global.add.u32 [%0], 1;" ::"l"(p) : "memory"); }
__device__ __forceinline__ void e_expect(uint32_t b, uint32_t tx) {
    asm volatile("{.reg .pred p; elect.sync _|p, 0xffffffff; @p mbarrier.arrive.expect_tx.shared.b64 _, [%0], %1;}" ::"r"(b), "r"(tx) : "memory");
}
__device__ __forceinline__ uint64_t evict_first() { uint64_t p; asm("createpolicy.fractional.L2::evict_first.b64 %0, 1.0;" : "=l"(p)); return p; }
__device__ __forceinline__ void e_tma2d_ef(uint32_t dst, const CUtensorMap* m, int c0, int c1, uint32_t bar) {
    asm volatile("{.reg .pred p; elect.sync _|p, 0xffffffff;\n @p cp.async.bulk.tensor.2d.shared::cluster.global.mbarrier::complete_tx::bytes.L2::cache_hint [%0], [%1, {%3, %4}], [%2], %5;}"
                 ::"r"(dst), "l"(m), "r"(bar), "r"(c0), "r"(c1), "l"(evict_first()) : "memory");
}
__device__ __forceinline__ void e_tma2d(uint32_t dst, const CUtensorMap* m, int c0, int c1, uint32_t bar) {
    asm volatile("{.reg .pred p; elect.sync _|p, 0xffffffff;\n @p cp.async.bulk.tensor.2d.shared::cluster.global.mbarrier::complete_tx::bytes [%0], [%1, {%3, %4}], [%2];}"
                 ::"r"(dst), "l"(m), "r"(bar), "r"(c0), "r"(c1) : "memory");
}
__device__ __forceinline__ void e_tma2d_mc_ef(uint32_t dst, const CUtensorMap* m, int c0, int c1, uint32_t bar) {
    asm volatile("{.reg .pred p; elect.sync _|p, 0xffffffff;\n @p cp.async.bulk.tensor.2d.shared::cluster.global.mbarrier::complete_tx::bytes.multicast::cluster.L2::cache_hint [%0], [%1, {%3, %4}], [%2], %5, %6;}"
                 ::"r"(dst), "l"(m), "r"(bar), "r"(c0), "r"(c1), "h"((uint16_t)3), "l"(evict_first()) : "memory");
}
__device__ __forceinline__ uint32_t wait_count_w(const uint32_t* p, uint32_t target) {
    int it = 0;
#pragma unroll 1
    while (true) {
        uint32_t v;
        asm volatile("ld.acquire.gpu.global.u32 %0, [%1];" : "=r"(v) : "l"(p) : "memory");
        if (__all_sync(~0u, v >= target)) return v;
        spin_guard(++it);
    }
}

__device__ __forceinline__ uint4 pack8(const float* x) {
    return make_uint4(pack2(x[0], x[1]), pack2(x[2], x[3]), pack2(x[4], x[5]), pack2(x[6], x[7]));
}
constexpr int NL = 6;
constexpr uint32_t HCH = 5120, HBUF = 8 * HCH;
constexpr uint32_t SM_SX = 0, SM_ST = 2560, SM_OX = 8192, SM_LX = 10240, SM_PX = 11392, SM_PA = 12288, SM_VF = 18432, SM_TAB = 26624, SM_WL2 = 41984, SM_HB = 49152, SM_WO = 131072,
                   SM_WL = 196608, SM_PRE = SM_WL, SM_BAR = 227328, SM_TRC = SM_BAR + 256, SM_REC_TOTAL = SM_TRC + 2688;
__host__ __device__ constexpr uint32_t sm_wl(int i) { return i < 5 ? SM_WL + i * 6144 : SM_WL2; }
constexpr uint32_t SB0 = 1024;
constexpr int B_WO = 0, B_HE = 1, B_ROLE = 2, B_HB = 3, B_W = 5;
constexpr int NB_MEM = 1, NB_QK = 2, NB_X1 = 3, NB_X2 = 4, NB_WIN = 5, NB_WG = 6, NB_KDONE = 7, NB_FIN0 = 8, NB_LN = 9, NB_MEM2 = 10, NB_H = 11, NB_A = 12, NB_B = 13, NB_C = 14, NB_F = 15;
constexpr int TPV_DLY = 3;
constexpr int L_AT = 0;
constexpr int D_X2 = 340;
constexpr int NPF1 = 6;
constexpr int NPF = 11;
constexpr int T_GO = 29;
constexpr int GATE_AT = 25;
constexpr int T_X2 = 1875;
constexpr int T_V = 300;
constexpr int VP_AT = 1;
constexpr int PD = 4;
constexpr int PV_FENCE = 0;
constexpr int SSG = 4;
constexpr int SSG_V = 5;
constexpr int SS0_K = 4;
constexpr int SS0_V = 6;
constexpr int NPF0 = 4;
constexpr int STG_FENCE = 1;
constexpr int WO_AT = 0x1100;
constexpr int W_SPEC = 7;
constexpr int NO_GUESS = 0;
constexpr int NPF2 = 9;
constexpr int PF_DLY = 6;
constexpr int H_D = 210;
constexpr int PIN_EPI = 1;

__device__ __forceinline__ uint32_t clk32() { uint32_t t; asm volatile("mov.u32 %0, %%clock;" : "=r"(t) :: "memory"); return t; }
__device__ __forceinline__ uint32_t gtime32() { uint32_t t; asm volatile("mov.u32 %0, %%globaltimer_lo;" : "=r"(t) :: "memory"); return t; }
template <int N> __device__ __forceinline__ uint32_t delay(uint32_t zero) {
    float x = __uint_as_float(clk32());
#pragma unroll
    for (int i = 0; i < N; i++) asm volatile("ex2.approx.ftz.f32 %0, %0;" : "+f"(x));
    return __float_as_uint(x) & zero;
}
__device__ __forceinline__ uint32_t clk_after(uint32_t x, uint32_t zero) {
    unsigned long long c = 0;
    asm volatile("{.reg .pred p; setp.eq.u32 p, %1, 0; @p mov.u64 %0, %%clock64;}" : "+l"(c) : "r"(x & zero) : "memory");
    return (uint32_t)c;
}
__device__ __forceinline__ uint32_t later(uint32_t a, uint32_t b) { return a + max((int)(b - a), 0); }
__device__ __forceinline__ void wait_clk(uint32_t t) {
#pragma unroll 1
    while (true) {
        unsigned long long c;
        asm volatile("mov.u64 %0, %%clock64;" : "=l"(c) :: "memory");
        if ((int)((uint32_t)c - t) >= 0) break;
    }
}
__device__ __forceinline__ uint32_t opaque(uint32_t v) { return __shfl_sync(~0u, v, threadIdx.x & 31); }
__device__ __forceinline__ uint32_t xor_or(uint32_t a, uint32_t b, uint32_t t) {
    uint32_t r; asm volatile("lop3.b32 %0, %1, %2, %3, 0x7E;" : "=r"(r) : "r"(a), "r"(b), "r"(t)); return r;
}
__device__ __forceinline__ uint32_t or3(uint32_t a, uint32_t b, uint32_t c) {
    uint32_t r; asm volatile("lop3.b32 %0, %1, %2, %3, 0xFE;" : "=r"(r) : "r"(a), "r"(b), "r"(c)); return r;
}
__device__ __forceinline__ uint32_t settag(uint32_t v, uint32_t tag) {
    uint32_t r; asm("lop3.b32 %0, %1, 1, %2, 0xB8;" : "=r"(r) : "r"(v), "r"(tag)); return r;
}
__device__ __forceinline__ void ldg1_if(uint32_t& v, const void* p, bool c) {
    asm volatile("{.reg .pred p; setp.ne.u32 p, %2, 0; @p ld.relaxed.gpu.global.u32 %0, [%1];}" : "+r"(v) : "l"(p), "r"((uint32_t)c) : "memory");
}
__device__ __forceinline__ void sts2(uint32_t a, float x, float y) { asm volatile("st.shared.v2.f32 [%0], {%1,%2};" ::"r"(a), "f"(x), "f"(y) : "memory"); }
__device__ __forceinline__ void sts4f(uint32_t a, float x, float y, float z, float w) {
    asm volatile("st.shared.v4.f32 [%0], {%1,%2,%3,%4};" ::"r"(a), "f"(x), "f"(y), "f"(z), "f"(w) : "memory");
}
__device__ __forceinline__ void sts1(uint32_t a, uint32_t x) { asm volatile("st.shared.u32 [%0], %1;" ::"r"(a), "r"(x) : "memory"); }
__device__ __forceinline__ uint32_t lds1(uint32_t a) { uint32_t v; asm volatile("ld.shared.u32 %0, [%1];" : "=r"(v) : "r"(a) : "memory"); return v; }
__device__ __forceinline__ float4 lds4f(uint32_t a) {
    float4 v; asm volatile("ld.shared.v4.f32 {%0,%1,%2,%3}, [%4];" : "=f"(v.x), "=f"(v.y), "=f"(v.z), "=f"(v.w) : "r"(a) : "memory"); return v;
}
__device__ __forceinline__ float2 lds2f(uint32_t a) {
    float2 v; asm volatile("ld.shared.v2.f32 {%0,%1}, [%2];" : "=f"(v.x), "=f"(v.y) : "r"(a) : "memory"); return v;
}
__device__ __forceinline__ bool any_bit0(uint32_t x) {
    uint32_t r;
    asm volatile("{.reg .pred p, q; .reg .b32 t; and.b32 t, %1, 1; setp.ne.u32 p, t, 0; vote.sync.any.pred q, p, 0xffffffff; selp.u32 %0, 1, 0, q;}" : "=r"(r) : "r"(x));
    return r;
}
__device__ __forceinline__ float rcp_fast(float x) { float r; asm("rcp.approx.ftz.f32 %0, %1;" : "=f"(r) : "f"(x)); return r; }
__device__ __forceinline__ void stsm4(uint32_t a, uint32_t r0, uint32_t r1, uint32_t r2, uint32_t r3) {
    asm volatile("stmatrix.sync.aligned.m8n8.x4.shared.b16 [%0], {%1,%2,%3,%4};" ::"r"(a), "r"(r0), "r"(r1), "r"(r2), "r"(r3) : "memory");
}
__device__ __forceinline__ void stsm4t(uint32_t a, uint32_t r0, uint32_t r1, uint32_t r2, uint32_t r3) {
    asm volatile("stmatrix.sync.aligned.m8n8.x4.trans.shared.b16 [%0], {%1,%2,%3,%4};" ::"r"(a), "r"(r0), "r"(r1), "r"(r2), "r"(r3) : "memory");
}
__device__ __forceinline__ void cp_async16(uint32_t dst, const void* src) { asm volatile("cp.async.cg.shared.global [%0], [%1], 16;" ::"r"(dst), "l"(src) : "memory"); }
__device__ __forceinline__ void cp_async16_ef(uint32_t dst, const void* src) {
    asm volatile("cp.async.cg.shared.global.L2::cache_hint [%0], [%1], 16, %2;" ::"r"(dst), "l"(src), "l"(evict_first()) : "memory");
}
__device__ __forceinline__ uint32_t prmt(uint32_t a, uint32_t b, uint32_t c) { uint32_t r; asm("prmt.b32 %0, %1, %2, %3;" : "=r"(r) : "r"(a), "r"(b), "r"(c)); return r; }
__device__ __forceinline__ uint32_t hadd2h(uint32_t a, uint32_t b) { uint32_t r; asm("add.rn.f16x2 %0, %1, %2;" : "=r"(r) : "r"(a), "r"(b)); return r; }
__device__ __forceinline__ uint32_t hmax2h(uint32_t a, uint32_t b) { uint32_t r; asm("max.f16x2 %0, %1, %2;" : "=r"(r) : "r"(a), "r"(b)); return r; }
__device__ __forceinline__ uint32_t max3u(uint32_t a, uint32_t b, uint32_t c) { return __vimax3_u32(a, b, c); }

__device__ __forceinline__ void h_load(uint32_t sb, const uint8_t* hsrc, int pass, uint32_t rank, uint32_t rot, uint32_t wq, bool arm = true, uint32_t skip = 0) {
    const uint32_t bar = sb + SM_BAR + 8 * (B_HB + (pass & 1)), c = (wq + rot) & 3, dst = sb + SM_HB + (pass & 1) * HBUF + (rank * 4 + c) * HCH + skip;
    const uint8_t* src = hsrc + ((size_t)pass * 65536 + c * 4096 + skip);
    if (arm && wq == 0) e_expect(bar, 32768 - 8 * skip);
    asm volatile("{.reg .pred p; elect.sync _|p, 0xffffffff;\n"
                 " @p cp.async.bulk.shared::cluster.global.mbarrier::complete_tx::bytes.multicast::cluster.L2::cache_hint [%0], [%1], %4, [%2], %3, %5;}"
                 ::"r"(dst), "l"(src), "r"(bar), "h"((uint16_t)3), "r"(4096 - skip), "l"(evict_first()) : "memory");
}
__device__ __forceinline__ uint4 ldg_b128(const void* p) {
    uint4 v;
    asm volatile("{.reg .b128 t; .reg .b64 a, b; ld.relaxed.gpu.global.b128 t, [%4]; mov.b128 {a, b}, t; mov.b64 {%0,%1}, a; mov.b64 {%2,%3}, b;}"
                 : "=r"(v.x), "=r"(v.y), "=r"(v.z), "=r"(v.w) : "l"(p) : "memory");
    return v;
}
__device__ __forceinline__ void stg_b128_if(bool c, void* p, uint32_t x, uint32_t y, uint32_t z, uint32_t w) {
    asm volatile("{.reg .pred p; .reg .b128 t; .reg .b64 a, b; setp.ne.u32 p, %5, 0; mov.b64 a, {%1,%2}; mov.b64 b, {%3,%4}; mov.b128 t, {a, b}; @p st.relaxed.gpu.global.b128 [%0], t;}"
                 ::"l"(p), "r"(x), "r"(y), "r"(z), "r"(w), "r"((uint32_t)c) : "memory");
}
__device__ __forceinline__ float pretag(float x, uint32_t add, uint32_t keep) { return __uint_as_float((__float_as_uint(x) + add) & keep); }

template <bool MASK, class F>
__device__ __forceinline__ void softmax_rows(uint32_t src, uint32_t dst, uint32_t g16, int row0, F mid) {
    const uint32_t u = (g16 >> 7) & 3, e = ((g16 >> 9) << 3) | ((g16 >> 4) & 7);
    const uint32_t se = src + e * 8, su = se + u * 1088;
    const float2 p0 = lds2f(su), p1 = lds2f(su + 256), p2 = lds2f(su + 512), p3 = lds2f(su + 768);
    const float2 m0 = lds2f(se + 4352), m1 = lds2f(se + 4352 + 256), m2 = lds2f(se + 4352 + 512), m3 = lds2f(se + 4352 + 768);
    float a0 = (p0.x + p1.x) + (p2.x + p3.x), a1 = (p0.y + p1.y) + (p2.y + p3.y);
    const float a2 = (m0.x + m1.x) + (m2.x + m3.x), a3 = (m0.y + m1.y) + (m2.y + m3.y);
    mid(__float_as_uint(a3));
    if (MASK) {
        const int vis = row0 + (e >> 2) - 2 * (e & 3) - 8 * u;
        if (vis < 0) a0 = -1e9f / 0.08838834764831845f;
        if (vis < 1) a1 = -1e9f / 0.08838834764831845f;
    }
    int k = __float_as_int(fmaxf(fmaxf(a0, a1), fmaxf(a2, a3)));
    k ^= (k >> 31) & 0x7fffffff;
    const bool hi = g16 & 64;
    const int k0 = __reduce_max_sync(~0u, hi ? INT_MIN : k), k1 = __reduce_max_sync(~0u, hi ? k : INT_MIN);
    k = hi ? k1 : k0;
    const float m = __int_as_float(k ^ ((k >> 31) & 0x7fffffff));
    const float sl2 = 0.08838834764831845f * 1.4426950408889634f, mb = -m * sl2;
    sts1(dst + e * 16 + u * 4, pack2(ex2(fmaf(a0, sl2, mb)), ex2(fmaf(a1, sl2, mb))));
    sts1(dst + 512 + e * 4, pack2(ex2(fmaf(a2, sl2, mb)), ex2(fmaf(a3, sl2, mb))));
}

__device__ __forceinline__ uint32_t pack_h2(float lo, float hi) {
    uint32_t r; asm("cvt.rn.satfinite.f16x2.f32 %0, %1, %2;" : "=r"(r) : "f"(hi), "f"(lo)); return r;
}
__device__ __forceinline__ float2 unpack_h2(uint32_t u) {
    float2 r; asm("{.reg .b16 l, h; mov.b32 {l, h}, %2; cvt.f32.f16 %0, l; cvt.f32.f16 %1, h;}" : "=f"(r.x), "=f"(r.y) : "r"(u)); return r;
}
__device__ __forceinline__ uint32_t h2bf(uint32_t u) {
    uint32_t r;
    asm volatile("{.reg .b16 l, h; .reg .f32 a, b; mov.b32 {l, h}, %1; cvt.f32.f16 a, l; cvt.f32.f16 b, h; cvt.rn.bf16x2.f32 %0, b, a;}" : "=r"(r) : "r"(u));
    return r;
}
__device__ __forceinline__ void red_h10(bool c, void* p, void* q, uint32_t x, uint32_t y, uint32_t z, uint32_t w, uint32_t e) {
    asm volatile("{.reg .pred p; setp.ne.u32 p, %7, 0; red.relaxed.gpu.global.add.noftz.v4.f16x2 [%0], {%2,%3,%4,%5};\n"
                 " @p red.relaxed.gpu.global.add.noftz.f16x2 [%1], %6;}" ::"l"(p), "l"(q), "r"(x), "r"(y), "r"(z), "r"(w), "r"(e), "r"((uint32_t)c) : "memory");
}
constexpr float Q_SCALE = 1024.0f;
constexpr float SM_L2E = 0.08838834764831845f * 1.4426950408889634f * Q_SCALE;
template <int V> struct IC { static constexpr int value = V; };
typedef unsigned long long u64;
__device__ __forceinline__ uint32_t lo32(u64 v) { return (uint32_t)v; }
__device__ __forceinline__ uint32_t hi32(u64 v) { return (uint32_t)(v >> 32); }
__device__ __forceinline__ u64 ldg_u64(const void* p) { u64 v; asm volatile("ld.relaxed.gpu.global.b64 %0, [%1];" : "=l"(v) : "l"(p) : "memory"); return v; }
struct RecTime { uint32_t go, x2, v, dx2, h; };
__device__ __forceinline__ void rec_main(uint32_t sb, const CUtensorMap* tWo, uint8_t* arena, int role, int hinfo, int wg, uint32_t zero, const RecTime& tm) {
    const int hA = hinfo & 255;
    const int tid = threadIdx.x, t = tid & 127, lane = tid & 31, wi = t >> 5;
    const uint32_t bars = sb + SM_BAR;
    const int head = role >> 2, qd = role & 3, j = blockIdx.x & 1, kh = role & 1;
    const uint32_t mypar = head >= hA;
    const uint32_t wiu = __reduce_max_sync(~0u, wi);
    const bool warp0 = wiu == 0;
    const uint8_t* hsrc = (const uint8_t*)g_himg + kh * 32768 + j * 16384;
    auto tokbase = [&](int ty) { return ((ty + 1) << 21) + blk(lb_tok(head), mypar ^ ((hinfo >> (8 + ty)) & 1)); };
    const uint32_t tbw = tokbase(wg), tbq = tokbase(0) + (qd >> 1) * 2048 + (qd & 1) * 8;
#define KS(p) (4 * (((p) >> 1) & 7) + ((p) >> 4) + 2 * ((p) & 1))
    uint32_t w[32 - NL][4];
    uint4 wl5;
    if (wg == 2) bar_arrive(NB_WIN, 384);
    const uint32_t po = (1 << 20) + j * 16384 + kh * 2048;
    const uint32_t c16 = kh * 2048 + ((2 * j + (wi >> 1)) * 32 + lane) * 16, xso = blk(lb_x2(head), mypar);
    const uint32_t x2o = xso + wg * 16384 + (wi & 1) * 2048 + (c16 >> 1), tko = tbw + (wi & 1) * 16384 + c16;
    {
        stg_rlx2(arena + x2o, 0, 0);
#pragma unroll
        for (int i = 0; i < 4; i++) stg_rlx4(arena + ((i & 1 ? tko : tbw + (po ^ 2048) + t * 16) + (i >> 1) * 32768), 0, 0, 0, 0);
    }
    const uint32_t frow = ((lane >> 4) * 8 + (lane & 7)) * 128, fx = ((lane >> 3) & 1) ^ (lane & 7);
    {
#pragma unroll 1
        for (int i = 0; i < 4; i++) mbar_wait_w(bars + 8 * (B_W + (wg == 2 ? 8 + i : 2 * i + wg)), 0);
        const uint32_t stg = sb + wg * 65536;
#pragma unroll
        for (int p = NL; p < 32; p++) ldsm4t(w[p - NL], stg + KS(p) * 2048 + frow + ((fx ^ (2 * wi)) << 4));
#pragma unroll
        for (int i = 0; i < NL; i++) {
            wl5 = lds4(stg + KS(i) * 2048 + t * 16);
            if (i < 5) sts4(sb + sm_wl(i) + tid * 16, wl5.x, wl5.y, wl5.z, wl5.w);
        }
        fence_async_smem();
        if (wg < 2) bar_sync(NB_WG, 256);
        if (wg > 0) wait_count_w(&g_tick[32 + (lane & 3) * 8], wg);
        if (wg == 1) {
            mbar_arrive_cluster_if(t == 0, bars + 8 * B_HE, j ^ 1);
            asm volatile("fence.proxy.async.global;" ::: "memory");
            mbar_wait_w(bars + 8 * B_HE, 0);
#pragma unroll 1
            for (int i = 0; i < 2; i++) h_load(sb, hsrc, i, j, head, wiu, true, i ? 0 : 2048);
        }
    }
    uint32_t g16 = opaque(t * 16);
    {
        const uint32_t wr = ((wg * 4 + wi) ^ head) & 7;
        const uint32_t pc = wg < 2 ? acc_piece(wr >> 2, qd, wr & 3) : acc_piece(kh, wi, 0);
        const uint32_t lm = sb + SM_HB + 4096 + (lane & 7) * 128;
        const uint32_t a0 = wg < 2 ? sb + SM_WL + wg * 2048 + frow + ((fx ^ (2 * wi)) << 4) : blk(LB_STAMP + (wi >> 1), mypar) + stamp_line(wi, lane >> 3) + (lane & 7) * 16;
        const uint32_t a1 = pc + lane * 16;
        const uint32_t a2 = wg < 2 ? pc + 512 + (lane >> 3) * 4 : (role >> 2) * 1024 + (lane < 8 ? (role & 3) * 128 : 384) + lane * 16;
        const uint32_t a3 = wg < 2 ? sb + SM_WO + (wr >> 2) * 32768 + frow + ((fx ^ (2 * (wr & 3))) << 4) : qd * 65536 + head * 2048 + wi * 512 + lane * 4;
        const uint32_t a4 = wg < 2 ? lm + ((fx ^ ((lane >> 4) * 4)) << 4) : lm + (fx << 4) + ((lane >> 4) + 2 * wi) * HCH;
        if (wg < 2) bar_arrive(NB_X2, 384);
        else bar_sync(NB_X2, 384);
        if (NL > 5) {
            sts4(sb + SM_WL2 + tid * 16, wl5.x, wl5.y, wl5.z, wl5.w);
            fence_async_smem();
            bar_sync(NB_WG + 1 + wg, 128);
        }
        sts4(sb + SM_TAB + wg * 5120 + g16, a0, x2o,
             wg ? xso + (wg == 2 ? 32768 : 0) + t * 8 : blk(LB_STAMP + ((lane >> 1) & 1), (lane >> 2) & 1) + stamp_line(lane, qd) + head * 4, tko);
        sts4(sb + SM_TAB + wg * 5120 + 2048 + g16, a1, a2, a3, a4);
        sts2(sb + SM_TAB + wg * 5120 + 4096 + t * 8, __uint_as_float(tbw + t * 16), __uint_as_float((wg ? tbq : tokbase(1)) + t * 16));
    }
    const uint32_t ONES = 0x3f803f80u, tabw = sb + SM_TAB + wg * 5120;
#define LAST ((g16 & 0x70) == 0x70)

    auto pa_ptr = [&](int p) { return arena + (((p & 1) ^ 1) * 32768 + po + lds1(tabw + 4096 + (g16 >> 1))); };
    auto pa_request = [&](int p) { cp_async16(sb + SM_PA + wg * 2048 + g16, pa_ptr(p)); };
    auto pa_get = [&](int p) {
        asm volatile("cp.async.wait_all;" ::: "memory");
        uint4 pa = lds4(sb + SM_PA + wg * 2048 + g16);
        int it = 0;
#pragma unroll 1
        while (any_bit0(pa.x ^ ((p - 1) >> 1) ^ 1) && p > 0 && p <= NSEG) { pa = ldg_b128(pa_ptr(p)); spin_guard(++it); }
        return pa;
    };
    auto pass_init = [&](float* acc, int n, uint4 pa) {
#pragma unroll
        for (int i = 0; i < 4; i++) { acc[2 * i] = bflo((&pa.x)[i]); acc[2 * i + 1] = bfhi((&pa.x)[i]); }
#pragma unroll
        for (int i = 8; i < n; i++) acc[i] = 0.f;
    };
    auto pass_run = [&](auto vc, int p, float* acc, auto mid) {
        constexpr bool V = decltype(vc)::value;
#define HB(ks) dadd(mkdesc(SB0 + SM_HB + ((ks) >> 2) * HCH + ((ks) & 3) * 32, 16, 1024, 1), (p & 1) * (HBUF / 16))
        wg_fence();
#pragma unroll
        for (int i = 0; i < 32; i++) {
            constexpr int GAP = V ? SSG_V : SSG, SS0 = V ? SS0_V : SS0_K;
            const int u = i < SS0 ? 0 : (i - SS0 + GAP - 1) / GAP, q = i - (u < NL ? u : NL);
            if (i >= SS0 && (i - SS0) % GAP == 0 && u < NL) wgmma_tok_ss<V>(acc, dadd(mkdesc(SB0 + sm_wl(u), 8192, 1024, 1), (V ? 2 : wg) * 128), HB(KS(u)));
            else wgmma_tok_rs<V>(acc, w[q], HB(KS(NL + q)), 1);
            mid(i);
        }
        wg_commit();
    };
    auto pass_out = [&](auto tc, int p, float* acc, auto mid) {
        constexpr int TY = decltype(tc)::value;
        const bool V = TY == 2 || (TY == 4 && wg == 2), Q = TY >= 3 && wg == 0;
        const int b = p & 1, s = p - 2;
        (void)s;
        const uint32_t ftag = (((p - 1) >> 1) & 1) ^ 1, ptag = ((p >> 1) & 1) ^ 1;
        const bool tg = V || !(g16 & 64);
        const uint32_t add = tg ? (ftag ^ 1) << 16 : 0u, keep = tg ? 0xfffe0000u : ~0u;
        const uint32_t add1 = V ? 0u : add, keep1 = V ? ~0u : keep;
        const uint32_t add2 = Q ? add : 0u, keep2 = Q ? keep : ~0u;
        uint8_t* pdst = arena + (b * 32768 + (po ^ 2048) + lds1(tabw + 4096 + (g16 >> 1)));
        uint8_t* fdst = arena + ((b ^ 1) * 32768 + lds1(tabw + 12 + g16));
        if (PIN_EPI) asm volatile("" : "+l"(pdst), "+l"(fdst));
        mid(0);
        uint32_t r0 = pack2(pretag(acc[0], add, keep), pretag(acc[1], add1, keep1));
        uint32_t r1 = pack2(acc[2], acc[3]), r3 = pack2(acc[6], acc[7]);
        uint32_t r2 = pack2(pretag(acc[4], add2, keep2), pretag(acc[5], add2, keep2));
        if (!V) { r0 = movm(r0); r1 = movm(r1); r2 = movm(r2); r3 = movm(r3); }
        mid(1);
        stg_b128_if(p < NSEG, pdst, settag(pack2(pretag(acc[8], (ptag ^ 1) << 16, 0xfffe0000u), acc[9]), ptag), pack2(acc[10], acc[11]), pack2(acc[12], acc[13]), pack2(acc[14], acc[15]));
        stg_b128_if(p > 0 && p <= NSEG, fdst, settag(r0, ftag), r1, Q ? settag(r2, ftag) : r2, r3);
    };
    auto nop = [](int) {};
    auto wait0 = [](int i) { if (i == 0) wg_wait<0>(); };
    uint4 tf[2][2];
    auto load_tok = [&](int s, uint32_t o) {
        const uint8_t* ts = arena + ((s & 1) * 32768 + o);
#pragma unroll
        for (int a = 0; a < 2; a++)
#pragma unroll
            for (int b = 0; b < 2; b++) tf[a][b] = ldg_b128(ts + a * 16384 + b * 2048);
    };

    auto wo_load = [&](int stage) {
        if (wg == 2 && ((WO_AT >> (4 * wiu)) & 15) == stage) {
            const int c0 = (wiu >> 1) * 512 + qd * 128 + (wiu & 1) * 64;
            e_expect(bars + 8 * B_WO, 16384);
            e_tma2d(sb + SM_WO + wiu * 16384, tWo, c0, head * DH, bars + 8 * B_WO);
            e_tma2d(sb + SM_WO + wiu * 16384 + 8192, tWo, c0, head * DH + 64, bars + 8 * B_WO);
        }
    };
#pragma unroll 1
    for (int p = 0; p <= (wg >> 1); p++) {
        mbar_wait_w(bars + 8 * (B_HB + p), 0);
        float acc[16];
        pass_init(acc, 16, pa_get(p));
        wo_load(p);
        pass_run(IC<0>(), p, acc, nop);
        if (p) {
            mbar_wait_w(bars + 8 * B_HE, 1);
            asm volatile("fence.proxy.async.global;" ::: "memory");
            h_load(sb, hsrc, 2, j, head, wiu);
        }
        pass_out(IC<4>(), p, acc, wait0);
        if (wg < 2) {
            bar_arrive(NB_C, 384);
            if (wg == 0) bar_arrive(NB_WIN, 384);
        } else if (p == 0) {
            bar_sync(NB_C, 384);
            mbar_arrive_cluster_if(g16 == 0, bars + 8 * B_HE, j ^ 1);
        }
        pa_request(p + 1);
    }
    if (wg < 2) {
        mbar_wait_w(bars + 8 * (B_HB + 1), 0);
        uint4 pa = pa_get(1);
        uint32_t wl = lds1(tabw + g16);
#pragma unroll 1
        for (int s = 0; s < NSEG; s++) {
            uint32_t w0[NL][4], xo, lm, fz = 0;
            float acc[16];
#pragma unroll
            for (int i = 0; i < 4; i++)
                asm volatile("shl.b32 %0, %4, 16; and.b32 %1, %4, 0xffff0000; mov.b32 %2, %5; mov.b32 %3, %5;"
                             : "=&f"(acc[2 * i]), "=f"(acc[2 * i + 1]), "=f"(acc[8 + 2 * i]), "=f"(acc[9 + 2 * i]) : "r"((&pa.x)[i]), "r"(zero));
#pragma unroll
            for (int i = 0; i < NL; i++) ldsm4t(w0[i], wl + (sm_wl(i) - SM_WL));
            if (wg == 0) bar_sync(NB_B, 256);
            else bar_sync(NB_WIN, 384);
            pass_run(IC<0>(), s + 1, acc, [&](int i) { if (i == GATE_AT && wg) bar_arrive(NB_B, 256); });
            xo = lds1(tabw + 4 + g16);
            lm = lds1(tabw + 2060 + g16) + (s & 1) * HBUF;
            pass_out(IC<3>(), s + 1, acc, [&](int i) {
                if (i == 0) {
                    wg_wait<0>();
                    if (wg == 0) bar_arrive(NB_MEM, 384);
                    fz |= clk32();
                }
                if (i == 1 && wg) bar_sync(NB_F, 256);
            });
            asm volatile("" : "+r"(lm));
            if (wg == 0) bar_sync(NB_MEM2, 256);
            else bar_sync(NB_MEM, 384);
            float c[4][4];
            uint32_t bq[PD][4];
#define MEMF(it) ((lm ^ (((it) >> 3) * 32)) + ((it) & 7) * HCH)
#pragma unroll
            for (int it = 0; it < PD; it++) ldsm4(bq[it], MEMF(it));
#pragma unroll
            for (int it = 0; it < 16; it++) {
                uint32_t* bfr = bq[it % PD];
                const uint32_t* wa = 2 * it < NL ? w0[2 * it < NL ? 2 * it : 0] : w[2 * it < NL ? 0 : 2 * it - NL];
                const uint32_t* wb = 2 * it + 1 < NL ? w0[2 * it + 1 < NL ? 2 * it + 1 : 0] : w[2 * it + 1 < NL ? 0 : 2 * it + 1 - NL];
                float *ca = c[(2 * it) & 3], *cb = c[(2 * it + 1) & 3];
                if (it < 2) { mma16816z(ca, wa, bfr[0], bfr[1]); mma16816z(cb, wb, bfr[2], bfr[3]); }
                else { mma16816(ca, wa[0], wa[1], wa[2], wa[3], bfr[0], bfr[1]); mma16816(cb, wb[0], wb[1], wb[2], wb[3], bfr[2], bfr[3]); }
                if (it + PD < 16) ldsm4(bfr, MEMF(it + PD));
            }
            const float qs = wg ? 1.0f : 1.0f / Q_SCALE;
#define CSUM(e) fmaf(c[2][e] + c[3][e], qs, (c[0][e] + c[1][e]) * qs)
            const uint32_t r0 = pack2(CSUM(0), CSUM(1)), r1 = pack2(CSUM(2), CSUM(3));
            bar_arrive(NB_QK + (r0 & zero), 384);
            stg_rlx2(arena + xo, settag(movm(r0), (s & 1) ^ 1), movm(r1));
            const uint32_t tx = later(lds1(sb + SM_LX + 1040) + tm.x2, clk_after(r0, zero) + tm.dx2);
            g16 |= (fz | tx) & zero;
            {
                const uint32_t l16 = sb + (g16 & 0x1f0), g8 = g16 >> 1;
                const uint32_t tag = (s & 1) ^ 1, ttag = ((s >> 1) & 1) ^ 1;
                uint32_t wf[NPF][4], a3;
#define WF(f) (a3 + ((f) & 1) * 16384 + ((f) >> 1) * 2048)
                if (wg == 1) {
                    float sc[5][4];
                    uint4 (&kf)[2][2] = tf;
                    uint32_t qa[2][4], km[4], fz;
                    const uint32_t sd = lds1(sb + SM_TAB + 8 + g16);
                    int it = 0;
                    bool bad;
#pragma unroll 1
                    do {
                        u64 qf[2], x[8];
                        const float2 u = lds2f(tabw + 4096 + g8);
                        load_tok(s, __float_as_uint(u.x));
                        const uint8_t *xp = arena + lds1(tabw + 8 + g16), *tq = arena + ((s & 1) * 32768 + __float_as_uint(u.y));
                        asm volatile("" : "+l"(xp));
                        asm volatile("" : "+l"(tq));
#pragma unroll
                        for (int a = 0; a < 2; a++) qf[a] = ldg_u64(tq + a * 16384);
                        spin_guard(++it);
                        wait_clk(tx);
#pragma unroll
                        for (int i = 0; i < 8; i++) x[i] = ldg_u64(xp + (i >> 2) * 16384 + (i & 3) * 1024);
                        fz = clk32();
                        const uint32_t bt = or3(xor_or(lo32(qf[0]), lo32(qf[1]), ttag), xor_or(kf[0][0].x, kf[0][1].x, ttag), xor_or(kf[1][0].x, kf[1][1].x, ttag));
#pragma unroll
                        for (int a = 0; a < 2; a++) { qa[a][1] = or3(lo32(qf[a]), zero, 0); qa[a][3] = or3(hi32(qf[a]), zero, 0); }
                        fz |= clk32();
#pragma unroll
                        for (int a = 0; a < 2; a++) { qa[a][0] = hadd2v(lo32(x[2 * a]), lo32(x[2 * a + 1])); qa[a][2] = hadd2v(hi32(x[2 * a]), hi32(x[2 * a + 1])); }
#pragma unroll
                        for (int a = 0; a < 2; a++) { km[2 * a] = hadd2v(lo32(x[4 + 2 * a]), lo32(x[5 + 2 * a])); km[2 * a + 1] = hadd2v(hi32(x[4 + 2 * a]), hi32(x[5 + 2 * a])); }
                        bad = any_bit0(or3(or3(bt, xor_or(lo32(x[0]), lo32(x[1]), tag), xor_or(lo32(x[2]), lo32(x[3]), tag)), xor_or(lo32(x[4]), lo32(x[5]), tag), xor_or(lo32(x[6]), lo32(x[7]), tag)));
                    } while (bad);
                    mma16816z(sc[0], qa[0], kf[0][0].x, kf[0][0].y);
                    mma16816z(sc[1], qa[0], kf[0][0].z, kf[0][0].w);
                    mma16816z(sc[2], qa[0], kf[0][1].x, kf[0][1].y);
                    mma16816z(sc[3], qa[0], kf[0][1].z, kf[0][1].w);
                    mma16816z(sc[4], qa[0], km[0], km[1]);
                    mma16816(sc[0], qa[1][0], qa[1][1], qa[1][2], qa[1][3], kf[1][0].x, kf[1][0].y);
                    mma16816(sc[1], qa[1][0], qa[1][1], qa[1][2], qa[1][3], kf[1][0].z, kf[1][0].w);
                    mma16816(sc[2], qa[1][0], qa[1][1], qa[1][2], qa[1][3], kf[1][1].x, kf[1][1].y);
                    mma16816(sc[3], qa[1][0], qa[1][1], qa[1][2], qa[1][3], kf[1][1].z, kf[1][1].w);
                    mma16816(sc[4], qa[1][0], qa[1][1], qa[1][2], qa[1][3], km[2], km[3]);
                    const uint32_t sx = sb + SM_SX + (g16 & 0x1f0) * 5;
                    sts4(sx + (g16 >> 5 & 0x30), pack_h2(sc[0][0], sc[0][1]), pack_h2(sc[1][0], sc[1][1]),
                         pack_h2(sc[2][0], sc[2][1]), pack_h2(sc[3][0], sc[3][1]));
                    sts1(sx + 64 + (g16 >> 7 & 0xc), pack_h2(sc[4][0], sc[4][1]));
                    bar_arrive(NB_X1, 256);
                    const uint32_t now = gtime32();
#pragma unroll
                    for (int n = 0; n < 5; n++) sts2(sb + SM_ST + g8 + n * 1088, sc[n][2], sc[n][3]);
                    bar_arrive(NB_H, 256);
                    a3 = lds1(tabw + 2056 + g16) | (fz & zero);
                    asm volatile("{.reg .pred p; setp.lt.u32 p, %2, 128; @p red.relaxed.gpu.global.max.u32 [%0], %1;}"
                                 ::"l"(arena + sd), "r"(__funnelshift_r(now * 8, s + 1, 8)), "r"(g16) : "memory");
                    if (s == 0) mbar_wait_w(bars + 8 * B_WO, 0);
                    a3 += delay<PF_DLY>(zero);
#pragma unroll
                    for (int f = 0; f < NPF; f++) ldsm4t(wf[f], WF(f));
                } else {
                    if (s == 0) { mbar_wait_w(bars + 8 * B_WO, 0); }
                    if (warp0 && !(s & 3)) {
                        const uint32_t need = min((s + 4) / 4 + 2, 17), a = sb + SM_LX + 1024 + ((g16 >> 2) & 12);
                        if (s == 0 || __any_sync(~0u, lds1(a) < need)) sts1(a, wait_count_w(&g_tick[32 + ((g16 >> 4) & 3) * 8], need));
                    }
                    a3 = lds1(tabw + 2056 + g16);
#pragma unroll
                    for (int f = 0; f < NPF0; f++) ldsm4t(wf[f], WF(f));
                    const float2 u = lds2f(tabw + 4096 + g8);
                    const uint8_t *q0 = arena + (tag * 32768 + po + __float_as_uint(u.x)), *q1 = arena + (tag * 32768 + po + __float_as_uint(u.y));
                    wait_clk(tx + tm.h);
                    int it = 0;
                    bool bad;
#pragma unroll 1
                    do {
                        const uint4 p0 = ldg_b128(q0), p1 = ldg_b128(q1);
                        spin_guard(++it);
                        wait_clk(tx + tm.v);
#pragma unroll
                        for (int f = NPF0; f < NPF1; f++) ldsm4t(wf[f], WF(f));
                        sts4(sb + SM_PA + g16, p0.x, p0.y, p0.z, p0.w);
                        sts4(sb + SM_PA + 2048 + g16, p1.x, p1.y, p1.z, p1.w);
                        bad = any_bit0(xor_or(p0.x, p1.x, ((s + 1) >> 1) ^ 1)) && s + 2 <= NSEG;
                    } while (bad);
                    bar_sync(NB_H, 256);
                    softmax_rows<true>(sb + SM_ST, sb + SM_PX, g16, qd * 8, [&](uint32_t v) {
                        a3 += v & zero;
#pragma unroll
                        for (int f = NPF1; f < NPF2; f++) ldsm4t(wf[f], WF(f));
                    });
#pragma unroll
                    for (int f = NPF2; f < NPF; f++) ldsm4t(wf[f], WF(f));
                }
                float2 ls, a12;
                uint8_t *d0, *d1;
                bar_sync(NB_X2, 384);
                float c[4][4];
#pragma unroll
                for (int q = 0; q < 4; q++) {
                    uint32_t ob[4];
                    ldsm4t(ob, l16 + SM_OX + q * 512);
                    if (q == L_AT) ls = lds2f(sb + SM_LX + g8);
                    if (q == 2) { pa = lds4(sb + SM_PA + wg * 2048 + g16); wl = lds1(tabw + g16); }
                    if (q == 2) { a12 = lds2f(tabw + 2048 + g16); d0 = arena + (acc_slot(s + 1) + __float_as_uint(a12.x)); d1 = arena + (acc_slot(s + 1) + __float_as_uint(a12.y)); }
#pragma unroll
                    for (int f = 4 * q; f < 4 * q + 4; f++) {
                        const uint32_t* a = wf[f % NPF];
                        if (f < 4) mma16816z(c[f], a, ob[f & 2], ob[(f & 2) + 1]);
                        else mma16816(c[f & 3], a[0], a[1], a[2], a[3], ob[f & 2], ob[(f & 2) + 1]);
                        if (f + NPF < 16) ldsm4t(wf[f % NPF], WF(f + NPF));
                    }
                }
                if (wg == 0) bar_arrive(NB_WIN, 384);
                const float i0 = rcp_fast(ls.x), i1 = rcp_fast(ls.y);
                uint32_t v[4];
#pragma unroll
                for (int m = 0; m < 4; m++) v[m] = pack_h2((c[m >> 1][(m & 1) * 2] + c[(m >> 1) + 2][(m & 1) * 2]) * i0, (c[m >> 1][(m & 1) * 2 + 1] + c[(m >> 1) + 2][(m & 1) * 2 + 1]) * i1);
                red_h10(LAST, d0, d1, v[0], v[1], v[2], prmt(v[3], ACC_ONE, LAST ? 0x7610 : 0x3210), prmt(v[3], ACC_ONE, 0x7632));
                g16 |= v[0] & zero;
            }
        }
        if (wg) bar_sync(NB_WIN, 384);
    } else {
        auto request = [&](int s, uint32_t o) {
            cp_async16(sb + SM_PA + 4096 + g16, arena + (((s & 1) ^ 1) * 32768 + po + o));
            const uint8_t* ts = arena + ((s & 1) * 32768 + o);
#pragma unroll
            for (int i = 0; i < 4; i++) cp_async16(sb + SM_VF + i * 2048 + g16, ts + (i >> 1) * 16384 + (i & 1) * 2048);
        };
        auto fetch = [&](int s, uint4 t1, auto wait, auto after) {
            const uint32_t mo = acc_slot(s) + t1.x, eo = mo - (g16 & 0x1f0) + 512 + ((g16 >> 5) & 12);
            const uint8_t *ms = arena + mo, *es = arena + eo;
            uint32_t e[4] = {0, 0, 0, 0}, sel = LAST ? 0x5410 : 0x3210, dst[4];
#pragma unroll
            for (int i = 0; i < 4; i++) dst[i] = (t1.w + (s & 1) * HBUF) ^ (i * 32);
            asm volatile("" : "+l"(ms), "+l"(es), "+r"(e[0]), "+r"(e[1]), "+r"(e[2]), "+r"(e[3]), "+r"(sel), "+r"(dst[0]), "+r"(dst[1]), "+r"(dst[2]), "+r"(dst[3]));
            uint32_t late = wait(), fz;
            int it = 0;
            bool bad;
#pragma unroll 1
            do {
                uint4 m[4];
                uint32_t b = 0;
#pragma unroll
                for (int i = 0; i < 4; i++) {
                    m[i] = ldg_rlx4(ms + i * 1024);
                    ldg1_if(e[i], es + i * 1024, LAST);
                }
                if (it == 0) bar_arrive(NB_F, 256);
                const uint32_t now = clk32();
                fz = now;
                after(now & zero);
                sts1(sb + SM_LX + 1040, now - min(late >> 8, 8u) * 57);
                late = 0;
                spin_guard(++it);
#pragma unroll
                for (int i = 0; i < 4; i++) {
                    if (STG_FENCE >> i & 1) fz |= clk32();
                    b |= xor_or(m[i].w, e[i], ACC_ALL);
                    stsm4t(dst[i], h2bf(m[i].x), h2bf(m[i].y), h2bf(m[i].z), h2bf(prmt(m[i].w, e[i], sel)));
                }
                bad = __any_sync(~0u, LAST && b > 0xffffu);
            } while (bad);
            bar_arrive(NB_MEM, 384);
            bar_arrive(NB_MEM2, 256);
            g16 |= fz & zero;
        };
        fetch(0, lds4(tabw + 2048 + g16), []() { return 0u; }, [&](uint32_t z) { request(0, lds1(tabw + 4096 + (g16 >> 1)) + z); });
        wo_load(2);
#pragma unroll 1
        for (int s = 0;; s++) {
            const uint32_t tag = (s & 1) ^ 1, ttag = ((s >> 1) & 1) ^ 1, l16 = sb + (g16 & 0x1f0), g8 = g16 >> 1;
            const int p = s + 2;
            fence_async_smem();
            stg_b128_if(g16 < ((role & 3) ? 128 : 160), arena + (acc_slot(s + 3) + lds1(tabw + 2052 + g16)), 0, 0, 0, 0);
            const uint4 pa = pa_get(p);
            if (p <= NSEG) mbar_wait_w(bars + 8 * (B_HB + (p & 1)), (p >> 1) & 1);
            asm volatile("fence.proxy.async.global;" ::: "memory");
            if (warp0 && s + 3 <= NSEG) e_expect(bars + 8 * (B_HB + ((s + 3) & 1)), 32768);
            uint8_t* xd = arena + lds1(tabw + 4 + g16);
            uint32_t tx;
            float acc[20];
            pass_init(acc, 20, pa);
            bar_sync(NB_QK, 384);
            pass_run(IC<1>(), p, acc, nop);
            pass_out(IC<2>(), p, acc, [&](int i) {
                if (i) return;
                wg_wait<0>();
                const uint32_t r0 = pack2(acc[16], acc[17]);
                stg_rlx2(xd, settag(r0, tag), pack2(acc[18], acc[19]));
                tx = clk_after(r0, zero) + 100;
            });
            uint4 (&vf)[2][2] = tf;
#pragma unroll
            for (int i = 0; i < 4; i++) vf[i >> 1][i & 1] = lds4(sb + SM_VF + i * 2048 + g16);
            uint32_t xv[4] = {0, 0, 0, 0};
            float oc[2][4], lc[4];
            auto pv = [&](uint32_t p0, uint32_t p1, uint32_t p2, uint32_t p3, uint32_t p4, auto mid) {
                lc[0] = lc[1] = lc[2] = lc[3] = 0.f;
                mma16816z(oc[0], &vf[0][0].x, p0, p1);
                mma16816z(oc[1], &vf[1][0].x, p0, p1);
                mma16816(lc, ONES, ONES, ONES, ONES, p0, p1);
                mma16816(oc[0], vf[0][1].x, vf[0][1].y, vf[0][1].z, vf[0][1].w, p2, p3);
                mma16816(oc[1], vf[1][1].x, vf[1][1].y, vf[1][1].z, vf[1][1].w, p2, p3);
                mma16816(lc, ONES, ONES, ONES, ONES, p2, p3);
                mid();
                mma1688(oc[0], xv[0], xv[1], p4);
                mma1688(oc[1], xv[2], xv[3], p4);
                mma1688(lc, ONES, ONES, p4);
            };
            uint32_t so, to, fz = 0;
            uint4 t1;
            int it = 0;
            bool bad;
#pragma unroll 1
            do {
#pragma unroll 1
                for (int i = it; i > 0; i &= zero) load_tok(s, lds1(tabw + 4096 + g8));
                u64 xr[4];
                const uint8_t* xp = arena + lds1(tabw + 8 + g16);
                asm volatile("" : "+l"(xp));
                const uint32_t bt = or3(xor_or(vf[0][0].x, vf[0][1].x, ttag), xor_or(vf[1][0].x, vf[1][1].x, ttag), 0);
                uint32_t sa = sb + SM_SX + (g16 & 0x1f0) * 5;
                asm volatile("" : "+r"(sa));
                spin_guard(it);
                wait_clk(tx);
                if (it++ == 0) bar_sync(NB_X1, 256);
                uint4 sx[5];
#pragma unroll
                for (int i = 0; i < 5; i++) sx[i] = lds4(sa + i * 16);
                __syncwarp();
#pragma unroll
                for (int i = 0; i < 4; i++) xr[i] = ldg_u64(xp + (VP_AT == 2 ? sx[0].x & zero : 0) + i * 1024);
                uint32_t a[5], pm[5];
#pragma unroll
                for (int n = 0; n < 5; n++) {
                    uint32_t u[4];
#pragma unroll
                    for (int w = 0; w < 4; w++) u[w] = n < 4 ? (&sx[w].x)[n] : (&sx[4].x)[w];
                    a[n] = hadd2h(hadd2h(u[0], u[1]), hadd2h(u[2], u[3]));
                }
                uint32_t m = hmax2h(hmax2h(hmax2h(a[0], a[1]), hmax2h(a[2], a[3])), a[4]);
                const uint32_t m1 = __shfl_xor_sync(~0u, m, 1), m2 = __shfl_xor_sync(~0u, m, 2), m3 = __shfl_xor_sync(~0u, m, 3);
                m = hmax2h(hmax2h(m, m1), hmax2h(m2, m3));
                so = lds1(tabw + g16); t1 = lds4(tabw + 2048 + g16); to = lds1(tabw + 4096 + g8);
                const float2 mm = unpack_h2(m);
                const float mf = -SM_L2E * fmaxf(mm.x, mm.y);
#pragma unroll
                for (int n = 0; n < 5; n++) { const float2 u = unpack_h2(a[n]); pm[n] = pack2(ex2(fmaf(u.x, SM_L2E, mf)), ex2(fmaf(u.y, SM_L2E, mf))); }
                pv(pm[0], pm[1], pm[2], pm[3], pm[4], [&]() {
                    if (PV_FENCE & 1) fz = clk32();
#pragma unroll
                    for (int i = 0; i < 2; i++) { xv[2 * i] = hadd2v(lo32(xr[2 * i]), lo32(xr[2 * i + 1])); xv[2 * i + 1] = hadd2v(hi32(xr[2 * i]), hi32(xr[2 * i + 1])); }
                });
                bad = any_bit0(or3(bt, xor_or(lo32(xr[0]), lo32(xr[1]), tag), xor_or(lo32(xr[2]), lo32(xr[3]), tag)));
                if (PV_FENCE & 2) fz |= clk32();
                stsm4(sb + SM_OX + g16, pack2(oc[0][0], oc[0][1]), pack2(oc[0][2], oc[0][3]), pack2(oc[1][0], oc[1][1]), pack2(oc[1][2], oc[1][3]));
                sts2(sb + SM_LX + g8, lc[0], lc[1]);
            } while (bad);
            bar_sync(NB_X2, 384);
            const uint8_t* sp = arena + so;
            uint4 sv = ldg_rlx4(sp);
            if (s + 3 <= NSEG) h_load(sb, hsrc, s + 3, j, head, wiu, false);
            const uint4 pp = lds4(l16 + SM_PX + delay<TPV_DLY>(zero));
            pv(pp.x, pp.y, pp.z, pp.w, lds1(sb + SM_PX + 512 + ((g16 >> 2) & 0x7c)), []() {});
            const float i0 = rcp_fast(lc[0]), i1 = rcp_fast(lc[1]);
            bar_arrive(NB_WIN + ((__float_as_uint(i0) | fz) & zero), 384);
            uint8_t* od = (uint8_t*)g_O + ((size_t)s * (32 * NH * DH * 2) + t1.z);
            const uint32_t ov[4] = {pack2(oc[0][0] * i0, oc[0][1] * i1), pack2(oc[0][2] * i0, oc[0][3] * i1), pack2(oc[1][0] * i0, oc[1][1] * i1), pack2(oc[1][2] * i0, oc[1][3] * i1)};
#pragma unroll
            for (int a = 0; a < 4; a++) if (s + 1 == NSEG) stg_rlx1(od + a * 128, ov[a]);
            if (s + 1 == NSEG) break;
            fetch(s + 1, t1, [&]() {
                int it = 0;
#pragma unroll 1
                while (__any_sync(~0u, (int)(min(__vimin3_u32(sv.x, sv.y, sv.z), sv.w) >> 24) <= s)) {
                    sv = ldg_rlx4(sp);
                    spin_guard(++it);
                }
                const uint32_t tgo = (__reduce_max_sync(~0u, max(max3u(sv.x, sv.y, sv.z), sv.w)) + tm.go + (sv.x & zero)) << 8;
                int late;
#pragma unroll 1
                do { late = gtime32() * 8 - tgo; } while (late < 0);
                __syncwarp();
                return (uint32_t)late;
            }, [&](uint32_t z) {
#pragma unroll
                for (int a = 0; a < 4; a++) stg_rlx1(od + a * 128, ov[a]);
                request(s + 1, to + z);
            });
        }
    }
    asm volatile("cp.async.wait_all;" ::: "memory");
}

struct RecMaps { CUtensorMap wq, wk, wv, wo; };
struct RecPtrs { const bf16 *x, *mem0, *c, *wmod, *w1, *w3; uint8_t* arena; uint32_t zero; RecTime tm; };

__device__ __forceinline__ float silu_bf(const bf16* c, int i) {
    const float v = __bfloat162float(c[i]);
    return bfround(__fdividef(v, 1.0f + __expf(-v)));
}
__device__ __noinline__ void rec_ln(float* coef, const RecPtrs& p, int id, int r0) {
    int r1 = 32;
    const int tid = threadIdx.x;
    const int lane = tid & 31, wid = tid >> 5;
    const uint32_t ring = smem_u32(coef) - SM_PRE + wid * 8192 + lane * 16;
    auto fetch = [&](int r) {
        if (r < r1) {
            const bf16* src = p.x + (size_t)(r * 64 + (id * 8 + wid) * 2) * DM + lane * 8;
#pragma unroll
            for (int i = 0; i < 8; i++) cp_async16(ring + (r & 1) * 4096 + i * 512, src + i * 256);
        }
        asm volatile("cp.async.commit_group;" ::: "memory");
    };
    auto row8 = [&](uint32_t a, float* f) {
        const uint4 v = lds4(a);
        f[0] = bflo(v.x); f[1] = bfhi(v.x); f[2] = bflo(v.y); f[3] = bfhi(v.y); f[4] = bflo(v.z); f[5] = bfhi(v.z); f[6] = bflo(v.w); f[7] = bfhi(v.w);
    };
#pragma unroll 1
    for (int r = r0 - 2; r < r1; r++) {
        if (r >= r0) {
            asm volatile("cp.async.wait_group 1;" ::: "memory");
            const uint32_t a = ring + (r & 1) * 4096;
            float m[2] = {0.f, 0.f}, t[2];
#pragma unroll 1
            for (int ps = 0; ps < 2; ps++) {
                t[0] = t[1] = 0.f;
#pragma unroll 1
                for (int i = 0; i < 4; i++)
#pragma unroll
                    for (int h = 0; h < 2; h++) {
                        float f[8];
                        row8(a + h * 2048 + i * 512, f);
#pragma unroll
                        for (int e = 0; e < 8; e++) { const float d = f[e] - m[h]; t[h] = fmaf(d, ps ? d : 1.0f, t[h]); }
                    }
#pragma unroll
                for (int o = 16; o; o >>= 1) { t[0] += __shfl_xor_sync(~0u, t[0], o); t[1] += __shfl_xor_sync(~0u, t[1], o); }
                if (ps == 0) { m[0] = t[0] * (1.0f / DM); m[1] = t[1] * (1.0f / DM); }
            }
            t[0] = rsqrtf(t[0] * (1.0f / DM) + 1e-5f); t[1] = rsqrtf(t[1] * (1.0f / DM) + 1e-5f);
            if (r == r0) {
#pragma unroll 1
                for (int i = tid; i < 2 * DM / 4; i += 256) {
                    float4 u;
                    int it = 0;
                    uint32_t ok;
#pragma unroll 1
                    do {
                        uint4 v[8];
#pragma unroll
                        for (int k = 0; k < 8; k++) v[k] = ldg_rlx4(g_modp + k * 2 * DM + i * 4);
                        ok = 1;
                        u = make_float4(0.f, 0.f, 0.f, 0.f);
#pragma unroll
                        for (int k = 0; k < 8; k++) {
                            ok &= v[k].x & v[k].y & v[k].z & v[k].w;
                            u.x += __uint_as_float(v[k].x); u.y += __uint_as_float(v[k].y); u.z += __uint_as_float(v[k].z); u.w += __uint_as_float(v[k].w);
                        }
                        spin_guard(++it);
                    } while (!ok);
                    const uint32_t lo = pack2(u.x, u.y), hi = pack2(u.z, u.w);
                    const float one = i >= DM / 4 ? 1.0f : 0.0f;
                    *(float4*)(coef + i * 4) = make_float4(bflo(lo) + one, bfhi(lo) + one, bflo(hi) + one, bfhi(hi) + one);
                }
                bar_sync(NB_FIN0, 256);
            }
            const int row = r * 64 + (id * 8 + wid) * 2;
#pragma unroll 1
            for (int i = 0; i < 4; i++) {
                const float4* cf = (const float4*)(coef + i * 256 + lane * 8);
                const float4 s0 = cf[0], s1 = cf[1], c0 = cf[256], c1 = cf[257];
                const float sh[8] = {s0.x, s0.y, s0.z, s0.w, s1.x, s1.y, s1.z, s1.w}, sc[8] = {c0.x, c0.y, c0.z, c0.w, c1.x, c1.y, c1.z, c1.w};
                const int own = ((row >> 4) & 1) == (i >> 1), rr = row & 15;
                const uint32_t off = ((row >> 5) + own) * 65536 + (i * 4 + (lane >> 3)) * 4096 + (rr + (own ? 0 : 16)) * 128 + (((lane & 7) ^ (rr & 7)) << 4);
#pragma unroll
                for (int h = 0; h < 2; h++) {
                    float y[8];
                    row8(a + h * 2048 + i * 512, y);
#pragma unroll
                    for (int e = 0; e < 8; e++) y[e] = fmaf((y[e] - m[h]) * t[h], sc[e], sh[e]);
                    *(uint4*)((uint8_t*)g_himg + (off ^ (h * 144))) = pack8(y);
                }
            }
            if (r == 0) {
                int v, it = 0;
#pragma unroll 1
                do { v = *(volatile int*)((uint8_t*)coef - SM_PRE + SM_BAR + 192); spin_guard(++it); } while (v == INT_MIN);
                if (v >= 0) r1 = 2;
            }
        }
        fetch(r + 2);
        if (r < r0 || (r > 0 && !(r & 1))) continue;
        bar_sync(r == 0 ? NB_C : r == 1 ? NB_FIN0 : NB_LN, r == 0 ? 320 : r == 1 ? 256 : 288);
        if (r < 2 && wid == r) {
            if (r == 1) bar_arrive(NB_B, 64);
            if (lane == 0) { signal_count(&g_tick[32 + id * 8]); }
            __syncwarp();
        }
    }
}
template <int NQ, int CG>
__device__ __forceinline__ void side_gemv(const bf16* w, int ld, int ncol, const float* coef, float* red, float* out, int ostride, bool round) {
    constexpr int KG = 384 / CG, W = CG * 8;
    const int tid = threadIdx.x, cg = tid % CG, kg = tid / CG;
    float acc[NQ][8];
#pragma unroll
    for (int q = 0; q < NQ; q++)
#pragma unroll
        for (int j = 0; j < 8; j++) acc[q][j] = 0.f;
    if (cg * 8 < ncol) {
        const bf16* src = w + cg * 8;
        const uint32_t ring = smem_u32(red) + 36864 + tid * 16;
        auto fetch = [&](int k0, int slot) {
#pragma unroll
            for (int i = 0; i < 4; i++)
                if (k0 + i * KG < DM) cp_async16_ef(ring + (slot * 4 + i) * 6144, src + (size_t)(k0 + i * KG) * ld);
            asm volatile("cp.async.commit_group;" ::: "memory");
        };
#pragma unroll 1
        for (int g = 0; g < 5; g++) fetch(kg + g * 4 * KG, g);
#pragma unroll 1
        for (int k0 = kg, slot = 0; k0 < DM; k0 += 4 * KG) {
            fetch(k0 + 20 * KG, slot ? slot - 1 : 5);
            asm volatile("cp.async.wait_group 5;" ::: "memory");
#pragma unroll
            for (int i = 0; i < 4; i++) {
                const int k = k0 + i * KG;
                if (k < DM) {
                    const uint4 v = lds4(ring + (slot * 4 + i) * 6144);
                    const float f[8] = {bflo(v.x), bfhi(v.x), bflo(v.y), bfhi(v.y), bflo(v.z), bfhi(v.z), bflo(v.w), bfhi(v.w)};
#pragma unroll
                    for (int q = 0; q < NQ; q++) {
                        const float cf = coef[q * DM + k];
#pragma unroll
                        for (int j = 0; j < 8; j++) acc[q][j] = fmaf(cf, f[j], acc[q][j]);
                    }
                }
            }
            slot = slot == 5 ? 0 : slot + 1;
        }
    }
    __syncthreads();
#pragma unroll
    for (int q = 0; q < NQ; q++)
#pragma unroll
        for (int j = 0; j < 8; j++) red[(kg * NQ + q) * W + cg * 8 + j] = acc[q][j];
    __syncthreads();
#pragma unroll 1
    for (int i = tid; i < NQ * W; i += 384) {
        const int q = i / W, cidx = i % W;
        float t = 0.f;
#pragma unroll
        for (int k = 0; k < KG; k++) t += red[k * NQ * W + i];
        if (cidx < ncol) out[q * ostride + cidx] = round ? bfround(t) : t;
    }
}
__device__ __noinline__ void rec_side(float* sm, const RecPtrs& p, int id) {
    const int tid = threadIdx.x;
    float *coef = sm, *red = sm + 3 * DM;
    if (tid < 256 && blockIdx.x < 128) rec_ln(sm + SM_PRE / 4, p, id, 2);
    if (tid >> 5 == 8) {
#pragma unroll 1
        for (int n = 1; n < 16; n++) {
            bar_sync(NB_LN, 288);
            if (tid == 256) { if (n == 1) wait_count1(&g_tick[32 + id * 8], 2); signal_count(&g_tick[32 + id * 8]); }
            __syncwarp();
        }
    }
    __syncthreads();
    for (int i = tid; i < 2 * S_; i += 384) g_st[id * 2 * S_ + i] = 0.f;
    if (id == 0) for (int i = tid; i < 2 * 32; i += 384) g_pcnt[i * 8] = 0;
    if (id == 1) for (int i = tid; i < 6 * 256; i += 384) g_pflag[i] = 0;
    for (int i = tid; i < DM; i += 384) { coef[i] = silu_bf(p.c, i); coef[2 * DM + i] = 1.0f; }
    __syncthreads();
    side_gemv<1, 128>(p.wmod + (2 + id) * DM, 6 * DM, DM, coef, red, g_mod + (2 + id) * DM, 0, true);
    __syncthreads();
    if (tid == 0) signal_count(&g_tick[8]);
    side_gemv<1, 128>(p.w3 + id * (FF / 4), FF, FF / 4, coef + 2 * DM, red, g_vec + 3 * DM + id * (FF / 4), 0, false);
    if (tid == 0) wait_count1(&g_tick[8], 4);
    __syncthreads();
    for (int i = tid; i < DM; i += 384) { coef[i] = 1.0f + __ldcg(g_mod + 4 * DM + i); coef[DM + i] = __ldcg(g_mod + 3 * DM + i); }
    __syncthreads();
    if (id == 1 && tid < 32) {
        float t[5] = {0, 0, 0, 0, 0};
        for (int i = tid; i < DM; i += 32) {
            const float a = coef[i], b = coef[DM + i];
            t[0] += a; t[1] += a * a; t[2] += a * b; t[3] += b; t[4] += b * b;
        }
#pragma unroll
        for (int q = 0; q < 5; q++) { const float r = warp_sum(t[q]); if (tid == 0) g_cst[q] = r * (1.0f / DM); }
    }
    side_gemv<3, 32>(p.w1 + id * 256, DM, 256, coef, red, g_vec + id * 256, DM, false);
}

__device__ __forceinline__ void pair_place(int c, int& d, int& pi) {
    const int c7 = ((c - 36) * 37) >> 8;
    d = c < 4 ? 0 : c < 36 ? (c - 4) & 7 : c - 35 - 7 * c7;
    pi = c < 4 ? c : c < 36 ? ((c - 4) >> 3) + (d ? 0 : 4) : 4 + c7;
}
__global__ void __cluster_dims__(2, 1, 1) __launch_bounds__(384, 1)
k_rec(const __grid_constant__ RecMaps mp, const __grid_constant__ RecPtrs p) {
    extern __shared__ uint8_t smraw[];
    const uint32_t sb = smem_u32(smraw);
    if ((sb & 0x3FFFF) != SB0) __trap();
    const uint32_t bars = sb + SM_BAR;
    const int tid = threadIdx.x, lane = tid & 31, b = blockIdx.x;
    const int wid = __reduce_max_sync(~0u, tid >> 5);
    const uint32_t rank = b & 1;
    uint8_t* arena = p.arena;
    volatile int* sinfo = (volatile int*)(smraw + SM_BAR + 192);
    if (tid == 0) sinfo[0] = INT_MIN;
    uint32_t smid;
    asm("mov.u32 %0, %%smid;" : "=r"(smid));
    smid = __reduce_max_sync(~0u, smid);
    int d, pi;
    pair_place(smid >= 124 ? (smid >> 1) - 62 : (smid >> 1) + 4, d, pi);
    const int guess = b < 128 && smid < 132 && (smid & ~3u) != 120 && (NO_GUESS == 0 || (NO_GUESS == 2 && b != 20)) ? d * 8 + pi : -9;
    if (wid == 8) {
        if (lane == 0) {
#pragma unroll
            for (int i = 0; i < 17; i++) mbar_init(bars + 8 * i, i == B_WO ? 4 : 1);
            asm volatile("fence.mbarrier_init.release.cluster; fence.proxy.async.shared::cta;" ::: "memory");
            mbar_expect(bars + 8 * B_ROLE, 8);
        }
        __syncwarp();
    }
    asm volatile("barrier.cluster.arrive.relaxed.aligned;" ::: "memory");
    int pr = 0, hA = 0;
    if (wid < 8) {
        if (b < 128) {
            const int cb = (b & 15) * 128, k0 = (b >> 4) * 128 + (tid >> 4);
            uint4 v[8];
#pragma unroll
            for (int i = 0; i < 8; i++) v[i] = __ldg((const uint4*)(p.wmod + (size_t)(k0 + 16 * i) * (6 * DM) + cb + (tid & 15) * 8));
            float acc[8] = {0, 0, 0, 0, 0, 0, 0, 0};
            const float sl = silu_bf(p.c, k0 + 16 * (lane & 7));
#pragma unroll
            for (int i = 0; i < 8; i++) {
                const float sv = __shfl_sync(~0u, sl, i, 16);
                acc[0] += sv * bflo(v[i].x); acc[1] += sv * bfhi(v[i].x); acc[2] += sv * bflo(v[i].y); acc[3] += sv * bfhi(v[i].y);
                acc[4] += sv * bflo(v[i].z); acc[5] += sv * bfhi(v[i].z); acc[6] += sv * bflo(v[i].w); acc[7] += sv * bfhi(v[i].w);
            }
            float* red = (float*)(smraw + SM_PRE);
            *(float4*)(red + (tid >> 4) * 128 + (tid & 15) * 8) = make_float4(acc[0], acc[1], acc[2], acc[3]);
            *(float4*)(red + (tid >> 4) * 128 + (tid & 15) * 8 + 4) = make_float4(acc[4], acc[5], acc[6], acc[7]);
            bar_sync(NB_FIN0, 256);
            if (wid < 4) {
                float t = 0;
#pragma unroll
                for (int i = 0; i < 16; i++) t += red[i * 128 + tid];
                stg_rlx1(&g_modp[(b >> 4) * 2 * DM + cb + tid], __float_as_uint(t) | 1u);
            }
        } else {
            rec_ln((float*)(smraw + SM_PRE), p, b - 128, 0);
        }
    } else if (wid >= 10 && b >= 128) {
        {
            const int u = (b - 128) * 2 + wid - 10;
            const uint16_t* src = (const uint16_t*)p.mem0 + (lane & 3) * 2 * DM + (u >> 1) * 128 + (u & 1) * 32 + (lane >> 2);
            stg_rlx4(arena + (LB_STAMP << 13) + u * 2048 + (lane >> 4) * 1024 + ((lane >> 3) & 1) * 256 + (lane & 7) * 16, 0, 0, 0, 0);
#pragma unroll 1
            for (int r = 0; r < 4; r++) {
                uint32_t w[5];
#pragma unroll
                for (int e = 0; e < 4; e++) {
                    const uint16_t* q = src + (r >> 1) * 512 + (r & 1) * 16 + (e & 2) * 32 + (e & 1) * 8;
                    w[e] = pack_h2(bflo(q[0]), bflo(q[DM]));
                }
                w[4] = __shfl_sync(~0u, __byte_perm(w[3], ACC_ALL, 0x7632), lane * 8 + 7);
                w[3] = __byte_perm(w[3], ACC_ALL, (lane & 7) == 7 ? 0x7610 : 0x3210);
#pragma unroll 1
                for (int i = 0; i < 3; i++) {
                    uint8_t* d = arena + acc_slot(i) + acc_piece(r >> 1, u >> 1, (u & 1) * 2 + (r & 1));
                    stg_rlx4(d + lane * 16, w[0], w[1], w[2], w[3]);
                    if (lane < 8) stg_rlx1(d + 512 + lane * 4, w[4]);
                    w[0] = w[1] = w[2] = w[3] = w[4] = 0;
                }
            }
            bar_arrive(NB_C, 320);
        }
    } else if (rank == 0 && (wid > 8 || b >= 128)) {
        uint32_t best = ~0u;
        const int pg = wid < 11 ? 0 : 1 + (b >> 1) % 3;
        uint32_t* q = (uint32_t*)(arena + (pg << 21) + (pg ? blk(b >> 1, 1) : blk(LB_PROBE, wid & 1) + b * 16));
        if (lane < 8) stg_rlx1(q + lane, 0);
        u64 tk2 = ldg_u64(&g_tick[0]);
        __syncwarp();
        if (lane == 0) {
            q += 3;
            uint32_t v = atomicAdd(q, 1u);
#pragma unroll 1
            for (int r = 0; r < NPROBE; r++) {
                const uint32_t t0 = clk32() + (v >> 8);
                v = atomicAdd(q + (v >> 8), 1u);
                uint32_t t1;
                asm volatile("{.reg .pred p; setp.eq.u32 p, %1, 0xffffffff; @p exit; mov.u32 %0, %%clock;}" : "=r"(t1) : "r"(v) : "memory");
                best = min(best, t1 - t0);
            }
            sinfo[pg ? 4 : 2 + (wid & 1)] = best;
        }
        bar_sync(NB_KDONE, b < 128 ? 96 : 64);
        if (wid == 9) {
            const int par = sinfo[2] > sinfo[3], ncl = gridDim.x >> 1;
            u64 add = (1u << (8 * par)) + 65536;
            if (b < 128) add += ((u64)((2 * sinfo[4] < sinfo[2] + sinfo[3]) != par) << (32 + 8 * ((b >> 1) % 3))) + (guess < 0 || (smid & 1) ? 1 << 24 : 0);
            int tk = 0, it = 0;
            if (NO_GUESS >= 3 ? b < 2 * (NO_GUESS - 2) || (NO_GUESS == 3 && b == 130) : b >= 128) {
#pragma unroll 1
                while (!__all_sync(~0u, (int)((lo32(tk2) >> 16) & 255) >= ncl - 2)) { tk2 = ldg_u64(&g_tick[0]); spin_guard(++it); }
            }
            if (lane == 0) {
                if (guess >= 0) add += atomicXor(&g_tick[2], par << (guess >> 1)) & p.zero;
                tk = (atomicAdd((u64*)&g_tick[0], add) >> (8 * par)) & 255;
            }
#pragma unroll 1
            while (!__all_sync(~0u, (int)((lo32(tk2) >> 16) & 255) >= ncl)) { tk2 = ldg_u64(&g_tick[0]); spin_guard(++it); }
            tk = __shfl_sync(~0u, tk, 0);
            const int n0 = tk2 & 255, n1 = (tk2 >> 8) & 255;
            hA = min(n0 >> 1, NH);
            const int q0 = 2 * hA, q1 = 2 * NH - q0;
            const int over = tk - (par ? q1 : q0), lack = max(par ? q0 - n0 : q1 - n1, 0);
            if (over < 0) pr = par ? q0 + tk : tk;
            else if (over < lack) pr = (par ? n0 : q0 + n1) + over;
            else pr = -1 - (over - lack + (par ? max(n0 - q0, 0) : 0));
            if (!(lo32(tk2) >> 24) && !ldg_rlx1(&g_tick[2])) { pr = guess; hA = par ? 0 : NH; }
#pragma unroll
            for (int i = 0; i < 3; i++) hA |= ((hi32(tk2) >> (8 * i)) & 255) > 10 ? 256 << i : 0;
        }
    }
    asm volatile("barrier.cluster.wait.aligned;" ::: "memory");
    if (wid == 9 && rank == 0) {
        asm volatile("{.reg .pred p; .reg .b32 a; setp.lt.u32 p, %3, 2; @p mapa.shared::cluster.u32 a, %0, %3;\n"
                     " @p st.async.shared::cluster.mbarrier::complete_tx::bytes.v2.u32 [a + 192], {%1, %2}, [a + %4];}"
                     ::"r"(bars), "r"(pr), "r"(hA), "r"(lane), "n"(8 * B_ROLE) : "memory");
        if (b >= 128) atomicOr(&g_tick[4], (pr < 0 ? 4u : 1u) << ((b - 128) >> 1));
    }
    if (wid == 8) {
        int pu = guess;
        bool fast = false, known = false;
#pragma unroll 1
        for (int n = 0; n < 12; n++) {
            if (!known && (n == W_SPEC || pu < 0)) {
                mbar_wait_w(bars + 8 * B_ROLE, 0);
                known = true;
                const int r = __reduce_max_sync(~0u, sinfo[0]);
                if (r != pu) {
#pragma unroll 1
                    for (; n > 0; n--) {
                        mbar_wait_w(bars + 8 * (B_W + n - 1), 0);
                        asm volatile("{.reg .pred p; elect.sync _|p, 0xffffffff; @p mbarrier.arrive.shared.b64 _, [%0];}" ::"r"(bars + 8 * (B_W + n - 1)) : "memory");
                    }
                    pu = r;
                }
                bar_arrive(NB_A, 384);
                if (b >= 128 && pu < 0) bar_sync(NB_B, 64);
                if (pu < 0) break;
            }
            const int rot = b >= 128 ? 8 : 0, i = (n + rot) % 12;
            if (rot && n == 4) bar_sync(NB_B, 64);
            if (n >= W_INFL && !fast) {
                const uint32_t v = ldg_rlx1(&g_tick[32 + (lane & 3) * 8]);
                mbar_wait_w(bars + 8 * (B_W + (n - W_INFL + rot) % 12), 0);
                fast = __all_sync(~0u, v != 0);
            }
            const int m = i < 8 ? i & 1 : 2, k = i < 8 ? i >> 1 : i - 8, c0 = (pu >> 1) * 128 + rank * 64, r0 = (pu & 1) * 512;
            const uint32_t dst = sb + m * 65536 + k * 16384, br = bars + 8 * (B_W + i);
            e_expect(br, 16384);
            e_tma2d_ef(dst, &mp.wq + m, c0, r0 + k * 128, br);
            e_tma2d_ef(dst + 8192, &mp.wq + m, c0, r0 + k * 128 + 64, br);
        }
    } else {
        bar_sync(NB_A, 384);
    }
    const int prr = __reduce_max_sync(~0u, sinfo[0]);
    hA = __reduce_max_sync(~0u, sinfo[1]);
    if (prr < 0) {
        int j = (b - 128) >> 1;
        if (b < 128) {
            uint32_t v;
            int it = 0;
#pragma unroll 1
            do { v = __reduce_max_sync(~0u, ldg_rlx1(&g_tick[4])); spin_guard(++it); } while (__popc(v) < 2);
            j = v == 3 ? -1 - prr : (v & 1) ^ 1;
        }
        rec_side((float*)smraw, p, j * 2 + rank);
        return;
    }
    const int role = (prr >> 1) * 4 + rank * 2 + (prr & 1);
    rec_main(sb, &mp.wo, arena, role, hA, wid >> 2, p.zero, p.tm);
}

__device__ __forceinline__ void wgmma_ss192(float* d, uint64_t a, uint64_t b, int sc) {
    asm volatile("{.reg .pred p; setp.ne.b32 p, %98, 0;\n wgmma.mma_async.sync.aligned.m64n192k16.f32.bf16.bf16 "
                 "{%0,%1,%2,%3,%4,%5,%6,%7,%8,%9,%10,%11,%12,%13,%14,%15,%16,%17,%18,%19,%20,%21,%22,%23,%24,%25,%26,%27,%28,%29,%30,%31,%32,%33,%34,%35,%36,%37,%38,%39,%40,%41,%42,%43,%44,%45,%46,%47,%48,%49,%50,%51,%52,%53,%54,%55,%56,%57,%58,%59,%60,%61,%62,%63,%64,%65,%66,%67,%68,%69,%70,%71,%72,%73,%74,%75,%76,%77,%78,%79,%80,%81,%82,%83,%84,%85,%86,%87,%88,%89,%90,%91,%92,%93,%94,%95}, %96, %97, p, 1, 1, 0, 1;}"
                 : F16(d, 0), F16(d, 16), F16(d, 32), F16(d, 48), F16(d, 64), F16(d, 80) : "l"(a), "l"(b), "r"(sc));
}

constexpr uint32_t P_B = 81920, P_PLANE = 40960, P_VEC = 212992, P_ROW = P_VEC + 6144, P_BAR = P_ROW + 4096, P_SMEM = P_BAR + 256;
constexpr uint32_t P_OUT = 180224, P_OUT3 = P_B + 2 * P_PLANE;
constexpr int E0 = 2;
constexpr int SL_B0 = 0x2222;
constexpr int SL_B1 = 0x8888;
constexpr int SL_C = 0x11110;
constexpr int SL_A0 = 0x5494;
constexpr int SL_A1 = 0x2929;
constexpr int X_DLY = 4000;
constexpr int P_ST = 5, P_ST0 = 4;
constexpr int PB_F = 0, PB_E = 5, PB_X = 10, PB_P = 12, PB_OUT = 14;
enum { C_Y = 0, C_G = 1, C_X1 = 2, C_U = 3, C_S1 = 8, C_S3 = 9 };
enum { V_GA = 0, V_A = 1, V_B = 2, V_GB = 3, V_VA = 4, V_VB = 5, V_VC = 6, V_C3 = 7 };
struct PostMaps { CUtensorMap o, wo, y, w1, g, w2, x1, w3, u, w4, out, x; };

struct GeluK { float k0, k1, kh; };
__device__ __forceinline__ GeluK gelu_k(float c) { return {0.7978845608028654f * c, 0.7978845608028654f * 0.044715f * c * c * c, 0.5f * c}; }
__device__ __forceinline__ float gelu_s(float t, const GeluK& k) {
    const float u = t * fmaf(t * t, k.k1, k.k0);
    float th; asm("tanh.approx.f32 %0, %1;" : "=f"(th) : "f"(u));
    const float hx = k.kh * t;
    return fmaf(hx, th, hx);
}
__device__ __forceinline__ float2 ldsv(uint32_t a) {
    float2 v; asm("ld.shared.v2.f32 {%0,%1}, [%2];" : "=f"(v.x), "=f"(v.y) : "r"(a)); return v;
}
__device__ __forceinline__ void wait_smem(uint32_t a, int target) {
    int it = 0;
#pragma unroll 1
    while (true) {
        int v;
        asm volatile("ld.acquire.cta.shared.u32 %0, [%1];" : "=r"(v) : "r"(a) : "memory");
        if (__all_sync(~0u, v >= target)) break;
        spin_guard(++it);
    }
}

struct Pipe { int st, ph; };
__device__ __forceinline__ void adv(Pipe& p) { if (++p.st == P_ST) { p.st = 0; p.ph ^= 1; } }
__device__ __forceinline__ int u_col(int r, int nb) { return r ? 512 + r * 1024 + nb * 128 : nb * 192; }

template <bool A>
__device__ __forceinline__ void post_produce(uint32_t sb, const PostMaps& mp, int mb, int nb, int rank) {
    const int rh = 2 * mb + rank, lane = threadIdx.x & 31;
    const uint32_t full = sb + P_BAR + 8 * PB_F, empty = sb + P_BAR + 8 * PB_E;
    Pipe p = {(P_ST0 + E0) % P_ST, !E0};
#pragma unroll 1
    for (int ph = 0; ph < 9; ph++) {
        const int GS = ph == 0 ? 8 : ph == 6 ? 3 : 2, kb0 = ph < 7 ? 0 : ph * 16 - 88;
        const CUtensorMap* tm = &mp.o + 2 * (ph < 3 ? ph : ph < 6 ? 3 : 4) + !A;
        const bool own = ph == 1 || ph == 3;
        const int n0 = ph >= 3 && ph < 6 ? u_col(ph - 3, nb) : nb * 128;
        const int amul = ph == 0 ? 256 : 64, arow = ph == 0 ? rh * 8 : rh * 64;
        const int wr = ph == 2 ? min(max(rh + min(lane >> 3, 2) - 1, 0), 31) : rh;
        const uint32_t* fl = &g_pflag[(ph < 3 ? ph - 1 : ph < 6 ? C_X1 : ph - 3) * 256 + wr * 8 + (lane & 7)];
        uint32_t have = ph == 0 || ph == 5 ? ~0u : 0u;
#pragma unroll 1
        for (int q = 0; q < 8; q++) {
            const int src = own && q < 2 ? nb ^ q : (q + (ph >= 1 && ph <= 3 ? nb & 6 : 0)) & 7;
            const bool skip = own && q == 0, both = own && q == 1;
            const uint32_t need = q < 2 && own ? 0 : (ph == 2 ? 0x10101 : 1) << src;
            if (A && both) {
                int it = 0;
                uint32_t ok;
#pragma unroll 1
                do {
                    asm volatile("{.reg .pred p; mbarrier.try_wait.parity.acquire.cluster.shared::cta.b64 p, [%1], %2; selp.u32 %0, 1, 0, p;}" : "=r"(ok) : "r"(sb + P_BAR + 8 * PB_P), "r"(ph >> 1) : "memory");
                    spin_guard(++it);
                } while (!__all_sync(~0u, ok));
                asm volatile("fence.proxy.async.global;" ::: "memory");
            }
            if (A && (have & need) != need) {
                int it = 0;
#pragma unroll 1
                do {
                    uint32_t v;
                    asm volatile("ld.acquire.gpu.global.u32 %0, [%1];" : "=r"(v) : "l"(fl) : "memory");
                    have = __ballot_sync(~0u, v != 0);
                    spin_guard(++it);
                } while ((have & need) != need);
                asm volatile("fence.proxy.async.global;" ::: "memory");
            }
            if (!A && q == 1 && (ph == 1 || ph == 2)) {
#pragma unroll 1
                for (int i = 0; i <= ph; i++)
                    asm volatile("{.reg .pred p; elect.sync _|p, 0xffffffff; @p cp.async.bulk.prefetch.tensor.2d.L2.global [%0, {%1, %2}];}"
                                 ::"l"(tm + 2), "r"((nb * (ph + 1) + i) * 64), "r"(mb * 64) : "memory");
            }
            if (!A && ph == 3 && q == 1) wait_smem(sb + P_BAR + 8 * (PB_OUT + (lane & 1)), 3);
            const int row = arow + (ph == 2 ? (int)((0x04000301u >> ((src & 6) * 4)) & 7) - 2 : 0);
            const uint32_t bytes = (skip ? 16384 : 32768) + (ph == 3 ? 8192 : 0);
            if ((ph | q) == 0) asm volatile("barrier.cluster.wait.aligned;" ::: "memory");
#pragma unroll 1
            for (int e = kb0 + (src + 1) * GS, kb = e - GS + (ph | q ? 0 : E0); kb < e; kb++) {
                const uint32_t f = full + 8 * p.st;
                if (!(A && skip)) mbar_wait_w(empty + 8 * p.st, p.ph ^ 1);
                if (A) {
                    const uint32_t a = sb + p.st * 16384 + rank * 8192;
                    if (both) { e_tma2d_ef(a, tm, kb * 64, row, f); e_tma2d_ef(a + 8192 - rank * 16384, tm, kb * 64, row ^ 64, f); }
                    else if (!skip) e_tma2d_mc_ef(a, tm, kb * amul, row, f);
                } else {
                    const uint32_t b = sb + P_B + p.st * 8192;
                    e_expect(f, bytes);
                    e_tma2d_ef(b, tm, n0, kb * 64, f);
                    e_tma2d_ef(b + P_PLANE, tm, n0 + 64, kb * 64, f);
                    if (ph == 3 && both) mbar_wait_w(empty + 8 * p.st - 16, p.ph);
                    if (ph == 3) e_tma2d_ef(b + 2 * P_PLANE, tm, n0 + 128, kb * 64, f);
                }
                adv(p);
            }
        }
    }
    if (A) {
#pragma unroll 1
        for (int i = 0; i < P_ST; i++) mbar_wait_w(empty + 8 * i, p.ph ^ (i >= p.st));
    }
}

#define I4(d, i) "f"(d[i]), "f"(d[i + 1]), "f"(d[i + 2]), "f"(d[i + 3])
#define I16(d, i) I4(d, i), I4(d, i + 4), I4(d, i + 8), I4(d, i + 12)
#define O4(d, i) "=f"(d[i]), "=f"(d[i + 1]), "=f"(d[i + 2]), "=f"(d[i + 3])
__device__ __forceinline__ void pick32(float* v, int n, const float* c1, const float* vc, const float* old) {
    asm volatile("{PKT: .branchtargets PK0, PK1, PK2, PK3, PK4, PK5; brx.idx.uni %16, PKT;\n"
                 "PK0: fma.rn.f32 %0, %17, %19, %27; fma.rn.f32 %1, %17, %20, %28; fma.rn.f32 %2, %18, %19, %29; fma.rn.f32 %3, %18, %20, %30; fma.rn.f32 %4, %17, %21, %31; fma.rn.f32 %5, %17, %22, %32; fma.rn.f32 %6, %18, %21, %33; fma.rn.f32 %7, %18, %22, %34; fma.rn.f32 %8, %17, %23, %35; fma.rn.f32 %9, %17, %24, %36; fma.rn.f32 %10, %18, %23, %37; fma.rn.f32 %11, %18, %24, %38; fma.rn.f32 %12, %17, %25, %39; fma.rn.f32 %13, %17, %26, %40; fma.rn.f32 %14, %18, %25, %41; fma.rn.f32 %15, %18, %26, %42; bra.uni PKE;\n"
                 "PK1: fma.rn.f32 %0, %17, %19, %43; fma.rn.f32 %1, %17, %20, %44; fma.rn.f32 %2, %18, %19, %45; fma.rn.f32 %3, %18, %20, %46; fma.rn.f32 %4, %17, %21, %47; fma.rn.f32 %5, %17, %22, %48; fma.rn.f32 %6, %18, %21, %49; fma.rn.f32 %7, %18, %22, %50; fma.rn.f32 %8, %17, %23, %51; fma.rn.f32 %9, %17, %24, %52; fma.rn.f32 %10, %18, %23, %53; fma.rn.f32 %11, %18, %24, %54; fma.rn.f32 %12, %17, %25, %55; fma.rn.f32 %13, %17, %26, %56; fma.rn.f32 %14, %18, %25, %57; fma.rn.f32 %15, %18, %26, %58; bra.uni PKE;\n"
                 "PK2: fma.rn.f32 %0, %17, %19, %59; fma.rn.f32 %1, %17, %20, %60; fma.rn.f32 %2, %18, %19, %61; fma.rn.f32 %3, %18, %20, %62; fma.rn.f32 %4, %17, %21, %63; fma.rn.f32 %5, %17, %22, %64; fma.rn.f32 %6, %18, %21, %65; fma.rn.f32 %7, %18, %22, %66; fma.rn.f32 %8, %17, %23, %67; fma.rn.f32 %9, %17, %24, %68; fma.rn.f32 %10, %18, %23, %69; fma.rn.f32 %11, %18, %24, %70; fma.rn.f32 %12, %17, %25, %71; fma.rn.f32 %13, %17, %26, %72; fma.rn.f32 %14, %18, %25, %73; fma.rn.f32 %15, %18, %26, %74; bra.uni PKE;\n"
                 "PK3: fma.rn.f32 %0, %17, %19, %75; fma.rn.f32 %1, %17, %20, %76; fma.rn.f32 %2, %18, %19, %77; fma.rn.f32 %3, %18, %20, %78; fma.rn.f32 %4, %17, %21, %79; fma.rn.f32 %5, %17, %22, %80; fma.rn.f32 %6, %18, %21, %81; fma.rn.f32 %7, %18, %22, %82; fma.rn.f32 %8, %17, %23, %83; fma.rn.f32 %9, %17, %24, %84; fma.rn.f32 %10, %18, %23, %85; fma.rn.f32 %11, %18, %24, %86; fma.rn.f32 %12, %17, %25, %87; fma.rn.f32 %13, %17, %26, %88; fma.rn.f32 %14, %18, %25, %89; fma.rn.f32 %15, %18, %26, %90; bra.uni PKE;\n"
                 "PK4: fma.rn.f32 %0, %17, %19, %91; fma.rn.f32 %1, %17, %20, %92; fma.rn.f32 %2, %18, %19, %93; fma.rn.f32 %3, %18, %20, %94; fma.rn.f32 %4, %17, %21, %95; fma.rn.f32 %5, %17, %22, %96; fma.rn.f32 %6, %18, %21, %97; fma.rn.f32 %7, %18, %22, %98; fma.rn.f32 %8, %17, %23, %99; fma.rn.f32 %9, %17, %24, %100; fma.rn.f32 %10, %18, %23, %101; fma.rn.f32 %11, %18, %24, %102; fma.rn.f32 %12, %17, %25, %103; fma.rn.f32 %13, %17, %26, %104; fma.rn.f32 %14, %18, %25, %105; fma.rn.f32 %15, %18, %26, %106; bra.uni PKE;\n"
                 "PK5: fma.rn.f32 %0, %17, %19, %107; fma.rn.f32 %1, %17, %20, %108; fma.rn.f32 %2, %18, %19, %109; fma.rn.f32 %3, %18, %20, %110; fma.rn.f32 %4, %17, %21, %111; fma.rn.f32 %5, %17, %22, %112; fma.rn.f32 %6, %18, %21, %113; fma.rn.f32 %7, %18, %22, %114; fma.rn.f32 %8, %17, %23, %115; fma.rn.f32 %9, %17, %24, %116; fma.rn.f32 %10, %18, %23, %117; fma.rn.f32 %11, %18, %24, %118; fma.rn.f32 %12, %17, %25, %119; fma.rn.f32 %13, %17, %26, %120; fma.rn.f32 %14, %18, %25, %121; fma.rn.f32 %15, %18, %26, %122;\n"
                 "PKE: }"
                 : O4(v, 0), O4(v, 4), O4(v, 8), O4(v, 12)
                 : "r"(n), "f"(c1[0]), "f"(c1[1]), I4(vc, 0), I4(vc, 4), I16(old, 0), I16(old, 16), I16(old, 32), I16(old, 48), I16(old, 64), I16(old, 80));
}
template <int PH, class F>
__device__ __forceinline__ void post_mma(uint32_t sb, float* acc, Pipe& p, int NK, int wg, uint32_t rel, bool lead, int pi, F hook) {
    const uint32_t full = sb + P_BAR + 8 * PB_F;
    constexpr uint64_t DA = PH == 0 ? mkdesc(SB0, 128, 1024, 0) : mkdesc(SB0, 16, 1024, 1);
    constexpr uint64_t DB = mkdesc(SB0 + P_B, P_PLANE, 1024, 1);
    auto release = [&](uint32_t a) { asm volatile("{.reg .pred p; setp.gt.u32 p, %0, 63; @p mbarrier.arrive.shared::cluster.b64 _, [%0];}" ::"r"(a) : "memory"); };
    uint32_t prev = 0;
    if (PH & 1) { fence_async_smem(); bar_sync(12 + wg, 128); }
    bool ok = false;
#pragma unroll 1
    for (int kb = 0; kb < NK; kb++) {
        if (!ok) mbar_wait_w(full + 8 * p.st, p.ph);
        const uint32_t a = (uint32_t)DA + ((PH & 1) && kb < 2 ? P_OUT / 16 + wg * 1024 + kb * 512 : p.st * 1024 + wg * 512), b = (uint32_t)DB + p.st * 512;
        wg_fence();
#pragma unroll
        for (int k = 0; k < 4; k++) {
            const uint64_t da = (DA & 0xffffffff00000000ull) | (a + k * (PH == 0 ? 16 : 2)), db = (DB & 0xffffffff00000000ull) | (b + k * 128);
            if (PH == 3) wgmma_ss192(acc, da, db, (kb | k) != 0);
            else wgmma_ss128<PH == 0>(acc, da, db, (kb | k) != 0);
        }
        wg_commit();
        const uint32_t cur = rel + 8 * p.st;
        adv(p);
        uint32_t t;
        asm volatile("{.reg .pred p; mbarrier.test_wait.parity.shared.b64 p, [%1], %2; selp.u32 %0, 1, 0, p;}" : "=r"(t) : "r"(full + 8 * p.st), "r"(p.ph) : "memory");
        wg_wait<1>();
        release(prev);
        ok = __all_sync(~0u, t);
        prev = cur;
        hook(kb);
    }
    wg_wait<0>();
    release(prev);
}

__global__ void __cluster_dims__(2, 1, 1) __launch_bounds__(384, 1)
k_post(const __grid_constant__ PostMaps mp) {
    extern __shared__ uint8_t smraw[];
    const uint32_t sb = smem_u32(smraw);
    if ((sb & 0x3FFFF) != SB0) __trap();
    const int tid = threadIdx.x, lane = tid & 31;
    int d, pi;
    pair_place(blockIdx.x >> 1, d, pi);
    const int rank = blockIdx.x & 1, mb = (d >> 2) * 8 + pi, nb = (d & 3) * 2 + rank;
    const uint32_t bars = sb + P_BAR;
    const int w = __reduce_max_sync(~0u, (tid >> 5) - 8);
    if (w == 1) {
        if (lane == 0) {
#pragma unroll
            for (int i = 0; i <= PB_P; i++) mbar_init(bars + 8 * i, i >= PB_E && i < PB_X ? 4 : i == PB_P ? 2 : 1);
            mbar_arrive(bars + 8 * (PB_F + P_ST0));
            asm volatile("mbarrier.arrive.shared.b64 _, [%0], 4;" ::"r"(bars + 8 * (PB_E + P_ST0)) : "memory");
            sts4(bars + 8 * PB_OUT, 0, 0, 0, 0);
            asm volatile("fence.mbarrier_init.release.cluster; fence.proxy.async.shared::cta;" ::: "memory");
        }
        __syncwarp();
    }
    asm volatile("barrier.cluster.arrive.relaxed.aligned;" ::: "memory");
    if (w == 1) {
#pragma unroll
        for (int i = 0; i < E0; i++) {
            const int st = (P_ST0 + i) % P_ST;
            const uint32_t f = bars + 8 * (PB_F + st);
            e_expect(f, 32768);
#pragma unroll
            for (int h = 0; h < 2; h++) {
                e_tma2d_ef(sb + st * 16384 + h * 8192, &mp.o, i * 256, mb * 16 + h * 8, f);
                e_tma2d_ef(sb + P_B + st * 8192 + h * P_PLANE, &mp.wo, nb * 128 + h * 64, i * 64, f);
            }
        }
    }
    if (w != 0 && w != 3) asm volatile("barrier.cluster.wait.aligned;" ::: "memory");
    if (w >= 0) {
        asm volatile("setmaxnreg.dec.sync.aligned.u32 40;");
        if (w == 0) {
            post_produce<false>(sb, mp, mb, nb, rank);
        } else if (w < 3) {
            const int wg = w - 1, rh = 2 * mb + wg;
            float* rowc = (float*)(smraw + P_ROW) + (wg * 64 + lane * 2) * 8;
            int nout = 0, sig = 0;
            __nanosleep(X_DLY);
            if (wg && lane < 9) asm volatile("prefetch.tensormap [%0];" ::"l"(&mp.y + lane) : "memory");
            e_expect(bars + 8 * (PB_X + wg), 16384);
            e_tma2d_ef(sb + P_OUT + wg * 16384, &mp.x, nb * 128, rh * 64, bars + 8 * (PB_X + wg));
            e_tma2d_ef(sb + P_OUT + wg * 16384 + 8192, &mp.x, nb * 128 + 64, rh * 64, bars + 8 * (PB_X + wg));
            if (wg == 0) {
#pragma unroll 1
                for (int i = 0; i < 11; i++) {
                    const float* src = i < 4 ? g_mod + ((0x5342 >> (4 * i)) & 15) * DM + nb * 128 : g_vec + (i < 7 ? (i - 4) * DM + nb * 128 : 3 * DM + u_col(max(i - 8, 0), nb) + (i == 8) * 128);
                    if (i != 8 || lane < 16) cp_async16(sb + P_VEC + i * 512 - (i > 8) * 256 + lane * 16, src + lane * 4);
                }
                *(uint4*)&g_modp[blockIdx.x * 128 + lane * 4] = make_uint4(0, 0, 0, 0);
                if (blockIdx.x == 64) *(uint2*)&g_tick[lane * 2] = make_uint2(0, 0);
                asm volatile("cp.async.wait_all;" ::: "memory");
                const float4 a = lds4f(sb + P_VEC + V_A * 512 + lane * 16);
                sts4f(sb + P_VEC + V_A * 512 + lane * 16, 1.0f + a.x, 1.0f + a.y, 1.0f + a.z, 1.0f + a.w);
                bar_arrive(3, 288);
            }
#pragma unroll 1
            for (int i = 0; i < 9; i++) {
                const int cnt = i == 8 ? 6 : (0x54392180u >> (4 * i)) & 15;
                if (cnt < C_S1) {
                    const bool isu = cnt >= C_U && cnt < 6;
                    const int ng = cnt == C_U ? 3 : 2, c0 = isu ? u_col(cnt - C_U, nb) : nb * 128;
                    const uint32_t src = sb + (cnt == C_U ? P_OUT3 : P_OUT) + wg * ng * 8192;
#pragma unroll 1
                    for (int j = 0; j < ng; j++) {
                        bar_sync(4 + 4 * wg + (sig++ & 3), 160);
                        if (lane == 0) {
                            fence_async_smem();
                            asm volatile("cp.async.bulk.tensor.2d.global.shared::cta.bulk_group [%0, {%2, %3}], [%1]; cp.async.bulk.commit_group;"
                                         ::"l"(&mp.y + 2 * (isu ? 3 : min(cnt, 4))), "r"(src + j * 8192), "r"(c0 + j * 64), "r"(rh * 64) : "memory");
                        }
                        __syncwarp();
                    }
                    if (lane == 0) {
                        asm volatile("cp.async.bulk.wait_group 0; fence.proxy.async.global;" ::: "memory");
                        asm volatile("st.release.cta.shared.u32 [%0], %1;" ::"r"(bars + 8 * (PB_OUT + wg)), "r"(nout + 1) : "memory");
                        if (cnt < 6) asm volatile("fence.acq_rel.gpu; st.relaxed.gpu.global.u32 [%0], %1;" ::"l"(&g_pflag[cnt * 256 + rh * 8 + nb]), "r"(1) : "memory");
                        if (cnt == C_Y || cnt == C_X1)
                            asm volatile("{.reg .b32 r; mapa.shared::cluster.u32 r, %0, %1; mbarrier.arrive.relaxed.cluster.shared::cluster.b64 _, [r];}" ::"r"(bars + 8 * PB_P), "r"(rank ^ 1) : "memory");
                    }
                    nout++;
                    __syncwarp();
                    continue;
                }
                bar_sync(4 + 4 * wg + (sig++ & 3), 160);
#pragma unroll 1
                for (int q = 0; q < (cnt == C_S1 ? 3 : 1); q++) {
                    const float4 v = lds4f(sb + P_ROW + wg * 2048 + q * 512 + lane * 16);
                    asm volatile("red.relaxed.gpu.global.add.v4.f32 [%0], {%1, %2, %3, %4};"
                                 ::"l"((float4*)g_st + (cnt == C_S1 ? q : 3) * (S_ / 2) + rh * 32 + lane), "f"(v.x), "f"(v.y), "f"(v.z), "f"(v.w) : "memory");
                }
                __syncwarp();
                uint32_t* c = &g_pcnt[(cnt - C_S1) * 256 + rh * 8];
                if (lane == 0) { signal_count(c); wait_count1(c, 8); }
                __syncwarp();
                const float4* sp = (const float4*)g_st + rh * 32 + lane;
                float4 u[3] = {__ldcg(sp + (cnt == C_S1 ? 0 : 3) * (S_ / 2)), __ldcg(sp + S_ / 2), __ldcg(sp + S_)};
#pragma unroll 1
                for (int h = 0; h < 2; h++) {
                    const float id = 1.0f / DM;
                    const float m = u[0].x * id, var = fmaxf(u[0].y * id - m * m, 0.f) + 1e-5f, r = rsqrtf(var);
                    float sc = r, m2 = 0.f;
                    if (cnt == C_S1) {
                        m2 = r * (u[1].x * id - m * g_cst[0]) + g_cst[3];
                        const float e2 = r * r * (u[2].x * id - 2.0f * m * u[1].y * id + m * m * g_cst[1]) + 2.0f * r * (u[2].y * id - m * g_cst[2]) + g_cst[4];
                        sc = r * rsqrtf(fmaxf(e2 - m2 * m2, 0.f) + 1e-5f);
                    }
                    const GeluK k = gelu_k(sc);
                    *(float4*)(rowc + h * 8) = make_float4(k.k0, k.k1, k.kh, -m);
                    *(float4*)(rowc + h * 8 + 4) = make_float4(var * r, -m2 * var * r, r, -m * r);
#pragma unroll
                    for (int q = 0; q < 3; q++) { u[q].x = u[q].z; u[q].y = u[q].w; }
                }
                bar_arrive(1 + wg, 160);
            }
        } else {
            post_produce<true>(sb, mp, mb, nb, rank);
        }
    } else {
        asm volatile("setmaxnreg.inc.sync.aligned.u32 232;");
        const int wg = __reduce_max_sync(~0u, tid >> 7), wi = (tid >> 5) & 3, g = lane >> 2, tq = lane & 3;
        const bool lead = (tid & 127) == 0;
        uint32_t rel = 0;
        if ((tid & 127) < 2) asm("mapa.shared::cluster.u32 %0, %1, %2;" : "=r"(rel) : "r"(bars + 8 * PB_E), "r"(tid & 1));
        uint32_t vec = sb + P_VEC + tq * 8;
        const uint32_t stw = sb + (wi * 16 + ((lane >> 3) & 1) * 8 + (lane & 7)) * 128 + (((lane >> 4) ^ (lane & 7)) << 4);
        int sig = 0;
        auto signal = [&]() { bar_arrive(4 + 4 * wg + (sig++ & 3), 160); };
        auto put64 = [&](uint32_t o, const float* v) {
#pragma unroll
            for (int jj = 0; jj < 4; jj++, v += 8) stsm4((stw + o) ^ (jj << 5), pack2(v[0], v[1]), pack2(v[2], v[3]), pack2(v[4], v[5]), pack2(v[6], v[7]));
            signal();
        };
        auto out_free = [&](int n) { wait_smem(bars + 8 * (PB_OUT + (lane & 1)), n); };
        const uint32_t rowc = sb + P_ROW + (wg * 64 + wi * 16 + g) * 32, o128 = P_OUT + wg * 16384;
        const uint32_t rsum = sb + P_ROW + wg * 2048 + (wi * 16 + g) * 8;
        Pipe pa = {P_ST0, 1};
        auto none = [](int) {};
        uint32_t keep[32];
#define KEEP(jn, e) (((e) & 1) ? bfhi(keep[2 * (jn) + ((e) >> 1)]) : bflo(keep[2 * (jn) + ((e) >> 1)]))
        float mu1[2], r1[2];
        {
            float acc[64];
            post_mma<0>(sb, acc, pa, 64, wg, rel, lead, 1, [&](int kb) {
                if (kb != 40) return;
                bar_sync(3, 288);
                mbar_wait_w(bars + 8 * (PB_X + wg), 0);
#pragma unroll
                for (int jj = 0; jj < 8; jj++) ldsm4(keep + jj * 4, (stw + o128 + (jj >> 2) * 8192) ^ ((jj & 3) << 5));
            });
            asm volatile("" : "+r"(vec) :: "memory");
            float st[2][6];
#pragma unroll
            for (int q = 0; q < 6; q++) st[0][q] = st[1][q] = 0.f;
#pragma unroll
            for (int jn = 0; jn < 16; jn++) {
                const float2 ga = ldsv(vec + V_GA * 512 + jn * 32), a = ldsv(vec + V_A * 512 + jn * 32);
                float xa[4];
#pragma unroll
                for (int e = 0; e < 4; e++) {
                    xa[e] = fmaf((e & 1) ? ga.y : ga.x, acc[4 * jn + e], KEEP(jn, e));
                    st[e >> 1][0] += xa[e]; st[e >> 1][1] = fmaf(xa[e], xa[e], st[e >> 1][1]);
                    acc[4 * jn + e] = ((e & 1) ? a.y : a.x) * xa[e];
                }
                keep[2 * jn] = pack2(xa[0], xa[1]); keep[2 * jn + 1] = pack2(xa[2], xa[3]);
                if ((jn & 7) == 7) put64(o128 + (jn >> 3) * 8192, acc + 4 * jn - 28);
            }
#pragma unroll
            for (int jn = 0; jn < 16; jn++) {
                const float2 a = ldsv(vec + V_A * 512 + jn * 32), b = ldsv(vec + V_B * 512 + jn * 32);
#pragma unroll
                for (int e = 0; e < 4; e++) {
                    const float y = acc[4 * jn + e], aa = (e & 1) ? a.y : a.x, bb = (e & 1) ? b.y : b.x;
                    float* s = st[e >> 1];
                    s[2] += y; s[3] = fmaf(aa, y, s[3]); s[4] = fmaf(y, y, s[4]); s[5] = fmaf(bb, y, s[5]);
                }
            }
#pragma unroll
            for (int h = 0; h < 2; h++)
#pragma unroll
                for (int q = 0; q < 6; q++) { st[h][q] += __shfl_xor_sync(~0u, st[h][q], 1); st[h][q] += __shfl_xor_sync(~0u, st[h][q], 2); }
            if (tq < 3) {
#pragma unroll
                for (int h = 0; h < 2; h++)
                    sts2(rsum + tq * 512 + h * 64, tq == 0 ? st[h][0] : tq == 1 ? st[h][2] : st[h][4], tq == 0 ? st[h][1] : tq == 1 ? st[h][3] : st[h][5]);
            }
            signal();
        }
        {
            float acc[64];
            post_mma<1>(sb, acc, pa, 16, wg, rel, lead, 4, none);
            float c1[2], c2[2], c3[2];
            GeluK gk[2];
            bar_sync(1 + wg, 160);
#pragma unroll
            for (int h = 0; h < 2; h++) {
                const float4 a = lds4f(rowc + h * 256), b = lds4f(rowc + h * 256 + 16);
                gk[h] = {a.x, a.y, a.z}; c1[h] = a.w; c2[h] = b.x; c3[h] = b.y; mu1[h] = b.w; r1[h] = b.z;
            }
#pragma unroll
            for (int jn = 0; jn < 16; jn++) {
                const float2 va = ldsv(vec + V_VA * 512 + jn * 32), vb = ldsv(vec + V_VB * 512 + jn * 32), vc = ldsv(vec + V_VC * 512 + jn * 32);
#pragma unroll
                for (int e = 0; e < 4; e++) {
                    const int h = e >> 1;
                    const float t = fmaf(c1[h], (e & 1) ? va.y : va.x, fmaf(c2[h], (e & 1) ? vb.y : vb.x, fmaf(c3[h], (e & 1) ? vc.y : vc.x, acc[4 * jn + e])));
                    acc[4 * jn + e] = gelu_s(t, gk[h]);
                }
                if ((jn & 7) == 7) put64(o128 + (jn >> 3) * 8192, acc + 4 * jn - 28);
            }
        }
        {
            float acc[64];
            post_mma<2>(sb, acc, pa, 16, wg, rel, lead, 7, none);
#pragma unroll
            for (int jn = 0; jn < 16; jn++) {
                const float2 a = ldsv(vec + V_A * 512 + jn * 32), b = ldsv(vec + V_B * 512 + jn * 32);
#pragma unroll
                for (int e = 0; e < 4; e++) {
                    const int h = e >> 1;
                    acc[4 * jn + e] += fmaf(fmaf(KEEP(jn, e), r1[h], mu1[h]), (e & 1) ? a.y : a.x, (e & 1) ? b.y : b.x);
                }
                if ((jn & 7) == 7) put64(o128 + (jn >> 3) * 8192, acc + 4 * jn - 28);
            }
            float st[2][2] = {{0.f, 0.f}, {0.f, 0.f}};
#pragma unroll
            for (int jn = 0; jn < 16; jn++) {
                const float2 gb = ldsv(vec + V_GB * 512 + jn * 32);
                float z[4];
#pragma unroll
                for (int e = 0; e < 4; e++) {
                    const float x1 = acc[4 * jn + e];
                    st[e >> 1][0] += x1; st[e >> 1][1] = fmaf(x1, x1, st[e >> 1][1]);
                    z[e] = fmaf((e & 1) ? gb.y : gb.x, x1, KEEP(jn, e));
                }
                keep[2 * jn] = pack2(z[0], z[1]); keep[2 * jn + 1] = pack2(z[2], z[3]);
            }
#pragma unroll
            for (int h = 0; h < 2; h++)
#pragma unroll
                for (int q = 0; q < 2; q++) { st[h][q] += __shfl_xor_sync(~0u, st[h][q], 1); st[h][q] += __shfl_xor_sync(~0u, st[h][q], 2); }
            if (tq < 2) sts2(rsum + tq * 64, tq ? st[1][0] : st[0][0], tq ? st[1][1] : st[0][1]);
            signal();
        }
        {
            float old[96], acc[64];
            post_mma<3>(sb, old, pa, 16, wg, rel, lead, 10, none);
            uint32_t v3 = vec + V_C3 * 512;
            float c1[2], vc[8];
            auto next_vc = [&]() {
#pragma unroll
                for (int i = 0; i < 4; i++) { const float2 u = lds2f(v3 + i * 32); vc[2 * i] = u.x; vc[2 * i + 1] = u.y; }
                v3 += 128;
            };
            next_vc();
            GeluK gk[2];
            bar_sync(1 + wg, 160);
#pragma unroll
            for (int h = 0; h < 2; h++) { const float4 a = lds4f(rowc + h * 256); gk[h] = {a.x, a.y, a.z}; c1[h] = a.w; }
            bar_arrive(14 + wg, 256);
#pragma unroll 1
            for (int r = 0; r < 3; r++) {
                const uint32_t o = stw + (r ? o128 : P_OUT3 + wg * 24576);
                uint32_t when = r == 0 ? (wg ? SL_A1 : SL_A0) : r == 1 ? (wg ? SL_B1 : SL_B0) : SL_C << (2 * wg), n = 0;
                post_mma<2>(sb, acc, pa, r < 2 ? 16 : 56, wg, rel, lead, 12 + 2 * r, [&](int kb) {
                    const bool now = when & 1;
                    when >>= 1;
                    if (!now) return;
                    if (n == 0) { if (r == 0) bar_sync(15 - wg, 256); out_free(3 + r); }
                    float v[16];
                    pick32(v, n, c1, vc, old);
                    next_vc();
#pragma unroll
                    for (int e = 0; e < 16; e++) v[e] = gelu_s(v[e], gk[(e >> 1) & 1]);
                    const uint32_t a = (o + (n >> 1) * 8192) ^ ((n & 1) << 6);
                    stsm4(a, pack2(v[0], v[1]), pack2(v[2], v[3]), pack2(v[4], v[5]), pack2(v[6], v[7]));
                    stsm4(a ^ 32, pack2(v[8], v[9]), pack2(v[10], v[11]), pack2(v[12], v[13]), pack2(v[14], v[15]));
                    if ((++n & 1) == 0) signal();
                });
                if (r == 2) break;
#pragma unroll
                for (int i = 0; i < 64; i++) old[i] = acc[i];
            }
#pragma unroll
            for (int jn = 0; jn < 16; jn++) {
                const float2 gb = ldsv(vec + V_GB * 512 + jn * 32);
#pragma unroll
                for (int e = 0; e < 4; e++) acc[4 * jn + e] = fmaf((e & 1) ? gb.y : gb.x, acc[4 * jn + e], KEEP(jn, e));
                if ((jn & 7) == 7) put64(o128 + (jn >> 3) * 8192, acc + 4 * jn - 28);
            }
        }
    }
}

typedef CUresult (*EncFn)(CUtensorMap*, CUtensorMapDataType, cuuint32_t, void*, const cuuint64_t*, const cuuint64_t*, const cuuint32_t*,
                          const cuuint32_t*, CUtensorMapInterleave, CUtensorMapSwizzle, CUtensorMapL2promotion, CUtensorMapFloatOOBfill);

static CUtensorMap make_map(EncFn enc, const void* p, uint64_t inner, uint64_t outer) {
    CUtensorMap m;
    cuuint64_t dims[2] = {inner, outer};
    cuuint64_t str[1] = {inner * 2};
    cuuint32_t box[2] = {64, 64};
    cuuint32_t es[2] = {1, 1};
    enc(&m, CU_TENSOR_MAP_DATA_TYPE_BFLOAT16, 2, (void*)p, dims, str, box, es, CU_TENSOR_MAP_INTERLEAVE_NONE,
        CU_TENSOR_MAP_SWIZZLE_128B, CU_TENSOR_MAP_L2_PROMOTION_L2_256B, CU_TENSOR_MAP_FLOAT_OOB_FILL_NONE);
    return m;
}
static CUtensorMap make_map_o(EncFn enc, const void* p) {
    CUtensorMap m;
    cuuint64_t dims[2] = {16384, 256};
    cuuint64_t str[1] = {65536};
    cuuint32_t box[2] = {256, 8};
    cuuint32_t es[2] = {1, 1};
    enc(&m, CU_TENSOR_MAP_DATA_TYPE_UINT32, 2, (void*)p, dims, str, box, es, CU_TENSOR_MAP_INTERLEAVE_NONE, CU_TENSOR_MAP_SWIZZLE_NONE,
        CU_TENSOR_MAP_L2_PROMOTION_L2_256B, CU_TENSOR_MAP_FLOAT_OOB_FILL_NONE);
    return m;
}
template <class T> static T* sym(T& s) { void* p = nullptr; cudaGetSymbolAddress(&p, s); return (T*)p; }

constexpr RecTime g_time = {T_GO, T_X2, T_V, D_X2, H_D};
extern "C" void kernel_launch(void* const* d_in, const int* in_sizes, int n_in, void* d_out, int out_size) {
    const bf16* x = (const bf16*)d_in[0];
    const bf16* mem0 = (const bf16*)d_in[1];
    const bf16 *Wq = (const bf16*)d_in[2], *Wk = (const bf16*)d_in[3], *Wv = (const bf16*)d_in[4], *Wo = (const bf16*)d_in[5];
    const bf16 *w1 = (const bf16*)d_in[8], *w2 = (const bf16*)d_in[9], *w3 = (const bf16*)d_in[10], *w4 = (const bf16*)d_in[11];
    const bf16 *c = (const bf16*)d_in[12], *wmod = (const bf16*)d_in[13];
    bf16* out = (bf16*)d_out;

    EncFn enc = nullptr;
    cudaDriverEntryPointQueryResult qr;
    cudaGetDriverEntryPoint("cuTensorMapEncodeTiled", (void**)&enc, cudaEnableDefault, &qr);
    CUtensorMap tWq = make_map(enc, Wq, NH * DH, DM), tWk = make_map(enc, Wk, NH * DH, DM), tWv = make_map(enc, Wv, NH * DH, DM);
    PostMaps mp;
    mp.o = make_map_o(enc, sym(g_O)); mp.wo = make_map(enc, Wo, DM, NH * DH);
    mp.y = make_map(enc, sym(g_y), DM, S_); mp.w1 = make_map(enc, w1, DM, DM);
    mp.g = make_map(enc, sym(g_g), DM, S_); mp.w2 = make_map(enc, w2, DM, DM);
    mp.x1 = make_map(enc, sym(g_x1), DM, S_); mp.w3 = make_map(enc, w3, FF, DM);
    mp.u = make_map(enc, sym(g_u), FF, S_); mp.w4 = make_map(enc, w4, DM, FF);
    mp.out = make_map(enc, out, DM, S_); mp.x = make_map(enc, x, DM, S_);
    cudaFuncSetAttribute(k_rec, cudaFuncAttributeMaxDynamicSharedMemorySize, SM_REC_TOTAL);
    cudaFuncSetAttribute(k_post, cudaFuncAttributeMaxDynamicSharedMemorySize, P_SMEM);

    uint8_t* arena = (uint8_t*)(((uintptr_t)sym(g_arena) + (2u << 20) - 1) & ~(uintptr_t)((2u << 20) - 1));
    const RecPtrs rp = {x, mem0, c, wmod, w1, w3, arena, 0u, g_time};
    const RecMaps rm = {tWq, tWk, tWv, mp.wo};
    k_rec<<<132, 384, SM_REC_TOTAL>>>(rm, rp);
    k_post<<<128, 384, P_SMEM>>>(mp);
}
```

```cpp
#include <cuda_runtime.h>
#include <cuda.h>
#include <cuda_bf16.h>
#include <stdint.h>
#include <limits.h>

typedef __nv_bfloat16 bf16;

constexpr int S_ = 2048, DM = 1024, NH = 32, DH = 128, NSEG = 64, FF = 3584;
constexpr int SPIN_LIMIT = 1 << 22;
constexpr int W_INFL = 2;
constexpr int NPROBE = 4;

__device__ uint8_t g_arena[10 << 20];
__device__ __align__(16) uint32_t g_tick[64];
__device__ __align__(16) uint32_t g_modp[8 * 2 * DM];
__host__ __device__ constexpr uint32_t blk(uint32_t lb, uint32_t par) {
    return (lb << 13) | ((((lb) ^ (lb >> 3) ^ (lb >> 4) ^ (lb >> 6) ^ par) & 1) << 12);
}
__host__ __device__ constexpr uint32_t lb_x2(uint32_t h) { return (h & 1) | ((h >> 1) << 3); }
__host__ __device__ constexpr uint32_t acc_slot(uint32_t s) { return (1u << 20) + (s & 1) * 32768 + (s & 2) * 131072; }
__host__ __device__ constexpr uint32_t acc_piece(uint32_t half, uint32_t qd, uint32_t mt) { return mt * 1024 + (qd & 1) * 4096 + half * 8192 + (qd >> 1) * 16384; }
constexpr uint32_t LB_STAMP = 6;
__host__ __device__ constexpr uint32_t stamp_line(uint32_t w, uint32_t q) { return ((w & 1) * 2 + (q >> 1)) * 1024 + (q & 1) * 256; }
constexpr uint32_t ACC_ONE = 0x3c000000u, ACC_ALL = 0x50000000u;
constexpr uint32_t LB_PROBE = 6 | 64;
__host__ __device__ constexpr uint32_t lb_tok(uint32_t h) { return (h & 1) | ((h >> 1) << 3); }
__device__ __align__(16) float g_mod[6 * DM];
__device__ __align__(1024) bf16 g_himg[(S_ + 32) * DM];
__device__ __align__(1024) bf16 g_O[S_ * NH * DH];
__device__ __align__(1024) bf16 g_y[S_ * DM];
__device__ __align__(1024) bf16 g_g[S_ * DM];
__device__ __align__(1024) bf16 g_x1[S_ * DM];
__device__ __align__(16) float g_st[4 * S_ * 2];
__device__ __align__(16) float g_vec[3 * DM + FF];
__device__ float g_cst[8];
__device__ uint32_t g_pcnt[2 * 32 * 8], g_pflag[6 * 32 * 8];
__device__ __align__(1024) bf16 g_u[S_ * FF];

__device__ __forceinline__ uint32_t smem_u32(const void* p) { return (uint32_t)__cvta_generic_to_shared(p); }
__device__ __forceinline__ void spin_guard(int it) {
    asm volatile("{.reg .pred p; setp.gt.s32 p, %0, %1; @p st.global.u32 [%2], %0;}" ::"r"(it), "n"(SPIN_LIMIT), "l"(1ull));
}
__device__ __forceinline__ void wg_fence() { asm volatile("wgmma.fence.sync.aligned;" ::: "memory"); }
__device__ __forceinline__ void wg_commit() { asm volatile("wgmma.commit_group.sync.aligned;" ::: "memory"); }
template <int N> __device__ __forceinline__ void wg_wait() { asm volatile("wgmma.wait_group.sync.aligned %0;" ::"n"(N) : "memory"); }
__host__ __device__ constexpr uint64_t mkdesc(uint32_t addr, uint32_t lbo, uint32_t sbo, uint32_t swz) {
    return (uint64_t)((addr & 0x3FFFF) >> 4) | ((uint64_t)(lbo >> 4) << 16) | ((uint64_t)(sbo >> 4) << 32) | ((uint64_t)swz << 62);
}
__device__ __forceinline__ uint64_t dadd(uint64_t d, uint32_t o) { return (d & 0xffffffff00000000ull) | (uint32_t)((uint32_t)d + o); }
__device__ __forceinline__ void mbar_init(uint32_t b, uint32_t c) { asm volatile("mbarrier.init.shared.b64 [%0], %1;" ::"r"(b), "r"(c) : "memory"); }
__device__ __forceinline__ void mbar_expect(uint32_t b, uint32_t tx) { asm volatile("mbarrier.arrive.expect_tx.shared.b64 _, [%0], %1;" ::"r"(b), "r"(tx) : "memory"); }
__device__ __forceinline__ void mbar_arrive(uint32_t b) { asm volatile("mbarrier.arrive.shared.b64 _, [%0];" ::"r"(b) : "memory"); }
__device__ __forceinline__ void mbar_arrive_cluster_if(bool c, uint32_t b, uint32_t cta) {
    asm volatile("{.reg .pred p; .reg .b32 r; setp.ne.u32 p, %2, 0; mapa.shared::cluster.u32 r, %0, %1; @p mbarrier.arrive.shared::cluster.b64 _, [r];}" ::"r"(b), "r"(cta), "r"((uint32_t)c) : "memory");
}
__device__ __forceinline__ bool mbar_try(uint32_t b, uint32_t par) {
    uint32_t ok;
    asm volatile("{.reg .pred p; mbarrier.try_wait.parity.shared.b64 p, [%1], %2; selp.u32 %0, 1, 0, p;}" : "=r"(ok) : "r"(b), "r"(par) : "memory");
    return ok;
}
__device__ __forceinline__ void mbar_wait_w(uint32_t b, uint32_t par) {
    int it = 0;
    bool ok;
#pragma unroll 1
    do { ok = __all_sync(~0u, mbar_try(b, par)); spin_guard(++it); } while (!ok);
}
__device__ __forceinline__ void bar_sync(int id, int n) { asm volatile("bar.sync %0, %1;" ::"r"(id), "r"(n) : "memory"); }
__device__ __forceinline__ void bar_arrive(int id, int n) { asm volatile("bar.arrive %0, %1;" ::"r"(id), "r"(n) : "memory"); }
__device__ __forceinline__ void fence_async_smem() { asm volatile("fence.proxy.async.shared::cta;" ::: "memory"); }
__device__ __forceinline__ void ldsm4t(uint32_t* r, uint32_t a) {
    asm volatile("ldmatrix.sync.aligned.m8n8.x4.trans.shared.b16 {%0,%1,%2,%3}, [%4];" : "=r"(r[0]), "=r"(r[1]), "=r"(r[2]), "=r"(r[3]) : "r"(a) : "memory");
}
__device__ __forceinline__ void ldsm4(uint32_t* r, uint32_t a) {
    asm volatile("ldmatrix.sync.aligned.m8n8.x4.shared.b16 {%0,%1,%2,%3}, [%4];" : "=r"(r[0]), "=r"(r[1]), "=r"(r[2]), "=r"(r[3]) : "r"(a) : "memory");
}
__device__ __forceinline__ uint32_t movm(uint32_t a) {
    uint32_t d; asm volatile("movmatrix.sync.aligned.m8n8.trans.b16 %0, %1;" : "=r"(d) : "r"(a)); return d;
}
__device__ __forceinline__ void mma16816(float* d, uint32_t a0, uint32_t a1, uint32_t a2, uint32_t a3, uint32_t b0, uint32_t b1) {
    asm volatile("mma.sync.aligned.m16n8k16.row.col.f32.bf16.bf16.f32 {%0,%1,%2,%3},{%4,%5,%6,%7},{%8,%9},{%0,%1,%2,%3};"
                 : "+f"(d[0]), "+f"(d[1]), "+f"(d[2]), "+f"(d[3]) : "r"(a0), "r"(a1), "r"(a2), "r"(a3), "r"(b0), "r"(b1));
}
__device__ __forceinline__ void mma16816z(float* d, const uint32_t* a, uint32_t b0, uint32_t b1) {
    asm volatile("mma.sync.aligned.m16n8k16.row.col.f32.bf16.bf16.f32 {%0,%1,%2,%3},{%4,%5,%6,%7},{%8,%9},{%10,%10,%10,%10};"
                 : "=f"(d[0]), "=f"(d[1]), "=f"(d[2]), "=f"(d[3]) : "r"(a[0]), "r"(a[1]), "r"(a[2]), "r"(a[3]), "r"(b0), "r"(b1), "f"(0.f));
}
__device__ __forceinline__ void mma1688(float* d, uint32_t a0, uint32_t a1, uint32_t b0) {
    asm volatile("mma.sync.aligned.m16n8k8.row.col.f32.bf16.bf16.f32 {%0,%1,%2,%3},{%4,%5},{%6},{%0,%1,%2,%3};"
                 : "+f"(d[0]), "+f"(d[1]), "+f"(d[2]), "+f"(d[3]) : "r"(a0), "r"(a1), "r"(b0));
}
__device__ __forceinline__ uint32_t pack2(float lo, float hi) {
    uint32_t r; asm("cvt.rn.bf16x2.f32 %0, %1, %2;" : "=r"(r) : "f"(hi), "f"(lo)); return r;
}
__device__ __forceinline__ uint32_t hadd2v(uint32_t a, uint32_t b) {
    uint32_t r; asm volatile("add.rn.bf16x2 %0, %1, %2;" : "=r"(r) : "r"(a), "r"(b)); return r;
}
__device__ __forceinline__ float bflo(uint32_t u) { return __uint_as_float(u << 16); }
__device__ __forceinline__ float bfhi(uint32_t u) { return __uint_as_float(u & 0xffff0000u); }
__device__ __forceinline__ float ex2(float x) { float r; asm("ex2.approx.ftz.f32 %0, %1;" : "=f"(r) : "f"(x)); return r; }
__device__ __forceinline__ uint4 ldg_rlx4(const void* p) {
    uint4 v; asm volatile("ld.relaxed.gpu.global.v4.u32 {%0,%1,%2,%3}, [%4];" : "=r"(v.x), "=r"(v.y), "=r"(v.z), "=r"(v.w) : "l"(p) : "memory"); return v;
}
__device__ __forceinline__ uint32_t ldg_rlx1(const void* p) {
    uint32_t v; asm volatile("ld.relaxed.gpu.global.u32 %0, [%1];" : "=r"(v) : "l"(p) : "memory"); return v;
}
__device__ __forceinline__ void stg_rlx1(void* p, uint32_t v) { asm volatile("st.relaxed.gpu.global.u32 [%0], %1;" ::"l"(p), "r"(v) : "memory"); }
__device__ __forceinline__ void stg_rlx2(void* p, uint32_t x, uint32_t y) {
    unsigned long long v = (unsigned long long)x | ((unsigned long long)y << 32);
    asm volatile("st.relaxed.gpu.global.b64 [%0], %1;" ::"l"(p), "l"(v) : "memory");
}
__device__ __forceinline__ void stg_rlx4(void* p, uint32_t x, uint32_t y, uint32_t z, uint32_t w) {
    asm volatile("st.relaxed.gpu.global.v4.u32 [%0], {%1,%2,%3,%4};" ::"l"(p), "r"(x), "r"(y), "r"(z), "r"(w) : "memory");
}
__device__ __forceinline__ void sts4(uint32_t a, uint32_t x, uint32_t y, uint32_t z, uint32_t w) {
    asm volatile("st.shared.v4.u32 [%0], {%1,%2,%3,%4};" ::"r"(a), "r"(x), "r"(y), "r"(z), "r"(w) : "memory");
}
__device__ __forceinline__ uint4 lds4(uint32_t a) {
    uint4 v; asm volatile("ld.shared.v4.u32 {%0,%1,%2,%3}, [%4];" : "=r"(v.x), "=r"(v.y), "=r"(v.z), "=r"(v.w) : "r"(a) : "memory"); return v;
}
#define F4(d, i) "+f"(d[i]), "+f"(d[i + 1]), "+f"(d[i + 2]), "+f"(d[i + 3])
template <bool V> __device__ __forceinline__ void wgmma_tok_rs(float* d, const uint32_t* a, uint64_t b, int sc) {
    if (V) asm volatile("{.reg .pred p; setp.ne.b32 p, %25, 0;\n wgmma.mma_async.sync.aligned.m64n40k16.f32.bf16.bf16 {%0,%1,%2,%3,%4,%5,%6,%7,%8,%9,%10,%11,%12,%13,%14,%15,%16,%17,%18,%19}, {%20,%21,%22,%23}, %24, p, 1, 1, 0;}"
                        : F4(d, 0), F4(d, 4), F4(d, 8), F4(d, 12), F4(d, 16) : "r"(a[0]), "r"(a[1]), "r"(a[2]), "r"(a[3]), "l"(b), "r"(sc));
    else asm volatile("{.reg .pred p; setp.ne.b32 p, %21, 0;\n wgmma.mma_async.sync.aligned.m64n32k16.f32.bf16.bf16 {%0,%1,%2,%3,%4,%5,%6,%7,%8,%9,%10,%11,%12,%13,%14,%15}, {%16,%17,%18,%19}, %20, p, 1, 1, 0;}"
                      : F4(d, 0), F4(d, 4), F4(d, 8), F4(d, 12) : "r"(a[0]), "r"(a[1]), "r"(a[2]), "r"(a[3]), "l"(b), "r"(sc));
}
template <bool V> __device__ __forceinline__ void wgmma_tok_ss(float* d, uint64_t a, uint64_t b) {
    if (V) asm volatile("wgmma.mma_async.sync.aligned.m64n40k16.f32.bf16.bf16 {%0,%1,%2,%3,%4,%5,%6,%7,%8,%9,%10,%11,%12,%13,%14,%15,%16,%17,%18,%19}, %20, %21, 1, 1, 1, 1, 0;"
                        : F4(d, 0), F4(d, 4), F4(d, 8), F4(d, 12), F4(d, 16) : "l"(a), "l"(b));
    else asm volatile("wgmma.mma_async.sync.aligned.m64n32k16.f32.bf16.bf16 {%0,%1,%2,%3,%4,%5,%6,%7,%8,%9,%10,%11,%12,%13,%14,%15}, %16, %17, 1, 1, 1, 1, 0;"
                      : F4(d, 0), F4(d, 4), F4(d, 8), F4(d, 12) : "l"(a), "l"(b));
}
#define F16(d, i) F4(d, i), F4(d, i + 4), F4(d, i + 8), F4(d, i + 12)
template <int TA>
__device__ __forceinline__ void wgmma_ss128(float* d, uint64_t a, uint64_t b, int sc) {
    asm volatile("{.reg .pred p; setp.ne.b32 p, %66, 0;\n wgmma.mma_async.sync.aligned.m64n128k16.f32.bf16.bf16 "
                 "{%0,%1,%2,%3,%4,%5,%6,%7,%8,%9,%10,%11,%12,%13,%14,%15,%16,%17,%18,%19,%20,%21,%22,%23,%24,%25,%26,%27,%28,%29,%30,%31,"
                 "%32,%33,%34,%35,%36,%37,%38,%39,%40,%41,%42,%43,%44,%45,%46,%47,%48,%49,%50,%51,%52,%53,%54,%55,%56,%57,%58,%59,%60,%61,%62,%63}, %64, %65, p, 1, 1, %67, 1;}"
                 : F16(d, 0), F16(d, 16), F16(d, 32), F16(d, 48) : "l"(a), "l"(b), "r"(sc), "n"(TA));
}

__device__ __forceinline__ float warp_sum(float v) {
#pragma unroll
    for (int o = 16; o; o >>= 1) v += __shfl_xor_sync(~0u, v, o);
    return v;
}
__device__ __forceinline__ float bfround(float x) { return __bfloat162float(__float2bfloat16(x)); }

__device__ __forceinline__ void wait_count1(const uint32_t* p, uint32_t target) {
    int it = 0;
#pragma unroll 1
    while (true) {
        uint32_t v;
        asm volatile("ld.acquire.gpu.global.u32 %0, [%1];" : "=r"(v) : "l"(p) : "memory");
        if (v >= target) break;
        spin_guard(++it);
    }
}
__device__ __forceinline__ void signal_count(uint32_t* p) { asm volatile("red.release.gpu.global.add.u32 [%0], 1;" ::"l"(p) : "memory"); }
__device__ __forceinline__ void e_expect(uint32_t b, uint32_t tx) {
    asm volatile("{.reg .pred p; elect.sync _|p, 0xffffffff; @p mbarrier.arrive.expect_tx.shared.b64 _, [%0], %1;}" ::"r"(b), "r"(tx) : "memory");
}
__device__ __forceinline__ uint64_t evict_first() { uint64_t p; asm("createpolicy.fractional.L2::evict_first.b64 %0, 1.0;" : "=l"(p)); return p; }
__device__ __forceinline__ void e_tma2d_ef(uint32_t dst, const CUtensorMap* m, int c0, int c1, uint32_t bar) {
    asm volatile("{.reg .pred p; elect.sync _|p, 0xffffffff;\n @p cp.async.bulk.tensor.2d.shared::cluster.global.mbarrier::complete_tx::bytes.L2::cache_hint [%0], [%1, {%3, %4}], [%2], %5;}"
                 ::"r"(dst), "l"(m), "r"(bar), "r"(c0), "r"(c1), "l"(evict_first()) : "memory");
}
__device__ __forceinline__ void e_tma2d(uint32_t dst, const CUtensorMap* m, int c0, int c1, uint32_t bar) {
    asm volatile("{.reg .pred p; elect.sync _|p, 0xffffffff;\n @p cp.async.bulk.tensor.2d.shared::cluster.global.mbarrier::complete_tx::bytes [%0], [%1, {%3, %4}], [%2];}"
                 ::"r"(dst), "l"(m), "r"(bar), "r"(c0), "r"(c1) : "memory");
}
__device__ __forceinline__ void e_tma2d_mc_ef(uint32_t dst, const CUtensorMap* m, int c0, int c1, uint32_t bar) {
    asm volatile("{.reg .pred p; elect.sync _|p, 0xffffffff;\n @p cp.async.bulk.tensor.2d.shared::cluster.global.mbarrier::complete_tx::bytes.multicast::cluster.L2::cache_hint [%0], [%1, {%3, %4}], [%2], %5, %6;}"
                 ::"r"(dst), "l"(m), "r"(bar), "r"(c0), "r"(c1), "h"((uint16_t)3), "l"(evict_first()) : "memory");
}
__device__ __forceinline__ uint32_t wait_count_w(const uint32_t* p, uint32_t target) {
    int it = 0;
#pragma unroll 1
    while (true) {
        uint32_t v;
        asm volatile("ld.acquire.gpu.global.u32 %0, [%1];" : "=r"(v) : "l"(p) : "memory");
        if (__all_sync(~0u, v >= target)) return v;
        spin_guard(++it);
    }
}

__device__ __forceinline__ uint4 pack8(const float* x) {
    return make_uint4(pack2(x[0], x[1]), pack2(x[2], x[3]), pack2(x[4], x[5]), pack2(x[6], x[7]));
}
constexpr int NL = 6;
constexpr uint32_t HCH = 5120, HBUF = 8 * HCH;
constexpr uint32_t SM_SX = 0, SM_ST = 2560, SM_OX = 8192, SM_LX = 10240, SM_PX = 11392, SM_PA = 12288, SM_VF = 18432, SM_TAB = 26624, SM_WL2 = 41984, SM_HB = 49152, SM_WO = 131072,
                   SM_WL = 196608, SM_PRE = SM_WL, SM_BAR = 227328, SM_TRC = SM_BAR + 256, SM_REC_TOTAL = SM_TRC + 2688;
__host__ __device__ constexpr uint32_t sm_wl(int i) { return i < 5 ? SM_WL + i * 6144 : SM_WL2; }
constexpr uint32_t SB0 = 1024;
constexpr int B_WO = 0, B_HE = 1, B_ROLE = 2, B_HB = 3, B_W = 5;
constexpr int NB_MEM = 1, NB_QK = 2, NB_X1 = 3, NB_X2 = 4, NB_WIN = 5, NB_WG = 6, NB_KDONE = 7, NB_FIN0 = 8, NB_LN = 9, NB_MEM2 = 10, NB_H = 11, NB_A = 12, NB_B = 13, NB_C = 14, NB_F = 15;
constexpr int TPV_DLY = 3;
constexpr int L_AT = 0;
constexpr int D_X2 = 340;
constexpr int NPF1 = 6;
constexpr int NPF = 11;
constexpr int T_GO = 29;
constexpr int GATE_AT = 25;
constexpr int T_X2 = 1875;
constexpr int T_V = 300;
constexpr int VP_AT = 1;
constexpr int PD = 4;
constexpr int PV_FENCE = 0;
constexpr int SSG = 4;
constexpr int SSG_V = 5;
constexpr int SS0_K = 4;
constexpr int SS0_V = 6;
constexpr int NPF0 = 4;
constexpr int STG_FENCE = 1;
constexpr int WO_AT = 0x1100;
constexpr int W_SPEC = 7;
constexpr int NO_GUESS = 0;
constexpr int NPF2 = 9;
constexpr int PF_DLY = 6;
constexpr int H_D = 210;
constexpr int PIN_EPI = 1;

__device__ __forceinline__ uint32_t clk32() { uint32_t t; asm volatile("mov.u32 %0, %%clock;" : "=r"(t) :: "memory"); return t; }
__device__ __forceinline__ uint32_t gtime32() { uint32_t t; asm volatile("mov.u32 %0, %%globaltimer_lo;" : "=r"(t) :: "memory"); return t; }
template <int N> __device__ __forceinline__ uint32_t delay(uint32_t zero) {
    float x = __uint_as_float(clk32());
#pragma unroll
    for (int i = 0; i < N; i++) asm volatile("ex2.approx.ftz.f32 %0, %0;" : "+f"(x));
    return __float_as_uint(x) & zero;
}
__device__ __forceinline__ uint32_t clk_after(uint32_t x, uint32_t zero) {
    unsigned long long c = 0;
    asm volatile("{.reg .pred p; setp.eq.u32 p, %1, 0; @p mov.u64 %0, %%clock64;}" : "+l"(c) : "r"(x & zero) : "memory");
    return (uint32_t)c;
}
__device__ __forceinline__ uint32_t later(uint32_t a, uint32_t b) { return a + max((int)(b - a), 0); }
__device__ __forceinline__ void wait_clk(uint32_t t) {
#pragma unroll 1
    while (true) {
        unsigned long long c;
        asm volatile("mov.u64 %0, %%clock64;" : "=l"(c) :: "memory");
        if ((int)((uint32_t)c - t) >= 0) break;
    }
}
__device__ __forceinline__ uint32_t opaque(uint32_t v) { return __shfl_sync(~0u, v, threadIdx.x & 31); }
__device__ __forceinline__ uint32_t xor_or(uint32_t a, uint32_t b, uint32_t t) {
    uint32_t r; asm volatile("lop3.b32 %0, %1, %2, %3, 0x7E;" : "=r"(r) : "r"(a), "r"(b), "r"(t)); return r;
}
__device__ __forceinline__ uint32_t or3(uint32_t a, uint32_t b, uint32_t c) {
    uint32_t r; asm volatile("lop3.b32 %0, %1, %2, %3, 0xFE;" : "=r"(r) : "r"(a), "r"(b), "r"(c)); return r;
}
__device__ __forceinline__ uint32_t settag(uint32_t v, uint32_t tag) {
    uint32_t r; asm("lop3.b32 %0, %1, 1, %2, 0xB8;" : "=r"(r) : "r"(v), "r"(tag)); return r;
}
__device__ __forceinline__ void ldg1_if(uint32_t& v, const void* p, bool c) {
    asm volatile("{.reg .pred p; setp.ne.u32 p, %2, 0; @p ld.relaxed.gpu.global.u32 %0, [%1];}" : "+r"(v) : "l"(p), "r"((uint32_t)c) : "memory");
}
__device__ __forceinline__ void sts2(uint32_t a, float x, float y) { asm volatile("st.shared.v2.f32 [%0], {%1,%2};" ::"r"(a), "f"(x), "f"(y) : "memory"); }
__device__ __forceinline__ void sts4f(uint32_t a, float x, float y, float z, float w) {
    asm volatile("st.shared.v4.f32 [%0], {%1,%2,%3,%4};" ::"r"(a), "f"(x), "f"(y), "f"(z), "f"(w) : "memory");
}
__device__ __forceinline__ void sts1(uint32_t a, uint32_t x) { asm volatile("st.shared.u32 [%0], %1;" ::"r"(a), "r"(x) : "memory"); }
__device__ __forceinline__ uint32_t lds1(uint32_t a) { uint32_t v; asm volatile("ld.shared.u32 %0, [%1];" : "=r"(v) : "r"(a) : "memory"); return v; }
__device__ __forceinline__ float4 lds4f(uint32_t a) {
    float4 v; asm volatile("ld.shared.v4.f32 {%0,%1,%2,%3}, [%4];" : "=f"(v.x), "=f"(v.y), "=f"(v.z), "=f"(v.w) : "r"(a) : "memory"); return v;
}
__device__ __forceinline__ float2 lds2f(uint32_t a) {
    float2 v; asm volatile("ld.shared.v2.f32 {%0,%1}, [%2];" : "=f"(v.x), "=f"(v.y) : "r"(a) : "memory"); return v;
}
__device__ __forceinline__ bool any_bit0(uint32_t x) {
    uint32_t r;
    asm volatile("{.reg .pred p, q; .reg .b32 t; and.b32 t, %1, 1; setp.ne.u32 p, t, 0; vote.sync.any.pred q, p, 0xffffffff; selp.u32 %0, 1, 0, q;}" : "=r"(r) : "r"(x));
    return r;
}
__device__ __forceinline__ float rcp_fast(float x) { float r; asm("rcp.approx.ftz.f32 %0, %1;" : "=f"(r) : "f"(x)); return r; }
__device__ __forceinline__ void stsm4(uint32_t a, uint32_t r0, uint32_t r1, uint32_t r2, uint32_t r3) {
    asm volatile("stmatrix.sync.aligned.m8n8.x4.shared.b16 [%0], {%1,%2,%3,%4};" ::"r"(a), "r"(r0), "r"(r1), "r"(r2), "r"(r3) : "memory");
}
__device__ __forceinline__ void stsm4t(uint32_t a, uint32_t r0, uint32_t r1, uint32_t r2, uint32_t r3) {
    asm volatile("stmatrix.sync.aligned.m8n8.x4.trans.shared.b16 [%0], {%1,%2,%3,%4};" ::"r"(a), "r"(r0), "r"(r1), "r"(r2), "r"(r3) : "memory");
}
__device__ __forceinline__ void cp_async16(uint32_t dst, const void* src) { asm volatile("cp.async.cg.shared.global [%0], [%1], 16;" ::"r"(dst), "l"(src) : "memory"); }
__device__ __forceinline__ void cp_async16_ef(uint32_t dst, const void* src) {
    asm volatile("cp.async.cg.shared.global.L2::cache_hint [%0], [%1], 16, %2;" ::"r"(dst), "l"(src), "l"(evict_first()) : "memory");
}
__device__ __forceinline__ uint32_t prmt(uint32_t a, uint32_t b, uint32_t c) { uint32_t r; asm("prmt.b32 %0, %1, %2, %3;" : "=r"(r) : "r"(a), "r"(b), "r"(c)); return r; }
__device__ __forceinline__ uint32_t hadd2h(uint32_t a, uint32_t b) { uint32_t r; asm("add.rn.f16x2 %0, %1, %2;" : "=r"(r) : "r"(a), "r"(b)); return r; }
__device__ __forceinline__ uint32_t hmax2h(uint32_t a, uint32_t b) { uint32_t r; asm("max.f16x2 %0, %1, %2;" : "=r"(r) : "r"(a), "r"(b)); return r; }
__device__ __forceinline__ uint32_t max3u(uint32_t a, uint32_t b, uint32_t c) { return __vimax3_u32(a, b, c); }

__device__ __forceinline__ void h_load(uint32_t sb, const uint8_t* hsrc, int pass, uint32_t rank, uint32_t rot, uint32_t wq, bool arm = true, uint32_t skip = 0) {
    const uint32_t bar = sb + SM_BAR + 8 * (B_HB + (pass & 1)), c = (wq + rot) & 3, dst = sb + SM_HB + (pass & 1) * HBUF + (rank * 4 + c) * HCH + skip;
    const uint8_t* src = hsrc + ((size_t)pass * 65536 + c * 4096 + skip);
    if (arm && wq == 0) e_expect(bar, 32768 - 8 * skip);
    asm volatile("{.reg .pred p; elect.sync _|p, 0xffffffff;\n"
                 " @p cp.async.bulk.shared::cluster.global.mbarrier::complete_tx::bytes.multicast::cluster.L2::cache_hint [%0], [%1], %4, [%2], %3, %5;}"
                 ::"r"(dst), "l"(src), "r"(bar), "h"((uint16_t)3), "r"(4096 - skip), "l"(evict_first()) : "memory");
}
__device__ __forceinline__ uint4 ldg_b128(const void* p) {
    uint4 v;
    asm volatile("{.reg .b128 t; .reg .b64 a, b; ld.relaxed.gpu.global.b128 t, [%4]; mov.b128 {a, b}, t; mov.b64 {%0,%1}, a; mov.b64 {%2,%3}, b;}"
                 : "=r"(v.x), "=r"(v.y), "=r"(v.z), "=r"(v.w) : "l"(p) : "memory");
    return v;
}
__device__ __forceinline__ void stg_b128_if(bool c, void* p, uint32_t x, uint32_t y, uint32_t z, uint32_t w) {
    asm volatile("{.reg .pred p; .reg .b128 t; .reg .b64 a, b; setp.ne.u32 p, %5, 0; mov.b64 a, {%1,%2}; mov.b64 b, {%3,%4}; mov.b128 t, {a, b}; @p st.relaxed.gpu.global.b128 [%0], t;}"
                 ::"l"(p), "r"(x), "r"(y), "r"(z), "r"(w), "r"((uint32_t)c) : "memory");
}
__device__ __forceinline__ float pretag(float x, uint32_t add, uint32_t keep) { return __uint_as_float((__float_as_uint(x) + add) & keep); }

template <bool MASK, class F>
__device__ __forceinline__ void softmax_rows(uint32_t src, uint32_t dst, uint32_t g16, int row0, F mid) {
    const uint32_t u = (g16 >> 7) & 3, e = ((g16 >> 9) << 3) | ((g16 >> 4) & 7);
    const uint32_t se = src + e * 8, su = se + u * 1088;
    const float2 p0 = lds2f(su), p1 = lds2f(su + 256), p2 = lds2f(su + 512), p3 = lds2f(su + 768);
    const float2 m0 = lds2f(se + 4352), m1 = lds2f(se + 4352 + 256), m2 = lds2f(se + 4352 + 512), m3 = lds2f(se + 4352 + 768);
    float a0 = (p0.x + p1.x) + (p2.x + p3.x), a1 = (p0.y + p1.y) + (p2.y + p3.y);
    const float a2 = (m0.x + m1.x) + (m2.x + m3.x), a3 = (m0.y + m1.y) + (m2.y + m3.y);
    mid(__float_as_uint(a3));
    if (MASK) {
        const int vis = row0 + (e >> 2) - 2 * (e & 3) - 8 * u;
        if (vis < 0) a0 = -1e9f / 0.08838834764831845f;
        if (vis < 1) a1 = -1e9f / 0.08838834764831845f;
    }
    int k = __float_as_int(fmaxf(fmaxf(a0, a1), fmaxf(a2, a3)));
    k ^= (k >> 31) & 0x7fffffff;
    const bool hi = g16 & 64;
    const int k0 = __reduce_max_sync(~0u, hi ? INT_MIN : k), k1 = __reduce_max_sync(~0u, hi ? k : INT_MIN);
    k = hi ? k1 : k0;
    const float m = __int_as_float(k ^ ((k >> 31) & 0x7fffffff));
    const float sl2 = 0.08838834764831845f * 1.4426950408889634f, mb = -m * sl2;
    sts1(dst + e * 16 + u * 4, pack2(ex2(fmaf(a0, sl2, mb)), ex2(fmaf(a1, sl2, mb))));
    sts1(dst + 512 + e * 4, pack2(ex2(fmaf(a2, sl2, mb)), ex2(fmaf(a3, sl2, mb))));
}

__device__ __forceinline__ uint32_t pack_h2(float lo, float hi) {
    uint32_t r; asm("cvt.rn.satfinite.f16x2.f32 %0, %1, %2;" : "=r"(r) : "f"(hi), "f"(lo)); return r;
}
__device__ __forceinline__ float2 unpack_h2(uint32_t u) {
    float2 r; asm("{.reg .b16 l, h; mov.b32 {l, h}, %2; cvt.f32.f16 %0, l; cvt.f32.f16 %1, h;}" : "=f"(r.x), "=f"(r.y) : "r"(u)); return r;
}
__device__ __forceinline__ uint32_t h2bf(uint32_t u) {
    uint32_t r;
    asm volatile("{.reg .b16 l, h; .reg .f32 a, b; mov.b32 {l, h}, %1; cvt.f32.f16 a, l; cvt.f32.f16 b, h; cvt.rn.bf16x2.f32 %0, b, a;}" : "=r"(r) : "r"(u));
    return r;
}
__device__ __forceinline__ void red_h10(bool c, void* p, void* q, uint32_t x, uint32_t y, uint32_t z, uint32_t w, uint32_t e) {
    asm volatile("{.reg .pred p; setp.ne.u32 p, %7, 0; red.relaxed.gpu.global.add.noftz.v4.f16x2 [%0], {%2,%3,%4,%5};\n"
                 " @p red.relaxed.gpu.global.add.noftz.f16x2 [%1], %6;}" ::"l"(p), "l"(q), "r"(x), "r"(y), "r"(z), "r"(w), "r"(e), "r"((uint32_t)c) : "memory");
}
constexpr float Q_SCALE = 1024.0f;
constexpr float SM_L2E = 0.08838834764831845f * 1.4426950408889634f * Q_SCALE;
template <int V> struct IC { static constexpr int value = V; };
typedef unsigned long long u64;
__device__ __forceinline__ uint32_t lo32(u64 v) { return (uint32_t)v; }
__device__ __forceinline__ uint32_t hi32(u64 v) { return (uint32_t)(v >> 32); }
__device__ __forceinline__ u64 ldg_u64(const void* p) { u64 v; asm volatile("ld.relaxed.gpu.global.b64 %0, [%1];" : "=l"(v) : "l"(p) : "memory"); return v; }
struct RecTime { uint32_t go, x2, v, dx2, h; };
__device__ __forceinline__ void rec_main(uint32_t sb, const CUtensorMap* tWo, uint8_t* arena, int role, int hinfo, int wg, uint32_t zero, const RecTime& tm) {
    const int hA = hinfo & 255;
    const int tid = threadIdx.x, t = tid & 127, lane = tid & 31, wi = t >> 5;
    const uint32_t bars = sb + SM_BAR;
    const int head = role >> 2, qd = role & 3, j = blockIdx.x & 1, kh = role & 1;
    const uint32_t mypar = head >= hA;
    const uint32_t wiu = __reduce_max_sync(~0u, wi);
    const bool warp0 = wiu == 0;
    const uint8_t* hsrc = (const uint8_t*)g_himg + kh * 32768 + j * 16384;
    auto tokbase = [&](int ty) { return ((ty + 1) << 21) + blk(lb_tok(head), mypar ^ ((hinfo >> (8 + ty)) & 1)); };
    const uint32_t tbw = tokbase(wg), tbq = tokbase(0) + (qd >> 1) * 2048 + (qd & 1) * 8;
#define KS(p) (4 * (((p) >> 1) & 7) + ((p) >> 4) + 2 * ((p) & 1))
    uint32_t w[32 - NL][4];
    uint4 wl5;
    if (wg == 2) bar_arrive(NB_WIN, 384);
    const uint32_t po = (1 << 20) + j * 16384 + kh * 2048;
    const uint32_t c16 = kh * 2048 + ((2 * j + (wi >> 1)) * 32 + lane) * 16, xso = blk(lb_x2(head), mypar);
    const uint32_t x2o = xso + wg * 16384 + (wi & 1) * 2048 + (c16 >> 1), tko = tbw + (wi & 1) * 16384 + c16;
    {
        stg_rlx2(arena + x2o, 0, 0);
#pragma unroll
        for (int i = 0; i < 4; i++) stg_rlx4(arena + ((i & 1 ? tko : tbw + (po ^ 2048) + t * 16) + (i >> 1) * 32768), 0, 0, 0, 0);
    }
    const uint32_t frow = ((lane >> 4) * 8 + (lane & 7)) * 128, fx = ((lane >> 3) & 1) ^ (lane & 7);
    {
#pragma unroll 1
        for (int i = 0; i < 4; i++) mbar_wait_w(bars + 8 * (B_W + (wg == 2 ? 8 + i : 2 * i + wg)), 0);
        const uint32_t stg = sb + wg * 65536;
#pragma unroll
        for (int p = NL; p < 32; p++) ldsm4t(w[p - NL], stg + KS(p) * 2048 + frow + ((fx ^ (2 * wi)) << 4));
#pragma unroll
        for (int i = 0; i < NL; i++) {
            wl5 = lds4(stg + KS(i) * 2048 + t * 16);
            if (i < 5) sts4(sb + sm_wl(i) + tid * 16, wl5.x, wl5.y, wl5.z, wl5.w);
        }
        fence_async_smem();
        if (wg < 2) bar_sync(NB_WG, 256);
        if (wg > 0) wait_count_w(&g_tick[32 + (lane & 3) * 8], wg);
        if (wg == 1) {
            mbar_arrive_cluster_if(t == 0, bars + 8 * B_HE, j ^ 1);
            asm volatile("fence.proxy.async.global;" ::: "memory");
            mbar_wait_w(bars + 8 * B_HE, 0);
#pragma unroll 1
            for (int i = 0; i < 2; i++) h_load(sb, hsrc, i, j, head, wiu, true, i ? 0 : 2048);
        }
    }
    uint32_t g16 = opaque(t * 16);
    {
        const uint32_t wr = ((wg * 4 + wi) ^ head) & 7;
        const uint32_t pc = wg < 2 ? acc_piece(wr >> 2, qd, wr & 3) : acc_piece(kh, wi, 0);
        const uint32_t lm = sb + SM_HB + 4096 + (lane & 7) * 128;
        const uint32_t a0 = wg < 2 ? sb + SM_WL + wg * 2048 + frow + ((fx ^ (2 * wi)) << 4) : blk(LB_STAMP + (wi >> 1), mypar) + stamp_line(wi, lane >> 3) + (lane & 7) * 16;
        const uint32_t a1 = pc + lane * 16;
        const uint32_t a2 = wg < 2 ? pc + 512 + (lane >> 3) * 4 : (role >> 2) * 1024 + (lane < 8 ? (role & 3) * 128 : 384) + lane * 16;
        const uint32_t a3 = wg < 2 ? sb + SM_WO + (wr >> 2) * 32768 + frow + ((fx ^ (2 * (wr & 3))) << 4) : qd * 65536 + head * 2048 + wi * 512 + lane * 4;
        const uint32_t a4 = wg < 2 ? lm + ((fx ^ ((lane >> 4) * 4)) << 4) : lm + (fx << 4) + ((lane >> 4) + 2 * wi) * HCH;
        if (wg < 2) bar_arrive(NB_X2, 384);
        else bar_sync(NB_X2, 384);
        if (NL > 5) {
            sts4(sb + SM_WL2 + tid * 16, wl5.x, wl5.y, wl5.z, wl5.w);
            fence_async_smem();
            bar_sync(NB_WG + 1 + wg, 128);
        }
        sts4(sb + SM_TAB + wg * 5120 + g16, a0, x2o,
             wg ? xso + (wg == 2 ? 32768 : 0) + t * 8 : blk(LB_STAMP + ((lane >> 1) & 1), (lane >> 2) & 1) + stamp_line(lane, qd) + head * 4, tko);
        sts4(sb + SM_TAB + wg * 5120 + 2048 + g16, a1, a2, a3, a4);
        sts2(sb + SM_TAB + wg * 5120 + 4096 + t * 8, __uint_as_float(tbw + t * 16), __uint_as_float((wg ? tbq : tokbase(1)) + t * 16));
    }
    const uint32_t ONES = 0x3f803f80u, tabw = sb + SM_TAB + wg * 5120;
#define LAST ((g16 & 0x70) == 0x70)

    auto pa_ptr = [&](int p) { return arena + (((p & 1) ^ 1) * 32768 + po + lds1(tabw + 4096 + (g16 >> 1))); };
    auto pa_request = [&](int p) { cp_async16(sb + SM_PA + wg * 2048 + g16, pa_ptr(p)); };
    auto pa_get = [&](int p) {
        asm volatile("cp.async.wait_all;" ::: "memory");
        uint4 pa = lds4(sb + SM_PA + wg * 2048 + g16);
        int it = 0;
#pragma unroll 1
        while (any_bit0(pa.x ^ ((p - 1) >> 1) ^ 1) && p > 0 && p <= NSEG) { pa = ldg_b128(pa_ptr(p)); spin_guard(++it); }
        return pa;
    };
    auto pass_init = [&](float* acc, int n, uint4 pa) {
#pragma unroll
        for (int i = 0; i < 4; i++) { acc[2 * i] = bflo((&pa.x)[i]); acc[2 * i + 1] = bfhi((&pa.x)[i]); }
#pragma unroll
        for (int i = 8; i < n; i++) acc[i] = 0.f;
    };
    auto pass_run = [&](auto vc, int p, float* acc, auto mid) {
        constexpr bool V = decltype(vc)::value;
#define HB(ks) dadd(mkdesc(SB0 + SM_HB + ((ks) >> 2) * HCH + ((ks) & 3) * 32, 16, 1024, 1), (p & 1) * (HBUF / 16))
        wg_fence();
#pragma unroll
        for (int i = 0; i < 32; i++) {
            constexpr int GAP = V ? SSG_V : SSG, SS0 = V ? SS0_V : SS0_K;
            const int u = i < SS0 ? 0 : (i - SS0 + GAP - 1) / GAP, q = i - (u < NL ? u : NL);
            if (i >= SS0 && (i - SS0) % GAP == 0 && u < NL) wgmma_tok_ss<V>(acc, dadd(mkdesc(SB0 + sm_wl(u), 8192, 1024, 1), (V ? 2 : wg) * 128), HB(KS(u)));
            else wgmma_tok_rs<V>(acc, w[q], HB(KS(NL + q)), 1);
            mid(i);
        }
        wg_commit();
    };
    auto pass_out = [&](auto tc, int p, float* acc, auto mid) {
        constexpr int TY = decltype(tc)::value;
        const bool V = TY == 2 || (TY == 4 && wg == 2), Q = TY >= 3 && wg == 0;
        const int b = p & 1, s = p - 2;
        (void)s;
        const uint32_t ftag = (((p - 1) >> 1) & 1) ^ 1, ptag = ((p >> 1) & 1) ^ 1;
        const bool tg = V || !(g16 & 64);
        const uint32_t add = tg ? (ftag ^ 1) << 16 : 0u, keep = tg ? 0xfffe0000u : ~0u;
        const uint32_t add1 = V ? 0u : add, keep1 = V ? ~0u : keep;
        const uint32_t add2 = Q ? add : 0u, keep2 = Q ? keep : ~0u;
        uint8_t* pdst = arena + (b * 32768 + (po ^ 2048) + lds1(tabw + 4096 + (g16 >> 1)));
        uint8_t* fdst = arena + ((b ^ 1) * 32768 + lds1(tabw + 12 + g16));
        if (PIN_EPI) asm volatile("" : "+l"(pdst), "+l"(fdst));
        mid(0);
        uint32_t r0 = pack2(pretag(acc[0], add, keep), pretag(acc[1], add1, keep1));
        uint32_t r1 = pack2(acc[2], acc[3]), r3 = pack2(acc[6], acc[7]);
        uint32_t r2 = pack2(pretag(acc[4], add2, keep2), pretag(acc[5], add2, keep2));
        if (!V) { r0 = movm(r0); r1 = movm(r1); r2 = movm(r2); r3 = movm(r3); }
        mid(1);
        stg_b128_if(p < NSEG, pdst, settag(pack2(pretag(acc[8], (ptag ^ 1) << 16, 0xfffe0000u), acc[9]), ptag), pack2(acc[10], acc[11]), pack2(acc[12], acc[13]), pack2(acc[14], acc[15]));
        stg_b128_if(p > 0 && p <= NSEG, fdst, settag(r0, ftag), r1, Q ? settag(r2, ftag) : r2, r3);
    };
    auto nop = [](int) {};
    auto wait0 = [](int i) { if (i == 0) wg_wait<0>(); };
    uint4 tf[2][2];
    auto load_tok = [&](int s, uint32_t o) {
        const uint8_t* ts = arena + ((s & 1) * 32768 + o);
#pragma unroll
        for (int a = 0; a < 2; a++)
#pragma unroll
            for (int b = 0; b < 2; b++) tf[a][b] = ldg_b128(ts + a * 16384 + b * 2048);
    };

    auto wo_load = [&](int stage) {
        if (wg == 2 && ((WO_AT >> (4 * wiu)) & 15) == stage) {
            const int c0 = (wiu >> 1) * 512 + qd * 128 + (wiu & 1) * 64;
            e_expect(bars + 8 * B_WO, 16384);
            e_tma2d(sb + SM_WO + wiu * 16384, tWo, c0, head * DH, bars + 8 * B_WO);
            e_tma2d(sb + SM_WO + wiu * 16384 + 8192, tWo, c0, head * DH + 64, bars + 8 * B_WO);
        }
    };
#pragma unroll 1
    for (int p = 0; p <= (wg >> 1); p++) {
        mbar_wait_w(bars + 8 * (B_HB + p), 0);
        float acc[16];
        pass_init(acc, 16, pa_get(p));
        wo_load(p);
        pass_run(IC<0>(), p, acc, nop);
        if (p) {
            mbar_wait_w(bars + 8 * B_HE, 1);
            asm volatile("fence.proxy.async.global;" ::: "memory");
            h_load(sb, hsrc, 2, j, head, wiu);
        }
        pass_out(IC<4>(), p, acc, wait0);
        if (wg < 2) {
            bar_arrive(NB_C, 384);
            if (wg == 0) bar_arrive(NB_WIN, 384);
        } else if (p == 0) {
            bar_sync(NB_C, 384);
            mbar_arrive_cluster_if(g16 == 0, bars + 8 * B_HE, j ^ 1);
        }
        pa_request(p + 1);
    }
    if (wg < 2) {
        mbar_wait_w(bars + 8 * (B_HB + 1), 0);
        uint4 pa = pa_get(1);
        uint32_t wl = lds1(tabw + g16);
#pragma unroll 1
        for (int s = 0; s < NSEG; s++) {
            uint32_t w0[NL][4], xo, lm, fz = 0;
            float acc[16];
#pragma unroll
            for (int i = 0; i < 4; i++)
                asm volatile("shl.b32 %0, %4, 16; and.b32 %1, %4, 0xffff0000; mov.b32 %2, %5; mov.b32 %3, %5;"
                             : "=&f"(acc[2 * i]), "=f"(acc[2 * i + 1]), "=f"(acc[8 + 2 * i]), "=f"(acc[9 + 2 * i]) : "r"((&pa.x)[i]), "r"(zero));
#pragma unroll
            for (int i = 0; i < NL; i++) ldsm4t(w0[i], wl + (sm_wl(i) - SM_WL));
            if (wg == 0) bar_sync(NB_B, 256);
            else bar_sync(NB_WIN, 384);
            pass_run(IC<0>(), s + 1, acc, [&](int i) { if (i == GATE_AT && wg) bar_arrive(NB_B, 256); });
            xo = lds1(tabw + 4 + g16);
            lm = lds1(tabw + 2060 + g16) + (s & 1) * HBUF;
            pass_out(IC<3>(), s + 1, acc, [&](int i) {
                if (i == 0) {
                    wg_wait<0>();
                    if (wg == 0) bar_arrive(NB_MEM, 384);
                    fz |= clk32();
                }
                if (i == 1 && wg) bar_sync(NB_F, 256);
            });
            asm volatile("" : "+r"(lm));
            if (wg == 0) bar_sync(NB_MEM2, 256);
            else bar_sync(NB_MEM, 384);
            float c[4][4];
            uint32_t bq[PD][4];
#define MEMF(it) ((lm ^ (((it) >> 3) * 32)) + ((it) & 7) * HCH)
#pragma unroll
            for (int it = 0; it < PD; it++) ldsm4(bq[it], MEMF(it));
#pragma unroll
            for (int it = 0; it < 16; it++) {
                uint32_t* bfr = bq[it % PD];
                const uint32_t* wa = 2 * it < NL ? w0[2 * it < NL ? 2 * it : 0] : w[2 * it < NL ? 0 : 2 * it - NL];
                const uint32_t* wb = 2 * it + 1 < NL ? w0[2 * it + 1 < NL ? 2 * it + 1 : 0] : w[2 * it + 1 < NL ? 0 : 2 * it + 1 - NL];
                float *ca = c[(2 * it) & 3], *cb = c[(2 * it + 1) & 3];
                if (it < 2) { mma16816z(ca, wa, bfr[0], bfr[1]); mma16816z(cb, wb, bfr[2], bfr[3]); }
                else { mma16816(ca, wa[0], wa[1], wa[2], wa[3], bfr[0], bfr[1]); mma16816(cb, wb[0], wb[1], wb[2], wb[3], bfr[2], bfr[3]); }
                if (it + PD < 16) ldsm4(bfr, MEMF(it + PD));
            }
            const float qs = wg ? 1.0f : 1.0f / Q_SCALE;
#define CSUM(e) fmaf(c[2][e] + c[3][e], qs, (c[0][e] + c[1][e]) * qs)
            const uint32_t r0 = pack2(CSUM(0), CSUM(1)), r1 = pack2(CSUM(2), CSUM(3));
            bar_arrive(NB_QK + (r0 & zero), 384);
            stg_rlx2(arena + xo, settag(movm(r0), (s & 1) ^ 1), movm(r1));
            const uint32_t tx = later(lds1(sb + SM_LX + 1040) + tm.x2, clk_after(r0, zero) + tm.dx2);
            g16 |= (fz | tx) & zero;
            {
                const uint32_t l16 = sb + (g16 & 0x1f0), g8 = g16 >> 1;
                const uint32_t tag = (s & 1) ^ 1, ttag = ((s >> 1) & 1) ^ 1;
                uint32_t wf[NPF][4], a3;
#define WF(f) (a3 + ((f) & 1) * 16384 + ((f) >> 1) * 2048)
                if (wg == 1) {
                    float sc[5][4];
                    uint4 (&kf)[2][2] = tf;
                    uint32_t qa[2][4], km[4], fz;
                    const uint32_t sd = lds1(sb + SM_TAB + 8 + g16);
                    int it = 0;
                    bool bad;
#pragma unroll 1
                    do {
                        u64 qf[2], x[8];
                        const float2 u = lds2f(tabw + 4096 + g8);
                        load_tok(s, __float_as_uint(u.x));
                        const uint8_t *xp = arena + lds1(tabw + 8 + g16), *tq = arena + ((s & 1) * 32768 + __float_as_uint(u.y));
                        asm volatile("" : "+l"(xp));
                        asm volatile("" : "+l"(tq));
#pragma unroll
                        for (int a = 0; a < 2; a++) qf[a] = ldg_u64(tq + a * 16384);
                        spin_guard(++it);
                        wait_clk(tx);
#pragma unroll
                        for (int i = 0; i < 8; i++) x[i] = ldg_u64(xp + (i >> 2) * 16384 + (i & 3) * 1024);
                        fz = clk32();
                        const uint32_t bt = or3(xor_or(lo32(qf[0]), lo32(qf[1]), ttag), xor_or(kf[0][0].x, kf[0][1].x, ttag), xor_or(kf[1][0].x, kf[1][1].x, ttag));
#pragma unroll
                        for (int a = 0; a < 2; a++) { qa[a][1] = or3(lo32(qf[a]), zero, 0); qa[a][3] = or3(hi32(qf[a]), zero, 0); }
                        fz |= clk32();
#pragma unroll
                        for (int a = 0; a < 2; a++) { qa[a][0] = hadd2v(lo32(x[2 * a]), lo32(x[2 * a + 1])); qa[a][2] = hadd2v(hi32(x[2 * a]), hi32(x[2 * a + 1])); }
#pragma unroll
                        for (int a = 0; a < 2; a++) { km[2 * a] = hadd2v(lo32(x[4 + 2 * a]), lo32(x[5 + 2 * a])); km[2 * a + 1] = hadd2v(hi32(x[4 + 2 * a]), hi32(x[5 + 2 * a])); }
                        bad = any_bit0(or3(or3(bt, xor_or(lo32(x[0]), lo32(x[1]), tag), xor_or(lo32(x[2]), lo32(x[3]), tag)), xor_or(lo32(x[4]), lo32(x[5]), tag), xor_or(lo32(x[6]), lo32(x[7]), tag)));
                    } while (bad);
                    mma16816z(sc[0], qa[0], kf[0][0].x, kf[0][0].y);
                    mma16816z(sc[1], qa[0], kf[0][0].z, kf[0][0].w);
                    mma16816z(sc[2], qa[0], kf[0][1].x, kf[0][1].y);
                    mma16816z(sc[3], qa[0], kf[0][1].z, kf[0][1].w);
                    mma16816z(sc[4], qa[0], km[0], km[1]);
                    mma16816(sc[0], qa[1][0], qa[1][1], qa[1][2], qa[1][3], kf[1][0].x, kf[1][0].y);
                    mma16816(sc[1], qa[1][0], qa[1][1], qa[1][2], qa[1][3], kf[1][0].z, kf[1][0].w);
                    mma16816(sc[2], qa[1][0], qa[1][1], qa[1][2], qa[1][3], kf[1][1].x, kf[1][1].y);
                    mma16816(sc[3], qa[1][0], qa[1][1], qa[1][2], qa[1][3], kf[1][1].z, kf[1][1].w);
                    mma16816(sc[4], qa[1][0], qa[1][1], qa[1][2], qa[1][3], km[2], km[3]);
                    const uint32_t sx = sb + SM_SX + (g16 & 0x1f0) * 5;
                    sts4(sx + (g16 >> 5 & 0x30), pack_h2(sc[0][0], sc[0][1]), pack_h2(sc[1][0], sc[1][1]),
                         pack_h2(sc[2][0], sc[2][1]), pack_h2(sc[3][0], sc[3][1]));
                    sts1(sx + 64 + (g16 >> 7 & 0xc), pack_h2(sc[4][0], sc[4][1]));
                    bar_arrive(NB_X1, 256);
                    const uint32_t now = gtime32();
#pragma unroll
                    for (int n = 0; n < 5; n++) sts2(sb + SM_ST + g8 + n * 1088, sc[n][2], sc[n][3]);
                    bar_arrive(NB_H, 256);
                    a3 = lds1(tabw + 2056 + g16) | (fz & zero);
                    asm volatile("{.reg .pred p; setp.lt.u32 p, %2, 128; @p red.relaxed.gpu.global.max.u32 [%0], %1;}"
                                 ::"l"(arena + sd), "r"(__funnelshift_r(now * 8, s + 1, 8)), "r"(g16) : "memory");
                    if (s == 0) mbar_wait_w(bars + 8 * B_WO, 0);
                    a3 += delay<PF_DLY>(zero);
#pragma unroll
                    for (int f = 0; f < NPF; f++) ldsm4t(wf[f], WF(f));
                } else {
                    if (s == 0) { mbar_wait_w(bars + 8 * B_WO, 0); }
                    if (warp0 && !(s & 3)) {
                        const uint32_t need = min((s + 4) / 4 + 2, 17), a = sb + SM_LX + 1024 + ((g16 >> 2) & 12);
                        if (s == 0 || __any_sync(~0u, lds1(a) < need)) sts1(a, wait_count_w(&g_tick[32 + ((g16 >> 4) & 3) * 8], need));
                    }
                    a3 = lds1(tabw + 2056 + g16);
#pragma unroll
                    for (int f = 0; f < NPF0; f++) ldsm4t(wf[f], WF(f));
                    const float2 u = lds2f(tabw + 4096 + g8);
                    const uint8_t *q0 = arena + (tag * 32768 + po + __float_as_uint(u.x)), *q1 = arena + (tag * 32768 + po + __float_as_uint(u.y));
                    wait_clk(tx + tm.h);
                    int it = 0;
                    bool bad;
#pragma unroll 1
                    do {
                        const uint4 p0 = ldg_b128(q0), p1 = ldg_b128(q1);
                        spin_guard(++it);
                        wait_clk(tx + tm.v);
#pragma unroll
                        for (int f = NPF0; f < NPF1; f++) ldsm4t(wf[f], WF(f));
                        sts4(sb + SM_PA + g16, p0.x, p0.y, p0.z, p0.w);
                        sts4(sb + SM_PA + 2048 + g16, p1.x, p1.y, p1.z, p1.w);
                        bad = any_bit0(xor_or(p0.x, p1.x, ((s + 1) >> 1) ^ 1)) && s + 2 <= NSEG;
                    } while (bad);
                    bar_sync(NB_H, 256);
                    softmax_rows<true>(sb + SM_ST, sb + SM_PX, g16, qd * 8, [&](uint32_t v) {
                        a3 += v & zero;
#pragma unroll
                        for (int f = NPF1; f < NPF2; f++) ldsm4t(wf[f], WF(f));
                    });
#pragma unroll
                    for (int f = NPF2; f < NPF; f++) ldsm4t(wf[f], WF(f));
                }
                float2 ls, a12;
                uint8_t *d0, *d1;
                bar_sync(NB_X2, 384);
                float c[4][4];
#pragma unroll
                for (int q = 0; q < 4; q++) {
                    uint32_t ob[4];
                    ldsm4t(ob, l16 + SM_OX + q * 512);
                    if (q == L_AT) ls = lds2f(sb + SM_LX + g8);
                    if (q == 2) { pa = lds4(sb + SM_PA + wg * 2048 + g16); wl = lds1(tabw + g16); }
                    if (q == 2) { a12 = lds2f(tabw + 2048 + g16); d0 = arena + (acc_slot(s + 1) + __float_as_uint(a12.x)); d1 = arena + (acc_slot(s + 1) + __float_as_uint(a12.y)); }
#pragma unroll
                    for (int f = 4 * q; f < 4 * q + 4; f++) {
                        const uint32_t* a = wf[f % NPF];
                        if (f < 4) mma16816z(c[f], a, ob[f & 2], ob[(f & 2) + 1]);
                        else mma16816(c[f & 3], a[0], a[1], a[2], a[3], ob[f & 2], ob[(f & 2) + 1]);
                        if (f + NPF < 16) ldsm4t(wf[f % NPF], WF(f + NPF));
                    }
                }
                if (wg == 0) bar_arrive(NB_WIN, 384);
                const float i0 = rcp_fast(ls.x), i1 = rcp_fast(ls.y);
                uint32_t v[4];
#pragma unroll
                for (int m = 0; m < 4; m++) v[m] = pack_h2((c[m >> 1][(m & 1) * 2] + c[(m >> 1) + 2][(m & 1) * 2]) * i0, (c[m >> 1][(m & 1) * 2 + 1] + c[(m >> 1) + 2][(m & 1) * 2 + 1]) * i1);
                red_h10(LAST, d0, d1, v[0], v[1], v[2], prmt(v[3], ACC_ONE, LAST ? 0x7610 : 0x3210), prmt(v[3], ACC_ONE, 0x7632));
                g16 |= v[0] & zero;
            }
        }
        if (wg) bar_sync(NB_WIN, 384);
    } else {
        auto request = [&](int s, uint32_t o) {
            cp_async16(sb + SM_PA + 4096 + g16, arena + (((s & 1) ^ 1) * 32768 + po + o));
            const uint8_t* ts = arena + ((s & 1) * 32768 + o);
#pragma unroll
            for (int i = 0; i < 4; i++) cp_async16(sb + SM_VF + i * 2048 + g16, ts + (i >> 1) * 16384 + (i & 1) * 2048);
        };
        auto fetch = [&](int s, uint4 t1, auto wait, auto after) {
            const uint32_t mo = acc_slot(s) + t1.x, eo = mo - (g16 & 0x1f0) + 512 + ((g16 >> 5) & 12);
            const uint8_t *ms = arena + mo, *es = arena + eo;
            uint32_t e[4] = {0, 0, 0, 0}, sel = LAST ? 0x5410 : 0x3210, dst[4];
#pragma unroll
            for (int i = 0; i < 4; i++) dst[i] = (t1.w + (s & 1) * HBUF) ^ (i * 32);
            asm volatile("" : "+l"(ms), "+l"(es), "+r"(e[0]), "+r"(e[1]), "+r"(e[2]), "+r"(e[3]), "+r"(sel), "+r"(dst[0]), "+r"(dst[1]), "+r"(dst[2]), "+r"(dst[3]));
            uint32_t late = wait(), fz;
            int it = 0;
            bool bad;
#pragma unroll 1
            do {
                uint4 m[4];
                uint32_t b = 0;
#pragma unroll
                for (int i = 0; i < 4; i++) {
                    m[i] = ldg_rlx4(ms + i * 1024);
                    ldg1_if(e[i], es + i * 1024, LAST);
                }
                if (it == 0) bar_arrive(NB_F, 256);
                const uint32_t now = clk32();
                fz = now;
                after(now & zero);
                sts1(sb + SM_LX + 1040, now - min(late >> 8, 8u) * 57);
                late = 0;
                spin_guard(++it);
#pragma unroll
                for (int i = 0; i < 4; i++) {
                    if (STG_FENCE >> i & 1) fz |= clk32();
                    b |= xor_or(m[i].w, e[i], ACC_ALL);
                    stsm4t(dst[i], h2bf(m[i].x), h2bf(m[i].y), h2bf(m[i].z), h2bf(prmt(m[i].w, e[i], sel)));
                }
                bad = __any_sync(~0u, LAST && b > 0xffffu);
            } while (bad);
            bar_arrive(NB_MEM, 384);
            bar_arrive(NB_MEM2, 256);
            g16 |= fz & zero;
        };
        fetch(0, lds4(tabw + 2048 + g16), []() { return 0u; }, [&](uint32_t z) { request(0, lds1(tabw + 4096 + (g16 >> 1)) + z); });
        wo_load(2);
#pragma unroll 1
        for (int s = 0;; s++) {
            const uint32_t tag = (s & 1) ^ 1, ttag = ((s >> 1) & 1) ^ 1, l16 = sb + (g16 & 0x1f0), g8 = g16 >> 1;
            const int p = s + 2;
            fence_async_smem();
            stg_b128_if(g16 < ((role & 3) ? 128 : 160), arena + (acc_slot(s + 3) + lds1(tabw + 2052 + g16)), 0, 0, 0, 0);
            const uint4 pa = pa_get(p);
            if (p <= NSEG) mbar_wait_w(bars + 8 * (B_HB + (p & 1)), (p >> 1) & 1);
            asm volatile("fence.proxy.async.global;" ::: "memory");
            if (warp0 && s + 3 <= NSEG) e_expect(bars + 8 * (B_HB + ((s + 3) & 1)), 32768);
            uint8_t* xd = arena + lds1(tabw + 4 + g16);
            uint32_t tx;
            float acc[20];
            pass_init(acc, 20, pa);
            bar_sync(NB_QK, 384);
            pass_run(IC<1>(), p, acc, nop);
            pass_out(IC<2>(), p, acc, [&](int i) {
                if (i) return;
                wg_wait<0>();
                const uint32_t r0 = pack2(acc[16], acc[17]);
                stg_rlx2(xd, settag(r0, tag), pack2(acc[18], acc[19]));
                tx = clk_after(r0, zero) + 100;
            });
            uint4 (&vf)[2][2] = tf;
#pragma unroll
            for (int i = 0; i < 4; i++) vf[i >> 1][i & 1] = lds4(sb + SM_VF + i * 2048 + g16);
            uint32_t xv[4] = {0, 0, 0, 0};
            float oc[2][4], lc[4];
            auto pv = [&](uint32_t p0, uint32_t p1, uint32_t p2, uint32_t p3, uint32_t p4, auto mid) {
                lc[0] = lc[1] = lc[2] = lc[3] = 0.f;
                mma16816z(oc[0], &vf[0][0].x, p0, p1);
                mma16816z(oc[1], &vf[1][0].x, p0, p1);
                mma16816(lc, ONES, ONES, ONES, ONES, p0, p1);
                mma16816(oc[0], vf[0][1].x, vf[0][1].y, vf[0][1].z, vf[0][1].w, p2, p3);
                mma16816(oc[1], vf[1][1].x, vf[1][1].y, vf[1][1].z, vf[1][1].w, p2, p3);
                mma16816(lc, ONES, ONES, ONES, ONES, p2, p3);
                mid();
                mma1688(oc[0], xv[0], xv[1], p4);
                mma1688(oc[1], xv[2], xv[3], p4);
                mma1688(lc, ONES, ONES, p4);
            };
            uint32_t so, to, fz = 0;
            uint4 t1;
            int it = 0;
            bool bad;
#pragma unroll 1
            do {
#pragma unroll 1
                for (int i = it; i > 0; i &= zero) load_tok(s, lds1(tabw + 4096 + g8));
                u64 xr[4];
                const uint8_t* xp = arena + lds1(tabw + 8 + g16);
                asm volatile("" : "+l"(xp));
                const uint32_t bt = or3(xor_or(vf[0][0].x, vf[0][1].x, ttag), xor_or(vf[1][0].x, vf[1][1].x, ttag), 0);
                uint32_t sa = sb + SM_SX + (g16 & 0x1f0) * 5;
                asm volatile("" : "+r"(sa));
                spin_guard(it);
                wait_clk(tx);
                if (it++ == 0) bar_sync(NB_X1, 256);
                uint4 sx[5];
#pragma unroll
                for (int i = 0; i < 5; i++) sx[i] = lds4(sa + i * 16);
                __syncwarp();
#pragma unroll
                for (int i = 0; i < 4; i++) xr[i] = ldg_u64(xp + (VP_AT == 2 ? sx[0].x & zero : 0) + i * 1024);
                uint32_t a[5], pm[5];
#pragma unroll
                for (int n = 0; n < 5; n++) {
                    uint32_t u[4];
#pragma unroll
                    for (int w = 0; w < 4; w++) u[w] = n < 4 ? (&sx[w].x)[n] : (&sx[4].x)[w];
                    a[n] = hadd2h(hadd2h(u[0], u[1]), hadd2h(u[2], u[3]));
                }
                uint32_t m = hmax2h(hmax2h(hmax2h(a[0], a[1]), hmax2h(a[2], a[3])), a[4]);
                const uint32_t m1 = __shfl_xor_sync(~0u, m, 1), m2 = __shfl_xor_sync(~0u, m, 2), m3 = __shfl_xor_sync(~0u, m, 3);
                m = hmax2h(hmax2h(m, m1), hmax2h(m2, m3));
                so = lds1(tabw + g16); t1 = lds4(tabw + 2048 + g16); to = lds1(tabw + 4096 + g8);
                const float2 mm = unpack_h2(m);
                const float mf = -SM_L2E * fmaxf(mm.x, mm.y);
#pragma unroll
                for (int n = 0; n < 5; n++) { const float2 u = unpack_h2(a[n]); pm[n] = pack2(ex2(fmaf(u.x, SM_L2E, mf)), ex2(fmaf(u.y, SM_L2E, mf))); }
                pv(pm[0], pm[1], pm[2], pm[3], pm[4], [&]() {
                    if (PV_FENCE & 1) fz = clk32();
#pragma unroll
                    for (int i = 0; i < 2; i++) { xv[2 * i] = hadd2v(lo32(xr[2 * i]), lo32(xr[2 * i + 1])); xv[2 * i + 1] = hadd2v(hi32(xr[2 * i]), hi32(xr[2 * i + 1])); }
                });
                bad = any_bit0(or3(bt, xor_or(lo32(xr[0]), lo32(xr[1]), tag), xor_or(lo32(xr[2]), lo32(xr[3]), tag)));
                if (PV_FENCE & 2) fz |= clk32();
                stsm4(sb + SM_OX + g16, pack2(oc[0][0], oc[0][1]), pack2(oc[0][2], oc[0][3]), pack2(oc[1][0], oc[1][1]), pack2(oc[1][2], oc[1][3]));
                sts2(sb + SM_LX + g8, lc[0], lc[1]);
            } while (bad);
            bar_sync(NB_X2, 384);
            const uint8_t* sp = arena + so;
            uint4 sv = ldg_rlx4(sp);
            if (s + 3 <= NSEG) h_load(sb, hsrc, s + 3, j, head, wiu, false);
            const uint4 pp = lds4(l16 + SM_PX + delay<TPV_DLY>(zero));
            pv(pp.x, pp.y, pp.z, pp.w, lds1(sb + SM_PX + 512 + ((g16 >> 2) & 0x7c)), []() {});
            const float i0 = rcp_fast(lc[0]), i1 = rcp_fast(lc[1]);
            bar_arrive(NB_WIN + ((__float_as_uint(i0) | fz) & zero), 384);
            uint8_t* od = (uint8_t*)g_O + ((size_t)s * (32 * NH * DH * 2) + t1.z);
            const uint32_t ov[4] = {pack2(oc[0][0] * i0, oc[0][1] * i1), pack2(oc[0][2] * i0, oc[0][3] * i1), pack2(oc[1][0] * i0, oc[1][1] * i1), pack2(oc[1][2] * i0, oc[1][3] * i1)};
#pragma unroll
            for (int a = 0; a < 4; a++) if (s + 1 == NSEG) stg_rlx1(od + a * 128, ov[a]);
            if (s + 1 == NSEG) break;
            fetch(s + 1, t1, [&]() {
                int it = 0;
#pragma unroll 1
                while (__any_sync(~0u, (int)(min(__vimin3_u32(sv.x, sv.y, sv.z), sv.w) >> 24) <= s)) {
                    sv = ldg_rlx4(sp);
                    spin_guard(++it);
                }
                const uint32_t tgo = (__reduce_max_sync(~0u, max(max3u(sv.x, sv.y, sv.z), sv.w)) + tm.go + (sv.x & zero)) << 8;
                int late;
#pragma unroll 1
                do { late = gtime32() * 8 - tgo; } while (late < 0);
                __syncwarp();
                return (uint32_t)late;
            }, [&](uint32_t z) {
#pragma unroll
                for (int a = 0; a < 4; a++) stg_rlx1(od + a * 128, ov[a]);
                request(s + 1, to + z);
            });
        }
    }
    asm volatile("cp.async.wait_all;" ::: "memory");
}

struct RecMaps { CUtensorMap wq, wk, wv, wo; };
struct RecPtrs { const bf16 *x, *mem0, *c, *wmod, *w1, *w3; uint8_t* arena; uint32_t zero; RecTime tm; };

__device__ __forceinline__ float silu_bf(const bf16* c, int i) {
    const float v = __bfloat162float(c[i]);
    return bfround(__fdividef(v, 1.0f + __expf(-v)));
}
__device__ __noinline__ void rec_ln(float* coef, const RecPtrs& p, int id, int r0) {
    int r1 = 32;
    const int tid = threadIdx.x;
    const int lane = tid & 31, wid = tid >> 5;
    const uint32_t ring = smem_u32(coef) - SM_PRE + wid * 8192 + lane * 16;
    auto fetch = [&](int r) {
        if (r < r1) {
            const bf16* src = p.x + (size_t)(r * 64 + (id * 8 + wid) * 2) * DM + lane * 8;
#pragma unroll
            for (int i = 0; i < 8; i++) cp_async16(ring + (r & 1) * 4096 + i * 512, src + i * 256);
        }
        asm volatile("cp.async.commit_group;" ::: "memory");
    };
    auto row8 = [&](uint32_t a, float* f) {
        const uint4 v = lds4(a);
        f[0] = bflo(v.x); f[1] = bfhi(v.x); f[2] = bflo(v.y); f[3] = bfhi(v.y); f[4] = bflo(v.z); f[5] = bfhi(v.z); f[6] = bflo(v.w); f[7] = bfhi(v.w);
    };
#pragma unroll 1
    for (int r = r0 - 2; r < r1; r++) {
        if (r >= r0) {
            asm volatile("cp.async.wait_group 1;" ::: "memory");
            const uint32_t a = ring + (r & 1) * 4096;
            float m[2] = {0.f, 0.f}, t[2];
#pragma unroll 1
            for (int ps = 0; ps < 2; ps++) {
                t[0] = t[1] = 0.f;
#pragma unroll 1
                for (int i = 0; i < 4; i++)
#pragma unroll
                    for (int h = 0; h < 2; h++) {
                        float f[8];
                        row8(a + h * 2048 + i * 512, f);
#pragma unroll
                        for (int e = 0; e < 8; e++) { const float d = f[e] - m[h]; t[h] = fmaf(d, ps ? d : 1.0f, t[h]); }
                    }
#pragma unroll
                for (int o = 16; o; o >>= 1) { t[0] += __shfl_xor_sync(~0u, t[0], o); t[1] += __shfl_xor_sync(~0u, t[1], o); }
                if (ps == 0) { m[0] = t[0] * (1.0f / DM); m[1] = t[1] * (1.0f / DM); }
            }
            t[0] = rsqrtf(t[0] * (1.0f / DM) + 1e-5f); t[1] = rsqrtf(t[1] * (1.0f / DM) + 1e-5f);
            if (r == r0) {
#pragma unroll 1
                for (int i = tid; i < 2 * DM / 4; i += 256) {
                    float4 u;
                    int it = 0;
                    uint32_t ok;
#pragma unroll 1
                    do {
                        uint4 v[8];
#pragma unroll
                        for (int k = 0; k < 8; k++) v[k] = ldg_rlx4(g_modp + k * 2 * DM + i * 4);
                        ok = 1;
                        u = make_float4(0.f, 0.f, 0.f, 0.f);
#pragma unroll
                        for (int k = 0; k < 8; k++) {
                            ok &= v[k].x & v[k].y & v[k].z & v[k].w;
                            u.x += __uint_as_float(v[k].x); u.y += __uint_as_float(v[k].y); u.z += __uint_as_float(v[k].z); u.w += __uint_as_float(v[k].w);
                        }
                        spin_guard(++it);
                    } while (!ok);
                    const uint32_t lo = pack2(u.x, u.y), hi = pack2(u.z, u.w);
                    const float one = i >= DM / 4 ? 1.0f : 0.0f;
                    *(float4*)(coef + i * 4) = make_float4(bflo(lo) + one, bfhi(lo) + one, bflo(hi) + one, bfhi(hi) + one);
                }
                bar_sync(NB_FIN0, 256);
            }
            const int row = r * 64 + (id * 8 + wid) * 2;
#pragma unroll 1
            for (int i = 0; i < 4; i++) {
                const float4* cf = (const float4*)(coef + i * 256 + lane * 8);
                const float4 s0 = cf[0], s1 = cf[1], c0 = cf[256], c1 = cf[257];
                const float sh[8] = {s0.x, s0.y, s0.z, s0.w, s1.x, s1.y, s1.z, s1.w}, sc[8] = {c0.x, c0.y, c0.z, c0.w, c1.x, c1.y, c1.z, c1.w};
                const int own = ((row >> 4) & 1) == (i >> 1), rr = row & 15;
                const uint32_t off = ((row >> 5) + own) * 65536 + (i * 4 + (lane >> 3)) * 4096 + (rr + (own ? 0 : 16)) * 128 + (((lane & 7) ^ (rr & 7)) << 4);
#pragma unroll
                for (int h = 0; h < 2; h++) {
                    float y[8];
                    row8(a + h * 2048 + i * 512, y);
#pragma unroll
                    for (int e = 0; e < 8; e++) y[e] = fmaf((y[e] - m[h]) * t[h], sc[e], sh[e]);
                    *(uint4*)((uint8_t*)g_himg + (off ^ (h * 144))) = pack8(y);
                }
            }
            if (r == 0) {
                int v, it = 0;
#pragma unroll 1
                do { v = *(volatile int*)((uint8_t*)coef - SM_PRE + SM_BAR + 192); spin_guard(++it); } while (v == INT_MIN);
                if (v >= 0) r1 = 2;
            }
        }
        fetch(r + 2);
        if (r < r0 || (r > 0 && !(r & 1))) continue;
        bar_sync(r == 0 ? NB_C : r == 1 ? NB_FIN0 : NB_LN, r == 0 ? 320 : r == 1 ? 256 : 288);
        if (r < 2 && wid == r) {
            if (r == 1) bar_arrive(NB_B, 64);
            if (lane == 0) { signal_count(&g_tick[32 + id * 8]); }
            __syncwarp();
        }
    }
}
template <int NQ, int CG>
__device__ __forceinline__ void side_gemv(const bf16* w, int ld, int ncol, const float* coef, float* red, float* out, int ostride, bool round) {
    constexpr int KG = 384 / CG, W = CG * 8;
    const int tid = threadIdx.x, cg = tid % CG, kg = tid / CG;
    float acc[NQ][8];
#pragma unroll
    for (int q = 0; q < NQ; q++)
#pragma unroll
        for (int j = 0; j < 8; j++) acc[q][j] = 0.f;
    if (cg * 8 < ncol) {
        const bf16* src = w + cg * 8;
        const uint32_t ring = smem_u32(red) + 36864 + tid * 16;
        auto fetch = [&](int k0, int slot) {
#pragma unroll
            for (int i = 0; i < 4; i++)
                if (k0 + i * KG < DM) cp_async16_ef(ring + (slot * 4 + i) * 6144, src + (size_t)(k0 + i * KG) * ld);
            asm volatile("cp.async.commit_group;" ::: "memory");
        };
#pragma unroll 1
        for (int g = 0; g < 5; g++) fetch(kg + g * 4 * KG, g);
#pragma unroll 1
        for (int k0 = kg, slot = 0; k0 < DM; k0 += 4 * KG) {
            fetch(k0 + 20 * KG, slot ? slot - 1 : 5);
            asm volatile("cp.async.wait_group 5;" ::: "memory");
#pragma unroll
            for (int i = 0; i < 4; i++) {
                const int k = k0 + i * KG;
                if (k < DM) {
                    const uint4 v = lds4(ring + (slot * 4 + i) * 6144);
                    const float f[8] = {bflo(v.x), bfhi(v.x), bflo(v.y), bfhi(v.y), bflo(v.z), bfhi(v.z), bflo(v.w), bfhi(v.w)};
#pragma unroll
                    for (int q = 0; q < NQ; q++) {
                        const float cf = coef[q * DM + k];
#pragma unroll
                        for (int j = 0; j < 8; j++) acc[q][j] = fmaf(cf, f[j], acc[q][j]);
                    }
                }
            }
            slot = slot == 5 ? 0 : slot + 1;
        }
    }
    __syncthreads();
#pragma unroll
    for (int q = 0; q < NQ; q++)
#pragma unroll
        for (int j = 0; j < 8; j++) red[(kg * NQ + q) * W + cg * 8 + j] = acc[q][j];
    __syncthreads();
#pragma unroll 1
    for (int i = tid; i < NQ * W; i += 384) {
        const int q = i / W, cidx = i % W;
        float t = 0.f;
#pragma unroll
        for (int k = 0; k < KG; k++) t += red[k * NQ * W + i];
        if (cidx < ncol) out[q * ostride + cidx] = round ? bfround(t) : t;
    }
}
__device__ __noinline__ void rec_side(float* sm, const RecPtrs& p, int id) {
    const int tid = threadIdx.x;
    float *coef = sm, *red = sm + 3 * DM;
    if (tid < 256 && blockIdx.x < 128) rec_ln(sm + SM_PRE / 4, p, id, 2);
    if (tid >> 5 == 8) {
#pragma unroll 1
        for (int n = 1; n < 16; n++) {
            bar_sync(NB_LN, 288);
            if (tid == 256) { if (n == 1) wait_count1(&g_tick[32 + id * 8], 2); signal_count(&g_tick[32 + id * 8]); }
            __syncwarp();
        }
    }
    __syncthreads();
    for (int i = tid; i < 2 * S_; i += 384) g_st[id * 2 * S_ + i] = 0.f;
    if (id == 0) for (int i = tid; i < 2 * 32; i += 384) g_pcnt[i * 8] = 0;
    if (id == 1) for (int i = tid; i < 6 * 256; i += 384) g_pflag[i] = 0;
    for (int i = tid; i < DM; i += 384) { coef[i] = silu_bf(p.c, i); coef[2 * DM + i] = 1.0f; }
    __syncthreads();
    side_gemv<1, 128>(p.wmod + (2 + id) * DM, 6 * DM, DM, coef, red, g_mod + (2 + id) * DM, 0, true);
    __syncthreads();
    if (tid == 0) signal_count(&g_tick[8]);
    side_gemv<1, 128>(p.w3 + id * (FF / 4), FF, FF / 4, coef + 2 * DM, red, g_vec + 3 * DM + id * (FF / 4), 0, false);
    if (tid == 0) wait_count1(&g_tick[8], 4);
    __syncthreads();
    for (int i = tid; i < DM; i += 384) { coef[i] = 1.0f + __ldcg(g_mod + 4 * DM + i); coef[DM + i] = __ldcg(g_mod + 3 * DM + i); }
    __syncthreads();
    if (id == 1 && tid < 32) {
        float t[5] = {0, 0, 0, 0, 0};
        for (int i = tid; i < DM; i += 32) {
            const float a = coef[i], b = coef[DM + i];
            t[0] += a; t[1] += a * a; t[2] += a * b; t[3] += b; t[4] += b * b;
        }
#pragma unroll
        for (int q = 0; q < 5; q++) { const float r = warp_sum(t[q]); if (tid == 0) g_cst[q] = r * (1.0f / DM); }
    }
    side_gemv<3, 32>(p.w1 + id * 256, DM, 256, coef, red, g_vec + id * 256, DM, false);
}

__device__ __forceinline__ void pair_place(int c, int& d, int& pi) {
    const int c7 = ((c - 36) * 37) >> 8;
    d = c < 4 ? 0 : c < 36 ? (c - 4) & 7 : c - 35 - 7 * c7;
    pi = c < 4 ? c : c < 36 ? ((c - 4) >> 3) + (d ? 0 : 4) : 4 + c7;
}
__global__ void __cluster_dims__(2, 1, 1) __launch_bounds__(384, 1)
k_rec(const __grid_constant__ RecMaps mp, const __grid_constant__ RecPtrs p) {
    extern __shared__ uint8_t smraw[];
    const uint32_t sb = smem_u32(smraw);
    if ((sb & 0x3FFFF) != SB0) __trap();
    const uint32_t bars = sb + SM_BAR;
    const int tid = threadIdx.x, lane = tid & 31, b = blockIdx.x;
    const int wid = __reduce_max_sync(~0u, tid >> 5);
    const uint32_t rank = b & 1;
    uint8_t* arena = p.arena;
    volatile int* sinfo = (volatile int*)(smraw + SM_BAR + 192);
    if (tid == 0) sinfo[0] = INT_MIN;
    uint32_t smid;
    asm("mov.u32 %0, %%smid;" : "=r"(smid));
    smid = __reduce_max_sync(~0u, smid);
    int d, pi;
    pair_place(smid >= 124 ? (smid >> 1) - 62 : (smid >> 1) + 4, d, pi);
    const int guess = b < 128 && smid < 132 && (smid & ~3u) != 120 && (NO_GUESS % 5 == 0 || (NO_GUESS == 2 && b != 20)) ? d * 8 + pi : -9;
    if (wid == 8) {
        if (lane == 0) {
#pragma unroll
            for (int i = 0; i < 17; i++) mbar_init(bars + 8 * i, i == B_WO ? 4 : 1);
            asm volatile("fence.mbarrier_init.release.cluster; fence.proxy.async.shared::cta;" ::: "memory");
            mbar_expect(bars + 8 * B_ROLE, 8);
        }
        __syncwarp();
    }
    asm volatile("barrier.cluster.arrive.relaxed.aligned;" ::: "memory");
    int pr = 0, hA = 0;
    if (wid < 8) {
        if (b < 128) {
            const int cb = (b & 15) * 128, k0 = (b >> 4) * 128 + (tid >> 4);
            uint4 v[8];
#pragma unroll
            for (int i = 0; i < 8; i++) v[i] = __ldg((const uint4*)(p.wmod + (size_t)(k0 + 16 * i) * (6 * DM) + cb + (tid & 15) * 8));
            float acc[8] = {0, 0, 0, 0, 0, 0, 0, 0};
            const float sl = silu_bf(p.c, k0 + 16 * (lane & 7));
#pragma unroll
            for (int i = 0; i < 8; i++) {
                const float sv = __shfl_sync(~0u, sl, i, 16);
                acc[0] += sv * bflo(v[i].x); acc[1] += sv * bfhi(v[i].x); acc[2] += sv * bflo(v[i].y); acc[3] += sv * bfhi(v[i].y);
                acc[4] += sv * bflo(v[i].z); acc[5] += sv * bfhi(v[i].z); acc[6] += sv * bflo(v[i].w); acc[7] += sv * bfhi(v[i].w);
            }
            float* red = (float*)(smraw + SM_PRE);
            *(float4*)(red + (tid >> 4) * 128 + (tid & 15) * 8) = make_float4(acc[0], acc[1], acc[2], acc[3]);
            *(float4*)(red + (tid >> 4) * 128 + (tid & 15) * 8 + 4) = make_float4(acc[4], acc[5], acc[6], acc[7]);
            bar_sync(NB_FIN0, 256);
            if (wid < 4) {
                float t = 0;
#pragma unroll
                for (int i = 0; i < 16; i++) t += red[i * 128 + tid];
                stg_rlx1(&g_modp[(b >> 4) * 2 * DM + cb + tid], __float_as_uint(t) | 1u);
            }
        } else {
            rec_ln((float*)(smraw + SM_PRE), p, b - 128, 0);
        }
    } else if (wid >= 10 && b >= 128) {
        {
            const int u = (b - 128) * 2 + wid - 10;
            const uint16_t* src = (const uint16_t*)p.mem0 + (lane & 3) * 2 * DM + (u >> 1) * 128 + (u & 1) * 32 + (lane >> 2);
            stg_rlx4(arena + (LB_STAMP << 13) + u * 2048 + (lane >> 4) * 1024 + ((lane >> 3) & 1) * 256 + (lane & 7) * 16, 0, 0, 0, 0);
#pragma unroll 1
            for (int r = 0; r < 4; r++) {
                uint32_t w[5];
#pragma unroll
                for (int e = 0; e < 4; e++) {
                    const uint16_t* q = src + (r >> 1) * 512 + (r & 1) * 16 + (e & 2) * 32 + (e & 1) * 8;
                    w[e] = pack_h2(bflo(q[0]), bflo(q[DM]));
                }
                w[4] = __shfl_sync(~0u, __byte_perm(w[3], ACC_ALL, 0x7632), lane * 8 + 7);
                w[3] = __byte_perm(w[3], ACC_ALL, (lane & 7) == 7 ? 0x7610 : 0x3210);
#pragma unroll 1
                for (int i = 0; i < 3; i++) {
                    uint8_t* d = arena + acc_slot(i) + acc_piece(r >> 1, u >> 1, (u & 1) * 2 + (r & 1));
                    stg_rlx4(d + lane * 16, w[0], w[1], w[2], w[3]);
                    if (lane < 8) stg_rlx1(d + 512 + lane * 4, w[4]);
                    w[0] = w[1] = w[2] = w[3] = w[4] = 0;
                }
            }
            bar_arrive(NB_C, 320);
        }
    } else if (rank == 0 && (wid > 8 || b >= 128)) {
        uint32_t best = ~0u;
        const int pg = wid < 11 ? 0 : 1 + (b >> 1) % 3;
        uint32_t* q = (uint32_t*)(arena + (pg << 21) + (pg ? blk(b >> 1, 1) : blk(LB_PROBE, wid & 1) + b * 16));
        if (lane < 8) stg_rlx1(q + lane, 0);
        u64 tk2 = ldg_u64(&g_tick[0]);
        __syncwarp();
        if (lane == 0) {
            q += 3;
            uint32_t v = atomicAdd(q, 1u);
#pragma unroll 1
            for (int r = 0; r < NPROBE; r++) {
                const uint32_t t0 = clk32() + (v >> 8);
                v = atomicAdd(q + (v >> 8), 1u);
                uint32_t t1;
                asm volatile("{.reg .pred p; setp.eq.u32 p, %1, 0xffffffff; @p exit; mov.u32 %0, %%clock;}" : "=r"(t1) : "r"(v) : "memory");
                best = min(best, t1 - t0);
            }
            sinfo[pg ? 4 : 2 + (wid & 1)] = best;
        }
        bar_sync(NB_KDONE, b < 128 ? 96 : 64);
        if (wid == 9) {
            const int par = (sinfo[2] > sinfo[3]) ^ (NO_GUESS == 5 && smid == 126), ncl = gridDim.x >> 1;
            const bool ok = guess >= 0 && !(smid & 1), reg = ok && guess >= 4;
            u64 add = (1u << (8 * par)) + 65536 + (reg ? 1ull << 24 : (1ull << (56 + 4 * par)) + ((u64)ok << 37));
            if (b < 128) add += (u64)((2 * sinfo[4] < sinfo[2] + sinfo[3]) != par) << (32 + 8 * ((b >> 1) % 3));
            int it = 0;
            if (NO_GUESS % 5 >= 3 ? b < 2 * (NO_GUESS - 2) || (NO_GUESS == 3 && b == 130) : b >= 128) {
#pragma unroll 1
                while (!__all_sync(~0u, (int)((lo32(tk2) >> 16) & 255) >= ncl - 2)) { tk2 = ldg_u64(&g_tick[0]); spin_guard(++it); }
            }
            if (lane == 0) {
                if (guess >= 0) add += atomicXor(&g_tick[2], par << (guess >> 1)) & p.zero;
                add = atomicAdd((u64*)&g_tick[0], add);
            }
#pragma unroll 1
            while (!__all_sync(~0u, (int)((lo32(tk2) >> 16) & 255) >= ncl)) { tk2 = ldg_u64(&g_tick[0]); spin_guard(++it); }
            add = __shfl_sync(~0u, add, 0);
            const uint32_t diff = ldg_rlx1(&g_tick[2]);
            const bool most = lo32(tk2) >> 24 == 60 && diff < 4;
            const int nh = most ? 2 : NH, sh = most ? 56 : 0, w = most ? 4 : 8, mk = (1 << w) - 1;
            const int n0 = (tk2 >> sh) & mk, n1 = (tk2 >> (sh + w)) & mk, tk = (add >> (sh + w * par)) & mk;
            hA = min(n0 >> 1, nh);
            const int q0 = 2 * hA, q1 = 2 * nh - q0;
            const int over = tk - (par ? q1 : q0), lack = max(par ? q0 - n0 : q1 - n1, 0);
            if (over < 0) pr = par ? q0 + tk : tk;
            else if (over < lack) pr = (par ? n0 : q0 + n1) + over;
            else pr = -1 - (over - lack + (par ? max(n0 - q0, 0) : 0));
            if (most && (reg || (!diff && (hi32(tk2) & 0xe0) == 0x80))) { pr = guess; hA = par ? 0 : NH; }
#pragma unroll
            for (int i = 0; i < 3; i++) hA |= ((hi32(tk2) >> (8 * i)) & 31) > 10 ? 256 << i : 0;
        }
    }
    asm volatile("barrier.cluster.wait.aligned;" ::: "memory");
    if (wid == 9 && rank == 0) {
        asm volatile("{.reg .pred p; .reg .b32 a; setp.lt.u32 p, %3, 2; @p mapa.shared::cluster.u32 a, %0, %3;\n"
                     " @p st.async.shared::cluster.mbarrier::complete_tx::bytes.v2.u32 [a + 192], {%1, %2}, [a + %4];}"
                     ::"r"(bars), "r"(pr), "r"(hA), "r"(lane), "n"(8 * B_ROLE) : "memory");
        if (b >= 128) atomicOr(&g_tick[4], (pr < 0 ? 4u : 1u) << ((b - 128) >> 1));
    }
    if (wid == 8) {
        int pu = guess;
        bool fast = false, known = false;
#pragma unroll 1
        for (int n = 0; n < 12; n++) {
            if (!known && (n == W_SPEC || pu < 0)) {
                mbar_wait_w(bars + 8 * B_ROLE, 0);
                known = true;
                const int r = __reduce_max_sync(~0u, sinfo[0]);
                if (r != pu) {
#pragma unroll 1
                    for (; n > 0; n--) {
                        mbar_wait_w(bars + 8 * (B_W + n - 1), 0);
                        asm volatile("{.reg .pred p; elect.sync _|p, 0xffffffff; @p mbarrier.arrive.shared.b64 _, [%0];}" ::"r"(bars + 8 * (B_W + n - 1)) : "memory");
                    }
                    pu = r;
                    fast = r < 4;
                }
                bar_arrive(NB_A, 384);
                if (b >= 128 && pu < 0) bar_sync(NB_B, 64);
                if (pu < 0) break;
            }
            const int rot = b >= 128 ? 8 : 0, i = (n + rot) % 12;
            if (rot && n == 4) bar_sync(NB_B, 64);
            if (n >= W_INFL && !fast) {
                const uint32_t v = ldg_rlx1(&g_tick[32 + (lane & 3) * 8]);
                mbar_wait_w(bars + 8 * (B_W + (n - W_INFL + rot) % 12), 0);
                fast = __all_sync(~0u, v != 0);
            }
            const int m = i < 8 ? i & 1 : 2, k = i < 8 ? i >> 1 : i - 8, c0 = (pu >> 1) * 128 + rank * 64, r0 = (pu & 1) * 512;
            const uint32_t dst = sb + m * 65536 + k * 16384, br = bars + 8 * (B_W + i);
            e_expect(br, 16384);
            e_tma2d_ef(dst, &mp.wq + m, c0, r0 + k * 128, br);
            e_tma2d_ef(dst + 8192, &mp.wq + m, c0, r0 + k * 128 + 64, br);
        }
    } else {
        bar_sync(NB_A, 384);
    }
    const int prr = __reduce_max_sync(~0u, sinfo[0]);
    hA = __reduce_max_sync(~0u, sinfo[1]);
    if (prr < 0) {
        int j = (b - 128) >> 1;
        if (b < 128) {
            uint32_t v;
            int it = 0;
#pragma unroll 1
            do { v = __reduce_max_sync(~0u, ldg_rlx1(&g_tick[4])); spin_guard(++it); } while (__popc(v) < 2);
            j = v == 3 ? -1 - prr : (v & 1) ^ 1;
        }
        rec_side((float*)smraw, p, j * 2 + rank);
        return;
    }
    const int role = (prr >> 1) * 4 + rank * 2 + (prr & 1);
    rec_main(sb, &mp.wo, arena, role, hA, wid >> 2, p.zero, p.tm);
}

__device__ __forceinline__ void wgmma_ss192(float* d, uint64_t a, uint64_t b, int sc) {
    asm volatile("{.reg .pred p; setp.ne.b32 p, %98, 0;\n wgmma.mma_async.sync.aligned.m64n192k16.f32.bf16.bf16 "
                 "{%0,%1,%2,%3,%4,%5,%6,%7,%8,%9,%10,%11,%12,%13,%14,%15,%16,%17,%18,%19,%20,%21,%22,%23,%24,%25,%26,%27,%28,%29,%30,%31,%32,%33,%34,%35,%36,%37,%38,%39,%40,%41,%42,%43,%44,%45,%46,%47,%48,%49,%50,%51,%52,%53,%54,%55,%56,%57,%58,%59,%60,%61,%62,%63,%64,%65,%66,%67,%68,%69,%70,%71,%72,%73,%74,%75,%76,%77,%78,%79,%80,%81,%82,%83,%84,%85,%86,%87,%88,%89,%90,%91,%92,%93,%94,%95}, %96, %97, p, 1, 1, 0, 1;}"
                 : F16(d, 0), F16(d, 16), F16(d, 32), F16(d, 48), F16(d, 64), F16(d, 80) : "l"(a), "l"(b), "r"(sc));
}

constexpr uint32_t P_B = 81920, P_PLANE = 40960, P_VEC = 212992, P_ROW = P_VEC + 6144, P_BAR = P_ROW + 4096, P_SMEM = P_BAR + 256;
constexpr uint32_t P_OUT = 180224, P_OUT3 = P_B + 2 * P_PLANE;
constexpr int E0 = 2;
constexpr int SL_B0 = 0x2222;
constexpr int SL_B1 = 0x8888;
constexpr int SL_C = 0x11110;
constexpr int SL_A0 = 0x5494;
constexpr int SL_A1 = 0x2929;
constexpr int X_DLY = 4000;
constexpr int P_ST = 5, P_ST0 = 4;
constexpr int PB_F = 0, PB_E = 5, PB_X = 10, PB_P = 12, PB_OUT = 14;
enum { C_Y = 0, C_G = 1, C_X1 = 2, C_U = 3, C_S1 = 8, C_S3 = 9 };
enum { V_GA = 0, V_A = 1, V_B = 2, V_GB = 3, V_VA = 4, V_VB = 5, V_VC = 6, V_C3 = 7 };
struct PostMaps { CUtensorMap o, wo, y, w1, g, w2, x1, w3, u, w4, out, x; };

struct GeluK { float k0, k1, kh; };
__device__ __forceinline__ GeluK gelu_k(float c) { return {0.7978845608028654f * c, 0.7978845608028654f * 0.044715f * c * c * c, 0.5f * c}; }
__device__ __forceinline__ float gelu_s(float t, const GeluK& k) {
    const float u = t * fmaf(t * t, k.k1, k.k0);
    float th; asm("tanh.approx.f32 %0, %1;" : "=f"(th) : "f"(u));
    const float hx = k.kh * t;
    return fmaf(hx, th, hx);
}
__device__ __forceinline__ float2 ldsv(uint32_t a) {
    float2 v; asm("ld.shared.v2.f32 {%0,%1}, [%2];" : "=f"(v.x), "=f"(v.y) : "r"(a)); return v;
}
__device__ __forceinline__ void wait_smem(uint32_t a, int target) {
    int it = 0;
#pragma unroll 1
    while (true) {
        int v;
        asm volatile("ld.acquire.cta.shared.u32 %0, [%1];" : "=r"(v) : "r"(a) : "memory");
        if (__all_sync(~0u, v >= target)) break;
        spin_guard(++it);
    }
}

struct Pipe { int st, ph; };
__device__ __forceinline__ void adv(Pipe& p) { if (++p.st == P_ST) { p.st = 0; p.ph ^= 1; } }
__device__ __forceinline__ int u_col(int r, int nb) { return r ? 512 + r * 1024 + nb * 128 : nb * 192; }

template <bool A>
__device__ __forceinline__ void post_produce(uint32_t sb, const PostMaps& mp, int mb, int nb, int rank) {
    const int rh = 2 * mb + rank, lane = threadIdx.x & 31;
    const uint32_t full = sb + P_BAR + 8 * PB_F, empty = sb + P_BAR + 8 * PB_E;
    Pipe p = {(P_ST0 + E0) % P_ST, !E0};
#pragma unroll 1
    for (int ph = 0; ph < 9; ph++) {
        const int GS = ph == 0 ? 8 : ph == 6 ? 3 : 2, kb0 = ph < 7 ? 0 : ph * 16 - 88;
        const CUtensorMap* tm = &mp.o + 2 * (ph < 3 ? ph : ph < 6 ? 3 : 4) + !A;
        const bool own = ph == 1 || ph == 3;
        const int n0 = ph >= 3 && ph < 6 ? u_col(ph - 3, nb) : nb * 128;
        const int amul = ph == 0 ? 256 : 64, arow = ph == 0 ? rh * 8 : rh * 64;
        const int wr = ph == 2 ? min(max(rh + min(lane >> 3, 2) - 1, 0), 31) : rh;
        const uint32_t* fl = &g_pflag[(ph < 3 ? ph - 1 : ph < 6 ? C_X1 : ph - 3) * 256 + wr * 8 + (lane & 7)];
        uint32_t have = ph == 0 || ph == 5 ? ~0u : 0u;
#pragma unroll 1
        for (int q = 0; q < 8; q++) {
            const int src = own && q < 2 ? nb ^ q : (q + (ph >= 1 && ph <= 3 ? nb & 6 : 0)) & 7;
            const bool skip = own && q == 0, both = own && q == 1;
            const uint32_t need = q < 2 && own ? 0 : (ph == 2 ? 0x10101 : 1) << src;
            if (A && both) {
                int it = 0;
                uint32_t ok;
#pragma unroll 1
                do {
                    asm volatile("{.reg .pred p; mbarrier.try_wait.parity.acquire.cluster.shared::cta.b64 p, [%1], %2; selp.u32 %0, 1, 0, p;}" : "=r"(ok) : "r"(sb + P_BAR + 8 * PB_P), "r"(ph >> 1) : "memory");
                    spin_guard(++it);
                } while (!__all_sync(~0u, ok));
                asm volatile("fence.proxy.async.global;" ::: "memory");
            }
            if (A && (have & need) != need) {
                int it = 0;
#pragma unroll 1
                do {
                    uint32_t v;
                    asm volatile("ld.acquire.gpu.global.u32 %0, [%1];" : "=r"(v) : "l"(fl) : "memory");
                    have = __ballot_sync(~0u, v != 0);
                    spin_guard(++it);
                } while ((have & need) != need);
                asm volatile("fence.proxy.async.global;" ::: "memory");
            }
            if (!A && q == 1 && (ph == 1 || ph == 2)) {
#pragma unroll 1
                for (int i = 0; i <= ph; i++)
                    asm volatile("{.reg .pred p; elect.sync _|p, 0xffffffff; @p cp.async.bulk.prefetch.tensor.2d.L2.global [%0, {%1, %2}];}"
                                 ::"l"(tm + 2), "r"((nb * (ph + 1) + i) * 64), "r"(mb * 64) : "memory");
            }
            if (!A && ph == 3 && q == 1) wait_smem(sb + P_BAR + 8 * (PB_OUT + (lane & 1)), 3);
            const int row = arow + (ph == 2 ? (int)((0x04000301u >> ((src & 6) * 4)) & 7) - 2 : 0);
            const uint32_t bytes = (skip ? 16384 : 32768) + (ph == 3 ? 8192 : 0);
            if ((ph | q) == 0) asm volatile("barrier.cluster.wait.aligned;" ::: "memory");
#pragma unroll 1
            for (int e = kb0 + (src + 1) * GS, kb = e - GS + (ph | q ? 0 : E0); kb < e; kb++) {
                const uint32_t f = full + 8 * p.st;
                if (!(A && skip)) mbar_wait_w(empty + 8 * p.st, p.ph ^ 1);
                if (A) {
                    const uint32_t a = sb + p.st * 16384 + rank * 8192;
                    if (both) { e_tma2d_ef(a, tm, kb * 64, row, f); e_tma2d_ef(a + 8192 - rank * 16384, tm, kb * 64, row ^ 64, f); }
                    else if (!skip) e_tma2d_mc_ef(a, tm, kb * amul, row, f);
                } else {
                    const uint32_t b = sb + P_B + p.st * 8192;
                    e_expect(f, bytes);
                    e_tma2d_ef(b, tm, n0, kb * 64, f);
                    e_tma2d_ef(b + P_PLANE, tm, n0 + 64, kb * 64, f);
                    if (ph == 3 && both) mbar_wait_w(empty + 8 * p.st - 16, p.ph);
                    if (ph == 3) e_tma2d_ef(b + 2 * P_PLANE, tm, n0 + 128, kb * 64, f);
                }
                adv(p);
            }
        }
    }
    if (A) {
#pragma unroll 1
        for (int i = 0; i < P_ST; i++) mbar_wait_w(empty + 8 * i, p.ph ^ (i >= p.st));
    }
}

#define I4(d, i) "f"(d[i]), "f"(d[i + 1]), "f"(d[i + 2]), "f"(d[i + 3])
#define I16(d, i) I4(d, i), I4(d, i + 4), I4(d, i + 8), I4(d, i + 12)
#define O4(d, i) "=f"(d[i]), "=f"(d[i + 1]), "=f"(d[i + 2]), "=f"(d[i + 3])
__device__ __forceinline__ void pick32(float* v, int n, const float* c1, const float* vc, const float* old) {
    asm volatile("{PKT: .branchtargets PK0, PK1, PK2, PK3, PK4, PK5; brx.idx.uni %16, PKT;\n"
                 "PK0: fma.rn.f32 %0, %17, %19, %27; fma.rn.f32 %1, %17, %20, %28; fma.rn.f32 %2, %18, %19, %29; fma.rn.f32 %3, %18, %20, %30; fma.rn.f32 %4, %17, %21, %31; fma.rn.f32 %5, %17, %22, %32; fma.rn.f32 %6, %18, %21, %33; fma.rn.f32 %7, %18, %22, %34; fma.rn.f32 %8, %17, %23, %35; fma.rn.f32 %9, %17, %24, %36; fma.rn.f32 %10, %18, %23, %37; fma.rn.f32 %11, %18, %24, %38; fma.rn.f32 %12, %17, %25, %39; fma.rn.f32 %13, %17, %26, %40; fma.rn.f32 %14, %18, %25, %41; fma.rn.f32 %15, %18, %26, %42; bra.uni PKE;\n"
                 "PK1: fma.rn.f32 %0, %17, %19, %43; fma.rn.f32 %1, %17, %20, %44; fma.rn.f32 %2, %18, %19, %45; fma.rn.f32 %3, %18, %20, %46; fma.rn.f32 %4, %17, %21, %47; fma.rn.f32 %5, %17, %22, %48; fma.rn.f32 %6, %18, %21, %49; fma.rn.f32 %7, %18, %22, %50; fma.rn.f32 %8, %17, %23, %51; fma.rn.f32 %9, %17, %24, %52; fma.rn.f32 %10, %18, %23, %53; fma.rn.f32 %11, %18, %24, %54; fma.rn.f32 %12, %17, %25, %55; fma.rn.f32 %13, %17, %26, %56; fma.rn.f32 %14, %18, %25, %57; fma.rn.f32 %15, %18, %26, %58; bra.uni PKE;\n"
                 "PK2: fma.rn.f32 %0, %17, %19, %59; fma.rn.f32 %1, %17, %20, %60; fma.rn.f32 %2, %18, %19, %61; fma.rn.f32 %3, %18, %20, %62; fma.rn.f32 %4, %17, %21, %63; fma.rn.f32 %5, %17, %22, %64; fma.rn.f32 %6, %18, %21, %65; fma.rn.f32 %7, %18, %22, %66; fma.rn.f32 %8, %17, %23, %67; fma.rn.f32 %9, %17, %24, %68; fma.rn.f32 %10, %18, %23, %69; fma.rn.f32 %11, %18, %24, %70; fma.rn.f32 %12, %17, %25, %71; fma.rn.f32 %13, %17, %26, %72; fma.rn.f32 %14, %18, %25, %73; fma.rn.f32 %15, %18, %26, %74; bra.uni PKE;\n"
                 "PK3: fma.rn.f32 %0, %17, %19, %75; fma.rn.f32 %1, %17, %20, %76; fma.rn.f32 %2, %18, %19, %77; fma.rn.f32 %3, %18, %20, %78; fma.rn.f32 %4, %17, %21, %79; fma.rn.f32 %5, %17, %22, %80; fma.rn.f32 %6, %18, %21, %81; fma.rn.f32 %7, %18, %22, %82; fma.rn.f32 %8, %17, %23, %83; fma.rn.f32 %9, %17, %24, %84; fma.rn.f32 %10, %18, %23, %85; fma.rn.f32 %11, %18, %24, %86; fma.rn.f32 %12, %17, %25, %87; fma.rn.f32 %13, %17, %26, %88; fma.rn.f32 %14, %18, %25, %89; fma.rn.f32 %15, %18, %26, %90; bra.uni PKE;\n"
                 "PK4: fma.rn.f32 %0, %17, %19, %91; fma.rn.f32 %1, %17, %20, %92; fma.rn.f32 %2, %18, %19, %93; fma.rn.f32 %3, %18, %20, %94; fma.rn.f32 %4, %17, %21, %95; fma.rn.f32 %5, %17, %22, %96; fma.rn.f32 %6, %18, %21, %97; fma.rn.f32 %7, %18, %22, %98; fma.rn.f32 %8, %17, %23, %99; fma.rn.f32 %9, %17, %24, %100; fma.rn.f32 %10, %18, %23, %101; fma.rn.f32 %11, %18, %24, %102; fma.rn.f32 %12, %17, %25, %103; fma.rn.f32 %13, %17, %26, %104; fma.rn.f32 %14, %18, %25, %105; fma.rn.f32 %15, %18, %26, %106; bra.uni PKE;\n"
                 "PK5: fma.rn.f32 %0, %17, %19, %107; fma.rn.f32 %1, %17, %20, %108; fma.rn.f32 %2, %18, %19, %109; fma.rn.f32 %3, %18, %20, %110; fma.rn.f32 %4, %17, %21, %111; fma.rn.f32 %5, %17, %22, %112; fma.rn.f32 %6, %18, %21, %113; fma.rn.f32 %7, %18, %22, %114; fma.rn.f32 %8, %17, %23, %115; fma.rn.f32 %9, %17, %24, %116; fma.rn.f32 %10, %18, %23, %117; fma.rn.f32 %11, %18, %24, %118; fma.rn.f32 %12, %17, %25, %119; fma.rn.f32 %13, %17, %26, %120; fma.rn.f32 %14, %18, %25, %121; fma.rn.f32 %15, %18, %26, %122;\n"
                 "PKE: }"
                 : O4(v, 0), O4(v, 4), O4(v, 8), O4(v, 12)
                 : "r"(n), "f"(c1[0]), "f"(c1[1]), I4(vc, 0), I4(vc, 4), I16(old, 0), I16(old, 16), I16(old, 32), I16(old, 48), I16(old, 64), I16(old, 80));
}
template <int PH, class F>
__device__ __forceinline__ void post_mma(uint32_t sb, float* acc, Pipe& p, int NK, int wg, uint32_t rel, bool lead, int pi, F hook) {
    const uint32_t full = sb + P_BAR + 8 * PB_F;
    constexpr uint64_t DA = PH == 0 ? mkdesc(SB0, 128, 1024, 0) : mkdesc(SB0, 16, 1024, 1);
    constexpr uint64_t DB = mkdesc(SB0 + P_B, P_PLANE, 1024, 1);
    auto release = [&](uint32_t a) { asm volatile("{.reg .pred p; setp.gt.u32 p, %0, 63; @p mbarrier.arrive.shared::cluster.b64 _, [%0];}" ::"r"(a) : "memory"); };
    uint32_t prev = 0;
    if (PH & 1) { fence_async_smem(); bar_sync(12 + wg, 128); }
    bool ok = false;
#pragma unroll 1
    for (int kb = 0; kb < NK; kb++) {
        if (!ok) mbar_wait_w(full + 8 * p.st, p.ph);
        const uint32_t a = (uint32_t)DA + ((PH & 1) && kb < 2 ? P_OUT / 16 + wg * 1024 + kb * 512 : p.st * 1024 + wg * 512), b = (uint32_t)DB + p.st * 512;
        wg_fence();
#pragma unroll
        for (int k = 0; k < 4; k++) {
            const uint64_t da = (DA & 0xffffffff00000000ull) | (a + k * (PH == 0 ? 16 : 2)), db = (DB & 0xffffffff00000000ull) | (b + k * 128);
            if (PH == 3) wgmma_ss192(acc, da, db, (kb | k) != 0);
            else wgmma_ss128<PH == 0>(acc, da, db, (kb | k) != 0);
        }
        wg_commit();
        const uint32_t cur = rel + 8 * p.st;
        adv(p);
        uint32_t t;
        asm volatile("{.reg .pred p; mbarrier.test_wait.parity.shared.b64 p, [%1], %2; selp.u32 %0, 1, 0, p;}" : "=r"(t) : "r"(full + 8 * p.st), "r"(p.ph) : "memory");
        wg_wait<1>();
        release(prev);
        ok = __all_sync(~0u, t);
        prev = cur;
        hook(kb);
    }
    wg_wait<0>();
    release(prev);
}

__global__ void __cluster_dims__(2, 1, 1) __launch_bounds__(384, 1)
k_post(const __grid_constant__ PostMaps mp) {
    extern __shared__ uint8_t smraw[];
    const uint32_t sb = smem_u32(smraw);
    if ((sb & 0x3FFFF) != SB0) __trap();
    const int tid = threadIdx.x, lane = tid & 31;
    int d, pi;
    pair_place(blockIdx.x >> 1, d, pi);
    const int rank = blockIdx.x & 1, mb = (d >> 2) * 8 + pi, nb = (d & 3) * 2 + rank;
    const uint32_t bars = sb + P_BAR;
    const int w = __reduce_max_sync(~0u, (tid >> 5) - 8);
    if (w == 1) {
        if (lane == 0) {
#pragma unroll
            for (int i = 0; i <= PB_P; i++) mbar_init(bars + 8 * i, i >= PB_E && i < PB_X ? 4 : i == PB_P ? 2 : 1);
            mbar_arrive(bars + 8 * (PB_F + P_ST0));
            asm volatile("mbarrier.arrive.shared.b64 _, [%0], 4;" ::"r"(bars + 8 * (PB_E + P_ST0)) : "memory");
            sts4(bars + 8 * PB_OUT, 0, 0, 0, 0);
            asm volatile("fence.mbarrier_init.release.cluster; fence.proxy.async.shared::cta;" ::: "memory");
        }
        __syncwarp();
    }
    asm volatile("barrier.cluster.arrive.relaxed.aligned;" ::: "memory");
    if (w == 1) {
#pragma unroll
        for (int i = 0; i < E0; i++) {
            const int st = (P_ST0 + i) % P_ST;
            const uint32_t f = bars + 8 * (PB_F + st);
            e_expect(f, 32768);
#pragma unroll
            for (int h = 0; h < 2; h++) {
                e_tma2d_ef(sb + st * 16384 + h * 8192, &mp.o, i * 256, mb * 16 + h * 8, f);
                e_tma2d_ef(sb + P_B + st * 8192 + h * P_PLANE, &mp.wo, nb * 128 + h * 64, i * 64, f);
            }
        }
    }
    if (w != 0 && w != 3) asm volatile("barrier.cluster.wait.aligned;" ::: "memory");
    if (w >= 0) {
        asm volatile("setmaxnreg.dec.sync.aligned.u32 40;");
        if (w == 0) {
            post_produce<false>(sb, mp, mb, nb, rank);
        } else if (w < 3) {
            const int wg = w - 1, rh = 2 * mb + wg;
            float* rowc = (float*)(smraw + P_ROW) + (wg * 64 + lane * 2) * 8;
            int nout = 0, sig = 0;
            __nanosleep(X_DLY);
            if (wg && lane < 9) asm volatile("prefetch.tensormap [%0];" ::"l"(&mp.y + lane) : "memory");
            e_expect(bars + 8 * (PB_X + wg), 16384);
            e_tma2d_ef(sb + P_OUT + wg * 16384, &mp.x, nb * 128, rh * 64, bars + 8 * (PB_X + wg));
            e_tma2d_ef(sb + P_OUT + wg * 16384 + 8192, &mp.x, nb * 128 + 64, rh * 64, bars + 8 * (PB_X + wg));
            if (wg == 0) {
#pragma unroll 1
                for (int i = 0; i < 11; i++) {
                    const float* src = i < 4 ? g_mod + ((0x5342 >> (4 * i)) & 15) * DM + nb * 128 : g_vec + (i < 7 ? (i - 4) * DM + nb * 128 : 3 * DM + u_col(max(i - 8, 0), nb) + (i == 8) * 128);
                    if (i != 8 || lane < 16) cp_async16(sb + P_VEC + i * 512 - (i > 8) * 256 + lane * 16, src + lane * 4);
                }
                *(uint4*)&g_modp[blockIdx.x * 128 + lane * 4] = make_uint4(0, 0, 0, 0);
                if (blockIdx.x == 64) *(uint2*)&g_tick[lane * 2] = make_uint2(0, 0);
                asm volatile("cp.async.wait_all;" ::: "memory");
                const float4 a = lds4f(sb + P_VEC + V_A * 512 + lane * 16);
                sts4f(sb + P_VEC + V_A * 512 + lane * 16, 1.0f + a.x, 1.0f + a.y, 1.0f + a.z, 1.0f + a.w);
                bar_arrive(3, 288);
            }
#pragma unroll 1
            for (int i = 0; i < 9; i++) {
                const int cnt = i == 8 ? 6 : (0x54392180u >> (4 * i)) & 15;
                if (cnt < C_S1) {
                    const bool isu = cnt >= C_U && cnt < 6;
                    const int ng = cnt == C_U ? 3 : 2, c0 = isu ? u_col(cnt - C_U, nb) : nb * 128;
                    const uint32_t src = sb + (cnt == C_U ? P_OUT3 : P_OUT) + wg * ng * 8192;
#pragma unroll 1
                    for (int j = 0; j < ng; j++) {
                        bar_sync(4 + 4 * wg + (sig++ & 3), 160);
                        if (lane == 0) {
                            fence_async_smem();
                            asm volatile("cp.async.bulk.tensor.2d.global.shared::cta.bulk_group [%0, {%2, %3}], [%1]; cp.async.bulk.commit_group;"
                                         ::"l"(&mp.y + 2 * (isu ? 3 : min(cnt, 4))), "r"(src + j * 8192), "r"(c0 + j * 64), "r"(rh * 64) : "memory");
                        }
                        __syncwarp();
                    }
                    if (lane == 0) {
                        asm volatile("cp.async.bulk.wait_group 0; fence.proxy.async.global;" ::: "memory");
                        asm volatile("st.release.cta.shared.u32 [%0], %1;" ::"r"(bars + 8 * (PB_OUT + wg)), "r"(nout + 1) : "memory");
                        if (cnt < 6) asm volatile("fence.acq_rel.gpu; st.relaxed.gpu.global.u32 [%0], %1;" ::"l"(&g_pflag[cnt * 256 + rh * 8 + nb]), "r"(1) : "memory");
                        if (cnt == C_Y || cnt == C_X1)
                            asm volatile("{.reg .b32 r; mapa.shared::cluster.u32 r, %0, %1; mbarrier.arrive.relaxed.cluster.shared::cluster.b64 _, [r];}" ::"r"(bars + 8 * PB_P), "r"(rank ^ 1) : "memory");
                    }
                    nout++;
                    __syncwarp();
                    continue;
                }
                bar_sync(4 + 4 * wg + (sig++ & 3), 160);
#pragma unroll 1
                for (int q = 0; q < (cnt == C_S1 ? 3 : 1); q++) {
                    const float4 v = lds4f(sb + P_ROW + wg * 2048 + q * 512 + lane * 16);
                    asm volatile("red.relaxed.gpu.global.add.v4.f32 [%0], {%1, %2, %3, %4};"
                                 ::"l"((float4*)g_st + (cnt == C_S1 ? q : 3) * (S_ / 2) + rh * 32 + lane), "f"(v.x), "f"(v.y), "f"(v.z), "f"(v.w) : "memory");
                }
                __syncwarp();
                uint32_t* c = &g_pcnt[(cnt - C_S1) * 256 + rh * 8];
                if (lane == 0) { signal_count(c); wait_count1(c, 8); }
                __syncwarp();
                const float4* sp = (const float4*)g_st + rh * 32 + lane;
                float4 u[3] = {__ldcg(sp + (cnt == C_S1 ? 0 : 3) * (S_ / 2)), __ldcg(sp + S_ / 2), __ldcg(sp + S_)};
#pragma unroll 1
                for (int h = 0; h < 2; h++) {
                    const float id = 1.0f / DM;
                    const float m = u[0].x * id, var = fmaxf(u[0].y * id - m * m, 0.f) + 1e-5f, r = rsqrtf(var);
                    float sc = r, m2 = 0.f;
                    if (cnt == C_S1) {
                        m2 = r * (u[1].x * id - m * g_cst[0]) + g_cst[3];
                        const float e2 = r * r * (u[2].x * id - 2.0f * m * u[1].y * id + m * m * g_cst[1]) + 2.0f * r * (u[2].y * id - m * g_cst[2]) + g_cst[4];
                        sc = r * rsqrtf(fmaxf(e2 - m2 * m2, 0.f) + 1e-5f);
                    }
                    const GeluK k = gelu_k(sc);
                    *(float4*)(rowc + h * 8) = make_float4(k.k0, k.k1, k.kh, -m);
                    *(float4*)(rowc + h * 8 + 4) = make_float4(var * r, -m2 * var * r, r, -m * r);
#pragma unroll
                    for (int q = 0; q < 3; q++) { u[q].x = u[q].z; u[q].y = u[q].w; }
                }
                bar_arrive(1 + wg, 160);
            }
        } else {
            post_produce<true>(sb, mp, mb, nb, rank);
        }
    } else {
        asm volatile("setmaxnreg.inc.sync.aligned.u32 232;");
        const int wg = __reduce_max_sync(~0u, tid >> 7), wi = (tid >> 5) & 3, g = lane >> 2, tq = lane & 3;
        const bool lead = (tid & 127) == 0;
        uint32_t rel = 0;
        if ((tid & 127) < 2) asm("mapa.shared::cluster.u32 %0, %1, %2;" : "=r"(rel) : "r"(bars + 8 * PB_E), "r"(tid & 1));
        uint32_t vec = sb + P_VEC + tq * 8;
        const uint32_t stw = sb + (wi * 16 + ((lane >> 3) & 1) * 8 + (lane & 7)) * 128 + (((lane >> 4) ^ (lane & 7)) << 4);
        int sig = 0;
        auto signal = [&]() { bar_arrive(4 + 4 * wg + (sig++ & 3), 160); };
        auto put64 = [&](uint32_t o, const float* v) {
#pragma unroll
            for (int jj = 0; jj < 4; jj++, v += 8) stsm4((stw + o) ^ (jj << 5), pack2(v[0], v[1]), pack2(v[2], v[3]), pack2(v[4], v[5]), pack2(v[6], v[7]));
            signal();
        };
        auto out_free = [&](int n) { wait_smem(bars + 8 * (PB_OUT + (lane & 1)), n); };
        const uint32_t rowc = sb + P_ROW + (wg * 64 + wi * 16 + g) * 32, o128 = P_OUT + wg * 16384;
        const uint32_t rsum = sb + P_ROW + wg * 2048 + (wi * 16 + g) * 8;
        Pipe pa = {P_ST0, 1};
        auto none = [](int) {};
        uint32_t keep[32];
#define KEEP(jn, e) (((e) & 1) ? bfhi(keep[2 * (jn) + ((e) >> 1)]) : bflo(keep[2 * (jn) + ((e) >> 1)]))
        float mu1[2], r1[2];
        {
            float acc[64];
            post_mma<0>(sb, acc, pa, 64, wg, rel, lead, 1, [&](int kb) {
                if (kb != 40) return;
                bar_sync(3, 288);
                mbar_wait_w(bars + 8 * (PB_X + wg), 0);
#pragma unroll
                for (int jj = 0; jj < 8; jj++) ldsm4(keep + jj * 4, (stw + o128 + (jj >> 2) * 8192) ^ ((jj & 3) << 5));
            });
            asm volatile("" : "+r"(vec) :: "memory");
            float st[2][6];
#pragma unroll
            for (int q = 0; q < 6; q++) st[0][q] = st[1][q] = 0.f;
#pragma unroll
            for (int jn = 0; jn < 16; jn++) {
                const float2 ga = ldsv(vec + V_GA * 512 + jn * 32), a = ldsv(vec + V_A * 512 + jn * 32);
                float xa[4];
#pragma unroll
                for (int e = 0; e < 4; e++) {
                    xa[e] = fmaf((e & 1) ? ga.y : ga.x, acc[4 * jn + e], KEEP(jn, e));
                    st[e >> 1][0] += xa[e]; st[e >> 1][1] = fmaf(xa[e], xa[e], st[e >> 1][1]);
                    acc[4 * jn + e] = ((e & 1) ? a.y : a.x) * xa[e];
                }
                keep[2 * jn] = pack2(xa[0], xa[1]); keep[2 * jn + 1] = pack2(xa[2], xa[3]);
                if ((jn & 7) == 7) put64(o128 + (jn >> 3) * 8192, acc + 4 * jn - 28);
            }
#pragma unroll
            for (int jn = 0; jn < 16; jn++) {
                const float2 a = ldsv(vec + V_A * 512 + jn * 32), b = ldsv(vec + V_B * 512 + jn * 32);
#pragma unroll
                for (int e = 0; e < 4; e++) {
                    const float y = acc[4 * jn + e], aa = (e & 1) ? a.y : a.x, bb = (e & 1) ? b.y : b.x;
                    float* s = st[e >> 1];
                    s[2] += y; s[3] = fmaf(aa, y, s[3]); s[4] = fmaf(y, y, s[4]); s[5] = fmaf(bb, y, s[5]);
                }
            }
#pragma unroll
            for (int h = 0; h < 2; h++)
#pragma unroll
                for (int q = 0; q < 6; q++) { st[h][q] += __shfl_xor_sync(~0u, st[h][q], 1); st[h][q] += __shfl_xor_sync(~0u, st[h][q], 2); }
            if (tq < 3) {
#pragma unroll
                for (int h = 0; h < 2; h++)
                    sts2(rsum + tq * 512 + h * 64, tq == 0 ? st[h][0] : tq == 1 ? st[h][2] : st[h][4], tq == 0 ? st[h][1] : tq == 1 ? st[h][3] : st[h][5]);
            }
            signal();
        }
        {
            float acc[64];
            post_mma<1>(sb, acc, pa, 16, wg, rel, lead, 4, none);
            float c1[2], c2[2], c3[2];
            GeluK gk[2];
            bar_sync(1 + wg, 160);
#pragma unroll
            for (int h = 0; h < 2; h++) {
                const float4 a = lds4f(rowc + h * 256), b = lds4f(rowc + h * 256 + 16);
                gk[h] = {a.x, a.y, a.z}; c1[h] = a.w; c2[h] = b.x; c3[h] = b.y; mu1[h] = b.w; r1[h] = b.z;
            }
#pragma unroll
            for (int jn = 0; jn < 16; jn++) {
                const float2 va = ldsv(vec + V_VA * 512 + jn * 32), vb = ldsv(vec + V_VB * 512 + jn * 32), vc = ldsv(vec + V_VC * 512 + jn * 32);
#pragma unroll
                for (int e = 0; e < 4; e++) {
                    const int h = e >> 1;
                    const float t = fmaf(c1[h], (e & 1) ? va.y : va.x, fmaf(c2[h], (e & 1) ? vb.y : vb.x, fmaf(c3[h], (e & 1) ? vc.y : vc.x, acc[4 * jn + e])));
                    acc[4 * jn + e] = gelu_s(t, gk[h]);
                }
                if ((jn & 7) == 7) put64(o128 + (jn >> 3) * 8192, acc + 4 * jn - 28);
            }
        }
        {
            float acc[64];
            post_mma<2>(sb, acc, pa, 16, wg, rel, lead, 7, none);
#pragma unroll
            for (int jn = 0; jn < 16; jn++) {
                const float2 a = ldsv(vec + V_A * 512 + jn * 32), b = ldsv(vec + V_B * 512 + jn * 32);
#pragma unroll
                for (int e = 0; e < 4; e++) {
                    const int h = e >> 1;
                    acc[4 * jn + e] += fmaf(fmaf(KEEP(jn, e), r1[h], mu1[h]), (e & 1) ? a.y : a.x, (e & 1) ? b.y : b.x);
                }
                if ((jn & 7) == 7) put64(o128 + (jn >> 3) * 8192, acc + 4 * jn - 28);
            }
            float st[2][2] = {{0.f, 0.f}, {0.f, 0.f}};
#pragma unroll
            for (int jn = 0; jn < 16; jn++) {
                const float2 gb = ldsv(vec + V_GB * 512 + jn * 32);
                float z[4];
#pragma unroll
                for (int e = 0; e < 4; e++) {
                    const float x1 = acc[4 * jn + e];
                    st[e >> 1][0] += x1; st[e >> 1][1] = fmaf(x1, x1, st[e >> 1][1]);
                    z[e] = fmaf((e & 1) ? gb.y : gb.x, x1, KEEP(jn, e));
                }
                keep[2 * jn] = pack2(z[0], z[1]); keep[2 * jn + 1] = pack2(z[2], z[3]);
            }
#pragma unroll
            for (int h = 0; h < 2; h++)
#pragma unroll
                for (int q = 0; q < 2; q++) { st[h][q] += __shfl_xor_sync(~0u, st[h][q], 1); st[h][q] += __shfl_xor_sync(~0u, st[h][q], 2); }
            if (tq < 2) sts2(rsum + tq * 64, tq ? st[1][0] : st[0][0], tq ? st[1][1] : st[0][1]);
            signal();
        }
        {
            float old[96], acc[64];
            post_mma<3>(sb, old, pa, 16, wg, rel, lead, 10, none);
            uint32_t v3 = vec + V_C3 * 512;
            float c1[2], vc[8];
            auto next_vc = [&]() {
#pragma unroll
                for (int i = 0; i < 4; i++) { const float2 u = lds2f(v3 + i * 32); vc[2 * i] = u.x; vc[2 * i + 1] = u.y; }
                v3 += 128;
            };
            next_vc();
            GeluK gk[2];
            bar_sync(1 + wg, 160);
#pragma unroll
            for (int h = 0; h < 2; h++) { const float4 a = lds4f(rowc + h * 256); gk[h] = {a.x, a.y, a.z}; c1[h] = a.w; }
            bar_arrive(14 + wg, 256);
#pragma unroll 1
            for (int r = 0; r < 3; r++) {
                const uint32_t o = stw + (r ? o128 : P_OUT3 + wg * 24576);
                uint32_t when = r == 0 ? (wg ? SL_A1 : SL_A0) : r == 1 ? (wg ? SL_B1 : SL_B0) : SL_C << (2 * wg), n = 0;
                post_mma<2>(sb, acc, pa, r < 2 ? 16 : 56, wg, rel, lead, 12 + 2 * r, [&](int kb) {
                    const bool now = when & 1;
                    when >>= 1;
                    if (!now) return;
                    if (n == 0) { if (r == 0) bar_sync(15 - wg, 256); out_free(3 + r); }
                    float v[16];
                    pick32(v, n, c1, vc, old);
                    next_vc();
#pragma unroll
                    for (int e = 0; e < 16; e++) v[e] = gelu_s(v[e], gk[(e >> 1) & 1]);
                    const uint32_t a = (o + (n >> 1) * 8192) ^ ((n & 1) << 6);
                    stsm4(a, pack2(v[0], v[1]), pack2(v[2], v[3]), pack2(v[4], v[5]), pack2(v[6], v[7]));
                    stsm4(a ^ 32, pack2(v[8], v[9]), pack2(v[10], v[11]), pack2(v[12], v[13]), pack2(v[14], v[15]));
                    if ((++n & 1) == 0) signal();
                });
                if (r == 2) break;
#pragma unroll
                for (int i = 0; i < 64; i++) old[i] = acc[i];
            }
#pragma unroll
            for (int jn = 0; jn < 16; jn++) {
                const float2 gb = ldsv(vec + V_GB * 512 + jn * 32);
#pragma unroll
                for (int e = 0; e < 4; e++) acc[4 * jn + e] = fmaf((e & 1) ? gb.y : gb.x, acc[4 * jn + e], KEEP(jn, e));
                if ((jn & 7) == 7) put64(o128 + (jn >> 3) * 8192, acc + 4 * jn - 28);
            }
        }
    }
}

typedef CUresult (*EncFn)(CUtensorMap*, CUtensorMapDataType, cuuint32_t, void*, const cuuint64_t*, const cuuint64_t*, const cuuint32_t*,
                          const cuuint32_t*, CUtensorMapInterleave, CUtensorMapSwizzle, CUtensorMapL2promotion, CUtensorMapFloatOOBfill);

static CUtensorMap make_map(EncFn enc, const void* p, uint64_t inner, uint64_t outer) {
    CUtensorMap m;
    cuuint64_t dims[2] = {inner, outer};
    cuuint64_t str[1] = {inner * 2};
    cuuint32_t box[2] = {64, 64};
    cuuint32_t es[2] = {1, 1};
    enc(&m, CU_TENSOR_MAP_DATA_TYPE_BFLOAT16, 2, (void*)p, dims, str, box, es, CU_TENSOR_MAP_INTERLEAVE_NONE,
        CU_TENSOR_MAP_SWIZZLE_128B, CU_TENSOR_MAP_L2_PROMOTION_L2_256B, CU_TENSOR_MAP_FLOAT_OOB_FILL_NONE);
    return m;
}
static CUtensorMap make_map_o(EncFn enc, const void* p) {
    CUtensorMap m;
    cuuint64_t dims[2] = {16384, 256};
    cuuint64_t str[1] = {65536};
    cuuint32_t box[2] = {256, 8};
    cuuint32_t es[2] = {1, 1};
    enc(&m, CU_TENSOR_MAP_DATA_TYPE_UINT32, 2, (void*)p, dims, str, box, es, CU_TENSOR_MAP_INTERLEAVE_NONE, CU_TENSOR_MAP_SWIZZLE_NONE,
        CU_TENSOR_MAP_L2_PROMOTION_L2_256B, CU_TENSOR_MAP_FLOAT_OOB_FILL_NONE);
    return m;
}
template <class T> static T* sym(T& s) { void* p = nullptr; cudaGetSymbolAddress(&p, s); return (T*)p; }

constexpr RecTime g_time = {T_GO, T_X2, T_V, D_X2, H_D};
extern "C" void kernel_launch(void* const* d_in, const int* in_sizes, int n_in, void* d_out, int out_size) {
    const bf16* x = (const bf16*)d_in[0];
    const bf16* mem0 = (const bf16*)d_in[1];
    const bf16 *Wq = (const bf16*)d_in[2], *Wk = (const bf16*)d_in[3], *Wv = (const bf16*)d_in[4], *Wo = (const bf16*)d_in[5];
    const bf16 *w1 = (const bf16*)d_in[8], *w2 = (const bf16*)d_in[9], *w3 = (const bf16*)d_in[10], *w4 = (const bf16*)d_in[11];
    const bf16 *c = (const bf16*)d_in[12], *wmod = (const bf16*)d_in[13];
    bf16* out = (bf16*)d_out;

    EncFn enc = nullptr;
    cudaDriverEntryPointQueryResult qr;
    cudaGetDriverEntryPoint("cuTensorMapEncodeTiled", (void**)&enc, cudaEnableDefault, &qr);
    CUtensorMap tWq = make_map(enc, Wq, NH * DH, DM), tWk = make_map(enc, Wk, NH * DH, DM), tWv = make_map(enc, Wv, NH * DH, DM);
    PostMaps mp;
    mp.o = make_map_o(enc, sym(g_O)); mp.wo = make_map(enc, Wo, DM, NH * DH);
    mp.y = make_map(enc, sym(g_y), DM, S_); mp.w1 = make_map(enc, w1, DM, DM);
    mp.g = make_map(enc, sym(g_g), DM, S_); mp.w2 = make_map(enc, w2, DM, DM);
    mp.x1 = make_map(enc, sym(g_x1), DM, S_); mp.w3 = make_map(enc, w3, FF, DM);
    mp.u = make_map(enc, sym(g_u), FF, S_); mp.w4 = make_map(enc, w4, DM, FF);
    mp.out = make_map(enc, out, DM, S_); mp.x = make_map(enc, x, DM, S_);
    cudaFuncSetAttribute(k_rec, cudaFuncAttributeMaxDynamicSharedMemorySize, SM_REC_TOTAL);
    cudaFuncSetAttribute(k_post, cudaFuncAttributeMaxDynamicSharedMemorySize, P_SMEM);

    uint8_t* arena = (uint8_t*)(((uintptr_t)sym(g_arena) + (2u << 20) - 1) & ~(uintptr_t)((2u << 20) - 1));
    const RecPtrs rp = {x, mem0, c, wmod, w1, w3, arena, 0u, g_time};
    const RecMaps rm = {tWq, tWk, tWv, mp.wo};
    k_rec<<<132, 384, SM_REC_TOTAL>>>(rm, rp);
    k_post<<<128, 384, P_SMEM>>>(mp);
}
```

```cpp
#include <cuda_runtime.h>
#include <cuda.h>
#include <cuda_bf16.h>
#include <stdint.h>
#include <limits.h>

typedef __nv_bfloat16 bf16;

constexpr int S_ = 2048, DM = 1024, NH = 32, DH = 128, NSEG = 64, FF = 3584;
constexpr int SPIN_LIMIT = 1 << 22;
constexpr int W_INFL = 2;
constexpr int NPROBE = 4;

__device__ uint8_t g_arena[10 << 20];
__device__ __align__(16) uint32_t g_tick[64];
__device__ __align__(16) uint32_t g_modp[8 * 2 * DM];
__host__ __device__ constexpr uint32_t blk(uint32_t lb, uint32_t par) {
    return (lb << 13) | ((((lb) ^ (lb >> 3) ^ (lb >> 4) ^ (lb >> 6) ^ par) & 1) << 12);
}
__host__ __device__ constexpr uint32_t lb_x2(uint32_t h) { return (h & 1) | ((h >> 1) << 3); }
__host__ __device__ constexpr uint32_t acc_slot(uint32_t s) { return (1u << 20) + (s & 1) * 32768 + (s & 2) * 131072; }
__host__ __device__ constexpr uint32_t acc_piece(uint32_t half, uint32_t qd, uint32_t mt) { return mt * 1024 + (qd & 1) * 4096 + half * 8192 + (qd >> 1) * 16384; }
constexpr uint32_t LB_STAMP = 6;
__host__ __device__ constexpr uint32_t stamp_line(uint32_t w, uint32_t q) { return ((w & 1) * 2 + (q >> 1)) * 1024 + (q & 1) * 256; }
constexpr uint32_t ACC_ONE = 0x3c000000u, ACC_ALL = 0x50000000u;
constexpr uint32_t LB_PROBE = 6 | 64;
__host__ __device__ constexpr uint32_t lb_tok(uint32_t h) { return (h & 1) | ((h >> 1) << 3); }
__device__ __align__(16) float g_mod[6 * DM];
__device__ __align__(1024) bf16 g_himg[(S_ + 32) * DM];
__device__ __align__(1024) bf16 g_O[S_ * NH * DH];
__device__ __align__(1024) bf16 g_y[S_ * DM];
__device__ __align__(1024) bf16 g_g[S_ * DM];
__device__ __align__(1024) bf16 g_x1[S_ * DM];
__device__ __align__(16) float g_st[4 * S_ * 2];
__device__ __align__(16) float g_vec[3 * DM + FF];
__device__ float g_cst[8];
__device__ uint32_t g_pcnt[2 * 32 * 8], g_pflag[6 * 32 * 8];
__device__ __align__(1024) bf16 g_u[S_ * FF];

__device__ __forceinline__ uint32_t smem_u32(const void* p) { return (uint32_t)__cvta_generic_to_shared(p); }
__device__ __forceinline__ void spin_guard(int it) {
    asm volatile("{.reg .pred p; setp.gt.s32 p, %0, %1; @p st.global.u32 [%2], %0;}" ::"r"(it), "n"(SPIN_LIMIT), "l"(1ull));
}
__device__ __forceinline__ void wg_fence() { asm volatile("wgmma.fence.sync.aligned;" ::: "memory"); }
__device__ __forceinline__ void wg_commit() { asm volatile("wgmma.commit_group.sync.aligned;" ::: "memory"); }
template <int N> __device__ __forceinline__ void wg_wait() { asm volatile("wgmma.wait_group.sync.aligned %0;" ::"n"(N) : "memory"); }
__host__ __device__ constexpr uint64_t mkdesc(uint32_t addr, uint32_t lbo, uint32_t sbo, uint32_t swz) {
    return (uint64_t)((addr & 0x3FFFF) >> 4) | ((uint64_t)(lbo >> 4) << 16) | ((uint64_t)(sbo >> 4) << 32) | ((uint64_t)swz << 62);
}
__device__ __forceinline__ uint64_t dadd(uint64_t d, uint32_t o) { return (d & 0xffffffff00000000ull) | (uint32_t)((uint32_t)d + o); }
__device__ __forceinline__ void mbar_init(uint32_t b, uint32_t c) { asm volatile("mbarrier.init.shared.b64 [%0], %1;" ::"r"(b), "r"(c) : "memory"); }
__device__ __forceinline__ void mbar_expect(uint32_t b, uint32_t tx) { asm volatile("mbarrier.arrive.expect_tx.shared.b64 _, [%0], %1;" ::"r"(b), "r"(tx) : "memory"); }
__device__ __forceinline__ void mbar_arrive(uint32_t b) { asm volatile("mbarrier.arrive.shared.b64 _, [%0];" ::"r"(b) : "memory"); }
__device__ __forceinline__ void mbar_arrive_cluster_if(bool c, uint32_t b, uint32_t cta) {
    asm volatile("{.reg .pred p; .reg .b32 r; setp.ne.u32 p, %2, 0; mapa.shared::cluster.u32 r, %0, %1; @p mbarrier.arrive.shared::cluster.b64 _, [r];}" ::"r"(b), "r"(cta), "r"((uint32_t)c) : "memory");
}
__device__ __forceinline__ bool mbar_try(uint32_t b, uint32_t par) {
    uint32_t ok;
    asm volatile("{.reg .pred p; mbarrier.try_wait.parity.shared.b64 p, [%1], %2; selp.u32 %0, 1, 0, p;}" : "=r"(ok) : "r"(b), "r"(par) : "memory");
    return ok;
}
__device__ __forceinline__ void mbar_wait_w(uint32_t b, uint32_t par) {
    int it = 0;
    bool ok;
#pragma unroll 1
    do { ok = __all_sync(~0u, mbar_try(b, par)); spin_guard(++it); } while (!ok);
}
__device__ __forceinline__ void bar_sync(int id, int n) { asm volatile("bar.sync %0, %1;" ::"r"(id), "r"(n) : "memory"); }
__device__ __forceinline__ void bar_arrive(int id, int n) { asm volatile("bar.arrive %0, %1;" ::"r"(id), "r"(n) : "memory"); }
__device__ __forceinline__ void fence_async_smem() { asm volatile("fence.proxy.async.shared::cta;" ::: "memory"); }
__device__ __forceinline__ void ldsm4t(uint32_t* r, uint32_t a) {
    asm volatile("ldmatrix.sync.aligned.m8n8.x4.trans.shared.b16 {%0,%1,%2,%3}, [%4];" : "=r"(r[0]), "=r"(r[1]), "=r"(r[2]), "=r"(r[3]) : "r"(a) : "memory");
}
__device__ __forceinline__ void ldsm4(uint32_t* r, uint32_t a) {
    asm volatile("ldmatrix.sync.aligned.m8n8.x4.shared.b16 {%0,%1,%2,%3}, [%4];" : "=r"(r[0]), "=r"(r[1]), "=r"(r[2]), "=r"(r[3]) : "r"(a) : "memory");
}
__device__ __forceinline__ uint32_t movm(uint32_t a) {
    uint32_t d; asm volatile("movmatrix.sync.aligned.m8n8.trans.b16 %0, %1;" : "=r"(d) : "r"(a)); return d;
}
__device__ __forceinline__ void mma16816(float* d, uint32_t a0, uint32_t a1, uint32_t a2, uint32_t a3, uint32_t b0, uint32_t b1) {
    asm volatile("mma.sync.aligned.m16n8k16.row.col.f32.bf16.bf16.f32 {%0,%1,%2,%3},{%4,%5,%6,%7},{%8,%9},{%0,%1,%2,%3};"
                 : "+f"(d[0]), "+f"(d[1]), "+f"(d[2]), "+f"(d[3]) : "r"(a0), "r"(a1), "r"(a2), "r"(a3), "r"(b0), "r"(b1));
}
__device__ __forceinline__ void mma16816z(float* d, const uint32_t* a, uint32_t b0, uint32_t b1) {
    asm volatile("mma.sync.aligned.m16n8k16.row.col.f32.bf16.bf16.f32 {%0,%1,%2,%3},{%4,%5,%6,%7},{%8,%9},{%10,%10,%10,%10};"
                 : "=f"(d[0]), "=f"(d[1]), "=f"(d[2]), "=f"(d[3]) : "r"(a[0]), "r"(a[1]), "r"(a[2]), "r"(a[3]), "r"(b0), "r"(b1), "f"(0.f));
}
__device__ __forceinline__ void mma1688(float* d, uint32_t a0, uint32_t a1, uint32_t b0) {
    asm volatile("mma.sync.aligned.m16n8k8.row.col.f32.bf16.bf16.f32 {%0,%1,%2,%3},{%4,%5},{%6},{%0,%1,%2,%3};"
                 : "+f"(d[0]), "+f"(d[1]), "+f"(d[2]), "+f"(d[3]) : "r"(a0), "r"(a1), "r"(b0));
}
__device__ __forceinline__ uint32_t pack2(float lo, float hi) {
    uint32_t r; asm("cvt.rn.bf16x2.f32 %0, %1, %2;" : "=r"(r) : "f"(hi), "f"(lo)); return r;
}
__device__ __forceinline__ uint32_t hadd2v(uint32_t a, uint32_t b) {
    uint32_t r; asm volatile("add.rn.bf16x2 %0, %1, %2;" : "=r"(r) : "r"(a), "r"(b)); return r;
}
__device__ __forceinline__ float bflo(uint32_t u) { return __uint_as_float(u << 16); }
__device__ __forceinline__ float bfhi(uint32_t u) { return __uint_as_float(u & 0xffff0000u); }
__device__ __forceinline__ float ex2(float x) { float r; asm("ex2.approx.ftz.f32 %0, %1;" : "=f"(r) : "f"(x)); return r; }
__device__ __forceinline__ uint4 ldg_rlx4(const void* p) {
    uint4 v; asm volatile("ld.relaxed.gpu.global.v4.u32 {%0,%1,%2,%3}, [%4];" : "=r"(v.x), "=r"(v.y), "=r"(v.z), "=r"(v.w) : "l"(p) : "memory"); return v;
}
__device__ __forceinline__ uint32_t ldg_rlx1(const void* p) {
    uint32_t v; asm volatile("ld.relaxed.gpu.global.u32 %0, [%1];" : "=r"(v) : "l"(p) : "memory"); return v;
}
__device__ __forceinline__ void stg_rlx1(void* p, uint32_t v) { asm volatile("st.relaxed.gpu.global.u32 [%0], %1;" ::"l"(p), "r"(v) : "memory"); }
__device__ __forceinline__ void stg_rlx2(void* p, uint32_t x, uint32_t y) {
    unsigned long long v = (unsigned long long)x | ((unsigned long long)y << 32);
    asm volatile("st.relaxed.gpu.global.b64 [%0], %1;" ::"l"(p), "l"(v) : "memory");
}
__device__ __forceinline__ void stg_rlx4(void* p, uint32_t x, uint32_t y, uint32_t z, uint32_t w) {
    asm volatile("st.relaxed.gpu.global.v4.u32 [%0], {%1,%2,%3,%4};" ::"l"(p), "r"(x), "r"(y), "r"(z), "r"(w) : "memory");
}
__device__ __forceinline__ void sts4(uint32_t a, uint32_t x, uint32_t y, uint32_t z, uint32_t w) {
    asm volatile("st.shared.v4.u32 [%0], {%1,%2,%3,%4};" ::"r"(a), "r"(x), "r"(y), "r"(z), "r"(w) : "memory");
}
__device__ __forceinline__ uint4 lds4(uint32_t a) {
    uint4 v; asm volatile("ld.shared.v4.u32 {%0,%1,%2,%3}, [%4];" : "=r"(v.x), "=r"(v.y), "=r"(v.z), "=r"(v.w) : "r"(a) : "memory"); return v;
}
#define F4(d, i) "+f"(d[i]), "+f"(d[i + 1]), "+f"(d[i + 2]), "+f"(d[i + 3])
template <bool V> __device__ __forceinline__ void wgmma_tok_rs(float* d, const uint32_t* a, uint64_t b, int sc) {
    if (V) asm volatile("{.reg .pred p; setp.ne.b32 p, %25, 0;\n wgmma.mma_async.sync.aligned.m64n40k16.f32.bf16.bf16 {%0,%1,%2,%3,%4,%5,%6,%7,%8,%9,%10,%11,%12,%13,%14,%15,%16,%17,%18,%19}, {%20,%21,%22,%23}, %24, p, 1, 1, 0;}"
                        : F4(d, 0), F4(d, 4), F4(d, 8), F4(d, 12), F4(d, 16) : "r"(a[0]), "r"(a[1]), "r"(a[2]), "r"(a[3]), "l"(b), "r"(sc));
    else asm volatile("{.reg .pred p; setp.ne.b32 p, %21, 0;\n wgmma.mma_async.sync.aligned.m64n32k16.f32.bf16.bf16 {%0,%1,%2,%3,%4,%5,%6,%7,%8,%9,%10,%11,%12,%13,%14,%15}, {%16,%17,%18,%19}, %20, p, 1, 1, 0;}"
                      : F4(d, 0), F4(d, 4), F4(d, 8), F4(d, 12) : "r"(a[0]), "r"(a[1]), "r"(a[2]), "r"(a[3]), "l"(b), "r"(sc));
}
template <bool V> __device__ __forceinline__ void wgmma_tok_ss(float* d, uint64_t a, uint64_t b) {
    if (V) asm volatile("wgmma.mma_async.sync.aligned.m64n40k16.f32.bf16.bf16 {%0,%1,%2,%3,%4,%5,%6,%7,%8,%9,%10,%11,%12,%13,%14,%15,%16,%17,%18,%19}, %20, %21, 1, 1, 1, 1, 0;"
                        : F4(d, 0), F4(d, 4), F4(d, 8), F4(d, 12), F4(d, 16) : "l"(a), "l"(b));
    else asm volatile("wgmma.mma_async.sync.aligned.m64n32k16.f32.bf16.bf16 {%0,%1,%2,%3,%4,%5,%6,%7,%8,%9,%10,%11,%12,%13,%14,%15}, %16, %17, 1, 1, 1, 1, 0;"
                      : F4(d, 0), F4(d, 4), F4(d, 8), F4(d, 12) : "l"(a), "l"(b));
}
#define F16(d, i) F4(d, i), F4(d, i + 4), F4(d, i + 8), F4(d, i + 12)
template <int TA>
__device__ __forceinline__ void wgmma_ss128(float* d, uint64_t a, uint64_t b, int sc) {
    asm volatile("{.reg .pred p; setp.ne.b32 p, %66, 0;\n wgmma.mma_async.sync.aligned.m64n128k16.f32.bf16.bf16 "
                 "{%0,%1,%2,%3,%4,%5,%6,%7,%8,%9,%10,%11,%12,%13,%14,%15,%16,%17,%18,%19,%20,%21,%22,%23,%24,%25,%26,%27,%28,%29,%30,%31,"
                 "%32,%33,%34,%35,%36,%37,%38,%39,%40,%41,%42,%43,%44,%45,%46,%47,%48,%49,%50,%51,%52,%53,%54,%55,%56,%57,%58,%59,%60,%61,%62,%63}, %64, %65, p, 1, 1, %67, 1;}"
                 : F16(d, 0), F16(d, 16), F16(d, 32), F16(d, 48) : "l"(a), "l"(b), "r"(sc), "n"(TA));
}

__device__ __forceinline__ float warp_sum(float v) {
#pragma unroll
    for (int o = 16; o; o >>= 1) v += __shfl_xor_sync(~0u, v, o);
    return v;
}
__device__ __forceinline__ float bfround(float x) { return __bfloat162float(__float2bfloat16(x)); }

__device__ __forceinline__ void wait_count1(const uint32_t* p, uint32_t target) {
    int it = 0;
#pragma unroll 1
    while (true) {
        uint32_t v;
        asm volatile("ld.acquire.gpu.global.u32 %0, [%1];" : "=r"(v) : "l"(p) : "memory");
        if (v >= target) break;
        spin_guard(++it);
    }
}
__device__ __forceinline__ void signal_count(uint32_t* p) { asm volatile("red.release.gpu.global.add.u32 [%0], 1;" ::"l"(p) : "memory"); }
__device__ __forceinline__ void e_expect(uint32_t b, uint32_t tx) {
    asm volatile("{.reg .pred p; elect.sync _|p, 0xffffffff; @p mbarrier.arrive.expect_tx.shared.b64 _, [%0], %1;}" ::"r"(b), "r"(tx) : "memory");
}
__device__ __forceinline__ uint64_t evict_first() { uint64_t p; asm("createpolicy.fractional.L2::evict_first.b64 %0, 1.0;" : "=l"(p)); return p; }
__device__ __forceinline__ void e_tma2d_ef(uint32_t dst, const CUtensorMap* m, int c0, int c1, uint32_t bar) {
    asm volatile("{.reg .pred p; elect.sync _|p, 0xffffffff;\n @p cp.async.bulk.tensor.2d.shared::cluster.global.mbarrier::complete_tx::bytes.L2::cache_hint [%0], [%1, {%3, %4}], [%2], %5;}"
                 ::"r"(dst), "l"(m), "r"(bar), "r"(c0), "r"(c1), "l"(evict_first()) : "memory");
}
__device__ __forceinline__ void e_tma2d(uint32_t dst, const CUtensorMap* m, int c0, int c1, uint32_t bar) {
    asm volatile("{.reg .pred p; elect.sync _|p, 0xffffffff;\n @p cp.async.bulk.tensor.2d.shared::cluster.global.mbarrier::complete_tx::bytes [%0], [%1, {%3, %4}], [%2];}"
                 ::"r"(dst), "l"(m), "r"(bar), "r"(c0), "r"(c1) : "memory");
}
__device__ __forceinline__ void e_tma2d_mc_ef(uint32_t dst, const CUtensorMap* m, int c0, int c1, uint32_t bar) {
    asm volatile("{.reg .pred p; elect.sync _|p, 0xffffffff;\n @p cp.async.bulk.tensor.2d.shared::cluster.global.mbarrier::complete_tx::bytes.multicast::cluster.L2::cache_hint [%0], [%1, {%3, %4}], [%2], %5, %6;}"
                 ::"r"(dst), "l"(m), "r"(bar), "r"(c0), "r"(c1), "h"((uint16_t)3), "l"(evict_first()) : "memory");
}
__device__ __forceinline__ uint32_t wait_count_w(const uint32_t* p, uint32_t target) {
    int it = 0;
#pragma unroll 1
    while (true) {
        uint32_t v;
        asm volatile("ld.acquire.gpu.global.u32 %0, [%1];" : "=r"(v) : "l"(p) : "memory");
        if (__all_sync(~0u, v >= target)) return v;
        spin_guard(++it);
    }
}

__device__ __forceinline__ uint4 pack8(const float* x) {
    return make_uint4(pack2(x[0], x[1]), pack2(x[2], x[3]), pack2(x[4], x[5]), pack2(x[6], x[7]));
}
constexpr int NL = 6;
constexpr uint32_t HCH = 5120, HBUF = 8 * HCH;
constexpr uint32_t SM_SX = 0, SM_ST = 2560, SM_OX = 8192, SM_LX = 10240, SM_PX = 11392, SM_PA = 12288, SM_VF = 18432, SM_TAB = 26624, SM_WL2 = 41984, SM_HB = 49152, SM_WO = 131072,
                   SM_WL = 196608, SM_PRE = SM_WL, SM_BAR = 227328, SM_TRC = SM_BAR + 256, SM_REC_TOTAL = SM_TRC + 2688;
__host__ __device__ constexpr uint32_t sm_wl(int i) { return i < 5 ? SM_WL + i * 6144 : SM_WL2; }
constexpr uint32_t SB0 = 1024;
constexpr int B_WO = 0, B_HE = 1, B_ROLE = 2, B_HB = 3, B_W = 5;
constexpr int NB_MEM = 1, NB_QK = 2, NB_X1 = 3, NB_X2 = 4, NB_WIN = 5, NB_WG = 6, NB_KDONE = 7, NB_FIN0 = 8, NB_LN = 9, NB_MEM2 = 10, NB_H = 11, NB_A = 12, NB_B = 13, NB_C = 14, NB_F = 15;
constexpr int TPV_DLY = 6;
constexpr int L_AT = 3;
constexpr int D_X2 = 340;
constexpr int NPF1 = 6;
constexpr int NPF = 11;
constexpr int T_GO = 28;
constexpr int GATE_AT = 25;
constexpr int T_X2 = 1920;
constexpr int T_V = 300;
constexpr int VP_AT = 1;
constexpr int PD = 4;
constexpr int PV_FENCE = 0;
constexpr int SSG = 5;
constexpr int SSG_V = 5;
constexpr int SS0_K = 4;
constexpr int SS0_V = 6;
constexpr int NPF0 = 3;
constexpr int STG_FENCE = 1;
constexpr int WO_AT = 0x1100;
constexpr int W_SPEC = 7;
constexpr int NO_GUESS = 0;
constexpr int W_T0 = 2800;
constexpr int NPF2 = 9;
constexpr int PF_DLY = 7;
constexpr int H_D = 210;
constexpr int PIN_EPI = 1;

__device__ __forceinline__ uint32_t clk32() { uint32_t t; asm volatile("mov.u32 %0, %%clock;" : "=r"(t) :: "memory"); return t; }
__device__ __forceinline__ uint32_t gtime32() { uint32_t t; asm volatile("mov.u32 %0, %%globaltimer_lo;" : "=r"(t) :: "memory"); return t; }
template <int N> __device__ __forceinline__ uint32_t delay(uint32_t zero) {
    float x = __uint_as_float(clk32());
#pragma unroll
    for (int i = 0; i < N; i++) asm volatile("ex2.approx.ftz.f32 %0, %0;" : "+f"(x));
    return __float_as_uint(x) & zero;
}
__device__ __forceinline__ uint32_t clk_after(uint32_t x, uint32_t zero) {
    unsigned long long c = 0;
    asm volatile("{.reg .pred p; setp.eq.u32 p, %1, 0; @p mov.u64 %0, %%clock64;}" : "+l"(c) : "r"(x & zero) : "memory");
    return (uint32_t)c;
}
__device__ __forceinline__ uint32_t later(uint32_t a, uint32_t b) { return a + max((int)(b - a), 0); }
__device__ __forceinline__ void wait_clk(uint32_t t) {
#pragma unroll 1
    while (true) {
        unsigned long long c;
        asm volatile("mov.u64 %0, %%clock64;" : "=l"(c) :: "memory");
        if ((int)((uint32_t)c - t) >= 0) break;
    }
}
__device__ __forceinline__ uint32_t opaque(uint32_t v) { return __shfl_sync(~0u, v, threadIdx.x & 31); }
__device__ __forceinline__ uint32_t xor_or(uint32_t a, uint32_t b, uint32_t t) {
    uint32_t r; asm volatile("lop3.b32 %0, %1, %2, %3, 0x7E;" : "=r"(r) : "r"(a), "r"(b), "r"(t)); return r;
}
__device__ __forceinline__ uint32_t or3(uint32_t a, uint32_t b, uint32_t c) {
    uint32_t r; asm volatile("lop3.b32 %0, %1, %2, %3, 0xFE;" : "=r"(r) : "r"(a), "r"(b), "r"(c)); return r;
}
__device__ __forceinline__ uint32_t settag(uint32_t v, uint32_t tag) {
    uint32_t r; asm("lop3.b32 %0, %1, 1, %2, 0xB8;" : "=r"(r) : "r"(v), "r"(tag)); return r;
}
__device__ __forceinline__ void ldg1_if(uint32_t& v, const void* p, bool c) {
    asm volatile("{.reg .pred p; setp.ne.u32 p, %2, 0; @p ld.relaxed.gpu.global.u32 %0, [%1];}" : "+r"(v) : "l"(p), "r"((uint32_t)c) : "memory");
}
__device__ __forceinline__ void sts2(uint32_t a, float x, float y) { asm volatile("st.shared.v2.f32 [%0], {%1,%2};" ::"r"(a), "f"(x), "f"(y) : "memory"); }
__device__ __forceinline__ void sts4f(uint32_t a, float x, float y, float z, float w) {
    asm volatile("st.shared.v4.f32 [%0], {%1,%2,%3,%4};" ::"r"(a), "f"(x), "f"(y), "f"(z), "f"(w) : "memory");
}
__device__ __forceinline__ void sts1(uint32_t a, uint32_t x) { asm volatile("st.shared.u32 [%0], %1;" ::"r"(a), "r"(x) : "memory"); }
__device__ __forceinline__ uint32_t lds1(uint32_t a) { uint32_t v; asm volatile("ld.shared.u32 %0, [%1];" : "=r"(v) : "r"(a) : "memory"); return v; }
__device__ __forceinline__ float4 lds4f(uint32_t a) {
    float4 v; asm volatile("ld.shared.v4.f32 {%0,%1,%2,%3}, [%4];" : "=f"(v.x), "=f"(v.y), "=f"(v.z), "=f"(v.w) : "r"(a) : "memory"); return v;
}
__device__ __forceinline__ float2 lds2f(uint32_t a) {
    float2 v; asm volatile("ld.shared.v2.f32 {%0,%1}, [%2];" : "=f"(v.x), "=f"(v.y) : "r"(a) : "memory"); return v;
}
__device__ __forceinline__ bool any_bit0(uint32_t x) {
    uint32_t r;
    asm volatile("{.reg .pred p, q; .reg .b32 t; and.b32 t, %1, 1; setp.ne.u32 p, t, 0; vote.sync.any.pred q, p, 0xffffffff; selp.u32 %0, 1, 0, q;}" : "=r"(r) : "r"(x));
    return r;
}
__device__ __forceinline__ float rcp_fast(float x) { float r; asm("rcp.approx.ftz.f32 %0, %1;" : "=f"(r) : "f"(x)); return r; }
__device__ __forceinline__ void stsm4(uint32_t a, uint32_t r0, uint32_t r1, uint32_t r2, uint32_t r3) {
    asm volatile("stmatrix.sync.aligned.m8n8.x4.shared.b16 [%0], {%1,%2,%3,%4};" ::"r"(a), "r"(r0), "r"(r1), "r"(r2), "r"(r3) : "memory");
}
__device__ __forceinline__ void stsm4t(uint32_t a, uint32_t r0, uint32_t r1, uint32_t r2, uint32_t r3) {
    asm volatile("stmatrix.sync.aligned.m8n8.x4.trans.shared.b16 [%0], {%1,%2,%3,%4};" ::"r"(a), "r"(r0), "r"(r1), "r"(r2), "r"(r3) : "memory");
}
__device__ __forceinline__ void cp_async16(uint32_t dst, const void* src) { asm volatile("cp.async.cg.shared.global [%0], [%1], 16;" ::"r"(dst), "l"(src) : "memory"); }
__device__ __forceinline__ void cp_async16_ef(uint32_t dst, const void* src) {
    asm volatile("cp.async.cg.shared.global.L2::cache_hint [%0], [%1], 16, %2;" ::"r"(dst), "l"(src), "l"(evict_first()) : "memory");
}
__device__ __forceinline__ uint32_t prmt(uint32_t a, uint32_t b, uint32_t c) { uint32_t r; asm("prmt.b32 %0, %1, %2, %3;" : "=r"(r) : "r"(a), "r"(b), "r"(c)); return r; }
__device__ __forceinline__ uint32_t hadd2h(uint32_t a, uint32_t b) { uint32_t r; asm("add.rn.f16x2 %0, %1, %2;" : "=r"(r) : "r"(a), "r"(b)); return r; }
__device__ __forceinline__ uint32_t hmax2h(uint32_t a, uint32_t b) { uint32_t r; asm("max.f16x2 %0, %1, %2;" : "=r"(r) : "r"(a), "r"(b)); return r; }
__device__ __forceinline__ uint32_t max3u(uint32_t a, uint32_t b, uint32_t c) { return __vimax3_u32(a, b, c); }

__device__ __forceinline__ void h_load(uint32_t sb, const uint8_t* hsrc, int pass, uint32_t rank, uint32_t rot, uint32_t wq, bool arm = true, uint32_t skip = 0) {
    const uint32_t bar = sb + SM_BAR + 8 * (B_HB + (pass & 1)), c = (wq + rot) & 3, dst = sb + SM_HB + (pass & 1) * HBUF + (rank * 4 + c) * HCH + skip;
    const uint8_t* src = hsrc + ((size_t)pass * 65536 + c * 4096 + skip);
    if (arm && wq == 0) e_expect(bar, 32768 - 8 * skip);
    asm volatile("{.reg .pred p; elect.sync _|p, 0xffffffff;\n"
                 " @p cp.async.bulk.shared::cluster.global.mbarrier::complete_tx::bytes.multicast::cluster.L2::cache_hint [%0], [%1], %4, [%2], %3, %5;}"
                 ::"r"(dst), "l"(src), "r"(bar), "h"((uint16_t)3), "r"(4096 - skip), "l"(evict_first()) : "memory");
}
__device__ __forceinline__ uint4 ldg_b128(const void* p) {
    uint4 v;
    asm volatile("{.reg .b128 t; .reg .b64 a, b; ld.relaxed.gpu.global.b128 t, [%4]; mov.b128 {a, b}, t; mov.b64 {%0,%1}, a; mov.b64 {%2,%3}, b;}"
                 : "=r"(v.x), "=r"(v.y), "=r"(v.z), "=r"(v.w) : "l"(p) : "memory");
    return v;
}
__device__ __forceinline__ void stg_b128_if(bool c, void* p, uint32_t x, uint32_t y, uint32_t z, uint32_t w) {
    asm volatile("{.reg .pred p; .reg .b128 t; .reg .b64 a, b; setp.ne.u32 p, %5, 0; mov.b64 a, {%1,%2}; mov.b64 b, {%3,%4}; mov.b128 t, {a, b}; @p st.relaxed.gpu.global.b128 [%0], t;}"
                 ::"l"(p), "r"(x), "r"(y), "r"(z), "r"(w), "r"((uint32_t)c) : "memory");
}
__device__ __forceinline__ float pretag(float x, uint32_t add, uint32_t keep) { return __uint_as_float((__float_as_uint(x) + add) & keep); }

template <bool MASK, class F>
__device__ __forceinline__ void softmax_rows(uint32_t src, uint32_t dst, uint32_t g16, int row0, F mid) {
    const uint32_t u = (g16 >> 7) & 3, e = ((g16 >> 9) << 3) | ((g16 >> 4) & 7);
    const uint32_t se = src + e * 8, su = se + u * 1088;
    const float2 p0 = lds2f(su), p1 = lds2f(su + 256), p2 = lds2f(su + 512), p3 = lds2f(su + 768);
    const float2 m0 = lds2f(se + 4352), m1 = lds2f(se + 4352 + 256), m2 = lds2f(se + 4352 + 512), m3 = lds2f(se + 4352 + 768);
    float a0 = (p0.x + p1.x) + (p2.x + p3.x), a1 = (p0.y + p1.y) + (p2.y + p3.y);
    const float a2 = (m0.x + m1.x) + (m2.x + m3.x), a3 = (m0.y + m1.y) + (m2.y + m3.y);
    mid(__float_as_uint(a3));
    if (MASK) {
        const int vis = row0 + (e >> 2) - 2 * (e & 3) - 8 * u;
        if (vis < 0) a0 = -1e9f / 0.08838834764831845f;
        if (vis < 1) a1 = -1e9f / 0.08838834764831845f;
    }
    int k = __float_as_int(fmaxf(fmaxf(a0, a1), fmaxf(a2, a3)));
    k ^= (k >> 31) & 0x7fffffff;
    const bool hi = g16 & 64;
    const int k0 = __reduce_max_sync(~0u, hi ? INT_MIN : k), k1 = __reduce_max_sync(~0u, hi ? k : INT_MIN);
    k = hi ? k1 : k0;
    const float m = __int_as_float(k ^ ((k >> 31) & 0x7fffffff));
    const float sl2 = 0.08838834764831845f * 1.4426950408889634f, mb = -m * sl2;
    sts1(dst + e * 16 + u * 4, pack2(ex2(fmaf(a0, sl2, mb)), ex2(fmaf(a1, sl2, mb))));
    sts1(dst + 512 + e * 4, pack2(ex2(fmaf(a2, sl2, mb)), ex2(fmaf(a3, sl2, mb))));
}

__device__ __forceinline__ uint32_t pack_h2(float lo, float hi) {
    uint32_t r; asm("cvt.rn.satfinite.f16x2.f32 %0, %1, %2;" : "=r"(r) : "f"(hi), "f"(lo)); return r;
}
__device__ __forceinline__ float2 unpack_h2(uint32_t u) {
    float2 r; asm("{.reg .b16 l, h; mov.b32 {l, h}, %2; cvt.f32.f16 %0, l; cvt.f32.f16 %1, h;}" : "=f"(r.x), "=f"(r.y) : "r"(u)); return r;
}
__device__ __forceinline__ uint32_t h2bf(uint32_t u) {
    uint32_t r;
    asm volatile("{.reg .b16 l, h; .reg .f32 a, b; mov.b32 {l, h}, %1; cvt.f32.f16 a, l; cvt.f32.f16 b, h; cvt.rn.bf16x2.f32 %0, b, a;}" : "=r"(r) : "r"(u));
    return r;
}
__device__ __forceinline__ void red_h10(bool c, void* p, void* q, uint32_t x, uint32_t y, uint32_t z, uint32_t w, uint32_t e) {
    asm volatile("{.reg .pred p; setp.ne.u32 p, %7, 0; red.relaxed.gpu.global.add.noftz.v4.f16x2 [%0], {%2,%3,%4,%5};\n"
                 " @p red.relaxed.gpu.global.add.noftz.f16x2 [%1], %6;}" ::"l"(p), "l"(q), "r"(x), "r"(y), "r"(z), "r"(w), "r"(e), "r"((uint32_t)c) : "memory");
}
constexpr float Q_SCALE = 1024.0f;
constexpr float SM_L2E = 0.08838834764831845f * 1.4426950408889634f * Q_SCALE;
template <int V> struct IC { static constexpr int value = V; };
typedef unsigned long long u64;
__device__ __forceinline__ uint32_t lo32(u64 v) { return (uint32_t)v; }
__device__ __forceinline__ uint32_t hi32(u64 v) { return (uint32_t)(v >> 32); }
__device__ __forceinline__ u64 ldg_u64(const void* p) { u64 v; asm volatile("ld.relaxed.gpu.global.b64 %0, [%1];" : "=l"(v) : "l"(p) : "memory"); return v; }
struct RecTime { uint32_t go, x2, v, dx2, h; };
__device__ __forceinline__ void rec_main(uint32_t sb, const CUtensorMap* tWo, uint8_t* arena, int role, int hinfo, int wg, uint32_t zero, const RecTime& tm) {
    const int hA = hinfo & 255;
    const int tid = threadIdx.x, t = tid & 127, lane = tid & 31, wi = t >> 5;
    const uint32_t bars = sb + SM_BAR;
    const int head = role >> 2, qd = role & 3, j = blockIdx.x & 1, kh = role & 1;
    const uint32_t mypar = head >= hA;
    const uint32_t wiu = __reduce_max_sync(~0u, wi);
    const bool warp0 = wiu == 0;
    const uint8_t* hsrc = (const uint8_t*)g_himg + kh * 32768 + j * 16384;
    auto tokbase = [&](int ty) { return ((ty + 1) << 21) + blk(lb_tok(head), mypar ^ ((hinfo >> (8 + ty)) & 1)); };
    const uint32_t tbw = tokbase(wg), tbq = tokbase(0) + (qd >> 1) * 2048 + (qd & 1) * 8;
#define KS(p) (4 * (((p) >> 1) & 7) + ((p) >> 4) + 2 * ((p) & 1))
    uint32_t w[32 - NL][4];
    uint4 wl5;
    if (wg == 2) bar_arrive(NB_WIN, 384);
    const uint32_t po = (1 << 20) + j * 16384 + kh * 2048;
    const uint32_t c16 = kh * 2048 + ((2 * j + (wi >> 1)) * 32 + lane) * 16, xso = blk(lb_x2(head), mypar);
    const uint32_t x2o = xso + wg * 16384 + (wi & 1) * 2048 + (c16 >> 1), tko = tbw + (wi & 1) * 16384 + c16;
    {
        stg_rlx2(arena + x2o, 0, 0);
#pragma unroll
        for (int i = 0; i < 4; i++) stg_rlx4(arena + ((i & 1 ? tko : tbw + (po ^ 2048) + t * 16) + (i >> 1) * 32768), 0, 0, 0, 0);
    }
    const uint32_t frow = ((lane >> 4) * 8 + (lane & 7)) * 128, fx = ((lane >> 3) & 1) ^ (lane & 7);
    {
#pragma unroll 1
        for (int i = 0; i < 4; i++) mbar_wait_w(bars + 8 * (B_W + (wg == 2 ? 8 + i : 2 * i + wg)), 0);
        const uint32_t stg = sb + wg * 65536;
#pragma unroll
        for (int p = NL; p < 32; p++) ldsm4t(w[p - NL], stg + KS(p) * 2048 + frow + ((fx ^ (2 * wi)) << 4));
#pragma unroll
        for (int i = 0; i < NL; i++) {
            wl5 = lds4(stg + KS(i) * 2048 + t * 16);
            if (i < 5) sts4(sb + sm_wl(i) + tid * 16, wl5.x, wl5.y, wl5.z, wl5.w);
        }
        fence_async_smem();
        if (wg < 2) bar_sync(NB_WG, 256);
        if (wg > 0) wait_count_w(&g_tick[32 + (lane & 3) * 8], wg);
        if (wg == 1) {
            mbar_arrive_cluster_if(t == 0, bars + 8 * B_HE, j ^ 1);
            asm volatile("fence.proxy.async.global;" ::: "memory");
            mbar_wait_w(bars + 8 * B_HE, 0);
#pragma unroll 1
            for (int i = 0; i < 2; i++) h_load(sb, hsrc, i, j, head, wiu, true, i ? 0 : 2048);
        }
    }
    uint32_t g16 = opaque(t * 16);
    {
        const uint32_t wr = ((wg * 4 + wi) ^ head) & 7;
        const uint32_t pc = wg < 2 ? acc_piece(wr >> 2, qd, wr & 3) : acc_piece(kh, wi, 0);
        const uint32_t lm = sb + SM_HB + 4096 + (lane & 7) * 128;
        const uint32_t a0 = wg < 2 ? sb + SM_WL + wg * 2048 + frow + ((fx ^ (2 * wi)) << 4) : blk(LB_STAMP + (wi >> 1), mypar) + stamp_line(wi, lane >> 3) + (lane & 7) * 16;
        const uint32_t a1 = pc + lane * 16;
        const uint32_t a2 = wg < 2 ? pc + 512 + (lane >> 3) * 4 : (role >> 2) * 1024 + (lane < 8 ? (role & 3) * 128 : 384) + lane * 16;
        const uint32_t a3 = wg < 2 ? sb + SM_WO + (wr >> 2) * 32768 + frow + ((fx ^ (2 * (wr & 3))) << 4) : qd * 65536 + head * 2048 + wi * 512 + lane * 4;
        const uint32_t a4 = wg < 2 ? lm + ((fx ^ ((lane >> 4) * 4)) << 4) : lm + (fx << 4) + ((lane >> 4) + 2 * wi) * HCH;
        if (wg < 2) bar_arrive(NB_X2, 384);
        else bar_sync(NB_X2, 384);
        if (NL > 5) {
            sts4(sb + SM_WL2 + tid * 16, wl5.x, wl5.y, wl5.z, wl5.w);
            fence_async_smem();
            bar_sync(NB_WG + 1 + wg, 128);
        }
        sts4(sb + SM_TAB + wg * 5120 + g16, a0, x2o,
             wg ? xso + (wg == 2 ? 32768 : 0) + t * 8 : blk(LB_STAMP + ((lane >> 1) & 1), (lane >> 2) & 1) + stamp_line(lane, qd) + head * 4, tko);
        sts4(sb + SM_TAB + wg * 5120 + 2048 + g16, a1, a2, a3, a4);
        sts2(sb + SM_TAB + wg * 5120 + 4096 + t * 8, __uint_as_float(tbw + t * 16), __uint_as_float((wg ? tbq : tokbase(1)) + t * 16));
    }
    const uint32_t ONES = 0x3f803f80u, tabw = sb + SM_TAB + wg * 5120;
#define LAST ((g16 & 0x70) == 0x70)

    auto pa_ptr = [&](int p) { return arena + (((p & 1) ^ 1) * 32768 + po + lds1(tabw + 4096 + (g16 >> 1))); };
    auto pa_request = [&](int p) { cp_async16(sb + SM_PA + wg * 2048 + g16, pa_ptr(p)); };
    auto pa_get = [&](int p) {
        asm volatile("cp.async.wait_all;" ::: "memory");
        uint4 pa = lds4(sb + SM_PA + wg * 2048 + g16);
        int it = 0;
#pragma unroll 1
        while (any_bit0(pa.x ^ ((p - 1) >> 1) ^ 1) && p > 0 && p <= NSEG) { pa = ldg_b128(pa_ptr(p)); spin_guard(++it); }
        return pa;
    };
    auto pass_init = [&](float* acc, int n, uint4 pa) {
#pragma unroll
        for (int i = 0; i < 4; i++) { acc[2 * i] = bflo((&pa.x)[i]); acc[2 * i + 1] = bfhi((&pa.x)[i]); }
#pragma unroll
        for (int i = 8; i < n; i++) acc[i] = 0.f;
    };
    auto pass_run = [&](auto vc, int p, float* acc, auto mid) {
        constexpr bool V = decltype(vc)::value;
#define HB(ks) dadd(mkdesc(SB0 + SM_HB + ((ks) >> 2) * HCH + ((ks) & 3) * 32, 16, 1024, 1), (p & 1) * (HBUF / 16))
        wg_fence();
#pragma unroll
        for (int i = 0; i < 32; i++) {
            constexpr int GAP = V ? SSG_V : SSG, SS0 = V ? SS0_V : SS0_K;
            const int u = i < SS0 ? 0 : (i - SS0 + GAP - 1) / GAP, q = i - (u < NL ? u : NL);
            if (i >= SS0 && (i - SS0) % GAP == 0 && u < NL) wgmma_tok_ss<V>(acc, dadd(mkdesc(SB0 + sm_wl(u), 8192, 1024, 1), (V ? 2 : wg) * 128), HB(KS(u)));
            else wgmma_tok_rs<V>(acc, w[q], HB(KS(NL + q)), 1);
            mid(i);
        }
        wg_commit();
    };
    auto pass_out = [&](auto tc, int p, float* acc, auto mid) {
        constexpr int TY = decltype(tc)::value;
        const bool V = TY == 2 || (TY == 4 && wg == 2), Q = TY >= 3 && wg == 0;
        const int b = p & 1, s = p - 2;
        (void)s;
        const uint32_t ftag = (((p - 1) >> 1) & 1) ^ 1, ptag = ((p >> 1) & 1) ^ 1;
        const bool tg = V || !(g16 & 64);
        const uint32_t add = tg ? (ftag ^ 1) << 16 : 0u, keep = tg ? 0xfffe0000u : ~0u;
        const uint32_t add1 = V ? 0u : add, keep1 = V ? ~0u : keep;
        const uint32_t add2 = Q ? add : 0u, keep2 = Q ? keep : ~0u;
        uint8_t* pdst = arena + (b * 32768 + (po ^ 2048) + lds1(tabw + 4096 + (g16 >> 1)));
        uint8_t* fdst = arena + ((b ^ 1) * 32768 + lds1(tabw + 12 + g16));
        if (PIN_EPI) asm volatile("" : "+l"(pdst), "+l"(fdst));
        mid(0);
        uint32_t r0 = pack2(pretag(acc[0], add, keep), pretag(acc[1], add1, keep1));
        uint32_t r1 = pack2(acc[2], acc[3]), r3 = pack2(acc[6], acc[7]);
        uint32_t r2 = pack2(pretag(acc[4], add2, keep2), pretag(acc[5], add2, keep2));
        if (!V) { r0 = movm(r0); r1 = movm(r1); r2 = movm(r2); r3 = movm(r3); }
        mid(1);
        stg_b128_if(p < NSEG, pdst, settag(pack2(pretag(acc[8], (ptag ^ 1) << 16, 0xfffe0000u), acc[9]), ptag), pack2(acc[10], acc[11]), pack2(acc[12], acc[13]), pack2(acc[14], acc[15]));
        stg_b128_if(p > 0 && p <= NSEG, fdst, settag(r0, ftag), r1, Q ? settag(r2, ftag) : r2, r3);
    };
    auto nop = [](int) {};
    auto wait0 = [](int i) { if (i == 0) wg_wait<0>(); };
    uint4 tf[2][2];
    auto load_tok = [&](int s, uint32_t o) {
        const uint8_t* ts = arena + ((s & 1) * 32768 + o);
#pragma unroll
        for (int a = 0; a < 2; a++)
#pragma unroll
            for (int b = 0; b < 2; b++) tf[a][b] = ldg_b128(ts + a * 16384 + b * 2048);
    };

    auto wo_load = [&](int stage) {
        if (wg == 2 && ((WO_AT >> (4 * wiu)) & 15) == stage) {
            const int c0 = (wiu >> 1) * 512 + qd * 128 + (wiu & 1) * 64;
            e_expect(bars + 8 * B_WO, 16384);
            e_tma2d(sb + SM_WO + wiu * 16384, tWo, c0, head * DH, bars + 8 * B_WO);
            e_tma2d(sb + SM_WO + wiu * 16384 + 8192, tWo, c0, head * DH + 64, bars + 8 * B_WO);
        }
    };
#pragma unroll 1
    for (int p = 0; p <= (wg >> 1); p++) {
        mbar_wait_w(bars + 8 * (B_HB + p), 0);
        float acc[16];
        pass_init(acc, 16, pa_get(p));
        wo_load(p);
        pass_run(IC<0>(), p, acc, nop);
        if (p) {
            mbar_wait_w(bars + 8 * B_HE, 1);
            asm volatile("fence.proxy.async.global;" ::: "memory");
            h_load(sb, hsrc, 2, j, head, wiu);
        }
        pass_out(IC<4>(), p, acc, wait0);
        if (wg < 2) {
            bar_arrive(NB_C, 384);
            if (wg == 0) bar_arrive(NB_WIN, 384);
        } else if (p == 0) {
            bar_sync(NB_C, 384);
            mbar_arrive_cluster_if(g16 == 0, bars + 8 * B_HE, j ^ 1);
        }
        pa_request(p + 1);
    }
    if (wg < 2) {
        mbar_wait_w(bars + 8 * (B_HB + 1), 0);
        uint4 pa = pa_get(1);
        uint32_t wl = lds1(tabw + g16);
#pragma unroll 1
        for (int s = 0; s < NSEG; s++) {
            uint32_t w0[NL][4], xo, lm, fz = 0;
            float acc[16];
#pragma unroll
            for (int i = 0; i < 4; i++)
                asm volatile("shl.b32 %0, %4, 16; and.b32 %1, %4, 0xffff0000; mov.b32 %2, %5; mov.b32 %3, %5;"
                             : "=&f"(acc[2 * i]), "=f"(acc[2 * i + 1]), "=f"(acc[8 + 2 * i]), "=f"(acc[9 + 2 * i]) : "r"((&pa.x)[i]), "r"(zero));
#pragma unroll
            for (int i = 0; i < NL; i++) ldsm4t(w0[i], wl + (sm_wl(i) - SM_WL));
            if (wg == 0) bar_sync(NB_B, 256);
            else bar_sync(NB_WIN, 384);
            pass_run(IC<0>(), s + 1, acc, [&](int i) { if (i == GATE_AT && wg) bar_arrive(NB_B, 256); });
            xo = lds1(tabw + 4 + g16);
            lm = lds1(tabw + 2060 + g16) + (s & 1) * HBUF;
            pass_out(IC<3>(), s + 1, acc, [&](int i) {
                if (i == 0) {
                    wg_wait<0>();
                    if (wg == 0) bar_arrive(NB_MEM, 384);
                    fz |= clk32();
                }
                if (i == 1 && wg) bar_sync(NB_F, 256);
            });
            asm volatile("" : "+r"(lm));
            if (wg == 0) bar_sync(NB_MEM2, 256);
            else bar_sync(NB_MEM, 384);
            float c[4][4];
            uint32_t bq[PD][4];
#define MEMF(it) ((lm ^ (((it) >> 3) * 32)) + ((it) & 7) * HCH)
#pragma unroll
            for (int it = 0; it < PD; it++) ldsm4(bq[it], MEMF(it));
#pragma unroll
            for (int it = 0; it < 16; it++) {
                uint32_t* bfr = bq[it % PD];
                const uint32_t* wa = 2 * it < NL ? w0[2 * it < NL ? 2 * it : 0] : w[2 * it < NL ? 0 : 2 * it - NL];
                const uint32_t* wb = 2 * it + 1 < NL ? w0[2 * it + 1 < NL ? 2 * it + 1 : 0] : w[2 * it + 1 < NL ? 0 : 2 * it + 1 - NL];
                float *ca = c[(2 * it) & 3], *cb = c[(2 * it + 1) & 3];
                if (it < 2) { mma16816z(ca, wa, bfr[0], bfr[1]); mma16816z(cb, wb, bfr[2], bfr[3]); }
                else { mma16816(ca, wa[0], wa[1], wa[2], wa[3], bfr[0], bfr[1]); mma16816(cb, wb[0], wb[1], wb[2], wb[3], bfr[2], bfr[3]); }
                if (it + PD < 16) ldsm4(bfr, MEMF(it + PD));
            }
            const float qs = wg ? 1.0f : 1.0f / Q_SCALE;
#define CSUM(e) fmaf(c[2][e] + c[3][e], qs, (c[0][e] + c[1][e]) * qs)
            const uint32_t r0 = pack2(CSUM(0), CSUM(1)), r1 = pack2(CSUM(2), CSUM(3));
            bar_arrive(NB_QK + (r0 & zero), 384);
            stg_rlx2(arena + xo, settag(movm(r0), (s & 1) ^ 1), movm(r1));
            const uint32_t tx = later(lds1(sb + SM_LX + 1040) + tm.x2, clk_after(r0, zero) + tm.dx2);
            g16 |= (fz | tx) & zero;
            {
                const uint32_t l16 = sb + (g16 & 0x1f0), g8 = g16 >> 1;
                const uint32_t tag = (s & 1) ^ 1, ttag = ((s >> 1) & 1) ^ 1;
                uint32_t wf[NPF][4], a3;
#define WF(f) (a3 + ((f) & 1) * 16384 + ((f) >> 1) * 2048)
                if (wg == 1) {
                    float sc[5][4];
                    uint4 (&kf)[2][2] = tf;
                    uint32_t qa[2][4], km[4], fz;
                    const uint32_t sd = lds1(sb + SM_TAB + 8 + g16);
                    int it = 0;
                    bool bad;
#pragma unroll 1
                    do {
                        u64 qf[2], x[8];
                        const float2 u = lds2f(tabw + 4096 + g8);
                        load_tok(s, __float_as_uint(u.x));
                        const uint8_t *xp = arena + lds1(tabw + 8 + g16), *tq = arena + ((s & 1) * 32768 + __float_as_uint(u.y));
                        asm volatile("" : "+l"(xp));
                        asm volatile("" : "+l"(tq));
#pragma unroll
                        for (int a = 0; a < 2; a++) qf[a] = ldg_u64(tq + a * 16384);
                        spin_guard(++it);
                        wait_clk(tx);
#pragma unroll
                        for (int i = 0; i < 8; i++) x[i] = ldg_u64(xp + (i >> 2) * 16384 + (i & 3) * 1024);
                        fz = clk32();
                        const uint32_t bt = or3(xor_or(lo32(qf[0]), lo32(qf[1]), ttag), xor_or(kf[0][0].x, kf[0][1].x, ttag), xor_or(kf[1][0].x, kf[1][1].x, ttag));
#pragma unroll
                        for (int a = 0; a < 2; a++) { qa[a][1] = or3(lo32(qf[a]), zero, 0); qa[a][3] = or3(hi32(qf[a]), zero, 0); }
                        fz |= clk32();
#pragma unroll
                        for (int a = 0; a < 2; a++) { qa[a][0] = hadd2v(lo32(x[2 * a]), lo32(x[2 * a + 1])); qa[a][2] = hadd2v(hi32(x[2 * a]), hi32(x[2 * a + 1])); }
#pragma unroll
                        for (int a = 0; a < 2; a++) { km[2 * a] = hadd2v(lo32(x[4 + 2 * a]), lo32(x[5 + 2 * a])); km[2 * a + 1] = hadd2v(hi32(x[4 + 2 * a]), hi32(x[5 + 2 * a])); }
                        bad = any_bit0(or3(or3(bt, xor_or(lo32(x[0]), lo32(x[1]), tag), xor_or(lo32(x[2]), lo32(x[3]), tag)), xor_or(lo32(x[4]), lo32(x[5]), tag), xor_or(lo32(x[6]), lo32(x[7]), tag)));
                    } while (bad);
                    mma16816z(sc[0], qa[0], kf[0][0].x, kf[0][0].y);
                    mma16816z(sc[1], qa[0], kf[0][0].z, kf[0][0].w);
                    mma16816z(sc[2], qa[0], kf[0][1].x, kf[0][1].y);
                    mma16816z(sc[3], qa[0], kf[0][1].z, kf[0][1].w);
                    mma16816z(sc[4], qa[0], km[0], km[1]);
                    mma16816(sc[0], qa[1][0], qa[1][1], qa[1][2], qa[1][3], kf[1][0].x, kf[1][0].y);
                    mma16816(sc[1], qa[1][0], qa[1][1], qa[1][2], qa[1][3], kf[1][0].z, kf[1][0].w);
                    mma16816(sc[2], qa[1][0], qa[1][1], qa[1][2], qa[1][3], kf[1][1].x, kf[1][1].y);
                    mma16816(sc[3], qa[1][0], qa[1][1], qa[1][2], qa[1][3], kf[1][1].z, kf[1][1].w);
                    mma16816(sc[4], qa[1][0], qa[1][1], qa[1][2], qa[1][3], km[2], km[3]);
                    const uint32_t sx = sb + SM_SX + (g16 & 0x1f0) * 5;
                    sts4(sx + (g16 >> 5 & 0x30), pack_h2(sc[0][0], sc[0][1]), pack_h2(sc[1][0], sc[1][1]),
                         pack_h2(sc[2][0], sc[2][1]), pack_h2(sc[3][0], sc[3][1]));
                    sts1(sx + 64 + (g16 >> 7 & 0xc), pack_h2(sc[4][0], sc[4][1]));
                    bar_arrive(NB_X1, 256);
                    const uint32_t now = gtime32();
#pragma unroll
                    for (int n = 0; n < 5; n++) sts2(sb + SM_ST + g8 + n * 1088, sc[n][2], sc[n][3]);
                    bar_arrive(NB_H, 256);
                    a3 = lds1(tabw + 2056 + g16) | (fz & zero);
                    asm volatile("{.reg .pred p; setp.lt.u32 p, %2, 128; @p red.relaxed.gpu.global.max.u32 [%0], %1;}"
                                 ::"l"(arena + sd), "r"(__funnelshift_r(now * 8, s + 1, 8)), "r"(g16) : "memory");
                    if (s == 0) mbar_wait_w(bars + 8 * B_WO, 0);
                    a3 += delay<PF_DLY>(zero);
#pragma unroll
                    for (int f = 0; f < NPF; f++) ldsm4t(wf[f], WF(f));
                } else {
                    if (s == 0) { mbar_wait_w(bars + 8 * B_WO, 0); }
                    const uint32_t need = warp0 ? min(s / 2 + 3, 32) : 0;
                    uint32_t seen = s ? lds1(sb + SM_LX + 1024 + ((g16 >> 2) & 12)) : 0;
                    const bool look = __any_sync(~0u, seen < need);
                    ldg1_if(seen, &g_tick[32 + ((g16 >> 4) & 3) * 8], look);
                    a3 = lds1(tabw + 2056 + g16);
#pragma unroll
                    for (int f = 0; f < NPF0; f++) ldsm4t(wf[f], WF(f));
                    const float2 u = lds2f(tabw + 4096 + g8);
                    const uint8_t *q0 = arena + (tag * 32768 + po + __float_as_uint(u.x)), *q1 = arena + (tag * 32768 + po + __float_as_uint(u.y));
                    wait_clk(tx + tm.h);
                    int it = 0;
                    bool bad;
#pragma unroll 1
                    do {
                        const uint4 p0 = ldg_b128(q0), p1 = ldg_b128(q1);
                        spin_guard(++it);
                        wait_clk(tx + tm.v);
#pragma unroll
                        for (int f = NPF0; f < NPF1; f++) ldsm4t(wf[f], WF(f));
                        sts4(sb + SM_PA + g16, p0.x, p0.y, p0.z, p0.w);
                        sts4(sb + SM_PA + 2048 + g16, p1.x, p1.y, p1.z, p1.w);
                        bad = any_bit0(xor_or(p0.x, p1.x, ((s + 1) >> 1) ^ 1)) && s + 2 <= NSEG;
                    } while (bad);
                    if (look) {
                        if (__any_sync(~0u, seen < need)) seen = wait_count_w(&g_tick[32 + ((g16 >> 4) & 3) * 8], need);
                        asm volatile("fence.acquire.gpu;" ::: "memory");
                        sts1(sb + SM_LX + 1024 + ((g16 >> 2) & 12), seen);
                    }
                    bar_sync(NB_H, 256);
                    softmax_rows<true>(sb + SM_ST, sb + SM_PX, g16, qd * 8, [&](uint32_t v) {
                        a3 += v & zero;
#pragma unroll
                        for (int f = NPF1; f < NPF2; f++) ldsm4t(wf[f], WF(f));
                    });
#pragma unroll
                    for (int f = NPF2; f < NPF; f++) ldsm4t(wf[f], WF(f));
                }
                float2 ls, a12;
                uint8_t *d0, *d1;
                bar_sync(NB_X2, 384);
                float c[4][4];
#pragma unroll
                for (int q = 0; q < 4; q++) {
                    uint32_t ob[4];
                    ldsm4t(ob, l16 + SM_OX + q * 512);
                    if (q == L_AT) ls = lds2f(sb + SM_LX + g8);
                    if (q == 2) { pa = lds4(sb + SM_PA + wg * 2048 + g16); wl = lds1(tabw + g16); }
                    if (q == 2) { a12 = lds2f(tabw + 2048 + g16); d0 = arena + (acc_slot(s + 1) + __float_as_uint(a12.x)); d1 = arena + (acc_slot(s + 1) + __float_as_uint(a12.y)); }
#pragma unroll
                    for (int f = 4 * q; f < 4 * q + 4; f++) {
                        const uint32_t* a = wf[f % NPF];
                        if (f < 4) mma16816z(c[f], a, ob[f & 2], ob[(f & 2) + 1]);
                        else mma16816(c[f & 3], a[0], a[1], a[2], a[3], ob[f & 2], ob[(f & 2) + 1]);
                        if (f + NPF < 16) ldsm4t(wf[f % NPF], WF(f + NPF));
                    }
                }
                if (wg == 0) bar_arrive(NB_WIN, 384);
                const float i0 = rcp_fast(ls.x), i1 = rcp_fast(ls.y);
                uint32_t v[4];
#pragma unroll
                for (int m = 0; m < 4; m++) v[m] = pack_h2((c[m >> 1][(m & 1) * 2] + c[(m >> 1) + 2][(m & 1) * 2]) * i0, (c[m >> 1][(m & 1) * 2 + 1] + c[(m >> 1) + 2][(m & 1) * 2 + 1]) * i1);
                red_h10(LAST, d0, d1, v[0], v[1], v[2], prmt(v[3], ACC_ONE, LAST ? 0x7610 : 0x3210), prmt(v[3], ACC_ONE, 0x7632));
                g16 |= v[0] & zero;
            }
        }
        if (wg) bar_sync(NB_WIN, 384);
    } else {
        auto request = [&](int s, uint32_t o) {
            cp_async16(sb + SM_PA + 4096 + g16, arena + (((s & 1) ^ 1) * 32768 + po + o));
            const uint8_t* ts = arena + ((s & 1) * 32768 + o);
#pragma unroll
            for (int i = 0; i < 4; i++) cp_async16(sb + SM_VF + i * 2048 + g16, ts + (i >> 1) * 16384 + (i & 1) * 2048);
        };
        auto fetch = [&](int s, uint4 t1, auto wait, auto after) {
            const uint32_t mo = acc_slot(s) + t1.x, eo = mo - (g16 & 0x1f0) + 512 + ((g16 >> 5) & 12);
            const uint8_t *ms = arena + mo, *es = arena + eo;
            uint32_t e[4] = {0, 0, 0, 0}, sel = LAST ? 0x5410 : 0x3210, dst[4];
#pragma unroll
            for (int i = 0; i < 4; i++) dst[i] = (t1.w + (s & 1) * HBUF) ^ (i * 32);
            asm volatile("" : "+l"(ms), "+l"(es), "+r"(e[0]), "+r"(e[1]), "+r"(e[2]), "+r"(e[3]), "+r"(sel), "+r"(dst[0]), "+r"(dst[1]), "+r"(dst[2]), "+r"(dst[3]));
            uint32_t late = wait(), fz;
            int it = 0;
            bool bad;
#pragma unroll 1
            do {
                uint4 m[4];
                uint32_t b = 0;
#pragma unroll
                for (int i = 0; i < 4; i++) {
                    m[i] = ldg_rlx4(ms + i * 1024);
                    ldg1_if(e[i], es + i * 1024, LAST);
                }
                if (it == 0) bar_arrive(NB_F, 256);
                const uint32_t now = clk32();
                fz = now;
                after(now & zero);
                sts1(sb + SM_LX + 1040, now - min(late >> 8, 8u) * 57);
                late = 0;
                spin_guard(++it);
#pragma unroll
                for (int i = 0; i < 4; i++) {
                    if (STG_FENCE >> i & 1) fz |= clk32();
                    b |= xor_or(m[i].w, e[i], ACC_ALL);
                    stsm4t(dst[i], h2bf(m[i].x), h2bf(m[i].y), h2bf(m[i].z), h2bf(prmt(m[i].w, e[i], sel)));
                }
                bad = __any_sync(~0u, LAST && b > 0xffffu);
            } while (bad);
            bar_arrive(NB_MEM, 384);
            bar_arrive(NB_MEM2, 256);
            g16 |= fz & zero;
        };
        fetch(0, lds4(tabw + 2048 + g16), []() { return 0u; }, [&](uint32_t z) { request(0, lds1(tabw + 4096 + (g16 >> 1)) + z); });
        wo_load(2);
#pragma unroll 1
        for (int s = 0;; s++) {
            const uint32_t tag = (s & 1) ^ 1, ttag = ((s >> 1) & 1) ^ 1, l16 = sb + (g16 & 0x1f0), g8 = g16 >> 1;
            const int p = s + 2;
            fence_async_smem();
            stg_b128_if(g16 < ((role & 3) ? 128 : 160), arena + (acc_slot(s + 3) + lds1(tabw + 2052 + g16)), 0, 0, 0, 0);
            const uint4 pa = pa_get(p);
            if (p <= NSEG) mbar_wait_w(bars + 8 * (B_HB + (p & 1)), (p >> 1) & 1);
            asm volatile("fence.proxy.async.global;" ::: "memory");
            if (warp0 && s + 3 <= NSEG) e_expect(bars + 8 * (B_HB + ((s + 3) & 1)), 32768);
            uint8_t* xd = arena + lds1(tabw + 4 + g16);
            uint32_t tx;
            float acc[20];
            pass_init(acc, 20, pa);
            bar_sync(NB_QK, 384);
            pass_run(IC<1>(), p, acc, nop);
            pass_out(IC<2>(), p, acc, [&](int i) {
                if (i) return;
                wg_wait<0>();
                const uint32_t r0 = pack2(acc[16], acc[17]);
                stg_rlx2(xd, settag(r0, tag), pack2(acc[18], acc[19]));
                tx = clk_after(r0, zero) + 100;
            });
            uint4 (&vf)[2][2] = tf;
#pragma unroll
            for (int i = 0; i < 4; i++) vf[i >> 1][i & 1] = lds4(sb + SM_VF + i * 2048 + g16);
            uint32_t xv[4] = {0, 0, 0, 0};
            float oc[2][4], lc[4];
            auto pv = [&](uint32_t p0, uint32_t p1, uint32_t p2, uint32_t p3, uint32_t p4, auto mid) {
                lc[0] = lc[1] = lc[2] = lc[3] = 0.f;
                mma16816z(oc[0], &vf[0][0].x, p0, p1);
                mma16816z(oc[1], &vf[1][0].x, p0, p1);
                mma16816(lc, ONES, ONES, ONES, ONES, p0, p1);
                mma16816(oc[0], vf[0][1].x, vf[0][1].y, vf[0][1].z, vf[0][1].w, p2, p3);
                mma16816(oc[1], vf[1][1].x, vf[1][1].y, vf[1][1].z, vf[1][1].w, p2, p3);
                mma16816(lc, ONES, ONES, ONES, ONES, p2, p3);
                mid();
                mma1688(oc[0], xv[0], xv[1], p4);
                mma1688(oc[1], xv[2], xv[3], p4);
                mma1688(lc, ONES, ONES, p4);
            };
            uint32_t so, to, fz = 0;
            uint4 t1;
            int it = 0;
            bool bad;
#pragma unroll 1
            do {
#pragma unroll 1
                for (int i = it; i > 0; i &= zero) load_tok(s, lds1(tabw + 4096 + g8));
                u64 xr[4];
                const uint8_t* xp = arena + lds1(tabw + 8 + g16);
                asm volatile("" : "+l"(xp));
                const uint32_t bt = or3(xor_or(vf[0][0].x, vf[0][1].x, ttag), xor_or(vf[1][0].x, vf[1][1].x, ttag), 0);
                uint32_t sa = sb + SM_SX + (g16 & 0x1f0) * 5;
                asm volatile("" : "+r"(sa));
                spin_guard(it);
                wait_clk(tx);
                if (it++ == 0) bar_sync(NB_X1, 256);
                uint4 sx[5];
#pragma unroll
                for (int i = 0; i < 5; i++) sx[i] = lds4(sa + i * 16);
                __syncwarp();
#pragma unroll
                for (int i = 0; i < 4; i++) xr[i] = ldg_u64(xp + (VP_AT == 2 ? sx[0].x & zero : 0) + i * 1024);
                uint32_t a[5], pm[5];
#pragma unroll
                for (int n = 0; n < 5; n++) {
                    uint32_t u[4];
#pragma unroll
                    for (int w = 0; w < 4; w++) u[w] = n < 4 ? (&sx[w].x)[n] : (&sx[4].x)[w];
                    a[n] = hadd2h(hadd2h(u[0], u[1]), hadd2h(u[2], u[3]));
                }
                uint32_t m = hmax2h(hmax2h(hmax2h(a[0], a[1]), hmax2h(a[2], a[3])), a[4]);
                const uint32_t m1 = __shfl_xor_sync(~0u, m, 1), m2 = __shfl_xor_sync(~0u, m, 2), m3 = __shfl_xor_sync(~0u, m, 3);
                m = hmax2h(hmax2h(m, m1), hmax2h(m2, m3));
                so = lds1(tabw + g16); t1 = lds4(tabw + 2048 + g16); to = lds1(tabw + 4096 + g8);
                const float2 mm = unpack_h2(m);
                const float mf = -SM_L2E * fmaxf(mm.x, mm.y);
#pragma unroll
                for (int n = 0; n < 5; n++) { const float2 u = unpack_h2(a[n]); pm[n] = pack2(ex2(fmaf(u.x, SM_L2E, mf)), ex2(fmaf(u.y, SM_L2E, mf))); }
                pv(pm[0], pm[1], pm[2], pm[3], pm[4], [&]() {
                    if (PV_FENCE & 1) fz = clk32();
#pragma unroll
                    for (int i = 0; i < 2; i++) { xv[2 * i] = hadd2v(lo32(xr[2 * i]), lo32(xr[2 * i + 1])); xv[2 * i + 1] = hadd2v(hi32(xr[2 * i]), hi32(xr[2 * i + 1])); }
                });
                bad = any_bit0(or3(bt, xor_or(lo32(xr[0]), lo32(xr[1]), tag), xor_or(lo32(xr[2]), lo32(xr[3]), tag)));
                if (PV_FENCE & 2) fz |= clk32();
                stsm4(sb + SM_OX + g16, pack2(oc[0][0], oc[0][1]), pack2(oc[0][2], oc[0][3]), pack2(oc[1][0], oc[1][1]), pack2(oc[1][2], oc[1][3]));
                sts2(sb + SM_LX + g8, lc[0], lc[1]);
            } while (bad);
            bar_sync(NB_X2, 384);
            const uint8_t* sp = arena + so;
            uint4 sv = ldg_rlx4(sp);
            if (s + 3 <= NSEG) h_load(sb, hsrc, s + 3, j, head, wiu, false);
            const uint4 pp = lds4(l16 + SM_PX + delay<TPV_DLY>(zero));
            pv(pp.x, pp.y, pp.z, pp.w, lds1(sb + SM_PX + 512 + ((g16 >> 2) & 0x7c)), []() {});
            const float i0 = rcp_fast(lc[0]), i1 = rcp_fast(lc[1]);
            bar_arrive(NB_WIN + ((__float_as_uint(i0) | fz) & zero), 384);
            uint8_t* od = (uint8_t*)g_O + ((size_t)s * (32 * NH * DH * 2) + t1.z);
            const uint32_t ov[4] = {pack2(oc[0][0] * i0, oc[0][1] * i1), pack2(oc[0][2] * i0, oc[0][3] * i1), pack2(oc[1][0] * i0, oc[1][1] * i1), pack2(oc[1][2] * i0, oc[1][3] * i1)};
#pragma unroll
            for (int a = 0; a < 4; a++) if (s + 1 == NSEG) stg_rlx1(od + a * 128, ov[a]);
            if (s + 1 == NSEG) break;
            fetch(s + 1, t1, [&]() {
                int it = 0;
#pragma unroll 1
                while (__any_sync(~0u, (int)(min(__vimin3_u32(sv.x, sv.y, sv.z), sv.w) >> 24) <= s)) {
                    sv = ldg_rlx4(sp);
                    spin_guard(++it);
                }
                const uint32_t tgo = (__reduce_max_sync(~0u, max(max3u(sv.x, sv.y, sv.z), sv.w)) + tm.go + (sv.x & zero)) << 8;
                int late;
#pragma unroll 1
                do { late = gtime32() * 8 - tgo; } while (late < 0);
                __syncwarp();
                return (uint32_t)late;
            }, [&](uint32_t z) {
#pragma unroll
                for (int a = 0; a < 4; a++) stg_rlx1(od + a * 128, ov[a]);
                request(s + 1, to + z);
            });
        }
    }
    asm volatile("cp.async.wait_all;" ::: "memory");
}

struct RecMaps { CUtensorMap wq, wk, wv, wo; };
struct RecPtrs { const bf16 *x, *mem0, *c, *wmod, *w1, *w3; uint8_t* arena; uint32_t zero; RecTime tm; };

__device__ __forceinline__ float silu_bf(const bf16* c, int i) {
    const float v = __bfloat162float(c[i]);
    return bfround(__fdividef(v, 1.0f + __expf(-v)));
}
__device__ __noinline__ void rec_ln(float* coef, const RecPtrs& p, int id, int r0) {
    int r1 = 32;
    const int tid = threadIdx.x;
    const int lane = tid & 31, wid = tid >> 5;
    const uint32_t ring = smem_u32(coef) - SM_PRE + wid * 8192 + lane * 16;
    auto fetch = [&](int r) {
        if (r < r1) {
            const bf16* src = p.x + (size_t)(r * 64 + (id * 8 + wid) * 2) * DM + lane * 8;
#pragma unroll
            for (int i = 0; i < 8; i++) cp_async16(ring + (r & 1) * 4096 + i * 512, src + i * 256);
        }
        asm volatile("cp.async.commit_group;" ::: "memory");
    };
    auto row8 = [&](uint32_t a, float* f) {
        const uint4 v = lds4(a);
        f[0] = bflo(v.x); f[1] = bfhi(v.x); f[2] = bflo(v.y); f[3] = bfhi(v.y); f[4] = bflo(v.z); f[5] = bfhi(v.z); f[6] = bflo(v.w); f[7] = bfhi(v.w);
    };
#pragma unroll 1
    for (int r = r0 - 2; r < r1; r++) {
        if (r >= r0) {
            asm volatile("cp.async.wait_group 1;" ::: "memory");
            const uint32_t a = ring + (r & 1) * 4096;
            float m[2] = {0.f, 0.f}, t[2];
#pragma unroll 1
            for (int ps = 0; ps < 2; ps++) {
                t[0] = t[1] = 0.f;
#pragma unroll 1
                for (int i = 0; i < 4; i++)
#pragma unroll
                    for (int h = 0; h < 2; h++) {
                        float f[8];
                        row8(a + h * 2048 + i * 512, f);
#pragma unroll
                        for (int e = 0; e < 8; e++) { const float d = f[e] - m[h]; t[h] = fmaf(d, ps ? d : 1.0f, t[h]); }
                    }
#pragma unroll
                for (int o = 16; o; o >>= 1) { t[0] += __shfl_xor_sync(~0u, t[0], o); t[1] += __shfl_xor_sync(~0u, t[1], o); }
                if (ps == 0) { m[0] = t[0] * (1.0f / DM); m[1] = t[1] * (1.0f / DM); }
            }
            t[0] = rsqrtf(t[0] * (1.0f / DM) + 1e-5f); t[1] = rsqrtf(t[1] * (1.0f / DM) + 1e-5f);
            if (r == r0) {
#pragma unroll 1
                for (int i = tid; i < 2 * DM / 4; i += 256) {
                    float4 u;
                    int it = 0;
                    uint32_t ok;
#pragma unroll 1
                    do {
                        uint4 v[8];
#pragma unroll
                        for (int k = 0; k < 8; k++) v[k] = ldg_rlx4(g_modp + k * 2 * DM + i * 4);
                        ok = 1;
                        u = make_float4(0.f, 0.f, 0.f, 0.f);
#pragma unroll
                        for (int k = 0; k < 8; k++) {
                            ok &= v[k].x & v[k].y & v[k].z & v[k].w;
                            u.x += __uint_as_float(v[k].x); u.y += __uint_as_float(v[k].y); u.z += __uint_as_float(v[k].z); u.w += __uint_as_float(v[k].w);
                        }
                        spin_guard(++it);
                    } while (!ok);
                    const uint32_t lo = pack2(u.x, u.y), hi = pack2(u.z, u.w);
                    const float one = i >= DM / 4 ? 1.0f : 0.0f;
                    *(float4*)(coef + i * 4) = make_float4(bflo(lo) + one, bfhi(lo) + one, bflo(hi) + one, bfhi(hi) + one);
                }
                bar_sync(NB_FIN0, 256);
            }
            const int row = r * 64 + (id * 8 + wid) * 2;
#pragma unroll 1
            for (int i = 0; i < 4; i++) {
                const float4* cf = (const float4*)(coef + i * 256 + lane * 8);
                const float4 s0 = cf[0], s1 = cf[1], c0 = cf[256], c1 = cf[257];
                const float sh[8] = {s0.x, s0.y, s0.z, s0.w, s1.x, s1.y, s1.z, s1.w}, sc[8] = {c0.x, c0.y, c0.z, c0.w, c1.x, c1.y, c1.z, c1.w};
                const int own = ((row >> 4) & 1) == (i >> 1), rr = row & 15;
                const uint32_t off = ((row >> 5) + own) * 65536 + (i * 4 + (lane >> 3)) * 4096 + (rr + (own ? 0 : 16)) * 128 + (((lane & 7) ^ (rr & 7)) << 4);
#pragma unroll
                for (int h = 0; h < 2; h++) {
                    float y[8];
                    row8(a + h * 2048 + i * 512, y);
#pragma unroll
                    for (int e = 0; e < 8; e++) y[e] = fmaf((y[e] - m[h]) * t[h], sc[e], sh[e]);
                    *(uint4*)((uint8_t*)g_himg + (off ^ (h * 144))) = pack8(y);
                }
            }
            if (r == 0) {
                int v, it = 0;
#pragma unroll 1
                do { v = *(volatile int*)((uint8_t*)coef - SM_PRE + SM_BAR + 192); spin_guard(++it); } while (v == INT_MIN);
                if (v >= 0) r1 = 2;
            }
        }
        fetch(r + 2);
        if (r < r0) continue;
        bar_sync(r == 0 ? NB_C : r == 1 ? NB_FIN0 : NB_LN, r == 0 ? 320 : r == 1 ? 256 : 288);
        if (r < 2 && wid == r) {
            if (r == 1) bar_arrive(NB_B, 64);
            if (lane == 0) { signal_count(&g_tick[32 + id * 8]); }
            __syncwarp();
        }
    }
}
template <int NQ, int CG>
__device__ __forceinline__ void side_gemv(const bf16* w, int ld, int ncol, const float* coef, float* red, float* out, int ostride, bool round) {
    constexpr int KG = 384 / CG, W = CG * 8;
    const int tid = threadIdx.x, cg = tid % CG, kg = tid / CG;
    float acc[NQ][8];
#pragma unroll
    for (int q = 0; q < NQ; q++)
#pragma unroll
        for (int j = 0; j < 8; j++) acc[q][j] = 0.f;
    if (cg * 8 < ncol) {
        const bf16* src = w + cg * 8;
        const uint32_t ring = smem_u32(red) + 36864 + tid * 16;
        auto fetch = [&](int k0, int slot) {
#pragma unroll
            for (int i = 0; i < 4; i++)
                if (k0 + i * KG < DM) cp_async16_ef(ring + (slot * 4 + i) * 6144, src + (size_t)(k0 + i * KG) * ld);
            asm volatile("cp.async.commit_group;" ::: "memory");
        };
#pragma unroll 1
        for (int g = 0; g < 5; g++) fetch(kg + g * 4 * KG, g);
#pragma unroll 1
        for (int k0 = kg, slot = 0; k0 < DM; k0 += 4 * KG) {
            fetch(k0 + 20 * KG, slot ? slot - 1 : 5);
            asm volatile("cp.async.wait_group 5;" ::: "memory");
#pragma unroll
            for (int i = 0; i < 4; i++) {
                const int k = k0 + i * KG;
                if (k < DM) {
                    const uint4 v = lds4(ring + (slot * 4 + i) * 6144);
                    const float f[8] = {bflo(v.x), bfhi(v.x), bflo(v.y), bfhi(v.y), bflo(v.z), bfhi(v.z), bflo(v.w), bfhi(v.w)};
#pragma unroll
                    for (int q = 0; q < NQ; q++) {
                        const float cf = coef[q * DM + k];
#pragma unroll
                        for (int j = 0; j < 8; j++) acc[q][j] = fmaf(cf, f[j], acc[q][j]);
                    }
                }
            }
            slot = slot == 5 ? 0 : slot + 1;
        }
    }
    __syncthreads();
#pragma unroll
    for (int q = 0; q < NQ; q++)
#pragma unroll
        for (int j = 0; j < 8; j++) red[(kg * NQ + q) * W + cg * 8 + j] = acc[q][j];
    __syncthreads();
#pragma unroll 1
    for (int i = tid; i < NQ * W; i += 384) {
        const int q = i / W, cidx = i % W;
        float t = 0.f;
#pragma unroll
        for (int k = 0; k < KG; k++) t += red[k * NQ * W + i];
        if (cidx < ncol) out[q * ostride + cidx] = round ? bfround(t) : t;
    }
}
__device__ __noinline__ void rec_side(float* sm, const RecPtrs& p, int id) {
    const int tid = threadIdx.x;
    float *coef = sm, *red = sm + 3 * DM;
    if (tid < 256 && blockIdx.x < 128) rec_ln(sm + SM_PRE / 4, p, id, 2);
    if (tid >> 5 == 8) {
#pragma unroll 1
        for (int n = 1; n < 31; n++) {
            bar_sync(NB_LN, 288);
            if (tid == 256) { if (n == 1) wait_count1(&g_tick[32 + id * 8], 2); signal_count(&g_tick[32 + id * 8]); }
            __syncwarp();
        }
    }
    __syncthreads();
    for (int i = tid; i < 2 * S_; i += 384) g_st[id * 2 * S_ + i] = 0.f;
    if (id == 0) for (int i = tid; i < 2 * 32; i += 384) g_pcnt[i * 8] = 0;
    if (id == 1) for (int i = tid; i < 6 * 256; i += 384) g_pflag[i] = 0;
    for (int i = tid; i < DM; i += 384) { coef[i] = silu_bf(p.c, i); coef[2 * DM + i] = 1.0f; }
    __syncthreads();
    side_gemv<1, 128>(p.wmod + (2 + id) * DM, 6 * DM, DM, coef, red, g_mod + (2 + id) * DM, 0, true);
    __syncthreads();
    if (tid == 0) signal_count(&g_tick[8]);
    side_gemv<1, 128>(p.w3 + id * (FF / 4), FF, FF / 4, coef + 2 * DM, red, g_vec + 3 * DM + id * (FF / 4), 0, false);
    if (tid == 0) wait_count1(&g_tick[8], 4);
    __syncthreads();
    for (int i = tid; i < DM; i += 384) { coef[i] = 1.0f + __ldcg(g_mod + 4 * DM + i); coef[DM + i] = __ldcg(g_mod + 3 * DM + i); }
    __syncthreads();
    if (id == 1 && tid < 32) {
        float t[5] = {0, 0, 0, 0, 0};
        for (int i = tid; i < DM; i += 32) {
            const float a = coef[i], b = coef[DM + i];
            t[0] += a; t[1] += a * a; t[2] += a * b; t[3] += b; t[4] += b * b;
        }
#pragma unroll
        for (int q = 0; q < 5; q++) { const float r = warp_sum(t[q]); if (tid == 0) g_cst[q] = r * (1.0f / DM); }
    }
    side_gemv<3, 32>(p.w1 + id * 256, DM, 256, coef, red, g_vec + id * 256, DM, false);
}

__device__ __forceinline__ void pair_place(int c, int& d, int& pi) {
    const int c7 = ((c - 36) * 37) >> 8;
    d = c < 4 ? 0 : c < 36 ? (c - 4) & 7 : c - 35 - 7 * c7;
    pi = c < 4 ? c : c < 36 ? ((c - 4) >> 3) + (d ? 0 : 4) : 4 + c7;
}
__global__ void __cluster_dims__(2, 1, 1) __launch_bounds__(384, 1)
k_rec(const __grid_constant__ RecMaps mp, const __grid_constant__ RecPtrs p) {
    extern __shared__ uint8_t smraw[];
    const uint32_t sb = smem_u32(smraw);
    if ((sb & 0x3FFFF) != SB0) __trap();
    const uint32_t bars = sb + SM_BAR;
    const int tid = threadIdx.x, lane = tid & 31, b = blockIdx.x;
    const int wid = __reduce_max_sync(~0u, tid >> 5);
    const uint32_t rank = b & 1;
    uint8_t* arena = p.arena;
    volatile int* sinfo = (volatile int*)(smraw + SM_BAR + 192);
    if (tid == 0) sinfo[0] = INT_MIN;
    uint32_t smid;
    asm("mov.u32 %0, %%smid;" : "=r"(smid));
    smid = __reduce_max_sync(~0u, smid);
    int d, pi;
    pair_place(smid >= 124 ? (smid >> 1) - 62 : (smid >> 1) + 4, d, pi);
    const int guess = b < 128 && smid < 132 && (smid & ~3u) != 120 && (NO_GUESS % 5 == 0 || (NO_GUESS == 2 && b != 20)) ? d * 8 + pi : -9;
    if (wid == 8) {
        if (lane == 0) {
#pragma unroll
            for (int i = 0; i < 17; i++) mbar_init(bars + 8 * i, i == B_WO ? 4 : 1);
            asm volatile("fence.mbarrier_init.release.cluster; fence.proxy.async.shared::cta;" ::: "memory");
            mbar_expect(bars + 8 * B_ROLE, 8);
        }
        __syncwarp();
    }
    asm volatile("barrier.cluster.arrive.relaxed.aligned;" ::: "memory");
    int pr = 0, hA = 0;
    if (wid < 8) {
        if (b < 128) {
            const int cb = (b & 15) * 128, k0 = (b >> 4) * 128 + (tid >> 4);
            uint4 v[8];
#pragma unroll
            for (int i = 0; i < 8; i++) v[i] = __ldg((const uint4*)(p.wmod + (size_t)(k0 + 16 * i) * (6 * DM) + cb + (tid & 15) * 8));
            float acc[8] = {0, 0, 0, 0, 0, 0, 0, 0};
            const float sl = silu_bf(p.c, k0 + 16 * (lane & 7));
#pragma unroll
            for (int i = 0; i < 8; i++) {
                const float sv = __shfl_sync(~0u, sl, i, 16);
                acc[0] += sv * bflo(v[i].x); acc[1] += sv * bfhi(v[i].x); acc[2] += sv * bflo(v[i].y); acc[3] += sv * bfhi(v[i].y);
                acc[4] += sv * bflo(v[i].z); acc[5] += sv * bfhi(v[i].z); acc[6] += sv * bflo(v[i].w); acc[7] += sv * bfhi(v[i].w);
            }
            float* red = (float*)(smraw + SM_PRE);
            *(float4*)(red + (tid >> 4) * 128 + (tid & 15) * 8) = make_float4(acc[0], acc[1], acc[2], acc[3]);
            *(float4*)(red + (tid >> 4) * 128 + (tid & 15) * 8 + 4) = make_float4(acc[4], acc[5], acc[6], acc[7]);
            bar_sync(NB_FIN0, 256);
            if (wid < 4) {
                float t = 0;
#pragma unroll
                for (int i = 0; i < 16; i++) t += red[i * 128 + tid];
                stg_rlx1(&g_modp[(b >> 4) * 2 * DM + cb + tid], __float_as_uint(t) | 1u);
            }
        } else {
            rec_ln((float*)(smraw + SM_PRE), p, b - 128, 0);
        }
    } else if (wid >= 10 && b >= 128) {
        {
            const int u = (b - 128) * 2 + wid - 10;
            const uint16_t* src = (const uint16_t*)p.mem0 + (lane & 3) * 2 * DM + (u >> 1) * 128 + (u & 1) * 32 + (lane >> 2);
            stg_rlx4(arena + (LB_STAMP << 13) + u * 2048 + (lane >> 4) * 1024 + ((lane >> 3) & 1) * 256 + (lane & 7) * 16, 0, 0, 0, 0);
#pragma unroll 1
            for (int r = 0; r < 4; r++) {
                uint32_t w[5];
#pragma unroll
                for (int e = 0; e < 4; e++) {
                    const uint16_t* q = src + (r >> 1) * 512 + (r & 1) * 16 + (e & 2) * 32 + (e & 1) * 8;
                    w[e] = pack_h2(bflo(q[0]), bflo(q[DM]));
                }
                w[4] = __shfl_sync(~0u, __byte_perm(w[3], ACC_ALL, 0x7632), lane * 8 + 7);
                w[3] = __byte_perm(w[3], ACC_ALL, (lane & 7) == 7 ? 0x7610 : 0x3210);
#pragma unroll 1
                for (int i = 0; i < 3; i++) {
                    uint8_t* d = arena + acc_slot(i) + acc_piece(r >> 1, u >> 1, (u & 1) * 2 + (r & 1));
                    stg_rlx4(d + lane * 16, w[0], w[1], w[2], w[3]);
                    if (lane < 8) stg_rlx1(d + 512 + lane * 4, w[4]);
                    w[0] = w[1] = w[2] = w[3] = w[4] = 0;
                }
            }
            bar_arrive(NB_C, 320);
        }
    } else if (rank == 0 && (wid > 8 || b >= 128)) {
        uint32_t best = ~0u;
        const int pg = wid < 11 ? 0 : 1 + (b >> 1) % 3;
        uint32_t* q = (uint32_t*)(arena + (pg << 21) + (pg ? blk(b >> 1, 1) : blk(LB_PROBE, wid & 1) + b * 16));
        if (lane < 8) stg_rlx1(q + lane, 0);
        u64 tk2 = ldg_u64(&g_tick[0]);
        __syncwarp();
        if (lane == 0) {
            q += 3;
            uint32_t v = atomicAdd(q, 1u);
#pragma unroll 1
            for (int r = 0; r < NPROBE; r++) {
                const uint32_t t0 = clk32() + (v >> 8);
                v = atomicAdd(q + (v >> 8), 1u);
                uint32_t t1;
                asm volatile("{.reg .pred p; setp.eq.u32 p, %1, 0xffffffff; @p exit; mov.u32 %0, %%clock;}" : "=r"(t1) : "r"(v) : "memory");
                best = min(best, t1 - t0);
            }
            sinfo[pg ? 4 : 2 + (wid & 1)] = best;
        }
        bar_sync(NB_KDONE, b < 128 ? 96 : 64);
        if (wid == 9) {
            const int par = (sinfo[2] > sinfo[3]) ^ (NO_GUESS == 5 && smid == 126), ncl = gridDim.x >> 1;
            const bool ok = guess >= 0 && !(smid & 1), reg = ok && guess >= 4;
            u64 add = (1u << (8 * par)) + 65536 + (reg ? 1ull << 24 : (1ull << (56 + 4 * par)) + ((u64)ok << 37));
            if (b < 128) add += (u64)((2 * sinfo[4] < sinfo[2] + sinfo[3]) != par) << (32 + 8 * ((b >> 1) % 3));
            int it = 0;
            if (NO_GUESS % 5 >= 3 ? b < 2 * (NO_GUESS - 2) || (NO_GUESS == 3 && b == 130) : b >= 128) {
#pragma unroll 1
                while (!__all_sync(~0u, (int)((lo32(tk2) >> 16) & 255) >= ncl - 2)) { tk2 = ldg_u64(&g_tick[0]); spin_guard(++it); }
            }
            if (lane == 0) {
                if (guess >= 0) add += atomicXor(&g_tick[2], par << (guess >> 1)) & p.zero;
                add = atomicAdd((u64*)&g_tick[0], add);
            }
#pragma unroll 1
            while (!__all_sync(~0u, (int)((lo32(tk2) >> 16) & 255) >= ncl)) { tk2 = ldg_u64(&g_tick[0]); spin_guard(++it); }
            add = __shfl_sync(~0u, add, 0);
            const uint32_t diff = ldg_rlx1(&g_tick[2]);
            const bool most = lo32(tk2) >> 24 == 60 && diff < 4;
            const int nh = most ? 2 : NH, sh = most ? 56 : 0, w = most ? 4 : 8, mk = (1 << w) - 1;
            const int n0 = (tk2 >> sh) & mk, n1 = (tk2 >> (sh + w)) & mk, tk = (add >> (sh + w * par)) & mk;
            hA = min(n0 >> 1, nh);
            const int q0 = 2 * hA, q1 = 2 * nh - q0;
            const int over = tk - (par ? q1 : q0), lack = max(par ? q0 - n0 : q1 - n1, 0);
            if (over < 0) pr = par ? q0 + tk : tk;
            else if (over < lack) pr = (par ? n0 : q0 + n1) + over;
            else pr = -1 - (over - lack + (par ? max(n0 - q0, 0) : 0));
            if (most && (reg || (!diff && (hi32(tk2) & 0xe0) == 0x80))) { pr = guess; hA = par ? 0 : NH; }
#pragma unroll
            for (int i = 0; i < 3; i++) hA |= ((hi32(tk2) >> (8 * i)) & 31) > 10 ? 256 << i : 0;
        }
    }
    asm volatile("barrier.cluster.wait.aligned;" ::: "memory");
    if (wid == 9 && rank == 0) {
        asm volatile("{.reg .pred p; .reg .b32 a; setp.lt.u32 p, %3, 2; @p mapa.shared::cluster.u32 a, %0, %3;\n"
                     " @p st.async.shared::cluster.mbarrier::complete_tx::bytes.v2.u32 [a + 192], {%1, %2}, [a + %4];}"
                     ::"r"(bars), "r"(pr), "r"(hA), "r"(lane), "n"(8 * B_ROLE) : "memory");
        if (b >= 128) atomicOr(&g_tick[4], (pr < 0 ? 4u : 1u) << ((b - 128) >> 1));
    }
    if (wid == 8) {
        int pu = guess;
        bool fast = false, known = false;
        wait_clk(clk32() + W_T0 + (lane & p.zero));
#pragma unroll 1
        for (int n = 0; n < 12; n++) {
            if (!known && (n == W_SPEC || pu < 0)) {
                mbar_wait_w(bars + 8 * B_ROLE, 0);
                known = true;
                const int r = __reduce_max_sync(~0u, sinfo[0]);
                if (r != pu) {
#pragma unroll 1
                    for (; n > 0; n--) {
                        mbar_wait_w(bars + 8 * (B_W + n - 1), 0);
                        asm volatile("{.reg .pred p; elect.sync _|p, 0xffffffff; @p mbarrier.arrive.shared.b64 _, [%0];}" ::"r"(bars + 8 * (B_W + n - 1)) : "memory");
                    }
                    pu = r;
                    fast = r < 4;
                }
                bar_arrive(NB_A, 384);
                if (b >= 128 && pu < 0) bar_sync(NB_B, 64);
                if (pu < 0) break;
            }
            const int rot = b >= 128 ? 8 : 0, i = (n + rot) % 12;
            if (rot && n == 4) bar_sync(NB_B, 64);
            if (n >= W_INFL && !fast) {
                const uint32_t v = ldg_rlx1(&g_tick[32 + (lane & 3) * 8]);
                mbar_wait_w(bars + 8 * (B_W + (n - W_INFL + rot) % 12), 0);
                fast = __all_sync(~0u, v != 0);
            }
            const int m = i < 8 ? i & 1 : 2, k = i < 8 ? i >> 1 : i - 8, c0 = (pu >> 1) * 128 + rank * 64, r0 = (pu & 1) * 512;
            const uint32_t dst = sb + m * 65536 + k * 16384, br = bars + 8 * (B_W + i);
            e_expect(br, 16384);
            e_tma2d_ef(dst, &mp.wq + m, c0, r0 + k * 128, br);
            e_tma2d_ef(dst + 8192, &mp.wq + m, c0, r0 + k * 128 + 64, br);
        }
    } else {
        bar_sync(NB_A, 384);
    }
    const int prr = __reduce_max_sync(~0u, sinfo[0]);
    hA = __reduce_max_sync(~0u, sinfo[1]);
    if (prr < 0) {
        int j = (b - 128) >> 1;
        if (b < 128) {
            uint32_t v;
            int it = 0;
#pragma unroll 1
            do { v = __reduce_max_sync(~0u, ldg_rlx1(&g_tick[4])); spin_guard(++it); } while (__popc(v) < 2);
            j = v == 3 ? -1 - prr : (v & 1) ^ 1;
        }
        rec_side((float*)smraw, p, j * 2 + rank);
        return;
    }
    const int role = (prr >> 1) * 4 + rank * 2 + (prr & 1);
    rec_main(sb, &mp.wo, arena, role, hA, wid >> 2, p.zero, p.tm);
}

__device__ __forceinline__ void wgmma_ss192(float* d, uint64_t a, uint64_t b, int sc) {
    asm volatile("{.reg .pred p; setp.ne.b32 p, %98, 0;\n wgmma.mma_async.sync.aligned.m64n192k16.f32.bf16.bf16 "
                 "{%0,%1,%2,%3,%4,%5,%6,%7,%8,%9,%10,%11,%12,%13,%14,%15,%16,%17,%18,%19,%20,%21,%22,%23,%24,%25,%26,%27,%28,%29,%30,%31,%32,%33,%34,%35,%36,%37,%38,%39,%40,%41,%42,%43,%44,%45,%46,%47,%48,%49,%50,%51,%52,%53,%54,%55,%56,%57,%58,%59,%60,%61,%62,%63,%64,%65,%66,%67,%68,%69,%70,%71,%72,%73,%74,%75,%76,%77,%78,%79,%80,%81,%82,%83,%84,%85,%86,%87,%88,%89,%90,%91,%92,%93,%94,%95}, %96, %97, p, 1, 1, 0, 1;}"
                 : F16(d, 0), F16(d, 16), F16(d, 32), F16(d, 48), F16(d, 64), F16(d, 80) : "l"(a), "l"(b), "r"(sc));
}

constexpr uint32_t P_B = 81920, P_PLANE = 40960, P_VEC = 212992, P_ROW = P_VEC + 6144, P_BAR = P_ROW + 4096, P_SMEM = P_BAR + 256;
constexpr uint32_t P_OUT = 180224, P_OUT3 = P_B + 2 * P_PLANE;
constexpr int E0 = 2;
constexpr int SL_B0 = 0x2222;
constexpr int SL_B1 = 0x8888;
constexpr int SL_C = 0x11110;
constexpr int SL_A0 = 0x5494;
constexpr int SL_A1 = 0x2929;
constexpr int X_DLY = 4000;
constexpr int P_ST = 5, P_ST0 = 4;
constexpr int PB_F = 0, PB_E = 5, PB_X = 10, PB_P = 12, PB_OUT = 14;
enum { C_Y = 0, C_G = 1, C_X1 = 2, C_U = 3, C_S1 = 8, C_S3 = 9 };
enum { V_GA = 0, V_A = 1, V_B = 2, V_GB = 3, V_VA = 4, V_VB = 5, V_VC = 6, V_C3 = 7 };
struct PostMaps { CUtensorMap o, wo, y, w1, g, w2, x1, w3, u, w4, out, x; };

struct GeluK { float k0, k1, kh; };
__device__ __forceinline__ GeluK gelu_k(float c) { return {0.7978845608028654f * c, 0.7978845608028654f * 0.044715f * c * c * c, 0.5f * c}; }
__device__ __forceinline__ float gelu_s(float t, const GeluK& k) {
    const float u = t * fmaf(t * t, k.k1, k.k0);
    float th; asm("tanh.approx.f32 %0, %1;" : "=f"(th) : "f"(u));
    const float hx = k.kh * t;
    return fmaf(hx, th, hx);
}
__device__ __forceinline__ float2 ldsv(uint32_t a) {
    float2 v; asm("ld.shared.v2.f32 {%0,%1}, [%2];" : "=f"(v.x), "=f"(v.y) : "r"(a)); return v;
}
__device__ __forceinline__ void wait_smem(uint32_t a, int target) {
    int it = 0;
#pragma unroll 1
    while (true) {
        int v;
        asm volatile("ld.acquire.cta.shared.u32 %0, [%1];" : "=r"(v) : "r"(a) : "memory");
        if (__all_sync(~0u, v >= target)) break;
        spin_guard(++it);
    }
}

struct Pipe { int st, ph; };
__device__ __forceinline__ void adv(Pipe& p) { if (++p.st == P_ST) { p.st = 0; p.ph ^= 1; } }
__device__ __forceinline__ int u_col(int r, int nb) { return r ? 512 + r * 1024 + nb * 128 : nb * 192; }

template <bool A>
__device__ __forceinline__ void post_produce(uint32_t sb, const PostMaps& mp, int mb, int nb, int rank) {
    const int rh = 2 * mb + rank, lane = threadIdx.x & 31;
    const uint32_t full = sb + P_BAR + 8 * PB_F, empty = sb + P_BAR + 8 * PB_E;
    Pipe p = {(P_ST0 + E0) % P_ST, !E0};
#pragma unroll 1
    for (int ph = 0; ph < 9; ph++) {
        const int GS = ph == 0 ? 8 : ph == 6 ? 3 : 2, kb0 = ph < 7 ? 0 : ph * 16 - 88;
        const CUtensorMap* tm = &mp.o + 2 * (ph < 3 ? ph : ph < 6 ? 3 : 4) + !A;
        const bool own = ph == 1 || ph == 3;
        const int n0 = ph >= 3 && ph < 6 ? u_col(ph - 3, nb) : nb * 128;
        const int amul = ph == 0 ? 256 : 64, arow = ph == 0 ? rh * 8 : rh * 64;
        const int wr = ph == 2 ? min(max(rh + min(lane >> 3, 2) - 1, 0), 31) : rh;
        const uint32_t* fl = &g_pflag[(ph < 3 ? ph - 1 : ph < 6 ? C_X1 : ph - 3) * 256 + wr * 8 + (lane & 7)];
        uint32_t have = ph == 0 || ph == 5 ? ~0u : 0u;
#pragma unroll 1
        for (int q = 0; q < 8; q++) {
            const int src = own && q < 2 ? nb ^ q : (q + (ph >= 1 && ph <= 3 ? nb & 6 : 0)) & 7;
            const bool skip = own && q == 0, both = own && q == 1;
            const uint32_t need = q < 2 && own ? 0 : (ph == 2 ? 0x10101 : 1) << src;
            if (A && both) {
                int it = 0;
                uint32_t ok;
#pragma unroll 1
                do {
                    asm volatile("{.reg .pred p; mbarrier.try_wait.parity.acquire.cluster.shared::cta.b64 p, [%1], %2; selp.u32 %0, 1, 0, p;}" : "=r"(ok) : "r"(sb + P_BAR + 8 * PB_P), "r"(ph >> 1) : "memory");
                    spin_guard(++it);
                } while (!__all_sync(~0u, ok));
                asm volatile("fence.proxy.async.global;" ::: "memory");
            }
            if (A && (have & need) != need) {
                int it = 0;
#pragma unroll 1
                do {
                    uint32_t v;
                    asm volatile("ld.acquire.gpu.global.u32 %0, [%1];" : "=r"(v) : "l"(fl) : "memory");
                    have = __ballot_sync(~0u, v != 0);
                    spin_guard(++it);
                } while ((have & need) != need);
                asm volatile("fence.proxy.async.global;" ::: "memory");
            }
            if (!A && q == 1 && (ph == 1 || ph == 2)) {
#pragma unroll 1
                for (int i = 0; i <= ph; i++)
                    asm volatile("{.reg .pred p; elect.sync _|p, 0xffffffff; @p cp.async.bulk.prefetch.tensor.2d.L2.global [%0, {%1, %2}];}"
                                 ::"l"(tm + 2), "r"((nb * (ph + 1) + i) * 64), "r"(mb * 64) : "memory");
            }
            if (!A && ph == 3 && q == 1) wait_smem(sb + P_BAR + 8 * (PB_OUT + (lane & 1)), 3);
            const int row = arow + (ph == 2 ? (int)((0x04000301u >> ((src & 6) * 4)) & 7) - 2 : 0);
            const uint32_t bytes = (skip ? 16384 : 32768) + (ph == 3 ? 8192 : 0);
            if ((ph | q) == 0) asm volatile("barrier.cluster.wait.aligned;" ::: "memory");
#pragma unroll 1
            for (int e = kb0 + (src + 1) * GS, kb = e - GS + (ph | q ? 0 : E0); kb < e; kb++) {
                const uint32_t f = full + 8 * p.st;
                if (!(A && skip)) mbar_wait_w(empty + 8 * p.st, p.ph ^ 1);
                if (A) {
                    const uint32_t a = sb + p.st * 16384 + rank * 8192;
                    if (both) { e_tma2d_ef(a, tm, kb * 64, row, f); e_tma2d_ef(a + 8192 - rank * 16384, tm, kb * 64, row ^ 64, f); }
                    else if (!skip) e_tma2d_mc_ef(a, tm, kb * amul, row, f);
                } else {
                    const uint32_t b = sb + P_B + p.st * 8192;
                    e_expect(f, bytes);
                    e_tma2d_ef(b, tm, n0, kb * 64, f);
                    e_tma2d_ef(b + P_PLANE, tm, n0 + 64, kb * 64, f);
                    if (ph == 3 && both) mbar_wait_w(empty + 8 * p.st - 16, p.ph);
                    if (ph == 3) e_tma2d_ef(b + 2 * P_PLANE, tm, n0 + 128, kb * 64, f);
                }
                adv(p);
            }
        }
    }
    if (A) {
#pragma unroll 1
        for (int i = 0; i < P_ST; i++) mbar_wait_w(empty + 8 * i, p.ph ^ (i >= p.st));
    }
}

#define I4(d, i) "f"(d[i]), "f"(d[i + 1]), "f"(d[i + 2]), "f"(d[i + 3])
#define I16(d, i) I4(d, i), I4(d, i + 4), I4(d, i + 8), I4(d, i + 12)
#define O4(d, i) "=f"(d[i]), "=f"(d[i + 1]), "=f"(d[i + 2]), "=f"(d[i + 3])
__device__ __forceinline__ void pick32(float* v, int n, const float* c1, const float* vc, const float* old) {
    asm volatile("{PKT: .branchtargets PK0, PK1, PK2, PK3, PK4, PK5; brx.idx.uni %16, PKT;\n"
                 "PK0: fma.rn.f32 %0, %17, %19, %27; fma.rn.f32 %1, %17, %20, %28; fma.rn.f32 %2, %18, %19, %29; fma.rn.f32 %3, %18, %20, %30; fma.rn.f32 %4, %17, %21, %31; fma.rn.f32 %5, %17, %22, %32; fma.rn.f32 %6, %18, %21, %33; fma.rn.f32 %7, %18, %22, %34; fma.rn.f32 %8, %17, %23, %35; fma.rn.f32 %9, %17, %24, %36; fma.rn.f32 %10, %18, %23, %37; fma.rn.f32 %11, %18, %24, %38; fma.rn.f32 %12, %17, %25, %39; fma.rn.f32 %13, %17, %26, %40; fma.rn.f32 %14, %18, %25, %41; fma.rn.f32 %15, %18, %26, %42; bra.uni PKE;\n"
                 "PK1: fma.rn.f32 %0, %17, %19, %43; fma.rn.f32 %1, %17, %20, %44; fma.rn.f32 %2, %18, %19, %45; fma.rn.f32 %3, %18, %20, %46; fma.rn.f32 %4, %17, %21, %47; fma.rn.f32 %5, %17, %22, %48; fma.rn.f32 %6, %18, %21, %49; fma.rn.f32 %7, %18, %22, %50; fma.rn.f32 %8, %17, %23, %51; fma.rn.f32 %9, %17, %24, %52; fma.rn.f32 %10, %18, %23, %53; fma.rn.f32 %11, %18, %24, %54; fma.rn.f32 %12, %17, %25, %55; fma.rn.f32 %13, %17, %26, %56; fma.rn.f32 %14, %18, %25, %57; fma.rn.f32 %15, %18, %26, %58; bra.uni PKE;\n"
                 "PK2: fma.rn.f32 %0, %17, %19, %59; fma.rn.f32 %1, %17, %20, %60; fma.rn.f32 %2, %18, %19, %61; fma.rn.f32 %3, %18, %20, %62; fma.rn.f32 %4, %17, %21, %63; fma.rn.f32 %5, %17, %22, %64; fma.rn.f32 %6, %18, %21, %65; fma.rn.f32 %7, %18, %22, %66; fma.rn.f32 %8, %17, %23, %67; fma.rn.f32 %9, %17, %24, %68; fma.rn.f32 %10, %18, %23, %69; fma.rn.f32 %11, %18, %24, %70; fma.rn.f32 %12, %17, %25, %71; fma.rn.f32 %13, %17, %26, %72; fma.rn.f32 %14, %18, %25, %73; fma.rn.f32 %15, %18, %26, %74; bra.uni PKE;\n"
                 "PK3: fma.rn.f32 %0, %17, %19, %75; fma.rn.f32 %1, %17, %20, %76; fma.rn.f32 %2, %18, %19, %77; fma.rn.f32 %3, %18, %20, %78; fma.rn.f32 %4, %17, %21, %79; fma.rn.f32 %5, %17, %22, %80; fma.rn.f32 %6, %18, %21, %81; fma.rn.f32 %7, %18, %22, %82; fma.rn.f32 %8, %17, %23, %83; fma.rn.f32 %9, %17, %24, %84; fma.rn.f32 %10, %18, %23, %85; fma.rn.f32 %11, %18, %24, %86; fma.rn.f32 %12, %17, %25, %87; fma.rn.f32 %13, %17, %26, %88; fma.rn.f32 %14, %18, %25, %89; fma.rn.f32 %15, %18, %26, %90; bra.uni PKE;\n"
                 "PK4: fma.rn.f32 %0, %17, %19, %91; fma.rn.f32 %1, %17, %20, %92; fma.rn.f32 %2, %18, %19, %93; fma.rn.f32 %3, %18, %20, %94; fma.rn.f32 %4, %17, %21, %95; fma.rn.f32 %5, %17, %22, %96; fma.rn.f32 %6, %18, %21, %97; fma.rn.f32 %7, %18, %22, %98; fma.rn.f32 %8, %17, %23, %99; fma.rn.f32 %9, %17, %24, %100; fma.rn.f32 %10, %18, %23, %101; fma.rn.f32 %11, %18, %24, %102; fma.rn.f32 %12, %17, %25, %103; fma.rn.f32 %13, %17, %26, %104; fma.rn.f32 %14, %18, %25, %105; fma.rn.f32 %15, %18, %26, %106; bra.uni PKE;\n"
                 "PK5: fma.rn.f32 %0, %17, %19, %107; fma.rn.f32 %1, %17, %20, %108; fma.rn.f32 %2, %18, %19, %109; fma.rn.f32 %3, %18, %20, %110; fma.rn.f32 %4, %17, %21, %111; fma.rn.f32 %5, %17, %22, %112; fma.rn.f32 %6, %18, %21, %113; fma.rn.f32 %7, %18, %22, %114; fma.rn.f32 %8, %17, %23, %115; fma.rn.f32 %9, %17, %24, %116; fma.rn.f32 %10, %18, %23, %117; fma.rn.f32 %11, %18, %24, %118; fma.rn.f32 %12, %17, %25, %119; fma.rn.f32 %13, %17, %26, %120; fma.rn.f32 %14, %18, %25, %121; fma.rn.f32 %15, %18, %26, %122;\n"
                 "PKE: }"
                 : O4(v, 0), O4(v, 4), O4(v, 8), O4(v, 12)
                 : "r"(n), "f"(c1[0]), "f"(c1[1]), I4(vc, 0), I4(vc, 4), I16(old, 0), I16(old, 16), I16(old, 32), I16(old, 48), I16(old, 64), I16(old, 80));
}
template <int PH, class F>
__device__ __forceinline__ void post_mma(uint32_t sb, float* acc, Pipe& p, int NK, int wg, uint32_t rel, bool lead, int pi, F hook) {
    const uint32_t full = sb + P_BAR + 8 * PB_F;
    constexpr uint64_t DA = PH == 0 ? mkdesc(SB0, 128, 1024, 0) : mkdesc(SB0, 16, 1024, 1);
    constexpr uint64_t DB = mkdesc(SB0 + P_B, P_PLANE, 1024, 1);
    auto release = [&](uint32_t a) { asm volatile("{.reg .pred p; setp.gt.u32 p, %0, 63; @p mbarrier.arrive.shared::cluster.b64 _, [%0];}" ::"r"(a) : "memory"); };
    uint32_t prev = 0;
    if (PH & 1) { fence_async_smem(); bar_sync(12 + wg, 128); }
    bool ok = false;
#pragma unroll 1
    for (int kb = 0; kb < NK; kb++) {
        if (!ok) mbar_wait_w(full + 8 * p.st, p.ph);
        const uint32_t a = (uint32_t)DA + ((PH & 1) && kb < 2 ? P_OUT / 16 + wg * 1024 + kb * 512 : p.st * 1024 + wg * 512), b = (uint32_t)DB + p.st * 512;
        wg_fence();
#pragma unroll
        for (int k = 0; k < 4; k++) {
            const uint64_t da = (DA & 0xffffffff00000000ull) | (a + k * (PH == 0 ? 16 : 2)), db = (DB & 0xffffffff00000000ull) | (b + k * 128);
            if (PH == 3) wgmma_ss192(acc, da, db, (kb | k) != 0);
            else wgmma_ss128<PH == 0>(acc, da, db, (kb | k) != 0);
        }
        wg_commit();
        const uint32_t cur = rel + 8 * p.st;
        adv(p);
        uint32_t t;
        asm volatile("{.reg .pred p; mbarrier.test_wait.parity.shared.b64 p, [%1], %2; selp.u32 %0, 1, 0, p;}" : "=r"(t) : "r"(full + 8 * p.st), "r"(p.ph) : "memory");
        wg_wait<1>();
        release(prev);
        ok = __all_sync(~0u, t);
        prev = cur;
        hook(kb);
    }
    wg_wait<0>();
    release(prev);
}

__global__ void __cluster_dims__(2, 1, 1) __launch_bounds__(384, 1)
k_post(const __grid_constant__ PostMaps mp) {
    extern __shared__ uint8_t smraw[];
    const uint32_t sb = smem_u32(smraw);
    if ((sb & 0x3FFFF) != SB0) __trap();
    const int tid = threadIdx.x, lane = tid & 31;
    int d, pi;
    pair_place(blockIdx.x >> 1, d, pi);
    const int rank = blockIdx.x & 1, mb = (d >> 2) * 8 + pi, nb = (d & 3) * 2 + rank;
    const uint32_t bars = sb + P_BAR;
    const int w = __reduce_max_sync(~0u, (tid >> 5) - 8);
    if (w == 1) {
        if (lane == 0) {
#pragma unroll
            for (int i = 0; i <= PB_P; i++) mbar_init(bars + 8 * i, i >= PB_E && i < PB_X ? 4 : i == PB_P ? 2 : 1);
            mbar_arrive(bars + 8 * (PB_F + P_ST0));
            asm volatile("mbarrier.arrive.shared.b64 _, [%0], 4;" ::"r"(bars + 8 * (PB_E + P_ST0)) : "memory");
            sts4(bars + 8 * PB_OUT, 0, 0, 0, 0);
            asm volatile("fence.mbarrier_init.release.cluster; fence.proxy.async.shared::cta;" ::: "memory");
        }
        __syncwarp();
    }
    asm volatile("barrier.cluster.arrive.relaxed.aligned;" ::: "memory");
    if (w == 1) {
#pragma unroll
        for (int i = 0; i < E0; i++) {
            const int st = (P_ST0 + i) % P_ST;
            const uint32_t f = bars + 8 * (PB_F + st);
            e_expect(f, 32768);
#pragma unroll
            for (int h = 0; h < 2; h++) {
                e_tma2d_ef(sb + st * 16384 + h * 8192, &mp.o, i * 256, mb * 16 + h * 8, f);
                e_tma2d_ef(sb + P_B + st * 8192 + h * P_PLANE, &mp.wo, nb * 128 + h * 64, i * 64, f);
            }
        }
    }
    if (w != 0 && w != 3) asm volatile("barrier.cluster.wait.aligned;" ::: "memory");
    if (w >= 0) {
        asm volatile("setmaxnreg.dec.sync.aligned.u32 40;");
        if (w == 0) {
            post_produce<false>(sb, mp, mb, nb, rank);
        } else if (w < 3) {
            const int wg = w - 1, rh = 2 * mb + wg;
            float* rowc = (float*)(smraw + P_ROW) + (wg * 64 + lane * 2) * 8;
            int nout = 0, sig = 0;
            __nanosleep(X_DLY);
            if (wg && lane < 9) asm volatile("prefetch.tensormap [%0];" ::"l"(&mp.y + lane) : "memory");
            e_expect(bars + 8 * (PB_X + wg), 16384);
            e_tma2d_ef(sb + P_OUT + wg * 16384, &mp.x, nb * 128, rh * 64, bars + 8 * (PB_X + wg));
            e_tma2d_ef(sb + P_OUT + wg * 16384 + 8192, &mp.x, nb * 128 + 64, rh * 64, bars + 8 * (PB_X + wg));
            if (wg == 0) {
#pragma unroll 1
                for (int i = 0; i < 11; i++) {
                    const float* src = i < 4 ? g_mod + ((0x5342 >> (4 * i)) & 15) * DM + nb * 128 : g_vec + (i < 7 ? (i - 4) * DM + nb * 128 : 3 * DM + u_col(max(i - 8, 0), nb) + (i == 8) * 128);
                    if (i != 8 || lane < 16) cp_async16(sb + P_VEC + i * 512 - (i > 8) * 256 + lane * 16, src + lane * 4);
                }
                *(uint4*)&g_modp[blockIdx.x * 128 + lane * 4] = make_uint4(0, 0, 0, 0);
                if (blockIdx.x == 64) *(uint2*)&g_tick[lane * 2] = make_uint2(0, 0);
                asm volatile("cp.async.wait_all;" ::: "memory");
                const float4 a = lds4f(sb + P_VEC + V_A * 512 + lane * 16);
                sts4f(sb + P_VEC + V_A * 512 + lane * 16, 1.0f + a.x, 1.0f + a.y, 1.0f + a.z, 1.0f + a.w);
                bar_arrive(3, 288);
            }
#pragma unroll 1
            for (int i = 0; i < 9; i++) {
                const int cnt = i == 8 ? 6 : (0x54392180u >> (4 * i)) & 15;
                if (cnt < C_S1) {
                    const bool isu = cnt >= C_U && cnt < 6;
                    const int ng = cnt == C_U ? 3 : 2, c0 = isu ? u_col(cnt - C_U, nb) : nb * 128;
                    const uint32_t src = sb + (cnt == C_U ? P_OUT3 : P_OUT) + wg * ng * 8192;
#pragma unroll 1
                    for (int j = 0; j < ng; j++) {
                        bar_sync(4 + 4 * wg + (sig++ & 3), 160);
                        if (lane == 0) {
                            fence_async_smem();
                            asm volatile("cp.async.bulk.tensor.2d.global.shared::cta.bulk_group [%0, {%2, %3}], [%1]; cp.async.bulk.commit_group;"
                                         ::"l"(&mp.y + 2 * (isu ? 3 : min(cnt, 4))), "r"(src + j * 8192), "r"(c0 + j * 64), "r"(rh * 64) : "memory");
                        }
                        __syncwarp();
                    }
                    if (lane == 0) {
                        asm volatile("cp.async.bulk.wait_group 0; fence.proxy.async.global;" ::: "memory");
                        asm volatile("st.release.cta.shared.u32 [%0], %1;" ::"r"(bars + 8 * (PB_OUT + wg)), "r"(nout + 1) : "memory");
                        if (cnt < 6) asm volatile("fence.acq_rel.gpu; st.relaxed.gpu.global.u32 [%0], %1;" ::"l"(&g_pflag[cnt * 256 + rh * 8 + nb]), "r"(1) : "memory");
                        if (cnt == C_Y || cnt == C_X1)
                            asm volatile("{.reg .b32 r; mapa.shared::cluster.u32 r, %0, %1; mbarrier.arrive.relaxed.cluster.shared::cluster.b64 _, [r];}" ::"r"(bars + 8 * PB_P), "r"(rank ^ 1) : "memory");
                    }
                    nout++;
                    __syncwarp();
                    continue;
                }
                bar_sync(4 + 4 * wg + (sig++ & 3), 160);
#pragma unroll 1
                for (int q = 0; q < (cnt == C_S1 ? 3 : 1); q++) {
                    const float4 v = lds4f(sb + P_ROW + wg * 2048 + q * 512 + lane * 16);
                    asm volatile("red.relaxed.gpu.global.add.v4.f32 [%0], {%1, %2, %3, %4};"
                                 ::"l"((float4*)g_st + (cnt == C_S1 ? q : 3) * (S_ / 2) + rh * 32 + lane), "f"(v.x), "f"(v.y), "f"(v.z), "f"(v.w) : "memory");
                }
                __syncwarp();
                uint32_t* c = &g_pcnt[(cnt - C_S1) * 256 + rh * 8];
                if (lane == 0) { signal_count(c); wait_count1(c, 8); }
                __syncwarp();
                const float4* sp = (const float4*)g_st + rh * 32 + lane;
                float4 u[3] = {__ldcg(sp + (cnt == C_S1 ? 0 : 3) * (S_ / 2)), __ldcg(sp + S_ / 2), __ldcg(sp + S_)};
#pragma unroll 1
                for (int h = 0; h < 2; h++) {
                    const float id = 1.0f / DM;
                    const float m = u[0].x * id, var = fmaxf(u[0].y * id - m * m, 0.f) + 1e-5f, r = rsqrtf(var);
                    float sc = r, m2 = 0.f;
                    if (cnt == C_S1) {
                        m2 = r * (u[1].x * id - m * g_cst[0]) + g_cst[3];
                        const float e2 = r * r * (u[2].x * id - 2.0f * m * u[1].y * id + m * m * g_cst[1]) + 2.0f * r * (u[2].y * id - m * g_cst[2]) + g_cst[4];
                        sc = r * rsqrtf(fmaxf(e2 - m2 * m2, 0.f) + 1e-5f);
                    }
                    const GeluK k = gelu_k(sc);
                    *(float4*)(rowc + h * 8) = make_float4(k.k0, k.k1, k.kh, -m);
                    *(float4*)(rowc + h * 8 + 4) = make_float4(var * r, -m2 * var * r, r, -m * r);
#pragma unroll
                    for (int q = 0; q < 3; q++) { u[q].x = u[q].z; u[q].y = u[q].w; }
                }
                bar_arrive(1 + wg, 160);
            }
        } else {
            post_produce<true>(sb, mp, mb, nb, rank);
        }
    } else {
        asm volatile("setmaxnreg.inc.sync.aligned.u32 232;");
        const int wg = __reduce_max_sync(~0u, tid >> 7), wi = (tid >> 5) & 3, g = lane >> 2, tq = lane & 3;
        const bool lead = (tid & 127) == 0;
        uint32_t rel = 0;
        if ((tid & 127) < 2) asm("mapa.shared::cluster.u32 %0, %1, %2;" : "=r"(rel) : "r"(bars + 8 * PB_E), "r"(tid & 1));
        uint32_t vec = sb + P_VEC + tq * 8;
        const uint32_t stw = sb + (wi * 16 + ((lane >> 3) & 1) * 8 + (lane & 7)) * 128 + (((lane >> 4) ^ (lane & 7)) << 4);
        int sig = 0;
        auto signal = [&]() { bar_arrive(4 + 4 * wg + (sig++ & 3), 160); };
        auto put64 = [&](uint32_t o, const float* v) {
#pragma unroll
            for (int jj = 0; jj < 4; jj++, v += 8) stsm4((stw + o) ^ (jj << 5), pack2(v[0], v[1]), pack2(v[2], v[3]), pack2(v[4], v[5]), pack2(v[6], v[7]));
            signal();
        };
        auto out_free = [&](int n) { wait_smem(bars + 8 * (PB_OUT + (lane & 1)), n); };
        const uint32_t rowc = sb + P_ROW + (wg * 64 + wi * 16 + g) * 32, o128 = P_OUT + wg * 16384;
        const uint32_t rsum = sb + P_ROW + wg * 2048 + (wi * 16 + g) * 8;
        Pipe pa = {P_ST0, 1};
        auto none = [](int) {};
        uint32_t keep[32];
#define KEEP(jn, e) (((e) & 1) ? bfhi(keep[2 * (jn) + ((e) >> 1)]) : bflo(keep[2 * (jn) + ((e) >> 1)]))
        float mu1[2], r1[2];
        {
            float acc[64];
            post_mma<0>(sb, acc, pa, 64, wg, rel, lead, 1, [&](int kb) {
                if (kb != 40) return;
                bar_sync(3, 288);
                mbar_wait_w(bars + 8 * (PB_X + wg), 0);
#pragma unroll
                for (int jj = 0; jj < 8; jj++) ldsm4(keep + jj * 4, (stw + o128 + (jj >> 2) * 8192) ^ ((jj & 3) << 5));
            });
            asm volatile("" : "+r"(vec) :: "memory");
            float st[2][6];
#pragma unroll
            for (int q = 0; q < 6; q++) st[0][q] = st[1][q] = 0.f;
#pragma unroll
            for (int jn = 0; jn < 16; jn++) {
                const float2 ga = ldsv(vec + V_GA * 512 + jn * 32), a = ldsv(vec + V_A * 512 + jn * 32);
                float xa[4];
#pragma unroll
                for (int e = 0; e < 4; e++) {
                    xa[e] = fmaf((e & 1) ? ga.y : ga.x, acc[4 * jn + e], KEEP(jn, e));
                    st[e >> 1][0] += xa[e]; st[e >> 1][1] = fmaf(xa[e], xa[e], st[e >> 1][1]);
                    acc[4 * jn + e] = ((e & 1) ? a.y : a.x) * xa[e];
                }
                keep[2 * jn] = pack2(xa[0], xa[1]); keep[2 * jn + 1] = pack2(xa[2], xa[3]);
                if ((jn & 7) == 7) put64(o128 + (jn >> 3) * 8192, acc + 4 * jn - 28);
            }
#pragma unroll
            for (int jn = 0; jn < 16; jn++) {
                const float2 a = ldsv(vec + V_A * 512 + jn * 32), b = ldsv(vec + V_B * 512 + jn * 32);
#pragma unroll
                for (int e = 0; e < 4; e++) {
                    const float y = acc[4 * jn + e], aa = (e & 1) ? a.y : a.x, bb = (e & 1) ? b.y : b.x;
                    float* s = st[e >> 1];
                    s[2] += y; s[3] = fmaf(aa, y, s[3]); s[4] = fmaf(y, y, s[4]); s[5] = fmaf(bb, y, s[5]);
                }
            }
#pragma unroll
            for (int h = 0; h < 2; h++)
#pragma unroll
                for (int q = 0; q < 6; q++) { st[h][q] += __shfl_xor_sync(~0u, st[h][q], 1); st[h][q] += __shfl_xor_sync(~0u, st[h][q], 2); }
            if (tq < 3) {
#pragma unroll
                for (int h = 0; h < 2; h++)
                    sts2(rsum + tq * 512 + h * 64, tq == 0 ? st[h][0] : tq == 1 ? st[h][2] : st[h][4], tq == 0 ? st[h][1] : tq == 1 ? st[h][3] : st[h][5]);
            }
            signal();
        }
        {
            float acc[64];
            post_mma<1>(sb, acc, pa, 16, wg, rel, lead, 4, none);
            float c1[2], c2[2], c3[2];
            GeluK gk[2];
            bar_sync(1 + wg, 160);
#pragma unroll
            for (int h = 0; h < 2; h++) {
                const float4 a = lds4f(rowc + h * 256), b = lds4f(rowc + h * 256 + 16);
                gk[h] = {a.x, a.y, a.z}; c1[h] = a.w; c2[h] = b.x; c3[h] = b.y; mu1[h] = b.w; r1[h] = b.z;
            }
#pragma unroll
            for (int jn = 0; jn < 16; jn++) {
                const float2 va = ldsv(vec + V_VA * 512 + jn * 32), vb = ldsv(vec + V_VB * 512 + jn * 32), vc = ldsv(vec + V_VC * 512 + jn * 32);
#pragma unroll
                for (int e = 0; e < 4; e++) {
                    const int h = e >> 1;
                    const float t = fmaf(c1[h], (e & 1) ? va.y : va.x, fmaf(c2[h], (e & 1) ? vb.y : vb.x, fmaf(c3[h], (e & 1) ? vc.y : vc.x, acc[4 * jn + e])));
                    acc[4 * jn + e] = gelu_s(t, gk[h]);
                }
                if ((jn & 7) == 7) put64(o128 + (jn >> 3) * 8192, acc + 4 * jn - 28);
            }
        }
        {
            float acc[64];
            post_mma<2>(sb, acc, pa, 16, wg, rel, lead, 7, none);
#pragma unroll
            for (int jn = 0; jn < 16; jn++) {
                const float2 a = ldsv(vec + V_A * 512 + jn * 32), b = ldsv(vec + V_B * 512 + jn * 32);
#pragma unroll
                for (int e = 0; e < 4; e++) {
                    const int h = e >> 1;
                    acc[4 * jn + e] += fmaf(fmaf(KEEP(jn, e), r1[h], mu1[h]), (e & 1) ? a.y : a.x, (e & 1) ? b.y : b.x);
                }
                if ((jn & 7) == 7) put64(o128 + (jn >> 3) * 8192, acc + 4 * jn - 28);
            }
            float st[2][2] = {{0.f, 0.f}, {0.f, 0.f}};
#pragma unroll
            for (int jn = 0; jn < 16; jn++) {
                const float2 gb = ldsv(vec + V_GB * 512 + jn * 32);
                float z[4];
#pragma unroll
                for (int e = 0; e < 4; e++) {
                    const float x1 = acc[4 * jn + e];
                    st[e >> 1][0] += x1; st[e >> 1][1] = fmaf(x1, x1, st[e >> 1][1]);
                    z[e] = fmaf((e & 1) ? gb.y : gb.x, x1, KEEP(jn, e));
                }
                keep[2 * jn] = pack2(z[0], z[1]); keep[2 * jn + 1] = pack2(z[2], z[3]);
            }
#pragma unroll
            for (int h = 0; h < 2; h++)
#pragma unroll
                for (int q = 0; q < 2; q++) { st[h][q] += __shfl_xor_sync(~0u, st[h][q], 1); st[h][q] += __shfl_xor_sync(~0u, st[h][q], 2); }
            if (tq < 2) sts2(rsum + tq * 64, tq ? st[1][0] : st[0][0], tq ? st[1][1] : st[0][1]);
            signal();
        }
        {
            float old[96], acc[64];
            post_mma<3>(sb, old, pa, 16, wg, rel, lead, 10, none);
            uint32_t v3 = vec + V_C3 * 512;
            float c1[2], vc[8];
            auto next_vc = [&]() {
#pragma unroll
                for (int i = 0; i < 4; i++) { const float2 u = lds2f(v3 + i * 32); vc[2 * i] = u.x; vc[2 * i + 1] = u.y; }
                v3 += 128;
            };
            next_vc();
            GeluK gk[2];
            bar_sync(1 + wg, 160);
#pragma unroll
            for (int h = 0; h < 2; h++) { const float4 a = lds4f(rowc + h * 256); gk[h] = {a.x, a.y, a.z}; c1[h] = a.w; }
            bar_arrive(14 + wg, 256);
#pragma unroll 1
            for (int r = 0; r < 3; r++) {
                const uint32_t o = stw + (r ? o128 : P_OUT3 + wg * 24576);
                uint32_t when = r == 0 ? (wg ? SL_A1 : SL_A0) : r == 1 ? (wg ? SL_B1 : SL_B0) : SL_C << (2 * wg), n = 0;
                post_mma<2>(sb, acc, pa, r < 2 ? 16 : 56, wg, rel, lead, 12 + 2 * r, [&](int kb) {
                    const bool now = when & 1;
                    when >>= 1;
                    if (!now) return;
                    if (n == 0) { if (r == 0) bar_sync(15 - wg, 256); out_free(3 + r); }
                    float v[16];
                    pick32(v, n, c1, vc, old);
                    next_vc();
#pragma unroll
                    for (int e = 0; e < 16; e++) v[e] = gelu_s(v[e], gk[(e >> 1) & 1]);
                    const uint32_t a = (o + (n >> 1) * 8192) ^ ((n & 1) << 6);
                    stsm4(a, pack2(v[0], v[1]), pack2(v[2], v[3]), pack2(v[4], v[5]), pack2(v[6], v[7]));
                    stsm4(a ^ 32, pack2(v[8], v[9]), pack2(v[10], v[11]), pack2(v[12], v[13]), pack2(v[14], v[15]));
                    if ((++n & 1) == 0) signal();
                });
                if (r == 2) break;
#pragma unroll
                for (int i = 0; i < 64; i++) old[i] = acc[i];
            }
#pragma unroll
            for (int jn = 0; jn < 16; jn++) {
                const float2 gb = ldsv(vec + V_GB * 512 + jn * 32);
#pragma unroll
                for (int e = 0; e < 4; e++) acc[4 * jn + e] = fmaf((e & 1) ? gb.y : gb.x, acc[4 * jn + e], KEEP(jn, e));
                if ((jn & 7) == 7) put64(o128 + (jn >> 3) * 8192, acc + 4 * jn - 28);
            }
        }
    }
}

typedef CUresult (*EncFn)(CUtensorMap*, CUtensorMapDataType, cuuint32_t, void*, const cuuint64_t*, const cuuint64_t*, const cuuint32_t*,
                          const cuuint32_t*, CUtensorMapInterleave, CUtensorMapSwizzle, CUtensorMapL2promotion, CUtensorMapFloatOOBfill);

static CUtensorMap make_map(EncFn enc, const void* p, uint64_t inner, uint64_t outer) {
    CUtensorMap m;
    cuuint64_t dims[2] = {inner, outer};
    cuuint64_t str[1] = {inner * 2};
    cuuint32_t box[2] = {64, 64};
    cuuint32_t es[2] = {1, 1};
    enc(&m, CU_TENSOR_MAP_DATA_TYPE_BFLOAT16, 2, (void*)p, dims, str, box, es, CU_TENSOR_MAP_INTERLEAVE_NONE,
        CU_TENSOR_MAP_SWIZZLE_128B, CU_TENSOR_MAP_L2_PROMOTION_L2_256B, CU_TENSOR_MAP_FLOAT_OOB_FILL_NONE);
    return m;
}
static CUtensorMap make_map_o(EncFn enc, const void* p) {
    CUtensorMap m;
    cuuint64_t dims[2] = {16384, 256};
    cuuint64_t str[1] = {65536};
    cuuint32_t box[2] = {256, 8};
    cuuint32_t es[2] = {1, 1};
    enc(&m, CU_TENSOR_MAP_DATA_TYPE_UINT32, 2, (void*)p, dims, str, box, es, CU_TENSOR_MAP_INTERLEAVE_NONE, CU_TENSOR_MAP_SWIZZLE_NONE,
        CU_TENSOR_MAP_L2_PROMOTION_L2_256B, CU_TENSOR_MAP_FLOAT_OOB_FILL_NONE);
    return m;
}
template <class T> static T* sym(T& s) { void* p = nullptr; cudaGetSymbolAddress(&p, s); return (T*)p; }

constexpr RecTime g_time = {T_GO, T_X2, T_V, D_X2, H_D};
extern "C" void kernel_launch(void* const* d_in, const int* in_sizes, int n_in, void* d_out, int out_size) {
    const bf16* x = (const bf16*)d_in[0];
    const bf16* mem0 = (const bf16*)d_in[1];
    const bf16 *Wq = (const bf16*)d_in[2], *Wk = (const bf16*)d_in[3], *Wv = (const bf16*)d_in[4], *Wo = (const bf16*)d_in[5];
    const bf16 *w1 = (const bf16*)d_in[8], *w2 = (const bf16*)d_in[9], *w3 = (const bf16*)d_in[10], *w4 = (const bf16*)d_in[11];
    const bf16 *c = (const bf16*)d_in[12], *wmod = (const bf16*)d_in[13];
    bf16* out = (bf16*)d_out;

    EncFn enc = nullptr;
    cudaDriverEntryPointQueryResult qr;
    cudaGetDriverEntryPoint("cuTensorMapEncodeTiled", (void**)&enc, cudaEnableDefault, &qr);
    CUtensorMap tWq = make_map(enc, Wq, NH * DH, DM), tWk = make_map(enc, Wk, NH * DH, DM), tWv = make_map(enc, Wv, NH * DH, DM);
    PostMaps mp;
    mp.o = make_map_o(enc, sym(g_O)); mp.wo = make_map(enc, Wo, DM, NH * DH);
    mp.y = make_map(enc, sym(g_y), DM, S_); mp.w1 = make_map(enc, w1, DM, DM);
    mp.g = make_map(enc, sym(g_g), DM, S_); mp.w2 = make_map(enc, w2, DM, DM);
    mp.x1 = make_map(enc, sym(g_x1), DM, S_); mp.w3 = make_map(enc, w3, FF, DM);
    mp.u = make_map(enc, sym(g_u), FF, S_); mp.w4 = make_map(enc, w4, DM, FF);
    mp.out = make_map(enc, out, DM, S_); mp.x = make_map(enc, x, DM, S_);
    cudaFuncSetAttribute(k_rec, cudaFuncAttributeMaxDynamicSharedMemorySize, SM_REC_TOTAL);
    cudaFuncSetAttribute(k_post, cudaFuncAttributeMaxDynamicSharedMemorySize, P_SMEM);

    uint8_t* arena = (uint8_t*)(((uintptr_t)sym(g_arena) + (2u << 20) - 1) & ~(uintptr_t)((2u << 20) - 1));
    const RecPtrs rp = {x, mem0, c, wmod, w1, w3, arena, 0u, g_time};
    const RecMaps rm = {tWq, tWk, tWv, mp.wo};
    k_rec<<<132, 384, SM_REC_TOTAL>>>(rm, rp);
    k_post<<<128, 384, P_SMEM>>>(mp);
}
```

```cpp
#include <cuda_runtime.h>
#include <cuda.h>
#include <cuda_bf16.h>
#include <stdint.h>
#include <limits.h>

typedef __nv_bfloat16 bf16;

constexpr int S_ = 2048, DM = 1024, NH = 32, DH = 128, NSEG = 64, FF = 3584;
constexpr int SPIN_LIMIT = 1 << 22;
constexpr int W_INFL = 2;
constexpr int NPROBE = 4;

__device__ uint8_t g_arena[10 << 20];
__device__ __align__(16) uint32_t g_tick[64];
__device__ __align__(16) uint32_t g_modp[8 * 2 * DM];
__host__ __device__ constexpr uint32_t blk(uint32_t lb, uint32_t par) {
    return (lb << 13) | ((((lb) ^ (lb >> 3) ^ (lb >> 4) ^ (lb >> 6) ^ par) & 1) << 12);
}
__host__ __device__ constexpr uint32_t lb_x2(uint32_t h) { return (h & 1) | ((h >> 1) << 3); }
__host__ __device__ constexpr uint32_t acc_slot(uint32_t s) { return (1u << 20) + (s & 1) * 32768 + (s & 2) * 131072; }
__host__ __device__ constexpr uint32_t acc_piece(uint32_t half, uint32_t qd, uint32_t mt) { return mt * 1024 + (qd & 1) * 4096 + half * 8192 + (qd >> 1) * 16384; }
constexpr uint32_t LB_STAMP = 6;
__host__ __device__ constexpr uint32_t stamp_line(uint32_t w, uint32_t q) { return ((w & 1) * 2 + (q >> 1)) * 1024 + (q & 1) * 256; }
constexpr uint32_t ACC_ONE = 0x3c000000u, ACC_ALL = 0x50000000u;
constexpr uint32_t LB_PROBE = 6 | 64;
__host__ __device__ constexpr uint32_t lb_tok(uint32_t h) { return (h & 1) | ((h >> 1) << 3); }
__device__ __align__(16) float g_mod[6 * DM];
__device__ __align__(1024) bf16 g_himg[(S_ + 32) * DM];
__device__ __align__(1024) bf16 g_O[S_ * NH * DH];
__device__ __align__(1024) bf16 g_y[S_ * DM];
__device__ __align__(1024) bf16 g_g[S_ * DM];
__device__ __align__(1024) bf16 g_x1[S_ * DM];
__device__ __align__(16) float g_st[4 * S_ * 2];
__device__ __align__(16) float g_vec[3 * DM + FF];
__device__ float g_cst[8];
__device__ uint32_t g_pcnt[2 * 32 * 8], g_pflag[6 * 32 * 8];
__device__ __align__(1024) bf16 g_u[S_ * FF];

__device__ __forceinline__ uint32_t smem_u32(const void* p) { return (uint32_t)__cvta_generic_to_shared(p); }
__device__ __forceinline__ void spin_guard(int it) {
    asm volatile("{.reg .pred p; setp.gt.s32 p, %0, %1; @p st.global.u32 [%2], %0;}" ::"r"(it), "n"(SPIN_LIMIT), "l"(1ull));
}
__device__ __forceinline__ void wg_fence() { asm volatile("wgmma.fence.sync.aligned;" ::: "memory"); }
__device__ __forceinline__ void wg_commit() { asm volatile("wgmma.commit_group.sync.aligned;" ::: "memory"); }
template <int N> __device__ __forceinline__ void wg_wait() { asm volatile("wgmma.wait_group.sync.aligned %0;" ::"n"(N) : "memory"); }
__host__ __device__ constexpr uint64_t mkdesc(uint32_t addr, uint32_t lbo, uint32_t sbo, uint32_t swz) {
    return (uint64_t)((addr & 0x3FFFF) >> 4) | ((uint64_t)(lbo >> 4) << 16) | ((uint64_t)(sbo >> 4) << 32) | ((uint64_t)swz << 62);
}
__device__ __forceinline__ uint64_t dadd(uint64_t d, uint32_t o) { return (d & 0xffffffff00000000ull) | (uint32_t)((uint32_t)d + o); }
__device__ __forceinline__ void mbar_init(uint32_t b, uint32_t c) { asm volatile("mbarrier.init.shared.b64 [%0], %1;" ::"r"(b), "r"(c) : "memory"); }
__device__ __forceinline__ void mbar_expect(uint32_t b, uint32_t tx) { asm volatile("mbarrier.arrive.expect_tx.shared.b64 _, [%0], %1;" ::"r"(b), "r"(tx) : "memory"); }
__device__ __forceinline__ void mbar_arrive(uint32_t b) { asm volatile("mbarrier.arrive.shared.b64 _, [%0];" ::"r"(b) : "memory"); }
__device__ __forceinline__ void mbar_arrive_cluster_if(bool c, uint32_t b, uint32_t cta) {
    asm volatile("{.reg .pred p; .reg .b32 r; setp.ne.u32 p, %2, 0; mapa.shared::cluster.u32 r, %0, %1; @p mbarrier.arrive.shared::cluster.b64 _, [r];}" ::"r"(b), "r"(cta), "r"((uint32_t)c) : "memory");
}
__device__ __forceinline__ bool mbar_try(uint32_t b, uint32_t par) {
    uint32_t ok;
    asm volatile("{.reg .pred p; mbarrier.try_wait.parity.shared.b64 p, [%1], %2; selp.u32 %0, 1, 0, p;}" : "=r"(ok) : "r"(b), "r"(par) : "memory");
    return ok;
}
__device__ __forceinline__ void mbar_wait_w(uint32_t b, uint32_t par) {
    int it = 0;
    bool ok;
#pragma unroll 1
    do { ok = __all_sync(~0u, mbar_try(b, par)); spin_guard(++it); } while (!ok);
}
__device__ __forceinline__ void bar_sync(int id, int n) { asm volatile("bar.sync %0, %1;" ::"r"(id), "r"(n) : "memory"); }
__device__ __forceinline__ void bar_arrive(int id, int n) { asm volatile("bar.arrive %0, %1;" ::"r"(id), "r"(n) : "memory"); }
__device__ __forceinline__ void fence_async_smem() { asm volatile("fence.proxy.async.shared::cta;" ::: "memory"); }
__device__ __forceinline__ void ldsm4t(uint32_t* r, uint32_t a) {
    asm volatile("ldmatrix.sync.aligned.m8n8.x4.trans.shared.b16 {%0,%1,%2,%3}, [%4];" : "=r"(r[0]), "=r"(r[1]), "=r"(r[2]), "=r"(r[3]) : "r"(a) : "memory");
}
__device__ __forceinline__ void ldsm4(uint32_t* r, uint32_t a) {
    asm volatile("ldmatrix.sync.aligned.m8n8.x4.shared.b16 {%0,%1,%2,%3}, [%4];" : "=r"(r[0]), "=r"(r[1]), "=r"(r[2]), "=r"(r[3]) : "r"(a) : "memory");
}
__device__ __forceinline__ uint32_t movm(uint32_t a) {
    uint32_t d; asm volatile("movmatrix.sync.aligned.m8n8.trans.b16 %0, %1;" : "=r"(d) : "r"(a)); return d;
}
__device__ __forceinline__ void mma16816(float* d, uint32_t a0, uint32_t a1, uint32_t a2, uint32_t a3, uint32_t b0, uint32_t b1) {
    asm volatile("mma.sync.aligned.m16n8k16.row.col.f32.bf16.bf16.f32 {%0,%1,%2,%3},{%4,%5,%6,%7},{%8,%9},{%0,%1,%2,%3};"
                 : "+f"(d[0]), "+f"(d[1]), "+f"(d[2]), "+f"(d[3]) : "r"(a0), "r"(a1), "r"(a2), "r"(a3), "r"(b0), "r"(b1));
}
__device__ __forceinline__ void mma16816z(float* d, const uint32_t* a, uint32_t b0, uint32_t b1) {
    asm volatile("mma.sync.aligned.m16n8k16.row.col.f32.bf16.bf16.f32 {%0,%1,%2,%3},{%4,%5,%6,%7},{%8,%9},{%10,%10,%10,%10};"
                 : "=f"(d[0]), "=f"(d[1]), "=f"(d[2]), "=f"(d[3]) : "r"(a[0]), "r"(a[1]), "r"(a[2]), "r"(a[3]), "r"(b0), "r"(b1), "f"(0.f));
}
__device__ __forceinline__ void mma1688(float* d, uint32_t a0, uint32_t a1, uint32_t b0) {
    asm volatile("mma.sync.aligned.m16n8k8.row.col.f32.bf16.bf16.f32 {%0,%1,%2,%3},{%4,%5},{%6},{%0,%1,%2,%3};"
                 : "+f"(d[0]), "+f"(d[1]), "+f"(d[2]), "+f"(d[3]) : "r"(a0), "r"(a1), "r"(b0));
}
__device__ __forceinline__ uint32_t pack2(float lo, float hi) {
    uint32_t r; asm("cvt.rn.bf16x2.f32 %0, %1, %2;" : "=r"(r) : "f"(hi), "f"(lo)); return r;
}
__device__ __forceinline__ uint32_t hadd2v(uint32_t a, uint32_t b) {
    uint32_t r; asm volatile("add.rn.bf16x2 %0, %1, %2;" : "=r"(r) : "r"(a), "r"(b)); return r;
}
__device__ __forceinline__ float bflo(uint32_t u) { return __uint_as_float(u << 16); }
__device__ __forceinline__ float bfhi(uint32_t u) { return __uint_as_float(u & 0xffff0000u); }
__device__ __forceinline__ float ex2(float x) { float r; asm("ex2.approx.ftz.f32 %0, %1;" : "=f"(r) : "f"(x)); return r; }
__device__ __forceinline__ uint4 ldg_rlx4(const void* p) {
    uint4 v; asm volatile("ld.relaxed.gpu.global.v4.u32 {%0,%1,%2,%3}, [%4];" : "=r"(v.x), "=r"(v.y), "=r"(v.z), "=r"(v.w) : "l"(p) : "memory"); return v;
}
__device__ __forceinline__ uint32_t ldg_rlx1(const void* p) {
    uint32_t v; asm volatile("ld.relaxed.gpu.global.u32 %0, [%1];" : "=r"(v) : "l"(p) : "memory"); return v;
}
__device__ __forceinline__ void stg_rlx1(void* p, uint32_t v) { asm volatile("st.relaxed.gpu.global.u32 [%0], %1;" ::"l"(p), "r"(v) : "memory"); }
__device__ __forceinline__ void stg_rlx2(void* p, uint32_t x, uint32_t y) {
    unsigned long long v = (unsigned long long)x | ((unsigned long long)y << 32);
    asm volatile("st.relaxed.gpu.global.b64 [%0], %1;" ::"l"(p), "l"(v) : "memory");
}
__device__ __forceinline__ void stg_rlx4(void* p, uint32_t x, uint32_t y, uint32_t z, uint32_t w) {
    asm volatile("st.relaxed.gpu.global.v4.u32 [%0], {%1,%2,%3,%4};" ::"l"(p), "r"(x), "r"(y), "r"(z), "r"(w) : "memory");
}
__device__ __forceinline__ void sts4(uint32_t a, uint32_t x, uint32_t y, uint32_t z, uint32_t w) {
    asm volatile("st.shared.v4.u32 [%0], {%1,%2,%3,%4};" ::"r"(a), "r"(x), "r"(y), "r"(z), "r"(w) : "memory");
}
__device__ __forceinline__ uint4 lds4(uint32_t a) {
    uint4 v; asm volatile("ld.shared.v4.u32 {%0,%1,%2,%3}, [%4];" : "=r"(v.x), "=r"(v.y), "=r"(v.z), "=r"(v.w) : "r"(a) : "memory"); return v;
}
#define F4(d, i) "+f"(d[i]), "+f"(d[i + 1]), "+f"(d[i + 2]), "+f"(d[i + 3])
template <bool V> __device__ __forceinline__ void wgmma_tok_rs(float* d, const uint32_t* a, uint64_t b, int sc) {
    if (V) asm volatile("{.reg .pred p; setp.ne.b32 p, %25, 0;\n wgmma.mma_async.sync.aligned.m64n40k16.f32.bf16.bf16 {%0,%1,%2,%3,%4,%5,%6,%7,%8,%9,%10,%11,%12,%13,%14,%15,%16,%17,%18,%19}, {%20,%21,%22,%23}, %24, p, 1, 1, 0;}"
                        : F4(d, 0), F4(d, 4), F4(d, 8), F4(d, 12), F4(d, 16) : "r"(a[0]), "r"(a[1]), "r"(a[2]), "r"(a[3]), "l"(b), "r"(sc));
    else asm volatile("{.reg .pred p; setp.ne.b32 p, %21, 0;\n wgmma.mma_async.sync.aligned.m64n32k16.f32.bf16.bf16 {%0,%1,%2,%3,%4,%5,%6,%7,%8,%9,%10,%11,%12,%13,%14,%15}, {%16,%17,%18,%19}, %20, p, 1, 1, 0;}"
                      : F4(d, 0), F4(d, 4), F4(d, 8), F4(d, 12) : "r"(a[0]), "r"(a[1]), "r"(a[2]), "r"(a[3]), "l"(b), "r"(sc));
}
template <bool V> __device__ __forceinline__ void wgmma_tok_ss(float* d, uint64_t a, uint64_t b) {
    if (V) asm volatile("wgmma.mma_async.sync.aligned.m64n40k16.f32.bf16.bf16 {%0,%1,%2,%3,%4,%5,%6,%7,%8,%9,%10,%11,%12,%13,%14,%15,%16,%17,%18,%19}, %20, %21, 1, 1, 1, 1, 0;"
                        : F4(d, 0), F4(d, 4), F4(d, 8), F4(d, 12), F4(d, 16) : "l"(a), "l"(b));
    else asm volatile("wgmma.mma_async.sync.aligned.m64n32k16.f32.bf16.bf16 {%0,%1,%2,%3,%4,%5,%6,%7,%8,%9,%10,%11,%12,%13,%14,%15}, %16, %17, 1, 1, 1, 1, 0;"
                      : F4(d, 0), F4(d, 4), F4(d, 8), F4(d, 12) : "l"(a), "l"(b));
}
#define F16(d, i) F4(d, i), F4(d, i + 4), F4(d, i + 8), F4(d, i + 12)
template <int TA>
__device__ __forceinline__ void wgmma_ss128(float* d, uint64_t a, uint64_t b, int sc) {
    asm volatile("{.reg .pred p; setp.ne.b32 p, %66, 0;\n wgmma.mma_async.sync.aligned.m64n128k16.f32.bf16.bf16 "
                 "{%0,%1,%2,%3,%4,%5,%6,%7,%8,%9,%10,%11,%12,%13,%14,%15,%16,%17,%18,%19,%20,%21,%22,%23,%24,%25,%26,%27,%28,%29,%30,%31,"
                 "%32,%33,%34,%35,%36,%37,%38,%39,%40,%41,%42,%43,%44,%45,%46,%47,%48,%49,%50,%51,%52,%53,%54,%55,%56,%57,%58,%59,%60,%61,%62,%63}, %64, %65, p, 1, 1, %67, 1;}"
                 : F16(d, 0), F16(d, 16), F16(d, 32), F16(d, 48) : "l"(a), "l"(b), "r"(sc), "n"(TA));
}

__device__ __forceinline__ float warp_sum(float v) {
#pragma unroll
    for (int o = 16; o; o >>= 1) v += __shfl_xor_sync(~0u, v, o);
    return v;
}
__device__ __forceinline__ float bfround(float x) { return __bfloat162float(__float2bfloat16(x)); }

__device__ __forceinline__ void wait_count1(const uint32_t* p, uint32_t target) {
    int it = 0;
#pragma unroll 1
    while (true) {
        uint32_t v;
        asm volatile("ld.acquire.gpu.global.u32 %0, [%1];" : "=r"(v) : "l"(p) : "memory");
        if (v >= target) break;
        spin_guard(++it);
    }
}
__device__ __forceinline__ void signal_count(uint32_t* p) { asm volatile("red.release.gpu.global.add.u32 [%0], 1;" ::"l"(p) : "memory"); }
__device__ __forceinline__ void e_expect(uint32_t b, uint32_t tx) {
    asm volatile("{.reg .pred p; elect.sync _|p, 0xffffffff; @p mbarrier.arrive.expect_tx.shared.b64 _, [%0], %1;}" ::"r"(b), "r"(tx) : "memory");
}
__device__ __forceinline__ uint64_t evict_first() { uint64_t p; asm("createpolicy.fractional.L2::evict_first.b64 %0, 1.0;" : "=l"(p)); return p; }
__device__ __forceinline__ void e_tma2d_ef(uint32_t dst, const CUtensorMap* m, int c0, int c1, uint32_t bar) {
    asm volatile("{.reg .pred p; elect.sync _|p, 0xffffffff;\n @p cp.async.bulk.tensor.2d.shared::cluster.global.mbarrier::complete_tx::bytes.L2::cache_hint [%0], [%1, {%3, %4}], [%2], %5;}"
                 ::"r"(dst), "l"(m), "r"(bar), "r"(c0), "r"(c1), "l"(evict_first()) : "memory");
}
__device__ __forceinline__ void e_tma2d(uint32_t dst, const CUtensorMap* m, int c0, int c1, uint32_t bar) {
    asm volatile("{.reg .pred p; elect.sync _|p, 0xffffffff;\n @p cp.async.bulk.tensor.2d.shared::cluster.global.mbarrier::complete_tx::bytes [%0], [%1, {%3, %4}], [%2];}"
                 ::"r"(dst), "l"(m), "r"(bar), "r"(c0), "r"(c1) : "memory");
}
__device__ __forceinline__ void e_tma2d_mc_ef(uint32_t dst, const CUtensorMap* m, int c0, int c1, uint32_t bar) {
    asm volatile("{.reg .pred p; elect.sync _|p, 0xffffffff;\n @p cp.async.bulk.tensor.2d.shared::cluster.global.mbarrier::complete_tx::bytes.multicast::cluster.L2::cache_hint [%0], [%1, {%3, %4}], [%2], %5, %6;}"
                 ::"r"(dst), "l"(m), "r"(bar), "r"(c0), "r"(c1), "h"((uint16_t)3), "l"(evict_first()) : "memory");
}
__device__ __forceinline__ uint32_t wait_count_w(const uint32_t* p, uint32_t target) {
    int it = 0;
#pragma unroll 1
    while (true) {
        uint32_t v;
        asm volatile("ld.acquire.gpu.global.u32 %0, [%1];" : "=r"(v) : "l"(p) : "memory");
        if (__all_sync(~0u, v >= target)) return v;
        spin_guard(++it);
    }
}

__device__ __forceinline__ uint4 pack8(const float* x) {
    return make_uint4(pack2(x[0], x[1]), pack2(x[2], x[3]), pack2(x[4], x[5]), pack2(x[6], x[7]));
}
constexpr int NL = 6;
constexpr uint32_t HCH = 5120, HBUF = 8 * HCH;
constexpr uint32_t SM_SX = 0, SM_ST = 2560, SM_OX = 8192, SM_LX = 10240, SM_PX = 11392, SM_PA = 12288, SM_VF = 18432, SM_TAB = 26624, SM_WL2 = 41984, SM_HB = 49152, SM_WO = 131072,
                   SM_WL = 196608, SM_PRE = SM_WL, SM_BAR = 227328, SM_TRC = SM_BAR + 256, SM_REC_TOTAL = SM_TRC + 2688;
__host__ __device__ constexpr uint32_t sm_wl(int i) { return i < 5 ? SM_WL + i * 6144 : SM_WL2; }
constexpr uint32_t SB0 = 1024;
constexpr int B_WO = 0, B_HE = 1, B_ROLE = 2, B_HB = 3, B_W = 5;
constexpr int NB_MEM = 1, NB_QK = 2, NB_X1 = 3, NB_X2 = 4, NB_WIN = 5, NB_WG = 6, NB_KDONE = 7, NB_FIN0 = 8, NB_LN = 9, NB_MEM2 = 10, NB_H = 11, NB_A = 12, NB_B = 13, NB_C = 14, NB_F = 15;
constexpr int TPV_DLY = 6;
constexpr int L_AT = 3;
constexpr int D_X2 = 340;
constexpr int NPF1 = 6;
constexpr int NPF = 11;
constexpr int T_GO = 28;
constexpr int GATE_AT = 25;
constexpr int T_X2 = 1920;
constexpr int T_V = 300;
constexpr int VP_AT = 1;
constexpr int PD = 4;
constexpr int PV_FENCE = 0;
constexpr int SSG = 5;
constexpr int SSG_V = 5;
constexpr int SS0_K = 4;
constexpr int SS0_V = 6;
constexpr int NPF0 = 3;
constexpr int STG_FENCE = 1;
constexpr int WO_AT = 0x1100;
constexpr int W_SPEC = 7;
constexpr int NO_GUESS = 0;
constexpr int W_T0 = 2800;
constexpr int NPF2 = 9;
constexpr int PF_DLY = 7;
constexpr int H_D = 210;
constexpr int PIN_EPI = 1;

__device__ __forceinline__ uint32_t clk32() { uint32_t t; asm volatile("mov.u32 %0, %%clock;" : "=r"(t) :: "memory"); return t; }
__device__ __forceinline__ uint32_t gtime32() { uint32_t t; asm volatile("mov.u32 %0, %%globaltimer_lo;" : "=r"(t) :: "memory"); return t; }
template <int N> __device__ __forceinline__ uint32_t delay(uint32_t zero) {
    float x = __uint_as_float(clk32());
#pragma unroll
    for (int i = 0; i < N; i++) asm volatile("ex2.approx.ftz.f32 %0, %0;" : "+f"(x));
    return __float_as_uint(x) & zero;
}
__device__ __forceinline__ uint32_t clk_after(uint32_t x, uint32_t zero) {
    unsigned long long c = 0;
    asm volatile("{.reg .pred p; setp.eq.u32 p, %1, 0; @p mov.u64 %0, %%clock64;}" : "+l"(c) : "r"(x & zero) : "memory");
    return (uint32_t)c;
}
__device__ __forceinline__ uint32_t later(uint32_t a, uint32_t b) { return a + max((int)(b - a), 0); }
__device__ __forceinline__ void wait_clk(uint32_t t) {
#pragma unroll 1
    while (true) {
        unsigned long long c;
        asm volatile("mov.u64 %0, %%clock64;" : "=l"(c) :: "memory");
        if ((int)((uint32_t)c - t) >= 0) break;
    }
}
__device__ __forceinline__ uint32_t opaque(uint32_t v) { return __shfl_sync(~0u, v, threadIdx.x & 31); }
__device__ __forceinline__ uint32_t xor_or(uint32_t a, uint32_t b, uint32_t t) {
    uint32_t r; asm volatile("lop3.b32 %0, %1, %2, %3, 0x7E;" : "=r"(r) : "r"(a), "r"(b), "r"(t)); return r;
}
__device__ __forceinline__ uint32_t or3(uint32_t a, uint32_t b, uint32_t c) {
    uint32_t r; asm volatile("lop3.b32 %0, %1, %2, %3, 0xFE;" : "=r"(r) : "r"(a), "r"(b), "r"(c)); return r;
}
__device__ __forceinline__ uint32_t settag(uint32_t v, uint32_t tag) {
    uint32_t r; asm("lop3.b32 %0, %1, 1, %2, 0xB8;" : "=r"(r) : "r"(v), "r"(tag)); return r;
}
__device__ __forceinline__ void ldg1_if(uint32_t& v, const void* p, bool c) {
    asm volatile("{.reg .pred p; setp.ne.u32 p, %2, 0; @p ld.relaxed.gpu.global.u32 %0, [%1];}" : "+r"(v) : "l"(p), "r"((uint32_t)c) : "memory");
}
__device__ __forceinline__ void sts2(uint32_t a, float x, float y) { asm volatile("st.shared.v2.f32 [%0], {%1,%2};" ::"r"(a), "f"(x), "f"(y) : "memory"); }
__device__ __forceinline__ void sts4f(uint32_t a, float x, float y, float z, float w) {
    asm volatile("st.shared.v4.f32 [%0], {%1,%2,%3,%4};" ::"r"(a), "f"(x), "f"(y), "f"(z), "f"(w) : "memory");
}
__device__ __forceinline__ void sts1(uint32_t a, uint32_t x) { asm volatile("st.shared.u32 [%0], %1;" ::"r"(a), "r"(x) : "memory"); }
__device__ __forceinline__ uint32_t lds1(uint32_t a) { uint32_t v; asm volatile("ld.shared.u32 %0, [%1];" : "=r"(v) : "r"(a) : "memory"); return v; }
__device__ __forceinline__ float4 lds4f(uint32_t a) {
    float4 v; asm volatile("ld.shared.v4.f32 {%0,%1,%2,%3}, [%4];" : "=f"(v.x), "=f"(v.y), "=f"(v.z), "=f"(v.w) : "r"(a) : "memory"); return v;
}
__device__ __forceinline__ float2 lds2f(uint32_t a) {
    float2 v; asm volatile("ld.shared.v2.f32 {%0,%1}, [%2];" : "=f"(v.x), "=f"(v.y) : "r"(a) : "memory"); return v;
}
__device__ __forceinline__ bool any_bit0(uint32_t x) {
    uint32_t r;
    asm volatile("{.reg .pred p, q; .reg .b32 t; and.b32 t, %1, 1; setp.ne.u32 p, t, 0; vote.sync.any.pred q, p, 0xffffffff; selp.u32 %0, 1, 0, q;}" : "=r"(r) : "r"(x));
    return r;
}
__device__ __forceinline__ float rcp_fast(float x) { float r; asm("rcp.approx.ftz.f32 %0, %1;" : "=f"(r) : "f"(x)); return r; }
__device__ __forceinline__ void stsm4(uint32_t a, uint32_t r0, uint32_t r1, uint32_t r2, uint32_t r3) {
    asm volatile("stmatrix.sync.aligned.m8n8.x4.shared.b16 [%0], {%1,%2,%3,%4};" ::"r"(a), "r"(r0), "r"(r1), "r"(r2), "r"(r3) : "memory");
}
__device__ __forceinline__ void stsm4t(uint32_t a, uint32_t r0, uint32_t r1, uint32_t r2, uint32_t r3) {
    asm volatile("stmatrix.sync.aligned.m8n8.x4.trans.shared.b16 [%0], {%1,%2,%3,%4};" ::"r"(a), "r"(r0), "r"(r1), "r"(r2), "r"(r3) : "memory");
}
__device__ __forceinline__ void cp_async16(uint32_t dst, const void* src) { asm volatile("cp.async.cg.shared.global [%0], [%1], 16;" ::"r"(dst), "l"(src) : "memory"); }
__device__ __forceinline__ void cp_async16_ef(uint32_t dst, const void* src) {
    asm volatile("cp.async.cg.shared.global.L2::cache_hint [%0], [%1], 16, %2;" ::"r"(dst), "l"(src), "l"(evict_first()) : "memory");
}
__device__ __forceinline__ uint32_t prmt(uint32_t a, uint32_t b, uint32_t c) { uint32_t r; asm("prmt.b32 %0, %1, %2, %3;" : "=r"(r) : "r"(a), "r"(b), "r"(c)); return r; }
__device__ __forceinline__ uint32_t hadd2h(uint32_t a, uint32_t b) { uint32_t r; asm("add.rn.f16x2 %0, %1, %2;" : "=r"(r) : "r"(a), "r"(b)); return r; }
__device__ __forceinline__ uint32_t hmax2h(uint32_t a, uint32_t b) { uint32_t r; asm("max.f16x2 %0, %1, %2;" : "=r"(r) : "r"(a), "r"(b)); return r; }
__device__ __forceinline__ uint32_t max3u(uint32_t a, uint32_t b, uint32_t c) { return __vimax3_u32(a, b, c); }

__device__ __forceinline__ void h_load(uint32_t sb, const uint8_t* hsrc, int pass, uint32_t rank, uint32_t rot, uint32_t wq, bool arm = true, uint32_t skip = 0) {
    const uint32_t bar = sb + SM_BAR + 8 * (B_HB + (pass & 1)), c = (wq + rot) & 3, dst = sb + SM_HB + (pass & 1) * HBUF + (rank * 4 + c) * HCH + skip;
    const uint8_t* src = hsrc + ((size_t)pass * 65536 + c * 4096 + skip);
    if (arm && wq == 0) e_expect(bar, 32768 - 8 * skip);
    asm volatile("{.reg .pred p; elect.sync _|p, 0xffffffff;\n"
                 " @p cp.async.bulk.shared::cluster.global.mbarrier::complete_tx::bytes.multicast::cluster.L2::cache_hint [%0], [%1], %4, [%2], %3, %5;}"
                 ::"r"(dst), "l"(src), "r"(bar), "h"((uint16_t)3), "r"(4096 - skip), "l"(evict_first()) : "memory");
}
__device__ __forceinline__ uint4 ldg_b128(const void* p) {
    uint4 v;
    asm volatile("{.reg .b128 t; .reg .b64 a, b; ld.relaxed.gpu.global.b128 t, [%4]; mov.b128 {a, b}, t; mov.b64 {%0,%1}, a; mov.b64 {%2,%3}, b;}"
                 : "=r"(v.x), "=r"(v.y), "=r"(v.z), "=r"(v.w) : "l"(p) : "memory");
    return v;
}
__device__ __forceinline__ void stg_b128_if(bool c, void* p, uint32_t x, uint32_t y, uint32_t z, uint32_t w) {
    asm volatile("{.reg .pred p; .reg .b128 t; .reg .b64 a, b; setp.ne.u32 p, %5, 0; mov.b64 a, {%1,%2}; mov.b64 b, {%3,%4}; mov.b128 t, {a, b}; @p st.relaxed.gpu.global.b128 [%0], t;}"
                 ::"l"(p), "r"(x), "r"(y), "r"(z), "r"(w), "r"((uint32_t)c) : "memory");
}
__device__ __forceinline__ float pretag(float x, uint32_t add, uint32_t keep) { return __uint_as_float((__float_as_uint(x) + add) & keep); }

template <bool MASK, class F>
__device__ __forceinline__ void softmax_rows(uint32_t src, uint32_t dst, uint32_t g16, int row0, F mid) {
    const uint32_t u = (g16 >> 7) & 3, e = ((g16 >> 9) << 3) | ((g16 >> 4) & 7);
    const uint32_t se = src + e * 8, su = se + u * 1088;
    const float2 p0 = lds2f(su), p1 = lds2f(su + 256), p2 = lds2f(su + 512), p3 = lds2f(su + 768);
    const float2 m0 = lds2f(se + 4352), m1 = lds2f(se + 4352 + 256), m2 = lds2f(se + 4352 + 512), m3 = lds2f(se + 4352 + 768);
    float a0 = (p0.x + p1.x) + (p2.x + p3.x), a1 = (p0.y + p1.y) + (p2.y + p3.y);
    const float a2 = (m0.x + m1.x) + (m2.x + m3.x), a3 = (m0.y + m1.y) + (m2.y + m3.y);
    mid(__float_as_uint(a3));
    if (MASK) {
        const int vis = row0 + (e >> 2) - 2 * (e & 3) - 8 * u;
        if (vis < 0) a0 = -1e9f / 0.08838834764831845f;
        if (vis < 1) a1 = -1e9f / 0.08838834764831845f;
    }
    int k = __float_as_int(fmaxf(fmaxf(a0, a1), fmaxf(a2, a3)));
    k ^= (k >> 31) & 0x7fffffff;
    const bool hi = g16 & 64;
    const int k0 = __reduce_max_sync(~0u, hi ? INT_MIN : k), k1 = __reduce_max_sync(~0u, hi ? k : INT_MIN);
    k = hi ? k1 : k0;
    const float m = __int_as_float(k ^ ((k >> 31) & 0x7fffffff));
    const float sl2 = 0.08838834764831845f * 1.4426950408889634f, mb = -m * sl2;
    sts1(dst + e * 16 + u * 4, pack2(ex2(fmaf(a0, sl2, mb)), ex2(fmaf(a1, sl2, mb))));
    sts1(dst + 512 + e * 4, pack2(ex2(fmaf(a2, sl2, mb)), ex2(fmaf(a3, sl2, mb))));
}

__device__ __forceinline__ uint32_t pack_h2(float lo, float hi) {
    uint32_t r; asm("cvt.rn.satfinite.f16x2.f32 %0, %1, %2;" : "=r"(r) : "f"(hi), "f"(lo)); return r;
}
__device__ __forceinline__ float2 unpack_h2(uint32_t u) {
    float2 r; asm("{.reg .b16 l, h; mov.b32 {l, h}, %2; cvt.f32.f16 %0, l; cvt.f32.f16 %1, h;}" : "=f"(r.x), "=f"(r.y) : "r"(u)); return r;
}
__device__ __forceinline__ uint32_t h2bf(uint32_t u) {
    uint32_t r;
    asm volatile("{.reg .b16 l, h; .reg .f32 a, b; mov.b32 {l, h}, %1; cvt.f32.f16 a, l; cvt.f32.f16 b, h; cvt.rn.bf16x2.f32 %0, b, a;}" : "=r"(r) : "r"(u));
    return r;
}
__device__ __forceinline__ void red_h10(bool c, void* p, void* q, uint32_t x, uint32_t y, uint32_t z, uint32_t w, uint32_t e) {
    asm volatile("{.reg .pred p; setp.ne.u32 p, %7, 0; red.relaxed.gpu.global.add.noftz.v4.f16x2 [%0], {%2,%3,%4,%5};\n"
                 " @p red.relaxed.gpu.global.add.noftz.f16x2 [%1], %6;}" ::"l"(p), "l"(q), "r"(x), "r"(y), "r"(z), "r"(w), "r"(e), "r"((uint32_t)c) : "memory");
}
constexpr float Q_SCALE = 1024.0f;
constexpr float SM_L2E = 0.08838834764831845f * 1.4426950408889634f * Q_SCALE;
template <int V> struct IC { static constexpr int value = V; };
typedef unsigned long long u64;
__device__ __forceinline__ uint32_t lo32(u64 v) { return (uint32_t)v; }
__device__ __forceinline__ uint32_t hi32(u64 v) { return (uint32_t)(v >> 32); }
__device__ __forceinline__ u64 ldg_u64(const void* p) { u64 v; asm volatile("ld.relaxed.gpu.global.b64 %0, [%1];" : "=l"(v) : "l"(p) : "memory"); return v; }
struct RecTime { uint32_t go, x2, v, dx2, h; };
__device__ __forceinline__ void rec_main(uint32_t sb, const CUtensorMap* tWo, uint8_t* arena, int role, int hinfo, int wg, uint32_t zero, const RecTime& tm) {
    const int hA = hinfo & 255;
    const int tid = threadIdx.x, t = tid & 127, lane = tid & 31, wi = t >> 5;
    const uint32_t bars = sb + SM_BAR;
    const int head = role >> 2, qd = role & 3, j = blockIdx.x & 1, kh = role & 1;
    const uint32_t mypar = head >= hA;
    const uint32_t wiu = __reduce_max_sync(~0u, wi);
    const bool warp0 = wiu == 0;
    const uint8_t* hsrc = (const uint8_t*)g_himg + kh * 32768 + j * 16384;
    auto tokbase = [&](int ty) { return ((ty + 1) << 21) + blk(lb_tok(head), mypar ^ ((hinfo >> (8 + ty)) & 1)); };
    const uint32_t tbw = tokbase(wg), tbq = tokbase(0) + (qd >> 1) * 2048 + (qd & 1) * 8;
#define KS(p) (4 * (((p) >> 1) & 7) + ((p) >> 4) + 2 * ((p) & 1))
    uint32_t w[32 - NL][4];
    uint4 wl5;
    if (wg == 2) bar_arrive(NB_WIN, 384);
    const uint32_t po = (1 << 20) + j * 16384 + kh * 2048;
    const uint32_t c16 = kh * 2048 + ((2 * j + (wi >> 1)) * 32 + lane) * 16, xso = blk(lb_x2(head), mypar);
    const uint32_t x2o = xso + wg * 16384 + (wi & 1) * 2048 + (c16 >> 1), tko = tbw + (wi & 1) * 16384 + c16;
    {
        stg_rlx2(arena + x2o, 0, 0);
#pragma unroll
        for (int i = 0; i < 4; i++) stg_rlx4(arena + ((i & 1 ? tko : tbw + (po ^ 2048) + t * 16) + (i >> 1) * 32768), 0, 0, 0, 0);
    }
    const uint32_t frow = ((lane >> 4) * 8 + (lane & 7)) * 128, fx = ((lane >> 3) & 1) ^ (lane & 7);
    {
#pragma unroll 1
        for (int i = 0; i < 4; i++) mbar_wait_w(bars + 8 * (B_W + (wg == 2 ? 8 + i : 2 * i + wg)), 0);
        const uint32_t stg = sb + wg * 65536;
#pragma unroll
        for (int p = NL; p < 32; p++) ldsm4t(w[p - NL], stg + KS(p) * 2048 + frow + ((fx ^ (2 * wi)) << 4));
#pragma unroll
        for (int i = 0; i < NL; i++) {
            wl5 = lds4(stg + KS(i) * 2048 + t * 16);
            if (i < 5) sts4(sb + sm_wl(i) + tid * 16, wl5.x, wl5.y, wl5.z, wl5.w);
        }
        fence_async_smem();
        if (wg < 2) bar_sync(NB_WG, 256);
        if (wg > 0) wait_count_w(&g_tick[32 + (lane & 3) * 8], wg);
        if (wg == 1) {
            mbar_arrive_cluster_if(t == 0, bars + 8 * B_HE, j ^ 1);
            asm volatile("fence.proxy.async.global;" ::: "memory");
            mbar_wait_w(bars + 8 * B_HE, 0);
#pragma unroll 1
            for (int i = 0; i < 2; i++) h_load(sb, hsrc, i, j, head, wiu, true, i ? 0 : 2048);
        }
    }
    uint32_t g16 = opaque(t * 16);
    {
        const uint32_t wr = ((wg * 4 + wi) ^ head) & 7;
        const uint32_t pc = wg < 2 ? acc_piece(wr >> 2, qd, wr & 3) : acc_piece(kh, wi, 0);
        const uint32_t lm = sb + SM_HB + 4096 + (lane & 7) * 128;
        const uint32_t a0 = wg < 2 ? sb + SM_WL + wg * 2048 + frow + ((fx ^ (2 * wi)) << 4) : blk(LB_STAMP + (wi >> 1), mypar) + stamp_line(wi, lane >> 3) + (lane & 7) * 16;
        const uint32_t a1 = pc + lane * 16;
        const uint32_t a2 = wg < 2 ? pc + 512 + (lane >> 3) * 4 : (role >> 2) * 1024 + (lane < 8 ? (role & 3) * 128 : 384) + lane * 16;
        const uint32_t a3 = wg < 2 ? sb + SM_WO + (wr >> 2) * 32768 + frow + ((fx ^ (2 * (wr & 3))) << 4) : qd * 65536 + head * 2048 + wi * 512 + lane * 4;
        const uint32_t a4 = wg < 2 ? lm + ((fx ^ ((lane >> 4) * 4)) << 4) : lm + (fx << 4) + ((lane >> 4) + 2 * wi) * HCH;
        if (wg < 2) bar_arrive(NB_X2, 384);
        else bar_sync(NB_X2, 384);
        if (NL > 5) {
            sts4(sb + SM_WL2 + tid * 16, wl5.x, wl5.y, wl5.z, wl5.w);
            fence_async_smem();
            bar_sync(NB_WG + 1 + wg, 128);
        }
        sts4(sb + SM_TAB + wg * 5120 + g16, a0, x2o,
             wg ? xso + (wg == 2 ? 32768 : 0) + t * 8 : blk(LB_STAMP + ((lane >> 1) & 1), (lane >> 2) & 1) + stamp_line(lane, qd) + head * 4, tko);
        sts4(sb + SM_TAB + wg * 5120 + 2048 + g16, a1, a2, a3, a4);
        sts2(sb + SM_TAB + wg * 5120 + 4096 + t * 8, __uint_as_float(tbw + t * 16), __uint_as_float((wg ? tbq : tokbase(1)) + t * 16));
    }
    const uint32_t ONES = 0x3f803f80u, tabw = sb + SM_TAB + wg * 5120;
#define LAST ((g16 & 0x70) == 0x70)

    auto pa_ptr = [&](int p) { return arena + (((p & 1) ^ 1) * 32768 + po + lds1(tabw + 4096 + (g16 >> 1))); };
    auto pa_request = [&](int p) { cp_async16(sb + SM_PA + wg * 2048 + g16, pa_ptr(p)); };
    auto pa_get = [&](int p) {
        asm volatile("cp.async.wait_all;" ::: "memory");
        uint4 pa = lds4(sb + SM_PA + wg * 2048 + g16);
        int it = 0;
#pragma unroll 1
        while (any_bit0(pa.x ^ ((p - 1) >> 1) ^ 1) && p > 0 && p <= NSEG) { pa = ldg_b128(pa_ptr(p)); spin_guard(++it); }
        return pa;
    };
    auto pass_init = [&](float* acc, int n, uint4 pa) {
#pragma unroll
        for (int i = 0; i < 4; i++) { acc[2 * i] = bflo((&pa.x)[i]); acc[2 * i + 1] = bfhi((&pa.x)[i]); }
#pragma unroll
        for (int i = 8; i < n; i++) acc[i] = 0.f;
    };
    auto pass_run = [&](auto vc, int p, float* acc, auto mid) {
        constexpr bool V = decltype(vc)::value;
#define HB(ks) dadd(mkdesc(SB0 + SM_HB + ((ks) >> 2) * HCH + ((ks) & 3) * 32, 16, 1024, 1), (p & 1) * (HBUF / 16))
        wg_fence();
#pragma unroll
        for (int i = 0; i < 32; i++) {
            constexpr int GAP = V ? SSG_V : SSG, SS0 = V ? SS0_V : SS0_K;
            const int u = i < SS0 ? 0 : (i - SS0 + GAP - 1) / GAP, q = i - (u < NL ? u : NL);
            if (i >= SS0 && (i - SS0) % GAP == 0 && u < NL) wgmma_tok_ss<V>(acc, dadd(mkdesc(SB0 + sm_wl(u), 8192, 1024, 1), (V ? 2 : wg) * 128), HB(KS(u)));
            else wgmma_tok_rs<V>(acc, w[q], HB(KS(NL + q)), 1);
            mid(i);
        }
        wg_commit();
    };
    auto pass_out = [&](auto tc, int p, float* acc, auto mid) {
        constexpr int TY = decltype(tc)::value;
        const bool V = TY == 2 || (TY == 4 && wg == 2), Q = TY >= 3 && wg == 0;
        const int b = p & 1, s = p - 2;
        (void)s;
        const uint32_t ftag = (((p - 1) >> 1) & 1) ^ 1, ptag = ((p >> 1) & 1) ^ 1;
        const bool tg = V || !(g16 & 64);
        const uint32_t add = tg ? (ftag ^ 1) << 16 : 0u, keep = tg ? 0xfffe0000u : ~0u;
        const uint32_t add1 = V ? 0u : add, keep1 = V ? ~0u : keep;
        const uint32_t add2 = Q ? add : 0u, keep2 = Q ? keep : ~0u;
        uint8_t* pdst = arena + (b * 32768 + (po ^ 2048) + lds1(tabw + 4096 + (g16 >> 1)));
        uint8_t* fdst = arena + ((b ^ 1) * 32768 + lds1(tabw + 12 + g16));
        if (PIN_EPI) asm volatile("" : "+l"(pdst), "+l"(fdst));
        mid(0);
        uint32_t r0 = pack2(pretag(acc[0], add, keep), pretag(acc[1], add1, keep1));
        uint32_t r1 = pack2(acc[2], acc[3]), r3 = pack2(acc[6], acc[7]);
        uint32_t r2 = pack2(pretag(acc[4], add2, keep2), pretag(acc[5], add2, keep2));
        if (!V) { r0 = movm(r0); r1 = movm(r1); r2 = movm(r2); r3 = movm(r3); }
        mid(1);
        stg_b128_if(p < NSEG, pdst, settag(pack2(pretag(acc[8], (ptag ^ 1) << 16, 0xfffe0000u), acc[9]), ptag), pack2(acc[10], acc[11]), pack2(acc[12], acc[13]), pack2(acc[14], acc[15]));
        stg_b128_if(p > 0 && p <= NSEG, fdst, settag(r0, ftag), r1, Q ? settag(r2, ftag) : r2, r3);
    };
    auto nop = [](int) {};
    auto wait0 = [](int i) { if (i == 0) wg_wait<0>(); };
    uint4 tf[2][2];
    auto load_tok = [&](int s, uint32_t o) {
        const uint8_t* ts = arena + ((s & 1) * 32768 + o);
#pragma unroll
        for (int a = 0; a < 2; a++)
#pragma unroll
            for (int b = 0; b < 2; b++) tf[a][b] = ldg_b128(ts + a * 16384 + b * 2048);
    };

    auto wo_load = [&](int stage) {
        if (wg == 2 && ((WO_AT >> (4 * wiu)) & 15) == stage) {
            const int c0 = (wiu >> 1) * 512 + qd * 128 + (wiu & 1) * 64;
            e_expect(bars + 8 * B_WO, 16384);
            e_tma2d(sb + SM_WO + wiu * 16384, tWo, c0, head * DH, bars + 8 * B_WO);
            e_tma2d(sb + SM_WO + wiu * 16384 + 8192, tWo, c0, head * DH + 64, bars + 8 * B_WO);
        }
    };
#pragma unroll 1
    for (int p = 0; p <= (wg >> 1); p++) {
        mbar_wait_w(bars + 8 * (B_HB + p), 0);
        float acc[16];
        pass_init(acc, 16, pa_get(p));
        wo_load(p);
        pass_run(IC<0>(), p, acc, nop);
        if (p) {
            mbar_wait_w(bars + 8 * B_HE, 1);
            asm volatile("fence.proxy.async.global;" ::: "memory");
            h_load(sb, hsrc, 2, j, head, wiu);
        }
        pass_out(IC<4>(), p, acc, wait0);
        if (wg < 2) {
            bar_arrive(NB_C, 384);
            if (wg == 0) bar_arrive(NB_WIN, 384);
        } else if (p == 0) {
            bar_sync(NB_C, 384);
            mbar_arrive_cluster_if(g16 == 0, bars + 8 * B_HE, j ^ 1);
        }
        pa_request(p + 1);
    }
    if (wg < 2) {
        mbar_wait_w(bars + 8 * (B_HB + 1), 0);
        uint4 pa = pa_get(1);
        uint32_t wl = lds1(tabw + g16);
#pragma unroll 1
        for (int s = 0; s < NSEG; s++) {
            uint32_t w0[NL][4], xo, lm, fz = 0;
            float acc[16];
#pragma unroll
            for (int i = 0; i < 4; i++)
                asm volatile("shl.b32 %0, %4, 16; and.b32 %1, %4, 0xffff0000; mov.b32 %2, %5; mov.b32 %3, %5;"
                             : "=&f"(acc[2 * i]), "=f"(acc[2 * i + 1]), "=f"(acc[8 + 2 * i]), "=f"(acc[9 + 2 * i]) : "r"((&pa.x)[i]), "r"(zero));
#pragma unroll
            for (int i = 0; i < NL; i++) ldsm4t(w0[i], wl + (sm_wl(i) - SM_WL));
            if (wg == 0) bar_sync(NB_B, 256);
            else bar_sync(NB_WIN, 384);
            pass_run(IC<0>(), s + 1, acc, [&](int i) { if (i == GATE_AT && wg) bar_arrive(NB_B, 256); });
            xo = lds1(tabw + 4 + g16);
            lm = lds1(tabw + 2060 + g16) + (s & 1) * HBUF;
            pass_out(IC<3>(), s + 1, acc, [&](int i) {
                if (i == 0) {
                    wg_wait<0>();
                    if (wg == 0) bar_arrive(NB_MEM, 384);
                    fz |= clk32();
                }
                if (i == 1 && wg) bar_sync(NB_F, 256);
            });
            asm volatile("" : "+r"(lm));
            if (wg == 0) bar_sync(NB_MEM2, 256);
            else bar_sync(NB_MEM, 384);
            float c[4][4];
            uint32_t bq[PD][4];
#define MEMF(it) ((lm ^ (((it) >> 3) * 32)) + ((it) & 7) * HCH)
#pragma unroll
            for (int it = 0; it < PD; it++) ldsm4(bq[it], MEMF(it));
#pragma unroll
            for (int it = 0; it < 16; it++) {
                uint32_t* bfr = bq[it % PD];
                const uint32_t* wa = 2 * it < NL ? w0[2 * it < NL ? 2 * it : 0] : w[2 * it < NL ? 0 : 2 * it - NL];
                const uint32_t* wb = 2 * it + 1 < NL ? w0[2 * it + 1 < NL ? 2 * it + 1 : 0] : w[2 * it + 1 < NL ? 0 : 2 * it + 1 - NL];
                float *ca = c[(2 * it) & 3], *cb = c[(2 * it + 1) & 3];
                if (it < 2) { mma16816z(ca, wa, bfr[0], bfr[1]); mma16816z(cb, wb, bfr[2], bfr[3]); }
                else { mma16816(ca, wa[0], wa[1], wa[2], wa[3], bfr[0], bfr[1]); mma16816(cb, wb[0], wb[1], wb[2], wb[3], bfr[2], bfr[3]); }
                if (it + PD < 16) ldsm4(bfr, MEMF(it + PD));
            }
            const float qs = wg ? 1.0f : 1.0f / Q_SCALE;
#define CSUM(e) fmaf(c[2][e] + c[3][e], qs, (c[0][e] + c[1][e]) * qs)
            const uint32_t r0 = pack2(CSUM(0), CSUM(1)), r1 = pack2(CSUM(2), CSUM(3));
            bar_arrive(NB_QK + (r0 & zero), 384);
            stg_rlx2(arena + xo, settag(movm(r0), (s & 1) ^ 1), movm(r1));
            const uint32_t tx = later(lds1(sb + SM_LX + 1040) + tm.x2, clk_after(r0, zero) + tm.dx2);
            g16 |= (fz | tx) & zero;
            {
                const uint32_t l16 = sb + (g16 & 0x1f0), g8 = g16 >> 1;
                const uint32_t tag = (s & 1) ^ 1, ttag = ((s >> 1) & 1) ^ 1;
                uint32_t wf[NPF][4], a3;
#define WF(f) (a3 + ((f) & 1) * 16384 + ((f) >> 1) * 2048)
                if (wg == 1) {
                    float sc[5][4];
                    uint4 (&kf)[2][2] = tf;
                    uint32_t qa[2][4], km[4], fz;
                    const uint32_t sd = lds1(sb + SM_TAB + 8 + g16);
                    int it = 0;
                    bool bad;
#pragma unroll 1
                    do {
                        u64 qf[2], x[8];
                        const float2 u = lds2f(tabw + 4096 + g8);
                        load_tok(s, __float_as_uint(u.x));
                        const uint8_t *xp = arena + lds1(tabw + 8 + g16), *tq = arena + ((s & 1) * 32768 + __float_as_uint(u.y));
                        asm volatile("" : "+l"(xp));
                        asm volatile("" : "+l"(tq));
#pragma unroll
                        for (int a = 0; a < 2; a++) qf[a] = ldg_u64(tq + a * 16384);
                        spin_guard(++it);
                        wait_clk(tx);
#pragma unroll
                        for (int i = 0; i < 8; i++) x[i] = ldg_u64(xp + (i >> 2) * 16384 + (i & 3) * 1024);
                        fz = clk32();
                        const uint32_t bt = or3(xor_or(lo32(qf[0]), lo32(qf[1]), ttag), xor_or(kf[0][0].x, kf[0][1].x, ttag), xor_or(kf[1][0].x, kf[1][1].x, ttag));
#pragma unroll
                        for (int a = 0; a < 2; a++) { qa[a][1] = or3(lo32(qf[a]), zero, 0); qa[a][3] = or3(hi32(qf[a]), zero, 0); }
                        fz |= clk32();
#pragma unroll
                        for (int a = 0; a < 2; a++) { qa[a][0] = hadd2v(lo32(x[2 * a]), lo32(x[2 * a + 1])); qa[a][2] = hadd2v(hi32(x[2 * a]), hi32(x[2 * a + 1])); }
#pragma unroll
                        for (int a = 0; a < 2; a++) { km[2 * a] = hadd2v(lo32(x[4 + 2 * a]), lo32(x[5 + 2 * a])); km[2 * a + 1] = hadd2v(hi32(x[4 + 2 * a]), hi32(x[5 + 2 * a])); }
                        bad = any_bit0(or3(or3(bt, xor_or(lo32(x[0]), lo32(x[1]), tag), xor_or(lo32(x[2]), lo32(x[3]), tag)), xor_or(lo32(x[4]), lo32(x[5]), tag), xor_or(lo32(x[6]), lo32(x[7]), tag)));
                    } while (bad);
                    mma16816z(sc[0], qa[0], kf[0][0].x, kf[0][0].y);
                    mma16816z(sc[1], qa[0], kf[0][0].z, kf[0][0].w);
                    mma16816z(sc[2], qa[0], kf[0][1].x, kf[0][1].y);
                    mma16816z(sc[3], qa[0], kf[0][1].z, kf[0][1].w);
                    mma16816z(sc[4], qa[0], km[0], km[1]);
                    mma16816(sc[0], qa[1][0], qa[1][1], qa[1][2], qa[1][3], kf[1][0].x, kf[1][0].y);
                    mma16816(sc[1], qa[1][0], qa[1][1], qa[1][2], qa[1][3], kf[1][0].z, kf[1][0].w);
                    mma16816(sc[2], qa[1][0], qa[1][1], qa[1][2], qa[1][3], kf[1][1].x, kf[1][1].y);
                    mma16816(sc[3], qa[1][0], qa[1][1], qa[1][2], qa[1][3], kf[1][1].z, kf[1][1].w);
                    mma16816(sc[4], qa[1][0], qa[1][1], qa[1][2], qa[1][3], km[2], km[3]);
                    const uint32_t sx = sb + SM_SX + (g16 & 0x1f0) * 5;
                    sts4(sx + (g16 >> 5 & 0x30), pack_h2(sc[0][0], sc[0][1]), pack_h2(sc[1][0], sc[1][1]),
                         pack_h2(sc[2][0], sc[2][1]), pack_h2(sc[3][0], sc[3][1]));
                    sts1(sx + 64 + (g16 >> 7 & 0xc), pack_h2(sc[4][0], sc[4][1]));
                    bar_arrive(NB_X1, 256);
                    const uint32_t now = gtime32();
#pragma unroll
                    for (int n = 0; n < 5; n++) sts2(sb + SM_ST + g8 + n * 1088, sc[n][2], sc[n][3]);
                    bar_arrive(NB_H, 256);
                    a3 = lds1(tabw + 2056 + g16) | (fz & zero);
                    asm volatile("{.reg .pred p; setp.lt.u32 p, %2, 128; @p red.relaxed.gpu.global.max.u32 [%0], %1;}"
                                 ::"l"(arena + sd), "r"(__funnelshift_r(now * 8, s + 1, 8)), "r"(g16) : "memory");
                    if (s == 0) mbar_wait_w(bars + 8 * B_WO, 0);
                    a3 += delay<PF_DLY>(zero);
#pragma unroll
                    for (int f = 0; f < NPF; f++) ldsm4t(wf[f], WF(f));
                } else {
                    if (s == 0) { mbar_wait_w(bars + 8 * B_WO, 0); }
                    const uint32_t need = warp0 ? min(s / 2 + 3, 32) : 0;
                    uint32_t seen = s ? lds1(sb + SM_LX + 1024 + ((g16 >> 2) & 12)) : 0;
                    const bool look = __any_sync(~0u, seen < need);
                    ldg1_if(seen, &g_tick[32 + ((g16 >> 4) & 3) * 8], look);
                    a3 = lds1(tabw + 2056 + g16);
#pragma unroll
                    for (int f = 0; f < NPF0; f++) ldsm4t(wf[f], WF(f));
                    const float2 u = lds2f(tabw + 4096 + g8);
                    const uint8_t *q0 = arena + (tag * 32768 + po + __float_as_uint(u.x)), *q1 = arena + (tag * 32768 + po + __float_as_uint(u.y));
                    wait_clk(tx + tm.h);
                    int it = 0;
                    bool bad;
#pragma unroll 1
                    do {
                        const uint4 p0 = ldg_b128(q0), p1 = ldg_b128(q1);
                        spin_guard(++it);
                        wait_clk(tx + tm.v);
#pragma unroll
                        for (int f = NPF0; f < NPF1; f++) ldsm4t(wf[f], WF(f));
                        sts4(sb + SM_PA + g16, p0.x, p0.y, p0.z, p0.w);
                        sts4(sb + SM_PA + 2048 + g16, p1.x, p1.y, p1.z, p1.w);
                        bad = any_bit0(xor_or(p0.x, p1.x, ((s + 1) >> 1) ^ 1)) && s + 2 <= NSEG;
                    } while (bad);
                    if (look) {
                        if (__any_sync(~0u, seen < need)) seen = wait_count_w(&g_tick[32 + ((g16 >> 4) & 3) * 8], need);
                        asm volatile("fence.acquire.gpu;" ::: "memory");
                        sts1(sb + SM_LX + 1024 + ((g16 >> 2) & 12), seen);
                    }
                    bar_sync(NB_H, 256);
                    softmax_rows<true>(sb + SM_ST, sb + SM_PX, g16, qd * 8, [&](uint32_t v) {
                        a3 += v & zero;
#pragma unroll
                        for (int f = NPF1; f < NPF2; f++) ldsm4t(wf[f], WF(f));
                    });
#pragma unroll
                    for (int f = NPF2; f < NPF; f++) ldsm4t(wf[f], WF(f));
                }
                float2 ls, a12;
                uint8_t *d0, *d1;
                bar_sync(NB_X2, 384);
                float c[4][4];
#pragma unroll
                for (int q = 0; q < 4; q++) {
                    uint32_t ob[4];
                    ldsm4t(ob, l16 + SM_OX + q * 512);
                    if (q == L_AT) ls = lds2f(sb + SM_LX + g8);
                    if (q == 2) { pa = lds4(sb + SM_PA + wg * 2048 + g16); wl = lds1(tabw + g16); }
                    if (q == 2) { a12 = lds2f(tabw + 2048 + g16); d0 = arena + (acc_slot(s + 1) + __float_as_uint(a12.x)); d1 = arena + (acc_slot(s + 1) + __float_as_uint(a12.y)); }
#pragma unroll
                    for (int f = 4 * q; f < 4 * q + 4; f++) {
                        const uint32_t* a = wf[f % NPF];
                        if (f < 4) mma16816z(c[f], a, ob[f & 2], ob[(f & 2) + 1]);
                        else mma16816(c[f & 3], a[0], a[1], a[2], a[3], ob[f & 2], ob[(f & 2) + 1]);
                        if (f + NPF < 16) ldsm4t(wf[f % NPF], WF(f + NPF));
                    }
                }
                if (wg == 0) bar_arrive(NB_WIN, 384);
                const float i0 = rcp_fast(ls.x), i1 = rcp_fast(ls.y);
                uint32_t v[4];
#pragma unroll
                for (int m = 0; m < 4; m++) v[m] = pack_h2((c[m >> 1][(m & 1) * 2] + c[(m >> 1) + 2][(m & 1) * 2]) * i0, (c[m >> 1][(m & 1) * 2 + 1] + c[(m >> 1) + 2][(m & 1) * 2 + 1]) * i1);
                red_h10(LAST, d0, d1, v[0], v[1], v[2], prmt(v[3], ACC_ONE, LAST ? 0x7610 : 0x3210), prmt(v[3], ACC_ONE, 0x7632));
                g16 |= v[0] & zero;
            }
        }
        if (wg) bar_sync(NB_WIN, 384);
    } else {
        auto request = [&](int s, uint32_t o) {
            cp_async16(sb + SM_PA + 4096 + g16, arena + (((s & 1) ^ 1) * 32768 + po + o));
            const uint8_t* ts = arena + ((s & 1) * 32768 + o);
#pragma unroll
            for (int i = 0; i < 4; i++) cp_async16(sb + SM_VF + i * 2048 + g16, ts + (i >> 1) * 16384 + (i & 1) * 2048);
        };
        auto fetch = [&](int s, uint4 t1, auto wait, auto after) {
            const uint32_t mo = acc_slot(s) + t1.x, eo = mo - (g16 & 0x1f0) + 512 + ((g16 >> 5) & 12);
            const uint8_t *ms = arena + mo, *es = arena + eo;
            uint32_t e[4] = {0, 0, 0, 0}, sel = LAST ? 0x5410 : 0x3210, dst[4];
#pragma unroll
            for (int i = 0; i < 4; i++) dst[i] = (t1.w + (s & 1) * HBUF) ^ (i * 32);
            asm volatile("" : "+l"(ms), "+l"(es), "+r"(e[0]), "+r"(e[1]), "+r"(e[2]), "+r"(e[3]), "+r"(sel), "+r"(dst[0]), "+r"(dst[1]), "+r"(dst[2]), "+r"(dst[3]));
            uint32_t late = wait(), fz;
            int it = 0;
            bool bad;
#pragma unroll 1
            do {
                uint4 m[4];
                uint32_t b = 0;
#pragma unroll
                for (int i = 0; i < 4; i++) {
                    m[i] = ldg_rlx4(ms + i * 1024);
                    ldg1_if(e[i], es + i * 1024, LAST);
                }
                if (it == 0) bar_arrive(NB_F, 256);
                const uint32_t now = clk32();
                fz = now;
                after(now & zero);
                sts1(sb + SM_LX + 1040, now - min(late >> 8, 8u) * 57);
                late = 0;
                spin_guard(++it);
#pragma unroll
                for (int i = 0; i < 4; i++) {
                    if (STG_FENCE >> i & 1) fz |= clk32();
                    b |= xor_or(m[i].w, e[i], ACC_ALL);
                    stsm4t(dst[i], h2bf(m[i].x), h2bf(m[i].y), h2bf(m[i].z), h2bf(prmt(m[i].w, e[i], sel)));
                }
                bad = __any_sync(~0u, LAST && b > 0xffffu);
            } while (bad);
            bar_arrive(NB_MEM, 384);
            bar_arrive(NB_MEM2, 256);
            g16 |= fz & zero;
        };
        fetch(0, lds4(tabw + 2048 + g16), []() { return 0u; }, [&](uint32_t z) { request(0, lds1(tabw + 4096 + (g16 >> 1)) + z); });
        wo_load(2);
#pragma unroll 1
        for (int s = 0;; s++) {
            const uint32_t tag = (s & 1) ^ 1, ttag = ((s >> 1) & 1) ^ 1, l16 = sb + (g16 & 0x1f0), g8 = g16 >> 1;
            const int p = s + 2;
            fence_async_smem();
            stg_b128_if(g16 < ((role & 3) ? 128 : 160), arena + (acc_slot(s + 3) + lds1(tabw + 2052 + g16)), 0, 0, 0, 0);
            const uint4 pa = pa_get(p);
            if (p <= NSEG) mbar_wait_w(bars + 8 * (B_HB + (p & 1)), (p >> 1) & 1);
            asm volatile("fence.proxy.async.global;" ::: "memory");
            if (warp0 && s + 3 <= NSEG) e_expect(bars + 8 * (B_HB + ((s + 3) & 1)), 32768);
            uint8_t* xd = arena + lds1(tabw + 4 + g16);
            uint32_t tx;
            float acc[20];
            pass_init(acc, 20, pa);
            bar_sync(NB_QK, 384);
            pass_run(IC<1>(), p, acc, nop);
            pass_out(IC<2>(), p, acc, [&](int i) {
                if (i) return;
                wg_wait<0>();
                const uint32_t r0 = pack2(acc[16], acc[17]);
                stg_rlx2(xd, settag(r0, tag), pack2(acc[18], acc[19]));
                tx = clk_after(r0, zero) + 100;
            });
            uint4 (&vf)[2][2] = tf;
#pragma unroll
            for (int i = 0; i < 4; i++) vf[i >> 1][i & 1] = lds4(sb + SM_VF + i * 2048 + g16);
            uint32_t xv[4] = {0, 0, 0, 0};
            float oc[2][4], lc[4];
            auto pv = [&](uint32_t p0, uint32_t p1, uint32_t p2, uint32_t p3, uint32_t p4, auto mid) {
                lc[0] = lc[1] = lc[2] = lc[3] = 0.f;
                mma16816z(oc[0], &vf[0][0].x, p0, p1);
                mma16816z(oc[1], &vf[1][0].x, p0, p1);
                mma16816(lc, ONES, ONES, ONES, ONES, p0, p1);
                mma16816(oc[0], vf[0][1].x, vf[0][1].y, vf[0][1].z, vf[0][1].w, p2, p3);
                mma16816(oc[1], vf[1][1].x, vf[1][1].y, vf[1][1].z, vf[1][1].w, p2, p3);
                mma16816(lc, ONES, ONES, ONES, ONES, p2, p3);
                mid();
                mma1688(oc[0], xv[0], xv[1], p4);
                mma1688(oc[1], xv[2], xv[3], p4);
                mma1688(lc, ONES, ONES, p4);
            };
            uint32_t so, to, fz = 0;
            uint4 t1;
            int it = 0;
            bool bad;
#pragma unroll 1
            do {
#pragma unroll 1
                for (int i = it; i > 0; i &= zero) load_tok(s, lds1(tabw + 4096 + g8));
                u64 xr[4];
                const uint8_t* xp = arena + lds1(tabw + 8 + g16);
                asm volatile("" : "+l"(xp));
                const uint32_t bt = or3(xor_or(vf[0][0].x, vf[0][1].x, ttag), xor_or(vf[1][0].x, vf[1][1].x, ttag), 0);
                uint32_t sa = sb + SM_SX + (g16 & 0x1f0) * 5;
                asm volatile("" : "+r"(sa));
                spin_guard(it);
                wait_clk(tx);
                if (it++ == 0) bar_sync(NB_X1, 256);
                uint4 sx[5];
#pragma unroll
                for (int i = 0; i < 5; i++) sx[i] = lds4(sa + i * 16);
                __syncwarp();
#pragma unroll
                for (int i = 0; i < 4; i++) xr[i] = ldg_u64(xp + (VP_AT == 2 ? sx[0].x & zero : 0) + i * 1024);
                uint32_t a[5], pm[5];
#pragma unroll
                for (int n = 0; n < 5; n++) {
                    uint32_t u[4];
#pragma unroll
                    for (int w = 0; w < 4; w++) u[w] = n < 4 ? (&sx[w].x)[n] : (&sx[4].x)[w];
                    a[n] = hadd2h(hadd2h(u[0], u[1]), hadd2h(u[2], u[3]));
                }
                uint32_t m = hmax2h(hmax2h(hmax2h(a[0], a[1]), hmax2h(a[2], a[3])), a[4]);
                const uint32_t m1 = __shfl_xor_sync(~0u, m, 1), m2 = __shfl_xor_sync(~0u, m, 2), m3 = __shfl_xor_sync(~0u, m, 3);
                m = hmax2h(hmax2h(m, m1), hmax2h(m2, m3));
                so = lds1(tabw + g16); t1 = lds4(tabw + 2048 + g16); to = lds1(tabw + 4096 + g8);
                const float2 mm = unpack_h2(m);
                const float mf = -SM_L2E * fmaxf(mm.x, mm.y);
#pragma unroll
                for (int n = 0; n < 5; n++) { const float2 u = unpack_h2(a[n]); pm[n] = pack2(ex2(fmaf(u.x, SM_L2E, mf)), ex2(fmaf(u.y, SM_L2E, mf))); }
                pv(pm[0], pm[1], pm[2], pm[3], pm[4], [&]() {
                    if (PV_FENCE & 1) fz = clk32();
#pragma unroll
                    for (int i = 0; i < 2; i++) { xv[2 * i] = hadd2v(lo32(xr[2 * i]), lo32(xr[2 * i + 1])); xv[2 * i + 1] = hadd2v(hi32(xr[2 * i]), hi32(xr[2 * i + 1])); }
                });
                bad = any_bit0(or3(bt, xor_or(lo32(xr[0]), lo32(xr[1]), tag), xor_or(lo32(xr[2]), lo32(xr[3]), tag)));
                if (PV_FENCE & 2) fz |= clk32();
                stsm4(sb + SM_OX + g16, pack2(oc[0][0], oc[0][1]), pack2(oc[0][2], oc[0][3]), pack2(oc[1][0], oc[1][1]), pack2(oc[1][2], oc[1][3]));
                sts2(sb + SM_LX + g8, lc[0], lc[1]);
            } while (bad);
            bar_sync(NB_X2, 384);
            const uint8_t* sp = arena + so;
            uint4 sv = ldg_rlx4(sp);
            if (s + 3 <= NSEG) h_load(sb, hsrc, s + 3, j, head, wiu, false);
            const uint4 pp = lds4(l16 + SM_PX + delay<TPV_DLY>(zero));
            pv(pp.x, pp.y, pp.z, pp.w, lds1(sb + SM_PX + 512 + ((g16 >> 2) & 0x7c)), []() {});
            const float i0 = rcp_fast(lc[0]), i1 = rcp_fast(lc[1]);
            bar_arrive(NB_WIN + ((__float_as_uint(i0) | fz) & zero), 384);
            uint8_t* od = (uint8_t*)g_O + ((size_t)s * (32 * NH * DH * 2) + t1.z);
            const uint32_t ov[4] = {pack2(oc[0][0] * i0, oc[0][1] * i1), pack2(oc[0][2] * i0, oc[0][3] * i1), pack2(oc[1][0] * i0, oc[1][1] * i1), pack2(oc[1][2] * i0, oc[1][3] * i1)};
#pragma unroll
            for (int a = 0; a < 4; a++) if (s + 1 == NSEG) stg_rlx1(od + a * 128, ov[a]);
            if (s + 1 == NSEG) break;
            fetch(s + 1, t1, [&]() {
                int it = 0;
#pragma unroll 1
                while (__any_sync(~0u, (int)(min(__vimin3_u32(sv.x, sv.y, sv.z), sv.w) >> 24) <= s)) {
                    sv = ldg_rlx4(sp);
                    spin_guard(++it);
                }
                const uint32_t tgo = (__reduce_max_sync(~0u, max(max3u(sv.x, sv.y, sv.z), sv.w)) + tm.go + (sv.x & zero)) << 8;
                int late;
#pragma unroll 1
                do { late = gtime32() * 8 - tgo; } while (late < 0);
                __syncwarp();
                return (uint32_t)late;
            }, [&](uint32_t z) {
#pragma unroll
                for (int a = 0; a < 4; a++) stg_rlx1(od + a * 128, ov[a]);
                request(s + 1, to + z);
            });
        }
    }
    asm volatile("cp.async.wait_all;" ::: "memory");
}

struct RecMaps { CUtensorMap wq, wk, wv, wo; };
struct RecPtrs { const bf16 *x, *mem0, *c, *wmod, *w1, *w3; uint8_t* arena; uint32_t zero; RecTime tm; };

__device__ __forceinline__ float silu_bf(const bf16* c, int i) {
    const float v = __bfloat162float(c[i]);
    return bfround(__fdividef(v, 1.0f + __expf(-v)));
}
__device__ __noinline__ void rec_ln(float* coef, const RecPtrs& p, int id, int r0) {
    int r1 = 32;
    const int tid = threadIdx.x;
    const int lane = tid & 31, wid = tid >> 5;
    const uint32_t ring = smem_u32(coef) - SM_PRE + wid * 8192 + lane * 16;
    auto fetch = [&](int r) {
        if (r < r1) {
            const bf16* src = p.x + (size_t)(r * 64 + (id * 8 + wid) * 2) * DM + lane * 8;
#pragma unroll
            for (int i = 0; i < 8; i++) cp_async16(ring + (r & 1) * 4096 + i * 512, src + i * 256);
        }
        asm volatile("cp.async.commit_group;" ::: "memory");
    };
    auto row8 = [&](uint32_t a, float* f) {
        const uint4 v = lds4(a);
        f[0] = bflo(v.x); f[1] = bfhi(v.x); f[2] = bflo(v.y); f[3] = bfhi(v.y); f[4] = bflo(v.z); f[5] = bfhi(v.z); f[6] = bflo(v.w); f[7] = bfhi(v.w);
    };
#pragma unroll 1
    for (int r = r0 - 2; r < r1; r++) {
        if (r >= r0) {
            asm volatile("cp.async.wait_group 1;" ::: "memory");
            const uint32_t a = ring + (r & 1) * 4096;
            float m[2] = {0.f, 0.f}, t[2];
#pragma unroll 1
            for (int ps = 0; ps < 2; ps++) {
                t[0] = t[1] = 0.f;
#pragma unroll 1
                for (int i = 0; i < 4; i++)
#pragma unroll
                    for (int h = 0; h < 2; h++) {
                        float f[8];
                        row8(a + h * 2048 + i * 512, f);
#pragma unroll
                        for (int e = 0; e < 8; e++) { const float d = f[e] - m[h]; t[h] = fmaf(d, ps ? d : 1.0f, t[h]); }
                    }
#pragma unroll
                for (int o = 16; o; o >>= 1) { t[0] += __shfl_xor_sync(~0u, t[0], o); t[1] += __shfl_xor_sync(~0u, t[1], o); }
                if (ps == 0) { m[0] = t[0] * (1.0f / DM); m[1] = t[1] * (1.0f / DM); }
            }
            t[0] = rsqrtf(t[0] * (1.0f / DM) + 1e-5f); t[1] = rsqrtf(t[1] * (1.0f / DM) + 1e-5f);
            if (r == r0) {
#pragma unroll 1
                for (int i = tid; i < 2 * DM / 4; i += 256) {
                    float4 u;
                    int it = 0;
                    uint32_t ok;
#pragma unroll 1
                    do {
                        uint4 v[8];
#pragma unroll
                        for (int k = 0; k < 8; k++) v[k] = ldg_rlx4(g_modp + k * 2 * DM + i * 4);
                        ok = 1;
                        u = make_float4(0.f, 0.f, 0.f, 0.f);
#pragma unroll
                        for (int k = 0; k < 8; k++) {
                            ok &= v[k].x & v[k].y & v[k].z & v[k].w;
                            u.x += __uint_as_float(v[k].x); u.y += __uint_as_float(v[k].y); u.z += __uint_as_float(v[k].z); u.w += __uint_as_float(v[k].w);
                        }
                        spin_guard(++it);
                    } while (!ok);
                    const uint32_t lo = pack2(u.x, u.y), hi = pack2(u.z, u.w);
                    const float one = i >= DM / 4 ? 1.0f : 0.0f;
                    *(float4*)(coef + i * 4) = make_float4(bflo(lo) + one, bfhi(lo) + one, bflo(hi) + one, bfhi(hi) + one);
                }
                bar_sync(NB_FIN0, 256);
            }
            const int row = r * 64 + (id * 8 + wid) * 2;
#pragma unroll 1
            for (int i = 0; i < 4; i++) {
                const float4* cf = (const float4*)(coef + i * 256 + lane * 8);
                const float4 s0 = cf[0], s1 = cf[1], c0 = cf[256], c1 = cf[257];
                const float sh[8] = {s0.x, s0.y, s0.z, s0.w, s1.x, s1.y, s1.z, s1.w}, sc[8] = {c0.x, c0.y, c0.z, c0.w, c1.x, c1.y, c1.z, c1.w};
                const int own = ((row >> 4) & 1) == (i >> 1), rr = row & 15;
                const uint32_t off = ((row >> 5) + own) * 65536 + (i * 4 + (lane >> 3)) * 4096 + (rr + (own ? 0 : 16)) * 128 + (((lane & 7) ^ (rr & 7)) << 4);
#pragma unroll
                for (int h = 0; h < 2; h++) {
                    float y[8];
                    row8(a + h * 2048 + i * 512, y);
#pragma unroll
                    for (int e = 0; e < 8; e++) y[e] = fmaf((y[e] - m[h]) * t[h], sc[e], sh[e]);
                    *(uint4*)((uint8_t*)g_himg + (off ^ (h * 144))) = pack8(y);
                }
            }
            if (r == 0) {
                int v, it = 0;
#pragma unroll 1
                do { v = *(volatile int*)((uint8_t*)coef - SM_PRE + SM_BAR + 192); spin_guard(++it); } while (v == INT_MIN);
                if (v >= 0) r1 = 2;
            }
        }
        fetch(r + 2);
        if (r < r0) continue;
        bar_sync(r == 0 ? NB_C : r == 1 ? NB_FIN0 : NB_LN, r == 0 ? 320 : r == 1 ? 256 : 288);
        if (r < 2 && wid == r) {
            if (r == 1) bar_arrive(NB_B, 64);
            if (lane == 0) { signal_count(&g_tick[32 + id * 8]); }
            __syncwarp();
        }
    }
}
template <int NQ, int CG>
__device__ __forceinline__ void side_gemv(const bf16* w, int ld, int ncol, const float* coef, float* red, float* out, int ostride, bool round) {
    constexpr int KG = 384 / CG, W = CG * 8;
    const int tid = threadIdx.x, cg = tid % CG, kg = tid / CG;
    float acc[NQ][8];
#pragma unroll
    for (int q = 0; q < NQ; q++)
#pragma unroll
        for (int j = 0; j < 8; j++) acc[q][j] = 0.f;
    if (cg * 8 < ncol) {
        const bf16* src = w + cg * 8;
        const uint32_t ring = smem_u32(red) + 36864 + tid * 16;
        auto fetch = [&](int k0, int slot) {
#pragma unroll
            for (int i = 0; i < 4; i++)
                if (k0 + i * KG < DM) cp_async16_ef(ring + (slot * 4 + i) * 6144, src + (size_t)(k0 + i * KG) * ld);
            asm volatile("cp.async.commit_group;" ::: "memory");
        };
#pragma unroll 1
        for (int g = 0; g < 5; g++) fetch(kg + g * 4 * KG, g);
#pragma unroll 1
        for (int k0 = kg, slot = 0; k0 < DM; k0 += 4 * KG) {
            fetch(k0 + 20 * KG, slot ? slot - 1 : 5);
            asm volatile("cp.async.wait_group 5;" ::: "memory");
#pragma unroll
            for (int i = 0; i < 4; i++) {
                const int k = k0 + i * KG;
                if (k < DM) {
                    const uint4 v = lds4(ring + (slot * 4 + i) * 6144);
                    const float f[8] = {bflo(v.x), bfhi(v.x), bflo(v.y), bfhi(v.y), bflo(v.z), bfhi(v.z), bflo(v.w), bfhi(v.w)};
#pragma unroll
                    for (int q = 0; q < NQ; q++) {
                        const float cf = coef[q * DM + k];
#pragma unroll
                        for (int j = 0; j < 8; j++) acc[q][j] = fmaf(cf, f[j], acc[q][j]);
                    }
                }
            }
            slot = slot == 5 ? 0 : slot + 1;
        }
    }
    __syncthreads();
#pragma unroll
    for (int q = 0; q < NQ; q++)
#pragma unroll
        for (int j = 0; j < 8; j++) red[(kg * NQ + q) * W + cg * 8 + j] = acc[q][j];
    __syncthreads();
#pragma unroll 1
    for (int i = tid; i < NQ * W; i += 384) {
        const int q = i / W, cidx = i % W;
        float t = 0.f;
#pragma unroll
        for (int k = 0; k < KG; k++) t += red[k * NQ * W + i];
        if (cidx < ncol) out[q * ostride + cidx] = round ? bfround(t) : t;
    }
}
__device__ __noinline__ void rec_side(float* sm, const RecPtrs& p, int id) {
    const int tid = threadIdx.x;
    float *coef = sm, *red = sm + 3 * DM;
    if (tid < 256 && blockIdx.x < 128) rec_ln(sm + SM_PRE / 4, p, id, 2);
    if (tid >> 5 == 8) {
#pragma unroll 1
        for (int n = 1; n < 31; n++) {
            bar_sync(NB_LN, 288);
            if (tid == 256) { if (n == 1) wait_count1(&g_tick[32 + id * 8], 2); signal_count(&g_tick[32 + id * 8]); }
            __syncwarp();
        }
    }
    __syncthreads();
    for (int i = tid; i < 2 * S_; i += 384) g_st[id * 2 * S_ + i] = 0.f;
    if (id == 0) for (int i = tid; i < 2 * 32; i += 384) g_pcnt[i * 8] = 0;
    if (id == 1) for (int i = tid; i < 6 * 256; i += 384) g_pflag[i] = 0;
    for (int i = tid; i < DM; i += 384) { coef[i] = silu_bf(p.c, i); coef[2 * DM + i] = 1.0f; }
    __syncthreads();
    side_gemv<1, 128>(p.wmod + (2 + id) * DM, 6 * DM, DM, coef, red, g_mod + (2 + id) * DM, 0, true);
    __syncthreads();
    if (tid == 0) signal_count(&g_tick[8]);
    side_gemv<1, 128>(p.w3 + id * (FF / 4), FF, FF / 4, coef + 2 * DM, red, g_vec + 3 * DM + id * (FF / 4), 0, false);
    if (tid == 0) wait_count1(&g_tick[8], 4);
    __syncthreads();
    for (int i = tid; i < DM; i += 384) { coef[i] = 1.0f + __ldcg(g_mod + 4 * DM + i); coef[DM + i] = __ldcg(g_mod + 3 * DM + i); }
    __syncthreads();
    if (id == 1 && tid < 32) {
        float t[5] = {0, 0, 0, 0, 0};
        for (int i = tid; i < DM; i += 32) {
            const float a = coef[i], b = coef[DM + i];
            t[0] += a; t[1] += a * a; t[2] += a * b; t[3] += b; t[4] += b * b;
        }
#pragma unroll
        for (int q = 0; q < 5; q++) { const float r = warp_sum(t[q]); if (tid == 0) g_cst[q] = r * (1.0f / DM); }
    }
    side_gemv<3, 32>(p.w1 + id * 256, DM, 256, coef, red, g_vec + id * 256, DM, false);
}

__device__ __forceinline__ void pair_place(int c, int& d, int& pi) {
    const int c7 = ((c - 36) * 37) >> 8;
    d = c < 4 ? 0 : c < 36 ? (c - 4) & 7 : c - 35 - 7 * c7;
    pi = c < 4 ? c : c < 36 ? ((c - 4) >> 3) + (d ? 0 : 4) : 4 + c7;
}
__global__ void __cluster_dims__(2, 1, 1) __launch_bounds__(384, 1)
k_rec(const __grid_constant__ RecMaps mp, const __grid_constant__ RecPtrs p) {
    extern __shared__ uint8_t smraw[];
    const uint32_t sb = smem_u32(smraw);
    if ((sb & 0x3FFFF) != SB0) __trap();
    const uint32_t bars = sb + SM_BAR;
    const int tid = threadIdx.x, lane = tid & 31, b = blockIdx.x;
    const int wid = __reduce_max_sync(~0u, tid >> 5);
    const uint32_t rank = b & 1;
    uint8_t* arena = p.arena;
    volatile int* sinfo = (volatile int*)(smraw + SM_BAR + 192);
    if (tid == 0) sinfo[0] = INT_MIN;
    uint32_t smid;
    asm("mov.u32 %0, %%smid;" : "=r"(smid));
    smid = __reduce_max_sync(~0u, smid);
    int d, pi;
    pair_place(smid >= 124 ? (smid >> 1) - 62 : (smid >> 1) + 4, d, pi);
    const int guess = b < 128 && smid < 132 && (smid & ~3u) != 120 && (NO_GUESS % 5 == 0 || (NO_GUESS == 2 && b != 20)) ? d * 8 + pi : -9;
    if (wid == 8) {
        if (lane == 0) {
#pragma unroll
            for (int i = 0; i < 17; i++) mbar_init(bars + 8 * i, i == B_WO ? 4 : 1);
            asm volatile("fence.mbarrier_init.release.cluster; fence.proxy.async.shared::cta;" ::: "memory");
            mbar_expect(bars + 8 * B_ROLE, 8);
        }
        __syncwarp();
    }
    asm volatile("barrier.cluster.arrive.relaxed.aligned;" ::: "memory");
    int pr = 0, hA = 0;
    if (wid < 8) {
        if (b < 128) {
            const int cb = (b & 15) * 128, k0 = (b >> 4) * 128 + (tid >> 4);
            uint4 v[8];
#pragma unroll
            for (int i = 0; i < 8; i++) v[i] = __ldg((const uint4*)(p.wmod + (size_t)(k0 + 16 * i) * (6 * DM) + cb + (tid & 15) * 8));
            float acc[8] = {0, 0, 0, 0, 0, 0, 0, 0};
            const float sl = silu_bf(p.c, k0 + 16 * (lane & 7));
#pragma unroll
            for (int i = 0; i < 8; i++) {
                const float sv = __shfl_sync(~0u, sl, i, 16);
                acc[0] += sv * bflo(v[i].x); acc[1] += sv * bfhi(v[i].x); acc[2] += sv * bflo(v[i].y); acc[3] += sv * bfhi(v[i].y);
                acc[4] += sv * bflo(v[i].z); acc[5] += sv * bfhi(v[i].z); acc[6] += sv * bflo(v[i].w); acc[7] += sv * bfhi(v[i].w);
            }
            float* red = (float*)(smraw + SM_PRE);
            *(float4*)(red + (tid >> 4) * 128 + (tid & 15) * 8) = make_float4(acc[0], acc[1], acc[2], acc[3]);
            *(float4*)(red + (tid >> 4) * 128 + (tid & 15) * 8 + 4) = make_float4(acc[4], acc[5], acc[6], acc[7]);
            bar_sync(NB_FIN0, 256);
            if (wid < 4) {
                float t = 0;
#pragma unroll
                for (int i = 0; i < 16; i++) t += red[i * 128 + tid];
                stg_rlx1(&g_modp[(b >> 4) * 2 * DM + cb + tid], __float_as_uint(t) | 1u);
            }
        } else {
            rec_ln((float*)(smraw + SM_PRE), p, b - 128, 0);
        }
    } else if (wid >= 10 && b >= 128) {
        {
            const int u = (b - 128) * 2 + wid - 10;
            const uint16_t* src = (const uint16_t*)p.mem0 + (lane & 3) * 2 * DM + (u >> 1) * 128 + (u & 1) * 32 + (lane >> 2);
            stg_rlx4(arena + (LB_STAMP << 13) + u * 2048 + (lane >> 4) * 1024 + ((lane >> 3) & 1) * 256 + (lane & 7) * 16, 0, 0, 0, 0);
#pragma unroll 1
            for (int r = 0; r < 4; r++) {
                uint32_t w[5];
#pragma unroll
                for (int e = 0; e < 4; e++) {
                    const uint16_t* q = src + (r >> 1) * 512 + (r & 1) * 16 + (e & 2) * 32 + (e & 1) * 8;
                    w[e] = pack_h2(bflo(q[0]), bflo(q[DM]));
                }
                w[4] = __shfl_sync(~0u, __byte_perm(w[3], ACC_ALL, 0x7632), lane * 8 + 7);
                w[3] = __byte_perm(w[3], ACC_ALL, (lane & 7) == 7 ? 0x7610 : 0x3210);
#pragma unroll 1
                for (int i = 0; i < 3; i++) {
                    uint8_t* d = arena + acc_slot(i) + acc_piece(r >> 1, u >> 1, (u & 1) * 2 + (r & 1));
                    stg_rlx4(d + lane * 16, w[0], w[1], w[2], w[3]);
                    if (lane < 8) stg_rlx1(d + 512 + lane * 4, w[4]);
                    w[0] = w[1] = w[2] = w[3] = w[4] = 0;
                }
            }
            bar_arrive(NB_C, 320);
        }
    } else if (rank == 0 && (wid > 8 || b >= 128)) {
        uint32_t best = ~0u;
        const int pg = wid < 11 ? 0 : 1 + (b >> 1) % 3;
        uint32_t* q = (uint32_t*)(arena + (pg << 21) + (pg ? blk(b >> 1, 1) : blk(LB_PROBE, wid & 1) + b * 16));
        if (lane < 8) stg_rlx1(q + lane, 0);
        u64 tk2 = ldg_u64(&g_tick[0]);
        __syncwarp();
        if (lane == 0) {
            q += 3;
            uint32_t v = atomicAdd(q, 1u);
#pragma unroll 1
            for (int r = 0; r < NPROBE; r++) {
                const uint32_t t0 = clk32() + (v >> 8);
                v = atomicAdd(q + (v >> 8), 1u);
                uint32_t t1;
                asm volatile("{.reg .pred p; setp.eq.u32 p, %1, 0xffffffff; @p exit; mov.u32 %0, %%clock;}" : "=r"(t1) : "r"(v) : "memory");
                best = min(best, t1 - t0);
            }
            sinfo[pg ? 4 : 2 + (wid & 1)] = best;
        }
        bar_sync(NB_KDONE, b < 128 ? 96 : 64);
        if (wid == 9) {
            const int par = (sinfo[2] > sinfo[3]) ^ (NO_GUESS == 5 && smid == 126), ncl = gridDim.x >> 1;
            const bool ok = guess >= 0 && !(smid & 1), reg = ok && guess >= 4;
            u64 add = (1u << (8 * par)) + 65536 + (reg ? 1ull << 24 : (1ull << (56 + 4 * par)) + ((u64)ok << 37));
            if (b < 128) add += (u64)((2 * sinfo[4] < sinfo[2] + sinfo[3]) != par) << (32 + 8 * ((b >> 1) % 3));
            int it = 0;
            if (NO_GUESS % 5 >= 3 ? b < 2 * (NO_GUESS - 2) || (NO_GUESS == 3 && b == 130) : b >= 128) {
#pragma unroll 1
                while (!__all_sync(~0u, (int)((lo32(tk2) >> 16) & 255) >= ncl - 2)) { tk2 = ldg_u64(&g_tick[0]); spin_guard(++it); }
            }
            if (lane == 0) {
                if (guess >= 0) add += atomicXor(&g_tick[2], par << (guess >> 1)) & p.zero;
                add = atomicAdd((u64*)&g_tick[0], add);
            }
#pragma unroll 1
            while (!__all_sync(~0u, (int)((lo32(tk2) >> 16) & 255) >= ncl)) { tk2 = ldg_u64(&g_tick[0]); spin_guard(++it); }
            add = __shfl_sync(~0u, add, 0);
            const uint32_t diff = ldg_rlx1(&g_tick[2]);
            const bool most = lo32(tk2) >> 24 == 60 && diff < 4;
            const int nh = most ? 2 : NH, sh = most ? 56 : 0, w = most ? 4 : 8, mk = (1 << w) - 1;
            const int n0 = (tk2 >> sh) & mk, n1 = (tk2 >> (sh + w)) & mk, tk = (add >> (sh + w * par)) & mk;
            hA = min(n0 >> 1, nh);
            const int q0 = 2 * hA, q1 = 2 * nh - q0;
            const int over = tk - (par ? q1 : q0), lack = max(par ? q0 - n0 : q1 - n1, 0);
            if (over < 0) pr = par ? q0 + tk : tk;
            else if (over < lack) pr = (par ? n0 : q0 + n1) + over;
            else pr = -1 - (over - lack + (par ? max(n0 - q0, 0) : 0));
            if (most && (reg || (!diff && (hi32(tk2) & 0xe0) == 0x80))) { pr = guess; hA = par ? 0 : NH; }
#pragma unroll
            for (int i = 0; i < 3; i++) hA |= ((hi32(tk2) >> (8 * i)) & 31) > 10 ? 256 << i : 0;
        }
    }
    asm volatile("barrier.cluster.wait.aligned;" ::: "memory");
    if (wid == 9 && rank == 0) {
        asm volatile("{.reg .pred p; .reg .b32 a; setp.lt.u32 p, %3, 2; @p mapa.shared::cluster.u32 a, %0, %3;\n"
                     " @p st.async.shared::cluster.mbarrier::complete_tx::bytes.v2.u32 [a + 192], {%1, %2}, [a + %4];}"
                     ::"r"(bars), "r"(pr), "r"(hA), "r"(lane), "n"(8 * B_ROLE) : "memory");
        if (b >= 128) atomicOr(&g_tick[4], (pr < 0 ? 4u : 1u) << ((b - 128) >> 1));
    }
    if (wid == 8) {
        int pu = guess;
        bool fast = false, known = false;
        wait_clk(clk32() + W_T0 + (lane & p.zero));
#pragma unroll 1
        for (int n = 0; n < 12; n++) {
            if (!known && (n == W_SPEC || pu < 0)) {
                mbar_wait_w(bars + 8 * B_ROLE, 0);
                known = true;
                const int r = __reduce_max_sync(~0u, sinfo[0]);
                if (r != pu) {
#pragma unroll 1
                    for (; n > 0; n--) {
                        mbar_wait_w(bars + 8 * (B_W + n - 1), 0);
                        asm volatile("{.reg .pred p; elect.sync _|p, 0xffffffff; @p mbarrier.arrive.shared.b64 _, [%0];}" ::"r"(bars + 8 * (B_W + n - 1)) : "memory");
                    }
                    pu = r;
                    fast = r < 4;
                }
                bar_arrive(NB_A, 384);
                if (b >= 128 && pu < 0) bar_sync(NB_B, 64);
                if (pu < 0) break;
            }
            const int rot = b >= 128 ? 8 : 0, i = (n + rot) % 12;
            if (rot && n == 4) bar_sync(NB_B, 64);
            if (n >= W_INFL && !fast) {
                const uint32_t v = ldg_rlx1(&g_tick[32 + (lane & 3) * 8]);
                mbar_wait_w(bars + 8 * (B_W + (n - W_INFL + rot) % 12), 0);
                fast = __all_sync(~0u, v != 0);
            }
            const int m = i < 8 ? i & 1 : 2, k = i < 8 ? i >> 1 : i - 8, c0 = (pu >> 1) * 128 + rank * 64, r0 = (pu & 1) * 512;
            const uint32_t dst = sb + m * 65536 + k * 16384, br = bars + 8 * (B_W + i);
            e_expect(br, 16384);
            e_tma2d_ef(dst, &mp.wq + m, c0, r0 + k * 128, br);
            e_tma2d_ef(dst + 8192, &mp.wq + m, c0, r0 + k * 128 + 64, br);
        }
    } else {
        bar_sync(NB_A, 384);
    }
    const int prr = __reduce_max_sync(~0u, sinfo[0]);
    hA = __reduce_max_sync(~0u, sinfo[1]);
    if (prr < 0) {
        int j = (b - 128) >> 1;
        if (b < 128) {
            uint32_t v;
            int it = 0;
#pragma unroll 1
            do { v = __reduce_max_sync(~0u, ldg_rlx1(&g_tick[4])); spin_guard(++it); } while (__popc(v) < 2);
            j = v == 3 ? -1 - prr : (v & 1) ^ 1;
        }
        rec_side((float*)smraw, p, j * 2 + rank);
        return;
    }
    const int role = (prr >> 1) * 4 + rank * 2 + (prr & 1);
    rec_main(sb, &mp.wo, arena, role, hA, wid >> 2, p.zero, p.tm);
}

__device__ __forceinline__ void wgmma_ss192(float* d, uint64_t a, uint64_t b, int sc) {
    asm volatile("{.reg .pred p; setp.ne.b32 p, %98, 0;\n wgmma.mma_async.sync.aligned.m64n192k16.f32.bf16.bf16 "
                 "{%0,%1,%2,%3,%4,%5,%6,%7,%8,%9,%10,%11,%12,%13,%14,%15,%16,%17,%18,%19,%20,%21,%22,%23,%24,%25,%26,%27,%28,%29,%30,%31,%32,%33,%34,%35,%36,%37,%38,%39,%40,%41,%42,%43,%44,%45,%46,%47,%48,%49,%50,%51,%52,%53,%54,%55,%56,%57,%58,%59,%60,%61,%62,%63,%64,%65,%66,%67,%68,%69,%70,%71,%72,%73,%74,%75,%76,%77,%78,%79,%80,%81,%82,%83,%84,%85,%86,%87,%88,%89,%90,%91,%92,%93,%94,%95}, %96, %97, p, 1, 1, 0, 1;}"
                 : F16(d, 0), F16(d, 16), F16(d, 32), F16(d, 48), F16(d, 64), F16(d, 80) : "l"(a), "l"(b), "r"(sc));
}

constexpr uint32_t P_B = 81920, P_PLANE = 40960, P_VEC = 212992, P_ROW = P_VEC + 6144, P_BAR = P_ROW + 4096, P_SMEM = P_BAR + 256;
constexpr uint32_t P_OUT = 180224, P_OUT3 = P_B + 2 * P_PLANE;
constexpr int E0 = 2;
constexpr int SL_B0 = 0x2222;
constexpr int SL_B1 = 0x8888;
constexpr int SL_C = 0x11110;
constexpr int SL_A0 = 0x5494;
constexpr int SL_A1 = 0x2929;
constexpr int X_DLY = 4000;
constexpr int P_ST = 5, P_ST0 = 4;
constexpr int PB_F = 0, PB_E = 5, PB_X = 10, PB_P = 12, PB_OUT = 14;
enum { C_Y = 0, C_G = 1, C_X1 = 2, C_U = 3, C_S1 = 8, C_S3 = 9 };
enum { V_GA = 0, V_A = 1, V_B = 2, V_GB = 3, V_VA = 4, V_VB = 5, V_VC = 6, V_C3 = 7 };
struct PostMaps { CUtensorMap o, wo, y, w1, g, w2, x1, w3, u, w4, out, x; };

struct GeluK { float k0, k1, kh; };
__device__ __forceinline__ GeluK gelu_k(float c) { return {0.7978845608028654f * c, 0.7978845608028654f * 0.044715f * c * c * c, 0.5f * c}; }
__device__ __forceinline__ float gelu_s(float t, const GeluK& k) {
    const float u = t * fmaf(t * t, k.k1, k.k0);
    float th; asm("tanh.approx.f32 %0, %1;" : "=f"(th) : "f"(u));
    const float hx = k.kh * t;
    return fmaf(hx, th, hx);
}
__device__ __forceinline__ float2 ldsv(uint32_t a) {
    float2 v; asm("ld.shared.v2.f32 {%0,%1}, [%2];" : "=f"(v.x), "=f"(v.y) : "r"(a)); return v;
}
__device__ __forceinline__ void wait_smem(uint32_t a, int target) {
    int it = 0;
#pragma unroll 1
    while (true) {
        int v;
        asm volatile("ld.acquire.cta.shared.u32 %0, [%1];" : "=r"(v) : "r"(a) : "memory");
        if (__all_sync(~0u, v >= target)) break;
        spin_guard(++it);
    }
}

struct Pipe { int st, ph; };
__device__ __forceinline__ void adv(Pipe& p) { if (++p.st == P_ST) { p.st = 0; p.ph ^= 1; } }
__device__ __forceinline__ int u_col(int r, int nb) { return r ? 512 + r * 1024 + nb * 128 : nb * 192; }

template <bool A>
__device__ __forceinline__ void post_produce(uint32_t sb, const PostMaps& mp, int mb, int nb, int rank) {
    const int rh = 2 * mb + rank, lane = threadIdx.x & 31;
    const uint32_t full = sb + P_BAR + 8 * PB_F, empty = sb + P_BAR + 8 * PB_E;
    Pipe p = {(P_ST0 + E0) % P_ST, !E0};
#pragma unroll 1
    for (int ph = 0; ph < 9; ph++) {
        const int GS = ph == 0 ? 8 : ph == 6 ? 3 : 2, kb0 = ph < 7 ? 0 : ph * 16 - 88;
        const CUtensorMap* tm = &mp.o + 2 * (ph < 3 ? ph : ph < 6 ? 3 : 4) + !A;
        const bool own = ph == 1 || ph == 3;
        const int n0 = ph >= 3 && ph < 6 ? u_col(ph - 3, nb) : nb * 128;
        const int amul = ph == 0 ? 256 : 64, arow = ph == 0 ? rh * 8 : rh * 64;
        const int wr = ph == 2 ? min(max(rh + min(lane >> 3, 2) - 1, 0), 31) : rh;
        const uint32_t* fl = &g_pflag[(ph < 3 ? ph - 1 : ph < 6 ? C_X1 : ph - 3) * 256 + wr * 8 + (lane & 7)];
        uint32_t have = ph == 0 || ph == 5 ? ~0u : 0u;
#pragma unroll 1
        for (int q = 0; q < 8; q++) {
            const int src = own && q < 2 ? nb ^ q : (q + (ph >= 1 && ph <= 3 ? nb & 6 : 0)) & 7;
            const bool skip = own && q == 0, both = own && q == 1;
            const uint32_t need = q < 2 && own ? 0 : (ph == 2 ? 0x10101 : 1) << src;
            if (A && both) {
                int it = 0;
                uint32_t ok;
#pragma unroll 1
                do {
                    asm volatile("{.reg .pred p; mbarrier.try_wait.parity.acquire.cluster.shared::cta.b64 p, [%1], %2; selp.u32 %0, 1, 0, p;}" : "=r"(ok) : "r"(sb + P_BAR + 8 * PB_P), "r"(ph >> 1) : "memory");
                    spin_guard(++it);
                } while (!__all_sync(~0u, ok));
                asm volatile("fence.proxy.async.global;" ::: "memory");
            }
            if (A && (have & need) != need) {
                int it = 0;
#pragma unroll 1
                do {
                    uint32_t v;
                    asm volatile("ld.acquire.gpu.global.u32 %0, [%1];" : "=r"(v) : "l"(fl) : "memory");
                    have = __ballot_sync(~0u, v != 0);
                    spin_guard(++it);
                } while ((have & need) != need);
                asm volatile("fence.proxy.async.global;" ::: "memory");
            }
            if (!A && q == 1 && (ph == 1 || ph == 2)) {
#pragma unroll 1
                for (int i = 0; i <= ph; i++)
                    asm volatile("{.reg .pred p; elect.sync _|p, 0xffffffff; @p cp.async.bulk.prefetch.tensor.2d.L2.global [%0, {%1, %2}];}"
                                 ::"l"(tm + 2), "r"((nb * (ph + 1) + i) * 64), "r"(mb * 64) : "memory");
            }
            if (!A && ph == 3 && q == 1) wait_smem(sb + P_BAR + 8 * (PB_OUT + (lane & 1)), 3);
            const int row = arow + (ph == 2 ? (int)((0x04000301u >> ((src & 6) * 4)) & 7) - 2 : 0);
            const uint32_t bytes = (skip ? 16384 : 32768) + (ph == 3 ? 8192 : 0);
            if ((ph | q) == 0) asm volatile("barrier.cluster.wait.aligned;" ::: "memory");
            if (A && (ph | q) == 0) asm volatile("griddepcontrol.wait;" ::: "memory");
#pragma unroll 1
            for (int e = kb0 + (src + 1) * GS, kb = e - GS + (ph | q ? 0 : E0); kb < e; kb++) {
                const uint32_t f = full + 8 * p.st;
                if (!(A && skip)) mbar_wait_w(empty + 8 * p.st, p.ph ^ 1);
                if (A) {
                    const uint32_t a = sb + p.st * 16384 + rank * 8192;
                    if (both) { e_tma2d_ef(a, tm, kb * 64, row, f); e_tma2d_ef(a + 8192 - rank * 16384, tm, kb * 64, row ^ 64, f); }
                    else if (!skip) e_tma2d_mc_ef(a, tm, kb * amul, row, f);
                } else {
                    const uint32_t b = sb + P_B + p.st * 8192;
                    e_expect(f, bytes);
                    e_tma2d_ef(b, tm, n0, kb * 64, f);
                    e_tma2d_ef(b + P_PLANE, tm, n0 + 64, kb * 64, f);
                    if (ph == 3 && both) mbar_wait_w(empty + 8 * p.st - 16, p.ph);
                    if (ph == 3) e_tma2d_ef(b + 2 * P_PLANE, tm, n0 + 128, kb * 64, f);
                }
                adv(p);
            }
        }
    }
    if (A) {
#pragma unroll 1
        for (int i = 0; i < P_ST; i++) mbar_wait_w(empty + 8 * i, p.ph ^ (i >= p.st));
    }
}

#define I4(d, i) "f"(d[i]), "f"(d[i + 1]), "f"(d[i + 2]), "f"(d[i + 3])
#define I16(d, i) I4(d, i), I4(d, i + 4), I4(d, i + 8), I4(d, i + 12)
#define O4(d, i) "=f"(d[i]), "=f"(d[i + 1]), "=f"(d[i + 2]), "=f"(d[i + 3])
__device__ __forceinline__ void pick32(float* v, int n, const float* c1, const float* vc, const float* old) {
    asm volatile("{PKT: .branchtargets PK0, PK1, PK2, PK3, PK4, PK5; brx.idx.uni %16, PKT;\n"
                 "PK0: fma.rn.f32 %0, %17, %19, %27; fma.rn.f32 %1, %17, %20, %28; fma.rn.f32 %2, %18, %19, %29; fma.rn.f32 %3, %18, %20, %30; fma.rn.f32 %4, %17, %21, %31; fma.rn.f32 %5, %17, %22, %32; fma.rn.f32 %6, %18, %21, %33; fma.rn.f32 %7, %18, %22, %34; fma.rn.f32 %8, %17, %23, %35; fma.rn.f32 %9, %17, %24, %36; fma.rn.f32 %10, %18, %23, %37; fma.rn.f32 %11, %18, %24, %38; fma.rn.f32 %12, %17, %25, %39; fma.rn.f32 %13, %17, %26, %40; fma.rn.f32 %14, %18, %25, %41; fma.rn.f32 %15, %18, %26, %42; bra.uni PKE;\n"
                 "PK1: fma.rn.f32 %0, %17, %19, %43; fma.rn.f32 %1, %17, %20, %44; fma.rn.f32 %2, %18, %19, %45; fma.rn.f32 %3, %18, %20, %46; fma.rn.f32 %4, %17, %21, %47; fma.rn.f32 %5, %17, %22, %48; fma.rn.f32 %6, %18, %21, %49; fma.rn.f32 %7, %18, %22, %50; fma.rn.f32 %8, %17, %23, %51; fma.rn.f32 %9, %17, %24, %52; fma.rn.f32 %10, %18, %23, %53; fma.rn.f32 %11, %18, %24, %54; fma.rn.f32 %12, %17, %25, %55; fma.rn.f32 %13, %17, %26, %56; fma.rn.f32 %14, %18, %25, %57; fma.rn.f32 %15, %18, %26, %58; bra.uni PKE;\n"
                 "PK2: fma.rn.f32 %0, %17, %19, %59; fma.rn.f32 %1, %17, %20, %60; fma.rn.f32 %2, %18, %19, %61; fma.rn.f32 %3, %18, %20, %62; fma.rn.f32 %4, %17, %21, %63; fma.rn.f32 %5, %17, %22, %64; fma.rn.f32 %6, %18, %21, %65; fma.rn.f32 %7, %18, %22, %66; fma.rn.f32 %8, %17, %23, %67; fma.rn.f32 %9, %17, %24, %68; fma.rn.f32 %10, %18, %23, %69; fma.rn.f32 %11, %18, %24, %70; fma.rn.f32 %12, %17, %25, %71; fma.rn.f32 %13, %17, %26, %72; fma.rn.f32 %14, %18, %25, %73; fma.rn.f32 %15, %18, %26, %74; bra.uni PKE;\n"
                 "PK3: fma.rn.f32 %0, %17, %19, %75; fma.rn.f32 %1, %17, %20, %76; fma.rn.f32 %2, %18, %19, %77; fma.rn.f32 %3, %18, %20, %78; fma.rn.f32 %4, %17, %21, %79; fma.rn.f32 %5, %17, %22, %80; fma.rn.f32 %6, %18, %21, %81; fma.rn.f32 %7, %18, %22, %82; fma.rn.f32 %8, %17, %23, %83; fma.rn.f32 %9, %17, %24, %84; fma.rn.f32 %10, %18, %23, %85; fma.rn.f32 %11, %18, %24, %86; fma.rn.f32 %12, %17, %25, %87; fma.rn.f32 %13, %17, %26, %88; fma.rn.f32 %14, %18, %25, %89; fma.rn.f32 %15, %18, %26, %90; bra.uni PKE;\n"
                 "PK4: fma.rn.f32 %0, %17, %19, %91; fma.rn.f32 %1, %17, %20, %92; fma.rn.f32 %2, %18, %19, %93; fma.rn.f32 %3, %18, %20, %94; fma.rn.f32 %4, %17, %21, %95; fma.rn.f32 %5, %17, %22, %96; fma.rn.f32 %6, %18, %21, %97; fma.rn.f32 %7, %18, %22, %98; fma.rn.f32 %8, %17, %23, %99; fma.rn.f32 %9, %17, %24, %100; fma.rn.f32 %10, %18, %23, %101; fma.rn.f32 %11, %18, %24, %102; fma.rn.f32 %12, %17, %25, %103; fma.rn.f32 %13, %17, %26, %104; fma.rn.f32 %14, %18, %25, %105; fma.rn.f32 %15, %18, %26, %106; bra.uni PKE;\n"
                 "PK5: fma.rn.f32 %0, %17, %19, %107; fma.rn.f32 %1, %17, %20, %108; fma.rn.f32 %2, %18, %19, %109; fma.rn.f32 %3, %18, %20, %110; fma.rn.f32 %4, %17, %21, %111; fma.rn.f32 %5, %17, %22, %112; fma.rn.f32 %6, %18, %21, %113; fma.rn.f32 %7, %18, %22, %114; fma.rn.f32 %8, %17, %23, %115; fma.rn.f32 %9, %17, %24, %116; fma.rn.f32 %10, %18, %23, %117; fma.rn.f32 %11, %18, %24, %118; fma.rn.f32 %12, %17, %25, %119; fma.rn.f32 %13, %17, %26, %120; fma.rn.f32 %14, %18, %25, %121; fma.rn.f32 %15, %18, %26, %122;\n"
                 "PKE: }"
                 : O4(v, 0), O4(v, 4), O4(v, 8), O4(v, 12)
                 : "r"(n), "f"(c1[0]), "f"(c1[1]), I4(vc, 0), I4(vc, 4), I16(old, 0), I16(old, 16), I16(old, 32), I16(old, 48), I16(old, 64), I16(old, 80));
}
template <int PH, class F>
__device__ __forceinline__ void post_mma(uint32_t sb, float* acc, Pipe& p, int NK, int wg, uint32_t rel, bool lead, int pi, F hook) {
    const uint32_t full = sb + P_BAR + 8 * PB_F;
    constexpr uint64_t DA = PH == 0 ? mkdesc(SB0, 128, 1024, 0) : mkdesc(SB0, 16, 1024, 1);
    constexpr uint64_t DB = mkdesc(SB0 + P_B, P_PLANE, 1024, 1);
    auto release = [&](uint32_t a) { asm volatile("{.reg .pred p; setp.gt.u32 p, %0, 63; @p mbarrier.arrive.shared::cluster.b64 _, [%0];}" ::"r"(a) : "memory"); };
    uint32_t prev = 0;
    if (PH & 1) { fence_async_smem(); bar_sync(12 + wg, 128); }
    bool ok = false;
#pragma unroll 1
    for (int kb = 0; kb < NK; kb++) {
        if (!ok) mbar_wait_w(full + 8 * p.st, p.ph);
        const uint32_t a = (uint32_t)DA + ((PH & 1) && kb < 2 ? P_OUT / 16 + wg * 1024 + kb * 512 : p.st * 1024 + wg * 512), b = (uint32_t)DB + p.st * 512;
        wg_fence();
#pragma unroll
        for (int k = 0; k < 4; k++) {
            const uint64_t da = (DA & 0xffffffff00000000ull) | (a + k * (PH == 0 ? 16 : 2)), db = (DB & 0xffffffff00000000ull) | (b + k * 128);
            if (PH == 3) wgmma_ss192(acc, da, db, (kb | k) != 0);
            else wgmma_ss128<PH == 0>(acc, da, db, (kb | k) != 0);
        }
        wg_commit();
        const uint32_t cur = rel + 8 * p.st;
        adv(p);
        uint32_t t;
        asm volatile("{.reg .pred p; mbarrier.test_wait.parity.shared.b64 p, [%1], %2; selp.u32 %0, 1, 0, p;}" : "=r"(t) : "r"(full + 8 * p.st), "r"(p.ph) : "memory");
        wg_wait<1>();
        release(prev);
        ok = __all_sync(~0u, t);
        prev = cur;
        hook(kb);
    }
    wg_wait<0>();
    release(prev);
}

__global__ void __cluster_dims__(2, 1, 1) __launch_bounds__(384, 1)
k_post(const __grid_constant__ PostMaps mp) {
    extern __shared__ uint8_t smraw[];
    const uint32_t sb = smem_u32(smraw);
    if ((sb & 0x3FFFF) != SB0) __trap();
    const int tid = threadIdx.x, lane = tid & 31;
    int d, pi;
    pair_place(blockIdx.x >> 1, d, pi);
    const int rank = blockIdx.x & 1, mb = (d >> 2) * 8 + pi, nb = (d & 3) * 2 + rank;
    const uint32_t bars = sb + P_BAR;
    const int w = __reduce_max_sync(~0u, (tid >> 5) - 8);
    if (w == 1) {
        if (lane == 0) {
#pragma unroll
            for (int i = 0; i <= PB_P; i++) mbar_init(bars + 8 * i, i >= PB_E && i < PB_X ? 4 : i == PB_P ? 2 : 1);
            mbar_arrive(bars + 8 * (PB_F + P_ST0));
            asm volatile("mbarrier.arrive.shared.b64 _, [%0], 4;" ::"r"(bars + 8 * (PB_E + P_ST0)) : "memory");
            sts4(bars + 8 * PB_OUT, 0, 0, 0, 0);
            asm volatile("fence.mbarrier_init.release.cluster; fence.proxy.async.shared::cta;" ::: "memory");
        }
        __syncwarp();
    }
    asm volatile("barrier.cluster.arrive.relaxed.aligned;" ::: "memory");
    if (w == 1 || w == 2) asm volatile("griddepcontrol.wait;" ::: "memory");
    if (w == 1) {
#pragma unroll
        for (int i = 0; i < E0; i++) {
            const int st = (P_ST0 + i) % P_ST;
            const uint32_t f = bars + 8 * (PB_F + st);
            e_expect(f, 32768);
#pragma unroll
            for (int h = 0; h < 2; h++) {
                e_tma2d_ef(sb + st * 16384 + h * 8192, &mp.o, i * 256, mb * 16 + h * 8, f);
                e_tma2d_ef(sb + P_B + st * 8192 + h * P_PLANE, &mp.wo, nb * 128 + h * 64, i * 64, f);
            }
        }
    }
    if (w != 0 && w != 3) asm volatile("barrier.cluster.wait.aligned;" ::: "memory");
    if (w >= 0) {
        asm volatile("setmaxnreg.dec.sync.aligned.u32 40;");
        if (w == 0) {
            post_produce<false>(sb, mp, mb, nb, rank);
        } else if (w < 3) {
            const int wg = w - 1, rh = 2 * mb + wg;
            float* rowc = (float*)(smraw + P_ROW) + (wg * 64 + lane * 2) * 8;
            int nout = 0, sig = 0;
            __nanosleep(X_DLY);
            if (wg && lane < 9) asm volatile("prefetch.tensormap [%0];" ::"l"(&mp.y + lane) : "memory");
            e_expect(bars + 8 * (PB_X + wg), 16384);
            e_tma2d_ef(sb + P_OUT + wg * 16384, &mp.x, nb * 128, rh * 64, bars + 8 * (PB_X + wg));
            e_tma2d_ef(sb + P_OUT + wg * 16384 + 8192, &mp.x, nb * 128 + 64, rh * 64, bars + 8 * (PB_X + wg));
            if (wg == 0) {
#pragma unroll 1
                for (int i = 0; i < 11; i++) {
                    const float* src = i < 4 ? g_mod + ((0x5342 >> (4 * i)) & 15) * DM + nb * 128 : g_vec + (i < 7 ? (i - 4) * DM + nb * 128 : 3 * DM + u_col(max(i - 8, 0), nb) + (i == 8) * 128);
                    if (i != 8 || lane < 16) cp_async16(sb + P_VEC + i * 512 - (i > 8) * 256 + lane * 16, src + lane * 4);
                }
                *(uint4*)&g_modp[blockIdx.x * 128 + lane * 4] = make_uint4(0, 0, 0, 0);
                if (blockIdx.x == 64) *(uint2*)&g_tick[lane * 2] = make_uint2(0, 0);
                asm volatile("cp.async.wait_all;" ::: "memory");
                const float4 a = lds4f(sb + P_VEC + V_A * 512 + lane * 16);
                sts4f(sb + P_VEC + V_A * 512 + lane * 16, 1.0f + a.x, 1.0f + a.y, 1.0f + a.z, 1.0f + a.w);
                bar_arrive(3, 288);
            }
#pragma unroll 1
            for (int i = 0; i < 9; i++) {
                const int cnt = i == 8 ? 6 : (0x54392180u >> (4 * i)) & 15;
                if (cnt < C_S1) {
                    const bool isu = cnt >= C_U && cnt < 6;
                    const int ng = cnt == C_U ? 3 : 2, c0 = isu ? u_col(cnt - C_U, nb) : nb * 128;
                    const uint32_t src = sb + (cnt == C_U ? P_OUT3 : P_OUT) + wg * ng * 8192;
#pragma unroll 1
                    for (int j = 0; j < ng; j++) {
                        bar_sync(4 + 4 * wg + (sig++ & 3), 160);
                        if (lane == 0) {
                            fence_async_smem();
                            asm volatile("cp.async.bulk.tensor.2d.global.shared::cta.bulk_group [%0, {%2, %3}], [%1]; cp.async.bulk.commit_group;"
                                         ::"l"(&mp.y + 2 * (isu ? 3 : min(cnt, 4))), "r"(src + j * 8192), "r"(c0 + j * 64), "r"(rh * 64) : "memory");
                        }
                        __syncwarp();
                    }
                    if (lane == 0) {
                        asm volatile("cp.async.bulk.wait_group 0; fence.proxy.async.global;" ::: "memory");
                        asm volatile("st.release.cta.shared.u32 [%0], %1;" ::"r"(bars + 8 * (PB_OUT + wg)), "r"(nout + 1) : "memory");
                        if (cnt < 6) asm volatile("fence.acq_rel.gpu; st.relaxed.gpu.global.u32 [%0], %1;" ::"l"(&g_pflag[cnt * 256 + rh * 8 + nb]), "r"(1) : "memory");
                        if (cnt == C_Y || cnt == C_X1)
                            asm volatile("{.reg .b32 r; mapa.shared::cluster.u32 r, %0, %1; mbarrier.arrive.relaxed.cluster.shared::cluster.b64 _, [r];}" ::"r"(bars + 8 * PB_P), "r"(rank ^ 1) : "memory");
                    }
                    nout++;
                    __syncwarp();
                    continue;
                }
                bar_sync(4 + 4 * wg + (sig++ & 3), 160);
#pragma unroll 1
                for (int q = 0; q < (cnt == C_S1 ? 3 : 1); q++) {
                    const float4 v = lds4f(sb + P_ROW + wg * 2048 + q * 512 + lane * 16);
                    asm volatile("red.relaxed.gpu.global.add.v4.f32 [%0], {%1, %2, %3, %4};"
                                 ::"l"((float4*)g_st + (cnt == C_S1 ? q : 3) * (S_ / 2) + rh * 32 + lane), "f"(v.x), "f"(v.y), "f"(v.z), "f"(v.w) : "memory");
                }
                __syncwarp();
                uint32_t* c = &g_pcnt[(cnt - C_S1) * 256 + rh * 8];
                if (lane == 0) { signal_count(c); wait_count1(c, 8); }
                __syncwarp();
                const float4* sp = (const float4*)g_st + rh * 32 + lane;
                float4 u[3] = {__ldcg(sp + (cnt == C_S1 ? 0 : 3) * (S_ / 2)), __ldcg(sp + S_ / 2), __ldcg(sp + S_)};
#pragma unroll 1
                for (int h = 0; h < 2; h++) {
                    const float id = 1.0f / DM;
                    const float m = u[0].x * id, var = fmaxf(u[0].y * id - m * m, 0.f) + 1e-5f, r = rsqrtf(var);
                    float sc = r, m2 = 0.f;
                    if (cnt == C_S1) {
                        m2 = r * (u[1].x * id - m * g_cst[0]) + g_cst[3];
                        const float e2 = r * r * (u[2].x * id - 2.0f * m * u[1].y * id + m * m * g_cst[1]) + 2.0f * r * (u[2].y * id - m * g_cst[2]) + g_cst[4];
                        sc = r * rsqrtf(fmaxf(e2 - m2 * m2, 0.f) + 1e-5f);
                    }
                    const GeluK k = gelu_k(sc);
                    *(float4*)(rowc + h * 8) = make_float4(k.k0, k.k1, k.kh, -m);
                    *(float4*)(rowc + h * 8 + 4) = make_float4(var * r, -m2 * var * r, r, -m * r);
#pragma unroll
                    for (int q = 0; q < 3; q++) { u[q].x = u[q].z; u[q].y = u[q].w; }
                }
                bar_arrive(1 + wg, 160);
            }
        } else {
            post_produce<true>(sb, mp, mb, nb, rank);
        }
    } else {
        asm volatile("setmaxnreg.inc.sync.aligned.u32 232;");
        const int wg = __reduce_max_sync(~0u, tid >> 7), wi = (tid >> 5) & 3, g = lane >> 2, tq = lane & 3;
        const bool lead = (tid & 127) == 0;
        uint32_t rel = 0;
        if ((tid & 127) < 2) asm("mapa.shared::cluster.u32 %0, %1, %2;" : "=r"(rel) : "r"(bars + 8 * PB_E), "r"(tid & 1));
        uint32_t vec = sb + P_VEC + tq * 8;
        const uint32_t stw = sb + (wi * 16 + ((lane >> 3) & 1) * 8 + (lane & 7)) * 128 + (((lane >> 4) ^ (lane & 7)) << 4);
        int sig = 0;
        auto signal = [&]() { bar_arrive(4 + 4 * wg + (sig++ & 3), 160); };
        auto put64 = [&](uint32_t o, const float* v) {
#pragma unroll
            for (int jj = 0; jj < 4; jj++, v += 8) stsm4((stw + o) ^ (jj << 5), pack2(v[0], v[1]), pack2(v[2], v[3]), pack2(v[4], v[5]), pack2(v[6], v[7]));
            signal();
        };
        auto out_free = [&](int n) { wait_smem(bars + 8 * (PB_OUT + (lane & 1)), n); };
        const uint32_t rowc = sb + P_ROW + (wg * 64 + wi * 16 + g) * 32, o128 = P_OUT + wg * 16384;
        const uint32_t rsum = sb + P_ROW + wg * 2048 + (wi * 16 + g) * 8;
        Pipe pa = {P_ST0, 1};
        auto none = [](int) {};
        uint32_t keep[32];
#define KEEP(jn, e) (((e) & 1) ? bfhi(keep[2 * (jn) + ((e) >> 1)]) : bflo(keep[2 * (jn) + ((e) >> 1)]))
        float mu1[2], r1[2];
        {
            float acc[64];
            post_mma<0>(sb, acc, pa, 64, wg, rel, lead, 1, [&](int kb) {
                if (kb != 40) return;
                bar_sync(3, 288);
                mbar_wait_w(bars + 8 * (PB_X + wg), 0);
#pragma unroll
                for (int jj = 0; jj < 8; jj++) ldsm4(keep + jj * 4, (stw + o128 + (jj >> 2) * 8192) ^ ((jj & 3) << 5));
            });
            asm volatile("" : "+r"(vec) :: "memory");
            float st[2][6];
#pragma unroll
            for (int q = 0; q < 6; q++) st[0][q] = st[1][q] = 0.f;
#pragma unroll
            for (int jn = 0; jn < 16; jn++) {
                const float2 ga = ldsv(vec + V_GA * 512 + jn * 32), a = ldsv(vec + V_A * 512 + jn * 32);
                float xa[4];
#pragma unroll
                for (int e = 0; e < 4; e++) {
                    xa[e] = fmaf((e & 1) ? ga.y : ga.x, acc[4 * jn + e], KEEP(jn, e));
                    st[e >> 1][0] += xa[e]; st[e >> 1][1] = fmaf(xa[e], xa[e], st[e >> 1][1]);
                    acc[4 * jn + e] = ((e & 1) ? a.y : a.x) * xa[e];
                }
                keep[2 * jn] = pack2(xa[0], xa[1]); keep[2 * jn + 1] = pack2(xa[2], xa[3]);
                if ((jn & 7) == 7) put64(o128 + (jn >> 3) * 8192, acc + 4 * jn - 28);
            }
#pragma unroll
            for (int jn = 0; jn < 16; jn++) {
                const float2 a = ldsv(vec + V_A * 512 + jn * 32), b = ldsv(vec + V_B * 512 + jn * 32);
#pragma unroll
                for (int e = 0; e < 4; e++) {
                    const float y = acc[4 * jn + e], aa = (e & 1) ? a.y : a.x, bb = (e & 1) ? b.y : b.x;
                    float* s = st[e >> 1];
                    s[2] += y; s[3] = fmaf(aa, y, s[3]); s[4] = fmaf(y, y, s[4]); s[5] = fmaf(bb, y, s[5]);
                }
            }
#pragma unroll
            for (int h = 0; h < 2; h++)
#pragma unroll
                for (int q = 0; q < 6; q++) { st[h][q] += __shfl_xor_sync(~0u, st[h][q], 1); st[h][q] += __shfl_xor_sync(~0u, st[h][q], 2); }
            if (tq < 3) {
#pragma unroll
                for (int h = 0; h < 2; h++)
                    sts2(rsum + tq * 512 + h * 64, tq == 0 ? st[h][0] : tq == 1 ? st[h][2] : st[h][4], tq == 0 ? st[h][1] : tq == 1 ? st[h][3] : st[h][5]);
            }
            signal();
        }
        {
            float acc[64];
            post_mma<1>(sb, acc, pa, 16, wg, rel, lead, 4, none);
            float c1[2], c2[2], c3[2];
            GeluK gk[2];
            bar_sync(1 + wg, 160);
#pragma unroll
            for (int h = 0; h < 2; h++) {
                const float4 a = lds4f(rowc + h * 256), b = lds4f(rowc + h * 256 + 16);
                gk[h] = {a.x, a.y, a.z}; c1[h] = a.w; c2[h] = b.x; c3[h] = b.y; mu1[h] = b.w; r1[h] = b.z;
            }
#pragma unroll
            for (int jn = 0; jn < 16; jn++) {
                const float2 va = ldsv(vec + V_VA * 512 + jn * 32), vb = ldsv(vec + V_VB * 512 + jn * 32), vc = ldsv(vec + V_VC * 512 + jn * 32);
#pragma unroll
                for (int e = 0; e < 4; e++) {
                    const int h = e >> 1;
                    const float t = fmaf(c1[h], (e & 1) ? va.y : va.x, fmaf(c2[h], (e & 1) ? vb.y : vb.x, fmaf(c3[h], (e & 1) ? vc.y : vc.x, acc[4 * jn + e])));
                    acc[4 * jn + e] = gelu_s(t, gk[h]);
                }
                if ((jn & 7) == 7) put64(o128 + (jn >> 3) * 8192, acc + 4 * jn - 28);
            }
        }
        {
            float acc[64];
            post_mma<2>(sb, acc, pa, 16, wg, rel, lead, 7, none);
#pragma unroll
            for (int jn = 0; jn < 16; jn++) {
                const float2 a = ldsv(vec + V_A * 512 + jn * 32), b = ldsv(vec + V_B * 512 + jn * 32);
#pragma unroll
                for (int e = 0; e < 4; e++) {
                    const int h = e >> 1;
                    acc[4 * jn + e] += fmaf(fmaf(KEEP(jn, e), r1[h], mu1[h]), (e & 1) ? a.y : a.x, (e & 1) ? b.y : b.x);
                }
                if ((jn & 7) == 7) put64(o128 + (jn >> 3) * 8192, acc + 4 * jn - 28);
            }
            float st[2][2] = {{0.f, 0.f}, {0.f, 0.f}};
#pragma unroll
            for (int jn = 0; jn < 16; jn++) {
                const float2 gb = ldsv(vec + V_GB * 512 + jn * 32);
                float z[4];
#pragma unroll
                for (int e = 0; e < 4; e++) {
                    const float x1 = acc[4 * jn + e];
                    st[e >> 1][0] += x1; st[e >> 1][1] = fmaf(x1, x1, st[e >> 1][1]);
                    z[e] = fmaf((e & 1) ? gb.y : gb.x, x1, KEEP(jn, e));
                }
                keep[2 * jn] = pack2(z[0], z[1]); keep[2 * jn + 1] = pack2(z[2], z[3]);
            }
#pragma unroll
            for (int h = 0; h < 2; h++)
#pragma unroll
                for (int q = 0; q < 2; q++) { st[h][q] += __shfl_xor_sync(~0u, st[h][q], 1); st[h][q] += __shfl_xor_sync(~0u, st[h][q], 2); }
            if (tq < 2) sts2(rsum + tq * 64, tq ? st[1][0] : st[0][0], tq ? st[1][1] : st[0][1]);
            signal();
        }
        {
            float old[96], acc[64];
            post_mma<3>(sb, old, pa, 16, wg, rel, lead, 10, none);
            uint32_t v3 = vec + V_C3 * 512;
            float c1[2], vc[8];
            auto next_vc = [&]() {
#pragma unroll
                for (int i = 0; i < 4; i++) { const float2 u = lds2f(v3 + i * 32); vc[2 * i] = u.x; vc[2 * i + 1] = u.y; }
                v3 += 128;
            };
            next_vc();
            GeluK gk[2];
            bar_sync(1 + wg, 160);
#pragma unroll
            for (int h = 0; h < 2; h++) { const float4 a = lds4f(rowc + h * 256); gk[h] = {a.x, a.y, a.z}; c1[h] = a.w; }
            bar_arrive(14 + wg, 256);
#pragma unroll 1
            for (int r = 0; r < 3; r++) {
                const uint32_t o = stw + (r ? o128 : P_OUT3 + wg * 24576);
                uint32_t when = r == 0 ? (wg ? SL_A1 : SL_A0) : r == 1 ? (wg ? SL_B1 : SL_B0) : SL_C << (2 * wg), n = 0;
                post_mma<2>(sb, acc, pa, r < 2 ? 16 : 56, wg, rel, lead, 12 + 2 * r, [&](int kb) {
                    const bool now = when & 1;
                    when >>= 1;
                    if (!now) return;
                    if (n == 0) { if (r == 0) bar_sync(15 - wg, 256); out_free(3 + r); }
                    float v[16];
                    pick32(v, n, c1, vc, old);
                    next_vc();
#pragma unroll
                    for (int e = 0; e < 16; e++) v[e] = gelu_s(v[e], gk[(e >> 1) & 1]);
                    const uint32_t a = (o + (n >> 1) * 8192) ^ ((n & 1) << 6);
                    stsm4(a, pack2(v[0], v[1]), pack2(v[2], v[3]), pack2(v[4], v[5]), pack2(v[6], v[7]));
                    stsm4(a ^ 32, pack2(v[8], v[9]), pack2(v[10], v[11]), pack2(v[12], v[13]), pack2(v[14], v[15]));
                    if ((++n & 1) == 0) signal();
                });
                if (r == 2) break;
#pragma unroll
                for (int i = 0; i < 64; i++) old[i] = acc[i];
            }
#pragma unroll
            for (int jn = 0; jn < 16; jn++) {
                const float2 gb = ldsv(vec + V_GB * 512 + jn * 32);
#pragma unroll
                for (int e = 0; e < 4; e++) acc[4 * jn + e] = fmaf((e & 1) ? gb.y : gb.x, acc[4 * jn + e], KEEP(jn, e));
                if ((jn & 7) == 7) put64(o128 + (jn >> 3) * 8192, acc + 4 * jn - 28);
            }
        }
    }
}

typedef CUresult (*EncFn)(CUtensorMap*, CUtensorMapDataType, cuuint32_t, void*, const cuuint64_t*, const cuuint64_t*, const cuuint32_t*,
                          const cuuint32_t*, CUtensorMapInterleave, CUtensorMapSwizzle, CUtensorMapL2promotion, CUtensorMapFloatOOBfill);

static CUtensorMap make_map(EncFn enc, const void* p, uint64_t inner, uint64_t outer) {
    CUtensorMap m;
    cuuint64_t dims[2] = {inner, outer};
    cuuint64_t str[1] = {inner * 2};
    cuuint32_t box[2] = {64, 64};
    cuuint32_t es[2] = {1, 1};
    enc(&m, CU_TENSOR_MAP_DATA_TYPE_BFLOAT16, 2, (void*)p, dims, str, box, es, CU_TENSOR_MAP_INTERLEAVE_NONE,
        CU_TENSOR_MAP_SWIZZLE_128B, CU_TENSOR_MAP_L2_PROMOTION_L2_256B, CU_TENSOR_MAP_FLOAT_OOB_FILL_NONE);
    return m;
}
static CUtensorMap make_map_o(EncFn enc, const void* p) {
    CUtensorMap m;
    cuuint64_t dims[2] = {16384, 256};
    cuuint64_t str[1] = {65536};
    cuuint32_t box[2] = {256, 8};
    cuuint32_t es[2] = {1, 1};
    enc(&m, CU_TENSOR_MAP_DATA_TYPE_UINT32, 2, (void*)p, dims, str, box, es, CU_TENSOR_MAP_INTERLEAVE_NONE, CU_TENSOR_MAP_SWIZZLE_NONE,
        CU_TENSOR_MAP_L2_PROMOTION_L2_256B, CU_TENSOR_MAP_FLOAT_OOB_FILL_NONE);
    return m;
}
template <class T> static T* sym(T& s) { void* p = nullptr; cudaGetSymbolAddress(&p, s); return (T*)p; }

constexpr RecTime g_time = {T_GO, T_X2, T_V, D_X2, H_D};
extern "C" void kernel_launch(void* const* d_in, const int* in_sizes, int n_in, void* d_out, int out_size) {
    const bf16* x = (const bf16*)d_in[0];
    const bf16* mem0 = (const bf16*)d_in[1];
    const bf16 *Wq = (const bf16*)d_in[2], *Wk = (const bf16*)d_in[3], *Wv = (const bf16*)d_in[4], *Wo = (const bf16*)d_in[5];
    const bf16 *w1 = (const bf16*)d_in[8], *w2 = (const bf16*)d_in[9], *w3 = (const bf16*)d_in[10], *w4 = (const bf16*)d_in[11];
    const bf16 *c = (const bf16*)d_in[12], *wmod = (const bf16*)d_in[13];
    bf16* out = (bf16*)d_out;

    EncFn enc = nullptr;
    cudaDriverEntryPointQueryResult qr;
    cudaGetDriverEntryPoint("cuTensorMapEncodeTiled", (void**)&enc, cudaEnableDefault, &qr);
    CUtensorMap tWq = make_map(enc, Wq, NH * DH, DM), tWk = make_map(enc, Wk, NH * DH, DM), tWv = make_map(enc, Wv, NH * DH, DM);
    PostMaps mp;
    mp.o = make_map_o(enc, sym(g_O)); mp.wo = make_map(enc, Wo, DM, NH * DH);
    mp.y = make_map(enc, sym(g_y), DM, S_); mp.w1 = make_map(enc, w1, DM, DM);
    mp.g = make_map(enc, sym(g_g), DM, S_); mp.w2 = make_map(enc, w2, DM, DM);
    mp.x1 = make_map(enc, sym(g_x1), DM, S_); mp.w3 = make_map(enc, w3, FF, DM);
    mp.u = make_map(enc, sym(g_u), FF, S_); mp.w4 = make_map(enc, w4, DM, FF);
    mp.out = make_map(enc, out, DM, S_); mp.x = make_map(enc, x, DM, S_);
    cudaFuncSetAttribute(k_rec, cudaFuncAttributeMaxDynamicSharedMemorySize, SM_REC_TOTAL);
    cudaFuncSetAttribute(k_post, cudaFuncAttributeMaxDynamicSharedMemorySize, P_SMEM);

    uint8_t* arena = (uint8_t*)(((uintptr_t)sym(g_arena) + (2u << 20) - 1) & ~(uintptr_t)((2u << 20) - 1));
    const RecPtrs rp = {x, mem0, c, wmod, w1, w3, arena, 0u, g_time};
    const RecMaps rm = {tWq, tWk, tWv, mp.wo};
    k_rec<<<132, 384, SM_REC_TOTAL>>>(rm, rp);
    cudaLaunchConfig_t cfg = {};
    cfg.gridDim = dim3(128); cfg.blockDim = dim3(384); cfg.dynamicSmemBytes = P_SMEM; cfg.stream = cudaStreamPerThread;
    cudaLaunchAttribute at[1];
    at[0].id = cudaLaunchAttributeProgrammaticStreamSerialization;
    at[0].val.programmaticStreamSerializationAllowed = 1;
    cfg.attrs = at; cfg.numAttrs = 1;
    cudaLaunchKernelEx(&cfg, k_post, mp);
}
```

```cpp
#include <cuda_runtime.h>
#include <cuda.h>
#include <cuda_bf16.h>
#include <stdint.h>
#include <limits.h>

typedef __nv_bfloat16 bf16;

constexpr int S_ = 2048, DM = 1024, NH = 32, DH = 128, NSEG = 64, FF = 3584;
constexpr int SPIN_LIMIT = 1 << 22;
constexpr int W_INFL = 2;
constexpr int NPROBE = 4;

__device__ uint8_t g_arena[10 << 20];
__device__ __align__(16) uint32_t g_tick[64];
__device__ __align__(16) uint32_t g_modp[8 * 2 * DM];
__host__ __device__ constexpr uint32_t blk(uint32_t lb, uint32_t par) {
    return (lb << 13) | ((((lb) ^ (lb >> 3) ^ (lb >> 4) ^ (lb >> 6) ^ par) & 1) << 12);
}
__host__ __device__ constexpr uint32_t lb_x2(uint32_t h) { return (h & 1) | ((h >> 1) << 3); }
__host__ __device__ constexpr uint32_t acc_slot(uint32_t s) { return (1u << 20) + (s & 1) * 32768 + (s & 2) * 131072; }
__host__ __device__ constexpr uint32_t acc_piece(uint32_t half, uint32_t qd, uint32_t mt) { return mt * 1024 + (qd & 1) * 4096 + half * 8192 + (qd >> 1) * 16384; }
constexpr uint32_t LB_STAMP = 6;
__host__ __device__ constexpr uint32_t stamp_line(uint32_t w, uint32_t q) { return ((w & 1) * 2 + (q >> 1)) * 1024 + (q & 1) * 256; }
constexpr uint32_t ACC_ONE = 0x3c000000u, ACC_ALL = 0x50000000u;
constexpr uint32_t LB_PROBE = 6 | 64;
__host__ __device__ constexpr uint32_t lb_tok(uint32_t h) { return (h & 1) | ((h >> 1) << 3); }
__device__ __align__(16) float g_mod[6 * DM];
__device__ __align__(1024) bf16 g_himg[(S_ + 32) * DM];
__device__ __align__(1024) bf16 g_O[S_ * NH * DH];
__device__ __align__(1024) bf16 g_y[S_ * DM];
__device__ __align__(1024) bf16 g_g[S_ * DM];
__device__ __align__(1024) bf16 g_x1[S_ * DM];
__device__ __align__(16) float g_st[4 * S_ * 2];
__device__ __align__(16) float g_vec[3 * DM + FF];
__device__ float g_cst[8];
__device__ uint32_t g_pcnt[2 * 32 * 8], g_pflag[6 * 32 * 8];
__device__ __align__(1024) bf16 g_u[S_ * FF];

__device__ __forceinline__ uint32_t smem_u32(const void* p) { return (uint32_t)__cvta_generic_to_shared(p); }
__device__ __forceinline__ void spin_guard(int it) {
    asm volatile("{.reg .pred p; setp.gt.s32 p, %0, %1; @p st.global.u32 [%2], %0;}" ::"r"(it), "n"(SPIN_LIMIT), "l"(1ull));
}
__device__ __forceinline__ void wg_fence() { asm volatile("wgmma.fence.sync.aligned;" ::: "memory"); }
__device__ __forceinline__ void wg_commit() { asm volatile("wgmma.commit_group.sync.aligned;" ::: "memory"); }
template <int N> __device__ __forceinline__ void wg_wait() { asm volatile("wgmma.wait_group.sync.aligned %0;" ::"n"(N) : "memory"); }
__host__ __device__ constexpr uint64_t mkdesc(uint32_t addr, uint32_t lbo, uint32_t sbo, uint32_t swz) {
    return (uint64_t)((addr & 0x3FFFF) >> 4) | ((uint64_t)(lbo >> 4) << 16) | ((uint64_t)(sbo >> 4) << 32) | ((uint64_t)swz << 62);
}
__device__ __forceinline__ uint64_t dadd(uint64_t d, uint32_t o) { return (d & 0xffffffff00000000ull) | (uint32_t)((uint32_t)d + o); }
__device__ __forceinline__ void mbar_init(uint32_t b, uint32_t c) { asm volatile("mbarrier.init.shared.b64 [%0], %1;" ::"r"(b), "r"(c) : "memory"); }
__device__ __forceinline__ void mbar_expect(uint32_t b, uint32_t tx) { asm volatile("mbarrier.arrive.expect_tx.shared.b64 _, [%0], %1;" ::"r"(b), "r"(tx) : "memory"); }
__device__ __forceinline__ void mbar_arrive(uint32_t b) { asm volatile("mbarrier.arrive.shared.b64 _, [%0];" ::"r"(b) : "memory"); }
__device__ __forceinline__ void mbar_arrive_cluster_if(bool c, uint32_t b, uint32_t cta) {
    asm volatile("{.reg .pred p; .reg .b32 r; setp.ne.u32 p, %2, 0; mapa.shared::cluster.u32 r, %0, %1; @p mbarrier.arrive.shared::cluster.b64 _, [r];}" ::"r"(b), "r"(cta), "r"((uint32_t)c) : "memory");
}
__device__ __forceinline__ bool mbar_try(uint32_t b, uint32_t par) {
    uint32_t ok;
    asm volatile("{.reg .pred p; mbarrier.try_wait.parity.shared.b64 p, [%1], %2; selp.u32 %0, 1, 0, p;}" : "=r"(ok) : "r"(b), "r"(par) : "memory");
    return ok;
}
__device__ __forceinline__ void mbar_wait_w(uint32_t b, uint32_t par) {
    int it = 0;
    bool ok;
#pragma unroll 1
    do { ok = __all_sync(~0u, mbar_try(b, par)); spin_guard(++it); } while (!ok);
}
__device__ __forceinline__ void bar_sync(int id, int n) { asm volatile("bar.sync %0, %1;" ::"r"(id), "r"(n) : "memory"); }
__device__ __forceinline__ void bar_arrive(int id, int n) { asm volatile("bar.arrive %0, %1;" ::"r"(id), "r"(n) : "memory"); }
__device__ __forceinline__ void fence_async_smem() { asm volatile("fence.proxy.async.shared::cta;" ::: "memory"); }
__device__ __forceinline__ void ldsm4t(uint32_t* r, uint32_t a) {
    asm volatile("ldmatrix.sync.aligned.m8n8.x4.trans.shared.b16 {%0,%1,%2,%3}, [%4];" : "=r"(r[0]), "=r"(r[1]), "=r"(r[2]), "=r"(r[3]) : "r"(a) : "memory");
}
__device__ __forceinline__ void ldsm4(uint32_t* r, uint32_t a) {
    asm volatile("ldmatrix.sync.aligned.m8n8.x4.shared.b16 {%0,%1,%2,%3}, [%4];" : "=r"(r[0]), "=r"(r[1]), "=r"(r[2]), "=r"(r[3]) : "r"(a) : "memory");
}
__device__ __forceinline__ uint32_t movm(uint32_t a) {
    uint32_t d; asm volatile("movmatrix.sync.aligned.m8n8.trans.b16 %0, %1;" : "=r"(d) : "r"(a)); return d;
}
__device__ __forceinline__ void mma16816(float* d, uint32_t a0, uint32_t a1, uint32_t a2, uint32_t a3, uint32_t b0, uint32_t b1) {
    asm volatile("mma.sync.aligned.m16n8k16.row.col.f32.bf16.bf16.f32 {%0,%1,%2,%3},{%4,%5,%6,%7},{%8,%9},{%0,%1,%2,%3};"
                 : "+f"(d[0]), "+f"(d[1]), "+f"(d[2]), "+f"(d[3]) : "r"(a0), "r"(a1), "r"(a2), "r"(a3), "r"(b0), "r"(b1));
}
__device__ __forceinline__ void mma16816z(float* d, const uint32_t* a, uint32_t b0, uint32_t b1) {
    asm volatile("mma.sync.aligned.m16n8k16.row.col.f32.bf16.bf16.f32 {%0,%1,%2,%3},{%4,%5,%6,%7},{%8,%9},{%10,%10,%10,%10};"
                 : "=f"(d[0]), "=f"(d[1]), "=f"(d[2]), "=f"(d[3]) : "r"(a[0]), "r"(a[1]), "r"(a[2]), "r"(a[3]), "r"(b0), "r"(b1), "f"(0.f));
}
__device__ __forceinline__ void mma1688(float* d, uint32_t a0, uint32_t a1, uint32_t b0) {
    asm volatile("mma.sync.aligned.m16n8k8.row.col.f32.bf16.bf16.f32 {%0,%1,%2,%3},{%4,%5},{%6},{%0,%1,%2,%3};"
                 : "+f"(d[0]), "+f"(d[1]), "+f"(d[2]), "+f"(d[3]) : "r"(a0), "r"(a1), "r"(b0));
}
__device__ __forceinline__ uint32_t pack2(float lo, float hi) {
    uint32_t r; asm("cvt.rn.bf16x2.f32 %0, %1, %2;" : "=r"(r) : "f"(hi), "f"(lo)); return r;
}
__device__ __forceinline__ uint32_t hadd2v(uint32_t a, uint32_t b) {
    uint32_t r; asm volatile("add.rn.bf16x2 %0, %1, %2;" : "=r"(r) : "r"(a), "r"(b)); return r;
}
__device__ __forceinline__ uint32_t hmul2b(uint32_t a, uint32_t b) {
    uint32_t r; asm("mul.rn.bf16x2 %0, %1, %2;" : "=r"(r) : "r"(a), "r"(b)); return r;
}
__device__ __forceinline__ float bflo(uint32_t u) { return __uint_as_float(u << 16); }
__device__ __forceinline__ float bfhi(uint32_t u) { return __uint_as_float(u & 0xffff0000u); }
__device__ __forceinline__ float ex2(float x) { float r; asm("ex2.approx.ftz.f32 %0, %1;" : "=f"(r) : "f"(x)); return r; }
__device__ __forceinline__ uint4 ldg_rlx4(const void* p) {
    uint4 v; asm volatile("ld.relaxed.gpu.global.v4.u32 {%0,%1,%2,%3}, [%4];" : "=r"(v.x), "=r"(v.y), "=r"(v.z), "=r"(v.w) : "l"(p) : "memory"); return v;
}
__device__ __forceinline__ uint32_t ldg_rlx1(const void* p) {
    uint32_t v; asm volatile("ld.relaxed.gpu.global.u32 %0, [%1];" : "=r"(v) : "l"(p) : "memory"); return v;
}
__device__ __forceinline__ void stg_rlx1(void* p, uint32_t v) { asm volatile("st.relaxed.gpu.global.u32 [%0], %1;" ::"l"(p), "r"(v) : "memory"); }
__device__ __forceinline__ void stg_rlx2(void* p, uint32_t x, uint32_t y) {
    unsigned long long v = (unsigned long long)x | ((unsigned long long)y << 32);
    asm volatile("st.relaxed.gpu.global.b64 [%0], %1;" ::"l"(p), "l"(v) : "memory");
}
__device__ __forceinline__ void stg_rlx4(void* p, uint32_t x, uint32_t y, uint32_t z, uint32_t w) {
    asm volatile("st.relaxed.gpu.global.v4.u32 [%0], {%1,%2,%3,%4};" ::"l"(p), "r"(x), "r"(y), "r"(z), "r"(w) : "memory");
}
__device__ __forceinline__ void sts4(uint32_t a, uint32_t x, uint32_t y, uint32_t z, uint32_t w) {
    asm volatile("st.shared.v4.u32 [%0], {%1,%2,%3,%4};" ::"r"(a), "r"(x), "r"(y), "r"(z), "r"(w) : "memory");
}
__device__ __forceinline__ uint4 lds4(uint32_t a) {
    uint4 v; asm volatile("ld.shared.v4.u32 {%0,%1,%2,%3}, [%4];" : "=r"(v.x), "=r"(v.y), "=r"(v.z), "=r"(v.w) : "r"(a) : "memory"); return v;
}
#define F4(d, i) "+f"(d[i]), "+f"(d[i + 1]), "+f"(d[i + 2]), "+f"(d[i + 3])
template <bool V> __device__ __forceinline__ void wgmma_tok_rs(float* d, const uint32_t* a, uint64_t b, int sc) {
    if (V) asm volatile("{.reg .pred p; setp.ne.b32 p, %25, 0;\n wgmma.mma_async.sync.aligned.m64n40k16.f32.bf16.bf16 {%0,%1,%2,%3,%4,%5,%6,%7,%8,%9,%10,%11,%12,%13,%14,%15,%16,%17,%18,%19}, {%20,%21,%22,%23}, %24, p, 1, 1, 0;}"
                        : F4(d, 0), F4(d, 4), F4(d, 8), F4(d, 12), F4(d, 16) : "r"(a[0]), "r"(a[1]), "r"(a[2]), "r"(a[3]), "l"(b), "r"(sc));
    else asm volatile("{.reg .pred p; setp.ne.b32 p, %21, 0;\n wgmma.mma_async.sync.aligned.m64n32k16.f32.bf16.bf16 {%0,%1,%2,%3,%4,%5,%6,%7,%8,%9,%10,%11,%12,%13,%14,%15}, {%16,%17,%18,%19}, %20, p, 1, 1, 0;}"
                      : F4(d, 0), F4(d, 4), F4(d, 8), F4(d, 12) : "r"(a[0]), "r"(a[1]), "r"(a[2]), "r"(a[3]), "l"(b), "r"(sc));
}
template <bool V> __device__ __forceinline__ void wgmma_tok_ss(float* d, uint64_t a, uint64_t b) {
    if (V) asm volatile("wgmma.mma_async.sync.aligned.m64n40k16.f32.bf16.bf16 {%0,%1,%2,%3,%4,%5,%6,%7,%8,%9,%10,%11,%12,%13,%14,%15,%16,%17,%18,%19}, %20, %21, 1, 1, 1, 1, 0;"
                        : F4(d, 0), F4(d, 4), F4(d, 8), F4(d, 12), F4(d, 16) : "l"(a), "l"(b));
    else asm volatile("wgmma.mma_async.sync.aligned.m64n32k16.f32.bf16.bf16 {%0,%1,%2,%3,%4,%5,%6,%7,%8,%9,%10,%11,%12,%13,%14,%15}, %16, %17, 1, 1, 1, 1, 0;"
                      : F4(d, 0), F4(d, 4), F4(d, 8), F4(d, 12) : "l"(a), "l"(b));
}
#define F16(d, i) F4(d, i), F4(d, i + 4), F4(d, i + 8), F4(d, i + 12)
template <int TA>
__device__ __forceinline__ void wgmma_ss128(float* d, uint64_t a, uint64_t b, int sc) {
    asm volatile("{.reg .pred p; setp.ne.b32 p, %66, 0;\n wgmma.mma_async.sync.aligned.m64n128k16.f32.bf16.bf16 "
                 "{%0,%1,%2,%3,%4,%5,%6,%7,%8,%9,%10,%11,%12,%13,%14,%15,%16,%17,%18,%19,%20,%21,%22,%23,%24,%25,%26,%27,%28,%29,%30,%31,"
                 "%32,%33,%34,%35,%36,%37,%38,%39,%40,%41,%42,%43,%44,%45,%46,%47,%48,%49,%50,%51,%52,%53,%54,%55,%56,%57,%58,%59,%60,%61,%62,%63}, %64, %65, p, 1, 1, %67, 1;}"
                 : F16(d, 0), F16(d, 16), F16(d, 32), F16(d, 48) : "l"(a), "l"(b), "r"(sc), "n"(TA));
}

__device__ __forceinline__ float warp_sum(float v) {
#pragma unroll
    for (int o = 16; o; o >>= 1) v += __shfl_xor_sync(~0u, v, o);
    return v;
}
__device__ __forceinline__ float bfround(float x) { return __bfloat162float(__float2bfloat16(x)); }

__device__ __forceinline__ void wait_count1(const uint32_t* p, uint32_t target) {
    int it = 0;
#pragma unroll 1
    while (true) {
        uint32_t v;
        asm volatile("ld.acquire.gpu.global.u32 %0, [%1];" : "=r"(v) : "l"(p) : "memory");
        if (v >= target) break;
        spin_guard(++it);
    }
}
__device__ __forceinline__ void signal_count(uint32_t* p) { asm volatile("red.release.gpu.global.add.u32 [%0], 1;" ::"l"(p) : "memory"); }
__device__ __forceinline__ void e_expect(uint32_t b, uint32_t tx) {
    asm volatile("{.reg .pred p; elect.sync _|p, 0xffffffff; @p mbarrier.arrive.expect_tx.shared.b64 _, [%0], %1;}" ::"r"(b), "r"(tx) : "memory");
}
__device__ __forceinline__ uint64_t evict_first() { uint64_t p; asm("createpolicy.fractional.L2::evict_first.b64 %0, 1.0;" : "=l"(p)); return p; }
__device__ __forceinline__ void e_tma2d_ef(uint32_t dst, const CUtensorMap* m, int c0, int c1, uint32_t bar) {
    asm volatile("{.reg .pred p; elect.sync _|p, 0xffffffff;\n @p cp.async.bulk.tensor.2d.shared::cluster.global.mbarrier::complete_tx::bytes.L2::cache_hint [%0], [%1, {%3, %4}], [%2], %5;}"
                 ::"r"(dst), "l"(m), "r"(bar), "r"(c0), "r"(c1), "l"(evict_first()) : "memory");
}
__device__ __forceinline__ void e_tma2d(uint32_t dst, const CUtensorMap* m, int c0, int c1, uint32_t bar) {
    asm volatile("{.reg .pred p; elect.sync _|p, 0xffffffff;\n @p cp.async.bulk.tensor.2d.shared::cluster.global.mbarrier::complete_tx::bytes [%0], [%1, {%3, %4}], [%2];}"
                 ::"r"(dst), "l"(m), "r"(bar), "r"(c0), "r"(c1) : "memory");
}
__device__ __forceinline__ void e_tma2d_mc_ef(uint32_t dst, const CUtensorMap* m, int c0, int c1, uint32_t bar) {
    asm volatile("{.reg .pred p; elect.sync _|p, 0xffffffff;\n @p cp.async.bulk.tensor.2d.shared::cluster.global.mbarrier::complete_tx::bytes.multicast::cluster.L2::cache_hint [%0], [%1, {%3, %4}], [%2], %5, %6;}"
                 ::"r"(dst), "l"(m), "r"(bar), "r"(c0), "r"(c1), "h"((uint16_t)3), "l"(evict_first()) : "memory");
}
__device__ __forceinline__ uint32_t wait_count_w(const uint32_t* p, uint32_t target) {
    int it = 0;
#pragma unroll 1
    while (true) {
        uint32_t v;
        asm volatile("ld.acquire.gpu.global.u32 %0, [%1];" : "=r"(v) : "l"(p) : "memory");
        if (__all_sync(~0u, v >= target)) return v;
        spin_guard(++it);
    }
}

constexpr int NL = 6;
constexpr uint32_t HCH = 5120, HBUF = 8 * HCH;
constexpr uint32_t SM_SX = 0, SM_ST = 2560, SM_OX = 8192, SM_LX = 10240, SM_PX = 11392, SM_PA = 12288, SM_VF = 18432, SM_TAB = 26624, SM_WL2 = 41984, SM_HB = 49152, SM_WO = 131072,
                   SM_WL = 196608, SM_PRE = SM_WL, SM_BAR = 227328, SM_TRC = SM_BAR + 256, SM_REC_TOTAL = SM_TRC + 2688;
__host__ __device__ constexpr uint32_t sm_wl(int i) { return i < 5 ? SM_WL + i * 6144 : SM_WL2; }
constexpr uint32_t SB0 = 1024;
constexpr int B_WO = 0, B_HE = 1, B_ROLE = 2, B_HB = 3, B_W = 5;
constexpr int NB_MEM = 1, NB_QK = 2, NB_X1 = 3, NB_X2 = 4, NB_WIN = 5, NB_WG = 6, NB_KDONE = 7, NB_FIN0 = 8, NB_LN = 9, NB_MEM2 = 10, NB_H = 11, NB_A = 12, NB_B = 13, NB_C = 14, NB_F = 15;
constexpr int TPV_DLY = 6;
constexpr int L_AT = 3;
constexpr int D_X2 = 340;
constexpr int NPF1 = 6;
constexpr int NPF = 11;
constexpr int T_GO = 28;
constexpr int GATE_AT = 25;
constexpr int T_X2 = 1920;
constexpr int T_V = 300;
constexpr int VP_AT = 1;
constexpr int PD = 4;
constexpr int PV_FENCE = 0;
constexpr int SSG = 5;
constexpr int SSG_V = 5;
constexpr int SS0_K = 4;
constexpr int SS0_V = 6;
constexpr int NPF0 = 3;
constexpr int STG_FENCE = 1;
constexpr int WO_AT = 0x1100;
constexpr int W_SPEC = 7;
constexpr int NO_GUESS = 0;
constexpr int W_T0 = 2800;
constexpr int NPF2 = 9;
constexpr int PF_DLY = 7;
constexpr int H_D = 210;
constexpr int PIN_EPI = 1;

__device__ __forceinline__ uint32_t clk32() { uint32_t t; asm volatile("mov.u32 %0, %%clock;" : "=r"(t) :: "memory"); return t; }
__device__ __forceinline__ uint32_t gtime32() { uint32_t t; asm volatile("mov.u32 %0, %%globaltimer_lo;" : "=r"(t) :: "memory"); return t; }
template <int N> __device__ __forceinline__ uint32_t delay(uint32_t zero) {
    float x = __uint_as_float(clk32());
#pragma unroll
    for (int i = 0; i < N; i++) asm volatile("ex2.approx.ftz.f32 %0, %0;" : "+f"(x));
    return __float_as_uint(x) & zero;
}
__device__ __forceinline__ uint32_t clk_after(uint32_t x, uint32_t zero) {
    unsigned long long c = 0;
    asm volatile("{.reg .pred p; setp.eq.u32 p, %1, 0; @p mov.u64 %0, %%clock64;}" : "+l"(c) : "r"(x & zero) : "memory");
    return (uint32_t)c;
}
__device__ __forceinline__ uint32_t later(uint32_t a, uint32_t b) { return a + max((int)(b - a), 0); }
__device__ __forceinline__ void wait_clk(uint32_t t) {
#pragma unroll 1
    while (true) {
        unsigned long long c;
        asm volatile("mov.u64 %0, %%clock64;" : "=l"(c) :: "memory");
        if ((int)((uint32_t)c - t) >= 0) break;
    }
}
__device__ __forceinline__ uint32_t opaque(uint32_t v) { return __shfl_sync(~0u, v, threadIdx.x & 31); }
__device__ __forceinline__ uint32_t xor_or(uint32_t a, uint32_t b, uint32_t t) {
    uint32_t r; asm volatile("lop3.b32 %0, %1, %2, %3, 0x7E;" : "=r"(r) : "r"(a), "r"(b), "r"(t)); return r;
}
__device__ __forceinline__ uint32_t or3(uint32_t a, uint32_t b, uint32_t c) {
    uint32_t r; asm volatile("lop3.b32 %0, %1, %2, %3, 0xFE;" : "=r"(r) : "r"(a), "r"(b), "r"(c)); return r;
}
__device__ __forceinline__ uint32_t settag(uint32_t v, uint32_t tag) {
    uint32_t r; asm("lop3.b32 %0, %1, 1, %2, 0xB8;" : "=r"(r) : "r"(v), "r"(tag)); return r;
}
__device__ __forceinline__ void ldg1_if(uint32_t& v, const void* p, bool c) {
    asm volatile("{.reg .pred p; setp.ne.u32 p, %2, 0; @p ld.relaxed.gpu.global.u32 %0, [%1];}" : "+r"(v) : "l"(p), "r"((uint32_t)c) : "memory");
}
__device__ __forceinline__ void sts2(uint32_t a, float x, float y) { asm volatile("st.shared.v2.f32 [%0], {%1,%2};" ::"r"(a), "f"(x), "f"(y) : "memory"); }
__device__ __forceinline__ void sts4f(uint32_t a, float x, float y, float z, float w) {
    asm volatile("st.shared.v4.f32 [%0], {%1,%2,%3,%4};" ::"r"(a), "f"(x), "f"(y), "f"(z), "f"(w) : "memory");
}
__device__ __forceinline__ void sts1(uint32_t a, uint32_t x) { asm volatile("st.shared.u32 [%0], %1;" ::"r"(a), "r"(x) : "memory"); }
__device__ __forceinline__ uint32_t lds1(uint32_t a) { uint32_t v; asm volatile("ld.shared.u32 %0, [%1];" : "=r"(v) : "r"(a) : "memory"); return v; }
__device__ __forceinline__ float4 lds4f(uint32_t a) {
    float4 v; asm volatile("ld.shared.v4.f32 {%0,%1,%2,%3}, [%4];" : "=f"(v.x), "=f"(v.y), "=f"(v.z), "=f"(v.w) : "r"(a) : "memory"); return v;
}
__device__ __forceinline__ float2 lds2f(uint32_t a) {
    float2 v; asm volatile("ld.shared.v2.f32 {%0,%1}, [%2];" : "=f"(v.x), "=f"(v.y) : "r"(a) : "memory"); return v;
}
__device__ __forceinline__ bool any_bit0(uint32_t x) {
    uint32_t r;
    asm volatile("{.reg .pred p, q; .reg .b32 t; and.b32 t, %1, 1; setp.ne.u32 p, t, 0; vote.sync.any.pred q, p, 0xffffffff; selp.u32 %0, 1, 0, q;}" : "=r"(r) : "r"(x));
    return r;
}
__device__ __forceinline__ float rcp_fast(float x) { float r; asm("rcp.approx.ftz.f32 %0, %1;" : "=f"(r) : "f"(x)); return r; }
__device__ __forceinline__ void stsm4(uint32_t a, uint32_t r0, uint32_t r1, uint32_t r2, uint32_t r3) {
    asm volatile("stmatrix.sync.aligned.m8n8.x4.shared.b16 [%0], {%1,%2,%3,%4};" ::"r"(a), "r"(r0), "r"(r1), "r"(r2), "r"(r3) : "memory");
}
__device__ __forceinline__ void stsm4t(uint32_t a, uint32_t r0, uint32_t r1, uint32_t r2, uint32_t r3) {
    asm volatile("stmatrix.sync.aligned.m8n8.x4.trans.shared.b16 [%0], {%1,%2,%3,%4};" ::"r"(a), "r"(r0), "r"(r1), "r"(r2), "r"(r3) : "memory");
}
__device__ __forceinline__ void cp_async16(uint32_t dst, const void* src) { asm volatile("cp.async.cg.shared.global [%0], [%1], 16;" ::"r"(dst), "l"(src) : "memory"); }
__device__ __forceinline__ void cp_async16_ef(uint32_t dst, const void* src) {
    asm volatile("cp.async.cg.shared.global.L2::cache_hint [%0], [%1], 16, %2;" ::"r"(dst), "l"(src), "l"(evict_first()) : "memory");
}
__device__ __forceinline__ uint32_t prmt(uint32_t a, uint32_t b, uint32_t c) { uint32_t r; asm("prmt.b32 %0, %1, %2, %3;" : "=r"(r) : "r"(a), "r"(b), "r"(c)); return r; }
__device__ __forceinline__ uint32_t hadd2h(uint32_t a, uint32_t b) { uint32_t r; asm("add.rn.f16x2 %0, %1, %2;" : "=r"(r) : "r"(a), "r"(b)); return r; }
__device__ __forceinline__ uint32_t hmax2h(uint32_t a, uint32_t b) { uint32_t r; asm("max.f16x2 %0, %1, %2;" : "=r"(r) : "r"(a), "r"(b)); return r; }
__device__ __forceinline__ uint32_t max3u(uint32_t a, uint32_t b, uint32_t c) { return __vimax3_u32(a, b, c); }

__device__ __forceinline__ void h_load(uint32_t sb, const uint8_t* hsrc, int pass, uint32_t rank, uint32_t rot, uint32_t wq, bool arm = true, uint32_t skip = 0) {
    const uint32_t bar = sb + SM_BAR + 8 * (B_HB + (pass & 1)), c = (wq + rot) & 3, dst = sb + SM_HB + (pass & 1) * HBUF + (rank * 4 + c) * HCH + skip;
    const uint8_t* src = hsrc + ((size_t)pass * 65536 + c * 4096 + skip);
    if (arm && wq == 0) e_expect(bar, 32768 - 8 * skip);
    asm volatile("{.reg .pred p; elect.sync _|p, 0xffffffff;\n"
                 " @p cp.async.bulk.shared::cluster.global.mbarrier::complete_tx::bytes.multicast::cluster.L2::cache_hint [%0], [%1], %4, [%2], %3, %5;}"
                 ::"r"(dst), "l"(src), "r"(bar), "h"((uint16_t)3), "r"(4096 - skip), "l"(evict_first()) : "memory");
}
__device__ __forceinline__ uint4 ldg_b128(const void* p) {
    uint4 v;
    asm volatile("{.reg .b128 t; .reg .b64 a, b; ld.relaxed.gpu.global.b128 t, [%4]; mov.b128 {a, b}, t; mov.b64 {%0,%1}, a; mov.b64 {%2,%3}, b;}"
                 : "=r"(v.x), "=r"(v.y), "=r"(v.z), "=r"(v.w) : "l"(p) : "memory");
    return v;
}
__device__ __forceinline__ void stg_b128_if(bool c, void* p, uint32_t x, uint32_t y, uint32_t z, uint32_t w) {
    asm volatile("{.reg .pred p; .reg .b128 t; .reg .b64 a, b; setp.ne.u32 p, %5, 0; mov.b64 a, {%1,%2}; mov.b64 b, {%3,%4}; mov.b128 t, {a, b}; @p st.relaxed.gpu.global.b128 [%0], t;}"
                 ::"l"(p), "r"(x), "r"(y), "r"(z), "r"(w), "r"((uint32_t)c) : "memory");
}
__device__ __forceinline__ float pretag(float x, uint32_t add, uint32_t keep) { return __uint_as_float((__float_as_uint(x) + add) & keep); }

template <bool MASK, class F>
__device__ __forceinline__ void softmax_rows(uint32_t src, uint32_t dst, uint32_t g16, int row0, F mid) {
    const uint32_t u = (g16 >> 7) & 3, e = ((g16 >> 9) << 3) | ((g16 >> 4) & 7);
    const uint32_t se = src + e * 8, su = se + u * 1088;
    const float2 p0 = lds2f(su), p1 = lds2f(su + 256), p2 = lds2f(su + 512), p3 = lds2f(su + 768);
    const float2 m0 = lds2f(se + 4352), m1 = lds2f(se + 4352 + 256), m2 = lds2f(se + 4352 + 512), m3 = lds2f(se + 4352 + 768);
    float a0 = (p0.x + p1.x) + (p2.x + p3.x), a1 = (p0.y + p1.y) + (p2.y + p3.y);
    const float a2 = (m0.x + m1.x) + (m2.x + m3.x), a3 = (m0.y + m1.y) + (m2.y + m3.y);
    mid(__float_as_uint(a3));
    if (MASK) {
        const int vis = row0 + (e >> 2) - 2 * (e & 3) - 8 * u;
        if (vis < 0) a0 = -1e9f / 0.08838834764831845f;
        if (vis < 1) a1 = -1e9f / 0.08838834764831845f;
    }
    int k = __float_as_int(fmaxf(fmaxf(a0, a1), fmaxf(a2, a3)));
    k ^= (k >> 31) & 0x7fffffff;
    const bool hi = g16 & 64;
    const int k0 = __reduce_max_sync(~0u, hi ? INT_MIN : k), k1 = __reduce_max_sync(~0u, hi ? k : INT_MIN);
    k = hi ? k1 : k0;
    const float m = __int_as_float(k ^ ((k >> 31) & 0x7fffffff));
    const float sl2 = 0.08838834764831845f * 1.4426950408889634f, mb = -m * sl2;
    sts1(dst + e * 16 + u * 4, pack2(ex2(fmaf(a0, sl2, mb)), ex2(fmaf(a1, sl2, mb))));
    sts1(dst + 512 + e * 4, pack2(ex2(fmaf(a2, sl2, mb)), ex2(fmaf(a3, sl2, mb))));
}

__device__ __forceinline__ uint32_t pack_h2(float lo, float hi) {
    uint32_t r; asm("cvt.rn.satfinite.f16x2.f32 %0, %1, %2;" : "=r"(r) : "f"(hi), "f"(lo)); return r;
}
__device__ __forceinline__ float2 unpack_h2(uint32_t u) {
    float2 r; asm("{.reg .b16 l, h; mov.b32 {l, h}, %2; cvt.f32.f16 %0, l; cvt.f32.f16 %1, h;}" : "=f"(r.x), "=f"(r.y) : "r"(u)); return r;
}
__device__ __forceinline__ uint32_t h2bf(uint32_t u) {
    uint32_t r;
    asm volatile("{.reg .b16 l, h; .reg .f32 a, b; mov.b32 {l, h}, %1; cvt.f32.f16 a, l; cvt.f32.f16 b, h; cvt.rn.bf16x2.f32 %0, b, a;}" : "=r"(r) : "r"(u));
    return r;
}
__device__ __forceinline__ void red_h10(bool c, void* p, void* q, uint32_t x, uint32_t y, uint32_t z, uint32_t w, uint32_t e) {
    asm volatile("{.reg .pred p; setp.ne.u32 p, %7, 0; red.relaxed.gpu.global.add.noftz.v4.f16x2 [%0], {%2,%3,%4,%5};\n"
                 " @p red.relaxed.gpu.global.add.noftz.f16x2 [%1], %6;}" ::"l"(p), "l"(q), "r"(x), "r"(y), "r"(z), "r"(w), "r"(e), "r"((uint32_t)c) : "memory");
}
constexpr float Q_SCALE = 1024.0f;
constexpr float SM_L2E = 0.08838834764831845f * 1.4426950408889634f * Q_SCALE;
template <int V> struct IC { static constexpr int value = V; };
typedef unsigned long long u64;
__device__ __forceinline__ uint32_t lo32(u64 v) { return (uint32_t)v; }
__device__ __forceinline__ uint32_t hi32(u64 v) { return (uint32_t)(v >> 32); }
__device__ __forceinline__ u64 ldg_u64(const void* p) { u64 v; asm volatile("ld.relaxed.gpu.global.b64 %0, [%1];" : "=l"(v) : "l"(p) : "memory"); return v; }
struct RecTime { uint32_t go, x2, v, dx2, h; };
__device__ __forceinline__ void rec_main(uint32_t sb, const CUtensorMap* tWo, uint8_t* arena, int role, int hinfo, int wg, uint32_t zero, const RecTime& tm) {
    const int hA = hinfo & 255;
    const int tid = threadIdx.x, t = tid & 127, lane = tid & 31, wi = t >> 5;
    const uint32_t bars = sb + SM_BAR;
    const int head = role >> 2, qd = role & 3, j = blockIdx.x & 1, kh = role & 1;
    const uint32_t mypar = head >= hA;
    const uint32_t wiu = __reduce_max_sync(~0u, wi);
    const bool warp0 = wiu == 0;
    const uint8_t* hsrc = (const uint8_t*)g_himg + kh * 32768 + j * 16384;
    auto tokbase = [&](int ty) { return ((ty + 1) << 21) + blk(lb_tok(head), mypar ^ ((hinfo >> (8 + ty)) & 1)); };
    const uint32_t tbw = tokbase(wg), tbq = tokbase(0) + (qd >> 1) * 2048 + (qd & 1) * 8;
#define KS(p) (4 * (((p) >> 1) & 7) + ((p) >> 4) + 2 * ((p) & 1))
    uint32_t w[32 - NL][4];
    uint4 wl5;
    if (wg == 2) bar_arrive(NB_WIN, 384);
    const uint32_t po = (1 << 20) + j * 16384 + kh * 2048;
    const uint32_t c16 = kh * 2048 + ((2 * j + (wi >> 1)) * 32 + lane) * 16, xso = blk(lb_x2(head), mypar);
    const uint32_t x2o = xso + wg * 16384 + (wi & 1) * 2048 + (c16 >> 1), tko = tbw + (wi & 1) * 16384 + c16;
    {
        stg_rlx2(arena + x2o, 0, 0);
#pragma unroll
        for (int i = 0; i < 4; i++) stg_rlx4(arena + ((i & 1 ? tko : tbw + (po ^ 2048) + t * 16) + (i >> 1) * 32768), 0, 0, 0, 0);
    }
    const uint32_t frow = ((lane >> 4) * 8 + (lane & 7)) * 128, fx = ((lane >> 3) & 1) ^ (lane & 7);
    {
#pragma unroll 1
        for (int i = 0; i < 4; i++) mbar_wait_w(bars + 8 * (B_W + (wg == 2 ? 8 + i : 2 * i + wg)), 0);
        const uint32_t stg = sb + wg * 65536;
#pragma unroll
        for (int p = NL; p < 32; p++) ldsm4t(w[p - NL], stg + KS(p) * 2048 + frow + ((fx ^ (2 * wi)) << 4));
#pragma unroll
        for (int i = 0; i < NL; i++) {
            wl5 = lds4(stg + KS(i) * 2048 + t * 16);
            if (i < 5) sts4(sb + sm_wl(i) + tid * 16, wl5.x, wl5.y, wl5.z, wl5.w);
        }
        fence_async_smem();
        if (wg < 2) bar_sync(NB_WG, 256);
        if (wg > 0) wait_count_w(&g_tick[32 + (lane & 3) * 8], wg);
        if (wg == 1) {
            mbar_arrive_cluster_if(t == 0, bars + 8 * B_HE, j ^ 1);
            asm volatile("fence.proxy.async.global;" ::: "memory");
            mbar_wait_w(bars + 8 * B_HE, 0);
#pragma unroll 1
            for (int i = 0; i < 2; i++) h_load(sb, hsrc, i, j, head, wiu, true, i ? 0 : 2048);
        }
    }
    uint32_t g16 = opaque(t * 16);
    {
        const uint32_t wr = ((wg * 4 + wi) ^ head) & 7;
        const uint32_t pc = wg < 2 ? acc_piece(wr >> 2, qd, wr & 3) : acc_piece(kh, wi, 0);
        const uint32_t lm = sb + SM_HB + 4096 + (lane & 7) * 128;
        const uint32_t a0 = wg < 2 ? sb + SM_WL + wg * 2048 + frow + ((fx ^ (2 * wi)) << 4) : blk(LB_STAMP + (wi >> 1), mypar) + stamp_line(wi, lane >> 3) + (lane & 7) * 16;
        const uint32_t a1 = pc + lane * 16;
        const uint32_t a2 = wg < 2 ? pc + 512 + (lane >> 3) * 4 : (role >> 2) * 1024 + (lane < 8 ? (role & 3) * 128 : 384) + lane * 16;
        const uint32_t a3 = wg < 2 ? sb + SM_WO + (wr >> 2) * 32768 + frow + ((fx ^ (2 * (wr & 3))) << 4) : qd * 65536 + head * 2048 + wi * 512 + lane * 4;
        const uint32_t a4 = wg < 2 ? lm + ((fx ^ ((lane >> 4) * 4)) << 4) : lm + (fx << 4) + ((lane >> 4) + 2 * wi) * HCH;
        if (wg < 2) bar_arrive(NB_X2, 384);
        else bar_sync(NB_X2, 384);
        if (NL > 5) {
            sts4(sb + SM_WL2 + tid * 16, wl5.x, wl5.y, wl5.z, wl5.w);
            fence_async_smem();
            bar_sync(NB_WG + 1 + wg, 128);
        }
        sts4(sb + SM_TAB + wg * 5120 + g16, a0, x2o,
             wg ? xso + (wg == 2 ? 32768 : 0) + t * 8 : blk(LB_STAMP + ((lane >> 1) & 1), (lane >> 2) & 1) + stamp_line(lane, qd) + head * 4, tko);
        sts4(sb + SM_TAB + wg * 5120 + 2048 + g16, a1, a2, a3, a4);
        sts2(sb + SM_TAB + wg * 5120 + 4096 + t * 8, __uint_as_float(tbw + t * 16), __uint_as_float((wg ? tbq : tokbase(1)) + t * 16));
    }
    const uint32_t ONES = 0x3f803f80u, tabw = sb + SM_TAB + wg * 5120;
#define LAST ((g16 & 0x70) == 0x70)

    auto pa_ptr = [&](int p) { return arena + (((p & 1) ^ 1) * 32768 + po + lds1(tabw + 4096 + (g16 >> 1))); };
    auto pa_request = [&](int p) { cp_async16(sb + SM_PA + wg * 2048 + g16, pa_ptr(p)); };
    auto pa_get = [&](int p) {
        asm volatile("cp.async.wait_all;" ::: "memory");
        uint4 pa = lds4(sb + SM_PA + wg * 2048 + g16);
        int it = 0;
#pragma unroll 1
        while (any_bit0(pa.x ^ ((p - 1) >> 1) ^ 1) && p > 0 && p <= NSEG) { pa = ldg_b128(pa_ptr(p)); spin_guard(++it); }
        return pa;
    };
    auto pass_init = [&](float* acc, int n, uint4 pa) {
#pragma unroll
        for (int i = 0; i < 4; i++) { acc[2 * i] = bflo((&pa.x)[i]); acc[2 * i + 1] = bfhi((&pa.x)[i]); }
#pragma unroll
        for (int i = 8; i < n; i++) acc[i] = 0.f;
    };
    auto pass_run = [&](auto vc, int p, float* acc, auto mid) {
        constexpr bool V = decltype(vc)::value;
#define HB(ks) dadd(mkdesc(SB0 + SM_HB + ((ks) >> 2) * HCH + ((ks) & 3) * 32, 16, 1024, 1), (p & 1) * (HBUF / 16))
        wg_fence();
#pragma unroll
        for (int i = 0; i < 32; i++) {
            constexpr int GAP = V ? SSG_V : SSG, SS0 = V ? SS0_V : SS0_K;
            const int u = i < SS0 ? 0 : (i - SS0 + GAP - 1) / GAP, q = i - (u < NL ? u : NL);
            if (i >= SS0 && (i - SS0) % GAP == 0 && u < NL) wgmma_tok_ss<V>(acc, dadd(mkdesc(SB0 + sm_wl(u), 8192, 1024, 1), (V ? 2 : wg) * 128), HB(KS(u)));
            else wgmma_tok_rs<V>(acc, w[q], HB(KS(NL + q)), 1);
            mid(i);
        }
        wg_commit();
    };
    auto pass_out = [&](auto tc, int p, float* acc, auto mid) {
        constexpr int TY = decltype(tc)::value;
        const bool V = TY == 2 || (TY == 4 && wg == 2), Q = TY >= 3 && wg == 0;
        const int b = p & 1, s = p - 2;
        (void)s;
        const uint32_t ftag = (((p - 1) >> 1) & 1) ^ 1, ptag = ((p >> 1) & 1) ^ 1;
        const bool tg = V || !(g16 & 64);
        const uint32_t add = tg ? (ftag ^ 1) << 16 : 0u, keep = tg ? 0xfffe0000u : ~0u;
        const uint32_t add1 = V ? 0u : add, keep1 = V ? ~0u : keep;
        const uint32_t add2 = Q ? add : 0u, keep2 = Q ? keep : ~0u;
        uint8_t* pdst = arena + (b * 32768 + (po ^ 2048) + lds1(tabw + 4096 + (g16 >> 1)));
        uint8_t* fdst = arena + ((b ^ 1) * 32768 + lds1(tabw + 12 + g16));
        if (PIN_EPI) asm volatile("" : "+l"(pdst), "+l"(fdst));
        mid(0);
        uint32_t r0 = pack2(pretag(acc[0], add, keep), pretag(acc[1], add1, keep1));
        uint32_t r1 = pack2(acc[2], acc[3]), r3 = pack2(acc[6], acc[7]);
        uint32_t r2 = pack2(pretag(acc[4], add2, keep2), pretag(acc[5], add2, keep2));
        if (!V) { r0 = movm(r0); r1 = movm(r1); r2 = movm(r2); r3 = movm(r3); }
        mid(1);
        stg_b128_if(p < NSEG, pdst, settag(pack2(pretag(acc[8], (ptag ^ 1) << 16, 0xfffe0000u), acc[9]), ptag), pack2(acc[10], acc[11]), pack2(acc[12], acc[13]), pack2(acc[14], acc[15]));
        stg_b128_if(p > 0 && p <= NSEG, fdst, settag(r0, ftag), r1, Q ? settag(r2, ftag) : r2, r3);
    };
    auto nop = [](int) {};
    auto wait0 = [](int i) { if (i == 0) wg_wait<0>(); };
    uint4 tf[2][2];
    auto load_tok = [&](int s, uint32_t o) {
        const uint8_t* ts = arena + ((s & 1) * 32768 + o);
#pragma unroll
        for (int a = 0; a < 2; a++)
#pragma unroll
            for (int b = 0; b < 2; b++) tf[a][b] = ldg_b128(ts + a * 16384 + b * 2048);
    };

    auto wo_load = [&](int stage) {
        if (wg == 2 && ((WO_AT >> (4 * wiu)) & 15) == stage) {
            const int c0 = (wiu >> 1) * 512 + qd * 128 + (wiu & 1) * 64;
            e_expect(bars + 8 * B_WO, 16384);
            e_tma2d(sb + SM_WO + wiu * 16384, tWo, c0, head * DH, bars + 8 * B_WO);
            e_tma2d(sb + SM_WO + wiu * 16384 + 8192, tWo, c0, head * DH + 64, bars + 8 * B_WO);
        }
    };
#pragma unroll 1
    for (int p = 0; p <= (wg >> 1); p++) {
        mbar_wait_w(bars + 8 * (B_HB + p), 0);
        float acc[16];
        pass_init(acc, 16, pa_get(p));
        wo_load(p);
        pass_run(IC<0>(), p, acc, nop);
        if (p) {
            mbar_wait_w(bars + 8 * B_HE, 1);
            asm volatile("fence.proxy.async.global;" ::: "memory");
            h_load(sb, hsrc, 2, j, head, wiu);
        }
        pass_out(IC<4>(), p, acc, wait0);
        if (wg < 2) {
            bar_arrive(NB_C, 384);
            if (wg == 0) bar_arrive(NB_WIN, 384);
        } else if (p == 0) {
            bar_sync(NB_C, 384);
            mbar_arrive_cluster_if(g16 == 0, bars + 8 * B_HE, j ^ 1);
        }
        pa_request(p + 1);
    }
    if (wg < 2) {
        mbar_wait_w(bars + 8 * (B_HB + 1), 0);
        uint4 pa = pa_get(1);
        uint32_t wl = lds1(tabw + g16);
#pragma unroll 1
        for (int s = 0; s < NSEG; s++) {
            uint32_t w0[NL][4], xo, lm, fz = 0;
            float acc[16];
#pragma unroll
            for (int i = 0; i < 4; i++)
                asm volatile("shl.b32 %0, %4, 16; and.b32 %1, %4, 0xffff0000; mov.b32 %2, %5; mov.b32 %3, %5;"
                             : "=&f"(acc[2 * i]), "=f"(acc[2 * i + 1]), "=f"(acc[8 + 2 * i]), "=f"(acc[9 + 2 * i]) : "r"((&pa.x)[i]), "r"(zero));
#pragma unroll
            for (int i = 0; i < NL; i++) ldsm4t(w0[i], wl + (sm_wl(i) - SM_WL));
            if (wg == 0) bar_sync(NB_B, 256);
            else bar_sync(NB_WIN, 384);
            pass_run(IC<0>(), s + 1, acc, [&](int i) { if (i == GATE_AT && wg) bar_arrive(NB_B, 256); });
            xo = lds1(tabw + 4 + g16);
            lm = lds1(tabw + 2060 + g16) + (s & 1) * HBUF;
            pass_out(IC<3>(), s + 1, acc, [&](int i) {
                if (i == 0) {
                    wg_wait<0>();
                    if (wg == 0) bar_arrive(NB_MEM, 384);
                    fz |= clk32();
                }
                if (i == 1 && wg) bar_sync(NB_F, 256);
            });
            asm volatile("" : "+r"(lm));
            if (wg == 0) bar_sync(NB_MEM2, 256);
            else bar_sync(NB_MEM, 384);
            float c[4][4];
            uint32_t bq[PD][4];
#define MEMF(it) ((lm ^ (((it) >> 3) * 32)) + ((it) & 7) * HCH)
#pragma unroll
            for (int it = 0; it < PD; it++) ldsm4(bq[it], MEMF(it));
#pragma unroll
            for (int it = 0; it < 16; it++) {
                uint32_t* bfr = bq[it % PD];
                const uint32_t* wa = 2 * it < NL ? w0[2 * it < NL ? 2 * it : 0] : w[2 * it < NL ? 0 : 2 * it - NL];
                const uint32_t* wb = 2 * it + 1 < NL ? w0[2 * it + 1 < NL ? 2 * it + 1 : 0] : w[2 * it + 1 < NL ? 0 : 2 * it + 1 - NL];
                float *ca = c[(2 * it) & 3], *cb = c[(2 * it + 1) & 3];
                if (it < 2) { mma16816z(ca, wa, bfr[0], bfr[1]); mma16816z(cb, wb, bfr[2], bfr[3]); }
                else { mma16816(ca, wa[0], wa[1], wa[2], wa[3], bfr[0], bfr[1]); mma16816(cb, wb[0], wb[1], wb[2], wb[3], bfr[2], bfr[3]); }
                if (it + PD < 16) ldsm4(bfr, MEMF(it + PD));
            }
            const float qs = wg ? 1.0f : 1.0f / Q_SCALE;
#define CSUM(e) fmaf(c[2][e] + c[3][e], qs, (c[0][e] + c[1][e]) * qs)
            const uint32_t r0 = pack2(CSUM(0), CSUM(1)), r1 = pack2(CSUM(2), CSUM(3));
            bar_arrive(NB_QK + (r0 & zero), 384);
            stg_rlx2(arena + xo, settag(movm(r0), (s & 1) ^ 1), movm(r1));
            const uint32_t tx = later(lds1(sb + SM_LX + 1040) + tm.x2, clk_after(r0, zero) + tm.dx2);
            g16 |= (fz | tx) & zero;
            {
                const uint32_t l16 = sb + (g16 & 0x1f0), g8 = g16 >> 1;
                const uint32_t tag = (s & 1) ^ 1, ttag = ((s >> 1) & 1) ^ 1;
                uint32_t wf[NPF][4], a3;
#define WF(f) (a3 + ((f) & 1) * 16384 + ((f) >> 1) * 2048)
                if (wg == 1) {
                    float sc[5][4];
                    uint4 (&kf)[2][2] = tf;
                    uint32_t qa[2][4], km[4], fz;
                    const uint32_t sd = lds1(sb + SM_TAB + 8 + g16);
                    int it = 0;
                    bool bad;
#pragma unroll 1
                    do {
                        u64 qf[2], x[8];
                        const float2 u = lds2f(tabw + 4096 + g8);
                        load_tok(s, __float_as_uint(u.x));
                        const uint8_t *xp = arena + lds1(tabw + 8 + g16), *tq = arena + ((s & 1) * 32768 + __float_as_uint(u.y));
                        asm volatile("" : "+l"(xp));
                        asm volatile("" : "+l"(tq));
#pragma unroll
                        for (int a = 0; a < 2; a++) qf[a] = ldg_u64(tq + a * 16384);
                        spin_guard(++it);
                        wait_clk(tx);
#pragma unroll
                        for (int i = 0; i < 8; i++) x[i] = ldg_u64(xp + (i >> 2) * 16384 + (i & 3) * 1024);
                        fz = clk32();
                        const uint32_t bt = or3(xor_or(lo32(qf[0]), lo32(qf[1]), ttag), xor_or(kf[0][0].x, kf[0][1].x, ttag), xor_or(kf[1][0].x, kf[1][1].x, ttag));
#pragma unroll
                        for (int a = 0; a < 2; a++) { qa[a][1] = or3(lo32(qf[a]), zero, 0); qa[a][3] = or3(hi32(qf[a]), zero, 0); }
                        fz |= clk32();
#pragma unroll
                        for (int a = 0; a < 2; a++) { qa[a][0] = hadd2v(lo32(x[2 * a]), lo32(x[2 * a + 1])); qa[a][2] = hadd2v(hi32(x[2 * a]), hi32(x[2 * a + 1])); }
#pragma unroll
                        for (int a = 0; a < 2; a++) { km[2 * a] = hadd2v(lo32(x[4 + 2 * a]), lo32(x[5 + 2 * a])); km[2 * a + 1] = hadd2v(hi32(x[4 + 2 * a]), hi32(x[5 + 2 * a])); }
                        bad = any_bit0(or3(or3(bt, xor_or(lo32(x[0]), lo32(x[1]), tag), xor_or(lo32(x[2]), lo32(x[3]), tag)), xor_or(lo32(x[4]), lo32(x[5]), tag), xor_or(lo32(x[6]), lo32(x[7]), tag)));
                    } while (bad);
                    mma16816z(sc[0], qa[0], kf[0][0].x, kf[0][0].y);
                    mma16816z(sc[1], qa[0], kf[0][0].z, kf[0][0].w);
                    mma16816z(sc[2], qa[0], kf[0][1].x, kf[0][1].y);
                    mma16816z(sc[3], qa[0], kf[0][1].z, kf[0][1].w);
                    mma16816z(sc[4], qa[0], km[0], km[1]);
                    mma16816(sc[0], qa[1][0], qa[1][1], qa[1][2], qa[1][3], kf[1][0].x, kf[1][0].y);
                    mma16816(sc[1], qa[1][0], qa[1][1], qa[1][2], qa[1][3], kf[1][0].z, kf[1][0].w);
                    mma16816(sc[2], qa[1][0], qa[1][1], qa[1][2], qa[1][3], kf[1][1].x, kf[1][1].y);
                    mma16816(sc[3], qa[1][0], qa[1][1], qa[1][2], qa[1][3], kf[1][1].z, kf[1][1].w);
                    mma16816(sc[4], qa[1][0], qa[1][1], qa[1][2], qa[1][3], km[2], km[3]);
                    const uint32_t sx = sb + SM_SX + (g16 & 0x1f0) * 5;
                    sts4(sx + (g16 >> 5 & 0x30), pack_h2(sc[0][0], sc[0][1]), pack_h2(sc[1][0], sc[1][1]),
                         pack_h2(sc[2][0], sc[2][1]), pack_h2(sc[3][0], sc[3][1]));
                    sts1(sx + 64 + (g16 >> 7 & 0xc), pack_h2(sc[4][0], sc[4][1]));
                    bar_arrive(NB_X1, 256);
                    const uint32_t now = gtime32();
#pragma unroll
                    for (int n = 0; n < 5; n++) sts2(sb + SM_ST + g8 + n * 1088, sc[n][2], sc[n][3]);
                    bar_arrive(NB_H, 256);
                    a3 = lds1(tabw + 2056 + g16) | (fz & zero);
                    asm volatile("{.reg .pred p; setp.lt.u32 p, %2, 128; @p red.relaxed.gpu.global.max.u32 [%0], %1;}"
                                 ::"l"(arena + sd), "r"(__funnelshift_r(now * 8, s + 1, 8)), "r"(g16) : "memory");
                    if (s == 0) mbar_wait_w(bars + 8 * B_WO, 0);
                    a3 += delay<PF_DLY>(zero);
#pragma unroll
                    for (int f = 0; f < NPF; f++) ldsm4t(wf[f], WF(f));
                } else {
                    if (s == 0) { mbar_wait_w(bars + 8 * B_WO, 0); }
                    const uint32_t need = warp0 ? min(s / 2 + 3, 32) : 0;
                    uint32_t seen = s ? lds1(sb + SM_LX + 1024 + ((g16 >> 2) & 12)) : 0;
                    const bool look = __any_sync(~0u, seen < need);
                    ldg1_if(seen, &g_tick[32 + ((g16 >> 4) & 3) * 8], look);
                    a3 = lds1(tabw + 2056 + g16);
#pragma unroll
                    for (int f = 0; f < NPF0; f++) ldsm4t(wf[f], WF(f));
                    const float2 u = lds2f(tabw + 4096 + g8);
                    const uint8_t *q0 = arena + (tag * 32768 + po + __float_as_uint(u.x)), *q1 = arena + (tag * 32768 + po + __float_as_uint(u.y));
                    wait_clk(tx + tm.h);
                    int it = 0;
                    bool bad;
#pragma unroll 1
                    do {
                        const uint4 p0 = ldg_b128(q0), p1 = ldg_b128(q1);
                        spin_guard(++it);
                        wait_clk(tx + tm.v);
#pragma unroll
                        for (int f = NPF0; f < NPF1; f++) ldsm4t(wf[f], WF(f));
                        sts4(sb + SM_PA + g16, p0.x, p0.y, p0.z, p0.w);
                        sts4(sb + SM_PA + 2048 + g16, p1.x, p1.y, p1.z, p1.w);
                        bad = any_bit0(xor_or(p0.x, p1.x, ((s + 1) >> 1) ^ 1)) && s + 2 <= NSEG;
                    } while (bad);
                    if (look) {
                        if (__any_sync(~0u, seen < need)) seen = wait_count_w(&g_tick[32 + ((g16 >> 4) & 3) * 8], need);
                        asm volatile("fence.acquire.gpu;" ::: "memory");
                        sts1(sb + SM_LX + 1024 + ((g16 >> 2) & 12), seen);
                    }
                    bar_sync(NB_H, 256);
                    softmax_rows<true>(sb + SM_ST, sb + SM_PX, g16, qd * 8, [&](uint32_t v) {
                        a3 += v & zero;
#pragma unroll
                        for (int f = NPF1; f < NPF2; f++) ldsm4t(wf[f], WF(f));
                    });
#pragma unroll
                    for (int f = NPF2; f < NPF; f++) ldsm4t(wf[f], WF(f));
                }
                float2 ls, a12;
                uint8_t *d0, *d1;
                bar_sync(NB_X2, 384);
                float c[4][4];
#pragma unroll
                for (int q = 0; q < 4; q++) {
                    uint32_t ob[4];
                    ldsm4t(ob, l16 + SM_OX + q * 512);
                    if (q == L_AT) ls = lds2f(sb + SM_LX + g8);
                    if (q == 2) { pa = lds4(sb + SM_PA + wg * 2048 + g16); wl = lds1(tabw + g16); }
                    if (q == 2) { a12 = lds2f(tabw + 2048 + g16); d0 = arena + (acc_slot(s + 1) + __float_as_uint(a12.x)); d1 = arena + (acc_slot(s + 1) + __float_as_uint(a12.y)); }
#pragma unroll
                    for (int f = 4 * q; f < 4 * q + 4; f++) {
                        const uint32_t* a = wf[f % NPF];
                        if (f < 4) mma16816z(c[f], a, ob[f & 2], ob[(f & 2) + 1]);
                        else mma16816(c[f & 3], a[0], a[1], a[2], a[3], ob[f & 2], ob[(f & 2) + 1]);
                        if (f + NPF < 16) ldsm4t(wf[f % NPF], WF(f + NPF));
                    }
                }
                if (wg == 0) bar_arrive(NB_WIN, 384);
                const float i0 = rcp_fast(ls.x), i1 = rcp_fast(ls.y);
                uint32_t v[4];
#pragma unroll
                for (int m = 0; m < 4; m++) v[m] = pack_h2((c[m >> 1][(m & 1) * 2] + c[(m >> 1) + 2][(m & 1) * 2]) * i0, (c[m >> 1][(m & 1) * 2 + 1] + c[(m >> 1) + 2][(m & 1) * 2 + 1]) * i1);
                red_h10(LAST, d0, d1, v[0], v[1], v[2], prmt(v[3], ACC_ONE, LAST ? 0x7610 : 0x3210), prmt(v[3], ACC_ONE, 0x7632));
                g16 |= v[0] & zero;
            }
        }
        if (wg) bar_sync(NB_WIN, 384);
    } else {
        auto request = [&](int s, uint32_t o) {
            cp_async16(sb + SM_PA + 4096 + g16, arena + (((s & 1) ^ 1) * 32768 + po + o));
            const uint8_t* ts = arena + ((s & 1) * 32768 + o);
#pragma unroll
            for (int i = 0; i < 4; i++) cp_async16(sb + SM_VF + i * 2048 + g16, ts + (i >> 1) * 16384 + (i & 1) * 2048);
        };
        auto fetch = [&](int s, uint4 t1, auto wait, auto after) {
            const uint32_t mo = acc_slot(s) + t1.x, eo = mo - (g16 & 0x1f0) + 512 + ((g16 >> 5) & 12);
            const uint8_t *ms = arena + mo, *es = arena + eo;
            uint32_t e[4] = {0, 0, 0, 0}, sel = LAST ? 0x5410 : 0x3210, dst[4];
#pragma unroll
            for (int i = 0; i < 4; i++) dst[i] = (t1.w + (s & 1) * HBUF) ^ (i * 32);
            asm volatile("" : "+l"(ms), "+l"(es), "+r"(e[0]), "+r"(e[1]), "+r"(e[2]), "+r"(e[3]), "+r"(sel), "+r"(dst[0]), "+r"(dst[1]), "+r"(dst[2]), "+r"(dst[3]));
            uint32_t late = wait(), fz;
            int it = 0;
            bool bad;
#pragma unroll 1
            do {
                uint4 m[4];
                uint32_t b = 0;
#pragma unroll
                for (int i = 0; i < 4; i++) {
                    m[i] = ldg_rlx4(ms + i * 1024);
                    ldg1_if(e[i], es + i * 1024, LAST);
                }
                if (it == 0) bar_arrive(NB_F, 256);
                const uint32_t now = clk32();
                fz = now;
                after(now & zero);
                sts1(sb + SM_LX + 1040, now - min(late >> 8, 8u) * 57);
                late = 0;
                spin_guard(++it);
#pragma unroll
                for (int i = 0; i < 4; i++) {
                    if (STG_FENCE >> i & 1) fz |= clk32();
                    b |= xor_or(m[i].w, e[i], ACC_ALL);
                    stsm4t(dst[i], h2bf(m[i].x), h2bf(m[i].y), h2bf(m[i].z), h2bf(prmt(m[i].w, e[i], sel)));
                }
                bad = __any_sync(~0u, LAST && b > 0xffffu);
            } while (bad);
            bar_arrive(NB_MEM, 384);
            bar_arrive(NB_MEM2, 256);
            g16 |= fz & zero;
        };
        fetch(0, lds4(tabw + 2048 + g16), []() { return 0u; }, [&](uint32_t z) { request(0, lds1(tabw + 4096 + (g16 >> 1)) + z); });
        wo_load(2);
#pragma unroll 1
        for (int s = 0;; s++) {
            const uint32_t tag = (s & 1) ^ 1, ttag = ((s >> 1) & 1) ^ 1, l16 = sb + (g16 & 0x1f0), g8 = g16 >> 1;
            const int p = s + 2;
            fence_async_smem();
            stg_b128_if(g16 < ((role & 3) ? 128 : 160), arena + (acc_slot(s + 3) + lds1(tabw + 2052 + g16)), 0, 0, 0, 0);
            const uint4 pa = pa_get(p);
            if (p <= NSEG) mbar_wait_w(bars + 8 * (B_HB + (p & 1)), (p >> 1) & 1);
            asm volatile("fence.proxy.async.global;" ::: "memory");
            if (warp0 && s + 3 <= NSEG) e_expect(bars + 8 * (B_HB + ((s + 3) & 1)), 32768);
            uint8_t* xd = arena + lds1(tabw + 4 + g16);
            uint32_t tx;
            float acc[20];
            pass_init(acc, 20, pa);
            bar_sync(NB_QK, 384);
            pass_run(IC<1>(), p, acc, nop);
            pass_out(IC<2>(), p, acc, [&](int i) {
                if (i) return;
                wg_wait<0>();
                const uint32_t r0 = pack2(acc[16], acc[17]);
                stg_rlx2(xd, settag(r0, tag), pack2(acc[18], acc[19]));
                tx = clk_after(r0, zero) + 100;
            });
            uint4 (&vf)[2][2] = tf;
#pragma unroll
            for (int i = 0; i < 4; i++) vf[i >> 1][i & 1] = lds4(sb + SM_VF + i * 2048 + g16);
            uint32_t xv[4] = {0, 0, 0, 0};
            float oc[2][4], lc[4];
            auto pv = [&](uint32_t p0, uint32_t p1, uint32_t p2, uint32_t p3, uint32_t p4, auto mid) {
                lc[0] = lc[1] = lc[2] = lc[3] = 0.f;
                mma16816z(oc[0], &vf[0][0].x, p0, p1);
                mma16816z(oc[1], &vf[1][0].x, p0, p1);
                mma16816(lc, ONES, ONES, ONES, ONES, p0, p1);
                mma16816(oc[0], vf[0][1].x, vf[0][1].y, vf[0][1].z, vf[0][1].w, p2, p3);
                mma16816(oc[1], vf[1][1].x, vf[1][1].y, vf[1][1].z, vf[1][1].w, p2, p3);
                mma16816(lc, ONES, ONES, ONES, ONES, p2, p3);
                mid();
                mma1688(oc[0], xv[0], xv[1], p4);
                mma1688(oc[1], xv[2], xv[3], p4);
                mma1688(lc, ONES, ONES, p4);
            };
            uint32_t so, to, fz = 0;
            uint4 t1;
            int it = 0;
            bool bad;
#pragma unroll 1
            do {
#pragma unroll 1
                for (int i = it; i > 0; i &= zero) load_tok(s, lds1(tabw + 4096 + g8));
                u64 xr[4];
                const uint8_t* xp = arena + lds1(tabw + 8 + g16);
                asm volatile("" : "+l"(xp));
                const uint32_t bt = or3(xor_or(vf[0][0].x, vf[0][1].x, ttag), xor_or(vf[1][0].x, vf[1][1].x, ttag), 0);
                uint32_t sa = sb + SM_SX + (g16 & 0x1f0) * 5;
                asm volatile("" : "+r"(sa));
                spin_guard(it);
                wait_clk(tx);
                if (it++ == 0) bar_sync(NB_X1, 256);
                uint4 sx[5];
#pragma unroll
                for (int i = 0; i < 5; i++) sx[i] = lds4(sa + i * 16);
                __syncwarp();
#pragma unroll
                for (int i = 0; i < 4; i++) xr[i] = ldg_u64(xp + (VP_AT == 2 ? sx[0].x & zero : 0) + i * 1024);
                uint32_t a[5], pm[5];
#pragma unroll
                for (int n = 0; n < 5; n++) {
                    uint32_t u[4];
#pragma unroll
                    for (int w = 0; w < 4; w++) u[w] = n < 4 ? (&sx[w].x)[n] : (&sx[4].x)[w];
                    a[n] = hadd2h(hadd2h(u[0], u[1]), hadd2h(u[2], u[3]));
                }
                uint32_t m = hmax2h(hmax2h(hmax2h(a[0], a[1]), hmax2h(a[2], a[3])), a[4]);
                const uint32_t m1 = __shfl_xor_sync(~0u, m, 1), m2 = __shfl_xor_sync(~0u, m, 2), m3 = __shfl_xor_sync(~0u, m, 3);
                m = hmax2h(hmax2h(m, m1), hmax2h(m2, m3));
                so = lds1(tabw + g16); t1 = lds4(tabw + 2048 + g16); to = lds1(tabw + 4096 + g8);
                const float2 mm = unpack_h2(m);
                const float mf = -SM_L2E * fmaxf(mm.x, mm.y);
#pragma unroll
                for (int n = 0; n < 5; n++) { const float2 u = unpack_h2(a[n]); pm[n] = pack2(ex2(fmaf(u.x, SM_L2E, mf)), ex2(fmaf(u.y, SM_L2E, mf))); }
                pv(pm[0], pm[1], pm[2], pm[3], pm[4], [&]() {
                    if (PV_FENCE & 1) fz = clk32();
#pragma unroll
                    for (int i = 0; i < 2; i++) { xv[2 * i] = hadd2v(lo32(xr[2 * i]), lo32(xr[2 * i + 1])); xv[2 * i + 1] = hadd2v(hi32(xr[2 * i]), hi32(xr[2 * i + 1])); }
                });
                bad = any_bit0(or3(bt, xor_or(lo32(xr[0]), lo32(xr[1]), tag), xor_or(lo32(xr[2]), lo32(xr[3]), tag)));
                if (PV_FENCE & 2) fz |= clk32();
                stsm4(sb + SM_OX + g16, pack2(oc[0][0], oc[0][1]), pack2(oc[0][2], oc[0][3]), pack2(oc[1][0], oc[1][1]), pack2(oc[1][2], oc[1][3]));
                sts2(sb + SM_LX + g8, lc[0], lc[1]);
            } while (bad);
            bar_sync(NB_X2, 384);
            const uint8_t* sp = arena + so;
            uint4 sv = ldg_rlx4(sp);
            if (s + 3 <= NSEG) h_load(sb, hsrc, s + 3, j, head, wiu, false);
            const uint4 pp = lds4(l16 + SM_PX + delay<TPV_DLY>(zero));
            pv(pp.x, pp.y, pp.z, pp.w, lds1(sb + SM_PX + 512 + ((g16 >> 2) & 0x7c)), []() {});
            const float i0 = rcp_fast(lc[0]), i1 = rcp_fast(lc[1]);
            bar_arrive(NB_WIN + ((__float_as_uint(i0) | fz) & zero), 384);
            uint8_t* od = (uint8_t*)g_O + ((size_t)s * (32 * NH * DH * 2) + t1.z);
            const uint32_t ov[4] = {pack2(oc[0][0] * i0, oc[0][1] * i1), pack2(oc[0][2] * i0, oc[0][3] * i1), pack2(oc[1][0] * i0, oc[1][1] * i1), pack2(oc[1][2] * i0, oc[1][3] * i1)};
#pragma unroll
            for (int a = 0; a < 4; a++) if (s + 1 == NSEG) stg_rlx1(od + a * 128, ov[a]);
            if (s + 1 == NSEG) break;
            fetch(s + 1, t1, [&]() {
                int it = 0;
#pragma unroll 1
                while (__any_sync(~0u, (int)(min(__vimin3_u32(sv.x, sv.y, sv.z), sv.w) >> 24) <= s)) {
                    sv = ldg_rlx4(sp);
                    spin_guard(++it);
                }
                const uint32_t tgo = (__reduce_max_sync(~0u, max(max3u(sv.x, sv.y, sv.z), sv.w)) + tm.go + (sv.x & zero)) << 8;
                int late;
#pragma unroll 1
                do { late = gtime32() * 8 - tgo; } while (late < 0);
                __syncwarp();
                return (uint32_t)late;
            }, [&](uint32_t z) {
#pragma unroll
                for (int a = 0; a < 4; a++) stg_rlx1(od + a * 128, ov[a]);
                request(s + 1, to + z);
            });
        }
    }
    asm volatile("cp.async.wait_all;" ::: "memory");
}

struct RecMaps { CUtensorMap wq, wk, wv, wo; };
struct RecPtrs { const bf16 *x, *mem0, *c, *wmod, *w1, *w3; uint8_t* arena; uint32_t zero; RecTime tm; };

__device__ __forceinline__ float silu_bf(const bf16* c, int i) {
    const float v = __bfloat162float(c[i]);
    return bfround(__fdividef(v, 1.0f + __expf(-v)));
}
__device__ __noinline__ void rec_ln(float* coef, const RecPtrs& p, int id, int r0) {
    int r1 = 32;
    const int tid = threadIdx.x;
    const int lane = tid & 31, wid = tid >> 5;
    const uint32_t ring = smem_u32(coef) - SM_PRE + wid * 8192 + lane * 16;
    auto fetch = [&](int r) {
        if (r < r1) {
            const bf16* src = p.x + (size_t)(r * 64 + (id * 8 + wid) * 2) * DM + lane * 8;
#pragma unroll
            for (int i = 0; i < 8; i++) cp_async16(ring + (r & 1) * 4096 + i * 512, src + i * 256);
        }
        asm volatile("cp.async.commit_group;" ::: "memory");
    };
    auto row8 = [&](uint32_t a, float* f) {
        const uint4 v = lds4(a);
        f[0] = bflo(v.x); f[1] = bfhi(v.x); f[2] = bflo(v.y); f[3] = bfhi(v.y); f[4] = bflo(v.z); f[5] = bfhi(v.z); f[6] = bflo(v.w); f[7] = bfhi(v.w);
    };
#pragma unroll 1
    for (int r = r0 - 2; r < r1; r++) {
        if (r >= r0) {
            asm volatile("cp.async.wait_group 1;" ::: "memory");
            const uint32_t a = ring + (r & 1) * 4096;
            float m[2] = {0.f, 0.f}, t[2];
#pragma unroll 1
            for (int ps = 0; ps < 2; ps++) {
                t[0] = t[1] = 0.f;
#pragma unroll 1
                for (int i = 0; i < 4; i++)
#pragma unroll
                    for (int h = 0; h < 2; h++) {
                        float f[8];
                        row8(a + h * 2048 + i * 512, f);
#pragma unroll
                        for (int e = 0; e < 8; e++) { const float d = f[e] - m[h]; t[h] = fmaf(d, ps ? d : 1.0f, t[h]); }
                    }
#pragma unroll
                for (int o = 16; o; o >>= 1) { t[0] += __shfl_xor_sync(~0u, t[0], o); t[1] += __shfl_xor_sync(~0u, t[1], o); }
                if (ps == 0) { m[0] = t[0] * (1.0f / DM); m[1] = t[1] * (1.0f / DM); }
            }
            uint32_t nm[2];
#pragma unroll
            for (int h = 0; h < 2; h++) { nm[h] = pack2(-m[h], -m[h]); t[h] = rcp_fast(bfround(sqrtf(bfround(bfround(t[h] * (1.0f / DM)) + 1e-5f)))); }
            if (r == r0) {
#pragma unroll 1
                for (int i = tid; i < 2 * DM / 4; i += 256) {
                    float4 u;
                    int it = 0;
                    uint32_t ok;
#pragma unroll 1
                    do {
                        uint4 v[8];
#pragma unroll
                        for (int k = 0; k < 8; k++) v[k] = ldg_rlx4(g_modp + k * 2 * DM + i * 4);
                        ok = 1;
                        u = make_float4(0.f, 0.f, 0.f, 0.f);
#pragma unroll
                        for (int k = 0; k < 8; k++) {
                            ok &= v[k].x & v[k].y & v[k].z & v[k].w;
                            u.x += __uint_as_float(v[k].x); u.y += __uint_as_float(v[k].y); u.z += __uint_as_float(v[k].z); u.w += __uint_as_float(v[k].w);
                        }
                        spin_guard(++it);
                    } while (!ok);
                    const uint32_t one = i >= DM / 4 ? 0x3f803f80u : 0u;
                    ((uint2*)coef)[i] = make_uint2(hadd2v(pack2(u.x, u.y), one), hadd2v(pack2(u.z, u.w), one));
                }
                bar_sync(NB_FIN0, 256);
            }
            const int row = r * 64 + (id * 8 + wid) * 2;
#pragma unroll 1
            for (int i = 0; i < 4; i++) {
                const uint4 sh = ((const uint4*)coef)[i * 32 + lane], sc = ((const uint4*)coef)[128 + i * 32 + lane];
                const int own = ((row >> 4) & 1) == (i >> 1), rr = row & 15;
                const uint32_t off = ((row >> 5) + own) * 65536 + (i * 4 + (lane >> 3)) * 4096 + (rr + (own ? 0 : 16)) * 128 + (((lane & 7) ^ (rr & 7)) << 4);
#pragma unroll
                for (int h = 0; h < 2; h++) {
                    uint4 y = lds4(a + h * 2048 + i * 512);
#pragma unroll
                    for (int e = 0; e < 4; e++) {
                        const uint32_t d = hadd2v((&y.x)[e], nm[h]);
                        (&y.x)[e] = hadd2v(hmul2b(pack2(bflo(d) * t[h], bfhi(d) * t[h]), (&sc.x)[e]), (&sh.x)[e]);
                    }
                    *(uint4*)((uint8_t*)g_himg + (off ^ (h * 144))) = y;
                }
            }
            if (r == 0) {
                int v, it = 0;
#pragma unroll 1
                do { v = *(volatile int*)((uint8_t*)coef - SM_PRE + SM_BAR + 192); spin_guard(++it); } while (v == INT_MIN);
                if (v >= 0) r1 = 2;
            }
        }
        fetch(r + 2);
        if (r < r0) continue;
        bar_sync(r == 0 ? NB_C : r == 1 ? NB_FIN0 : NB_LN, r == 0 ? 320 : r == 1 ? 256 : 288);
        if (r < 2 && wid == r) {
            if (r == 1) bar_arrive(NB_B, 64);
            if (lane == 0) { signal_count(&g_tick[32 + id * 8]); }
            __syncwarp();
        }
    }
}
template <int NQ, int CG>
__device__ __forceinline__ void side_gemv(const bf16* w, int ld, int ncol, const float* coef, float* red, float* out, int ostride, bool round) {
    constexpr int KG = 384 / CG, W = CG * 8;
    const int tid = threadIdx.x, cg = tid % CG, kg = tid / CG;
    float acc[NQ][8];
#pragma unroll
    for (int q = 0; q < NQ; q++)
#pragma unroll
        for (int j = 0; j < 8; j++) acc[q][j] = 0.f;
    if (cg * 8 < ncol) {
        const bf16* src = w + cg * 8;
        const uint32_t ring = smem_u32(red) + 36864 + tid * 16;
        auto fetch = [&](int k0, int slot) {
#pragma unroll
            for (int i = 0; i < 4; i++)
                if (k0 + i * KG < DM) cp_async16_ef(ring + (slot * 4 + i) * 6144, src + (size_t)(k0 + i * KG) * ld);
            asm volatile("cp.async.commit_group;" ::: "memory");
        };
#pragma unroll 1
        for (int g = 0; g < 5; g++) fetch(kg + g * 4 * KG, g);
#pragma unroll 1
        for (int k0 = kg, slot = 0; k0 < DM; k0 += 4 * KG) {
            fetch(k0 + 20 * KG, slot ? slot - 1 : 5);
            asm volatile("cp.async.wait_group 5;" ::: "memory");
#pragma unroll
            for (int i = 0; i < 4; i++) {
                const int k = k0 + i * KG;
                if (k < DM) {
                    const uint4 v = lds4(ring + (slot * 4 + i) * 6144);
                    const float f[8] = {bflo(v.x), bfhi(v.x), bflo(v.y), bfhi(v.y), bflo(v.z), bfhi(v.z), bflo(v.w), bfhi(v.w)};
#pragma unroll
                    for (int q = 0; q < NQ; q++) {
                        const float cf = coef[q * DM + k];
#pragma unroll
                        for (int j = 0; j < 8; j++) acc[q][j] = fmaf(cf, f[j], acc[q][j]);
                    }
                }
            }
            slot = slot == 5 ? 0 : slot + 1;
        }
    }
    __syncthreads();
#pragma unroll
    for (int q = 0; q < NQ; q++)
#pragma unroll
        for (int j = 0; j < 8; j++) red[(kg * NQ + q) * W + cg * 8 + j] = acc[q][j];
    __syncthreads();
#pragma unroll 1
    for (int i = tid; i < NQ * W; i += 384) {
        const int q = i / W, cidx = i % W;
        float t = 0.f;
#pragma unroll
        for (int k = 0; k < KG; k++) t += red[k * NQ * W + i];
        if (cidx < ncol) out[q * ostride + cidx] = round ? bfround(t) : t;
    }
}
__device__ __noinline__ void rec_side(float* sm, const RecPtrs& p, int id) {
    const int tid = threadIdx.x;
    float *coef = sm, *red = sm + 3 * DM;
    if (tid < 256 && blockIdx.x < 128) rec_ln(sm + SM_PRE / 4, p, id, 2);
    if (tid >> 5 == 8) {
#pragma unroll 1
        for (int n = 1; n < 31; n++) {
            bar_sync(NB_LN, 288);
            if (tid == 256) { if (n == 1) wait_count1(&g_tick[32 + id * 8], 2); signal_count(&g_tick[32 + id * 8]); }
            __syncwarp();
        }
    }
    __syncthreads();
    for (int i = tid; i < 2 * S_; i += 384) g_st[id * 2 * S_ + i] = 0.f;
    if (id == 0) for (int i = tid; i < 2 * 32; i += 384) g_pcnt[i * 8] = 0;
    if (id == 1) for (int i = tid; i < 6 * 256; i += 384) g_pflag[i] = 0;
    for (int i = tid; i < DM; i += 384) { coef[i] = silu_bf(p.c, i); coef[2 * DM + i] = 1.0f; }
    __syncthreads();
    side_gemv<1, 128>(p.wmod + (2 + id) * DM, 6 * DM, DM, coef, red, g_mod + (2 + id) * DM, 0, true);
    __syncthreads();
    if (tid == 0) signal_count(&g_tick[8]);
    side_gemv<1, 128>(p.w3 + id * (FF / 4), FF, FF / 4, coef + 2 * DM, red, g_vec + 3 * DM + id * (FF / 4), 0, false);
    if (tid == 0) wait_count1(&g_tick[8], 4);
    __syncthreads();
    for (int i = tid; i < DM; i += 384) { coef[i] = 1.0f + __ldcg(g_mod + 4 * DM + i); coef[DM + i] = __ldcg(g_mod + 3 * DM + i); }
    __syncthreads();
    if (id == 1 && tid < 32) {
        float t[5] = {0, 0, 0, 0, 0};
        for (int i = tid; i < DM; i += 32) {
            const float a = coef[i], b = coef[DM + i];
            t[0] += a; t[1] += a * a; t[2] += a * b; t[3] += b; t[4] += b * b;
        }
#pragma unroll
        for (int q = 0; q < 5; q++) { const float r = warp_sum(t[q]); if (tid == 0) g_cst[q] = r * (1.0f / DM); }
    }
    side_gemv<3, 32>(p.w1 + id * 256, DM, 256, coef, red, g_vec + id * 256, DM, false);
}

__device__ __forceinline__ void pair_place(int c, int& d, int& pi) {
    const int c7 = ((c - 36) * 37) >> 8;
    d = c < 4 ? 0 : c < 36 ? (c - 4) & 7 : c - 35 - 7 * c7;
    pi = c < 4 ? c : c < 36 ? ((c - 4) >> 3) + (d ? 0 : 4) : 4 + c7;
}
__global__ void __cluster_dims__(2, 1, 1) __launch_bounds__(384, 1)
k_rec(const __grid_constant__ RecMaps mp, const __grid_constant__ RecPtrs p) {
    extern __shared__ uint8_t smraw[];
    const uint32_t sb = smem_u32(smraw);
    if ((sb & 0x3FFFF) != SB0) __trap();
    const uint32_t bars = sb + SM_BAR;
    const int tid = threadIdx.x, lane = tid & 31, b = blockIdx.x;
    const int wid = __reduce_max_sync(~0u, tid >> 5);
    const uint32_t rank = b & 1;
    uint8_t* arena = p.arena;
    volatile int* sinfo = (volatile int*)(smraw + SM_BAR + 192);
    if (tid == 0) sinfo[0] = INT_MIN;
    uint32_t smid;
    asm("mov.u32 %0, %%smid;" : "=r"(smid));
    smid = __reduce_max_sync(~0u, smid);
    int d, pi;
    pair_place(smid >= 124 ? (smid >> 1) - 62 : (smid >> 1) + 4, d, pi);
    const int guess = b < 128 && smid < 132 && (smid & ~3u) != 120 && (NO_GUESS % 5 == 0 || (NO_GUESS == 2 && b != 20)) ? d * 8 + pi : -9;
    if (wid == 8) {
        if (lane == 0) {
#pragma unroll
            for (int i = 0; i < 17; i++) mbar_init(bars + 8 * i, i == B_WO ? 4 : 1);
            asm volatile("fence.mbarrier_init.release.cluster; fence.proxy.async.shared::cta;" ::: "memory");
            mbar_expect(bars + 8 * B_ROLE, 8);
        }
        __syncwarp();
    }
    asm volatile("barrier.cluster.arrive.relaxed.aligned;" ::: "memory");
    int pr = 0, hA = 0;
    if (wid < 8) {
        if (b < 128) {
            const int cb = (b & 15) * 128, k0 = (b >> 4) * 128 + (tid >> 4);
            uint4 v[8];
#pragma unroll
            for (int i = 0; i < 8; i++) v[i] = __ldg((const uint4*)(p.wmod + (size_t)(k0 + 16 * i) * (6 * DM) + cb + (tid & 15) * 8));
            float acc[8] = {0, 0, 0, 0, 0, 0, 0, 0};
            const float sl = silu_bf(p.c, k0 + 16 * (lane & 7));
#pragma unroll
            for (int i = 0; i < 8; i++) {
                const float sv = __shfl_sync(~0u, sl, i, 16);
                acc[0] += sv * bflo(v[i].x); acc[1] += sv * bfhi(v[i].x); acc[2] += sv * bflo(v[i].y); acc[3] += sv * bfhi(v[i].y);
                acc[4] += sv * bflo(v[i].z); acc[5] += sv * bfhi(v[i].z); acc[6] += sv * bflo(v[i].w); acc[7] += sv * bfhi(v[i].w);
            }
            float* red = (float*)(smraw + SM_PRE);
            *(float4*)(red + (tid >> 4) * 128 + (tid & 15) * 8) = make_float4(acc[0], acc[1], acc[2], acc[3]);
            *(float4*)(red + (tid >> 4) * 128 + (tid & 15) * 8 + 4) = make_float4(acc[4], acc[5], acc[6], acc[7]);
            bar_sync(NB_FIN0, 256);
            if (wid < 4) {
                float t = 0;
#pragma unroll
                for (int i = 0; i < 16; i++) t += red[i * 128 + tid];
                stg_rlx1(&g_modp[(b >> 4) * 2 * DM + cb + tid], __float_as_uint(t) | 1u);
            }
        } else {
            rec_ln((float*)(smraw + SM_PRE), p, b - 128, 0);
        }
    } else if (wid >= 10 && b >= 128) {
        {
            const int u = (b - 128) * 2 + wid - 10;
            const uint16_t* src = (const uint16_t*)p.mem0 + (lane & 3) * 2 * DM + (u >> 1) * 128 + (u & 1) * 32 + (lane >> 2);
            stg_rlx4(arena + (LB_STAMP << 13) + u * 2048 + (lane >> 4) * 1024 + ((lane >> 3) & 1) * 256 + (lane & 7) * 16, 0, 0, 0, 0);
#pragma unroll 1
            for (int r = 0; r < 4; r++) {
                uint32_t w[5];
#pragma unroll
                for (int e = 0; e < 4; e++) {
                    const uint16_t* q = src + (r >> 1) * 512 + (r & 1) * 16 + (e & 2) * 32 + (e & 1) * 8;
                    w[e] = pack_h2(bflo(q[0]), bflo(q[DM]));
                }
                w[4] = __shfl_sync(~0u, __byte_perm(w[3], ACC_ALL, 0x7632), lane * 8 + 7);
                w[3] = __byte_perm(w[3], ACC_ALL, (lane & 7) == 7 ? 0x7610 : 0x3210);
#pragma unroll 1
                for (int i = 0; i < 3; i++) {
                    uint8_t* d = arena + acc_slot(i) + acc_piece(r >> 1, u >> 1, (u & 1) * 2 + (r & 1));
                    stg_rlx4(d + lane * 16, w[0], w[1], w[2], w[3]);
                    if (lane < 8) stg_rlx1(d + 512 + lane * 4, w[4]);
                    w[0] = w[1] = w[2] = w[3] = w[4] = 0;
                }
            }
            bar_arrive(NB_C, 320);
        }
    } else if (rank == 0 && (wid > 8 || b >= 128)) {
        uint32_t best = ~0u;
        const int pg = wid < 11 ? 0 : 1 + (b >> 1) % 3;
        uint32_t* q = (uint32_t*)(arena + (pg << 21) + (pg ? blk(b >> 1, 1) : blk(LB_PROBE, wid & 1) + b * 16));
        if (lane < 8) stg_rlx1(q + lane, 0);
        u64 tk2 = ldg_u64(&g_tick[0]);
        __syncwarp();
        if (lane == 0) {
            q += 3;
            uint32_t v = atomicAdd(q, 1u);
#pragma unroll 1
            for (int r = 0; r < NPROBE; r++) {
                const uint32_t t0 = clk32() + (v >> 8);
                v = atomicAdd(q + (v >> 8), 1u);
                uint32_t t1;
                asm volatile("{.reg .pred p; setp.eq.u32 p, %1, 0xffffffff; @p exit; mov.u32 %0, %%clock;}" : "=r"(t1) : "r"(v) : "memory");
                best = min(best, t1 - t0);
            }
            sinfo[pg ? 4 : 2 + (wid & 1)] = best;
        }
        bar_sync(NB_KDONE, b < 128 ? 96 : 64);
        if (wid == 9) {
            const int par = (sinfo[2] > sinfo[3]) ^ (NO_GUESS == 5 && smid == 126), ncl = gridDim.x >> 1;
            const bool ok = guess >= 0 && !(smid & 1), reg = ok && guess >= 4;
            u64 add = (1u << (8 * par)) + 65536 + (reg ? 1ull << 24 : (1ull << (56 + 4 * par)) + ((u64)ok << 37));
            if (b < 128) add += (u64)((2 * sinfo[4] < sinfo[2] + sinfo[3]) != par) << (32 + 8 * ((b >> 1) % 3));
            int it = 0;
            if (NO_GUESS % 5 >= 3 ? b < 2 * (NO_GUESS - 2) || (NO_GUESS == 3 && b == 130) : b >= 128) {
#pragma unroll 1
                while (!__all_sync(~0u, (int)((lo32(tk2) >> 16) & 255) >= ncl - 2)) { tk2 = ldg_u64(&g_tick[0]); spin_guard(++it); }
            }
            if (lane == 0) {
                if (guess >= 0) add += atomicXor(&g_tick[2], par << (guess >> 1)) & p.zero;
                add = atomicAdd((u64*)&g_tick[0], add);
            }
#pragma unroll 1
            while (!__all_sync(~0u, (int)((lo32(tk2) >> 16) & 255) >= ncl)) { tk2 = ldg_u64(&g_tick[0]); spin_guard(++it); }
            add = __shfl_sync(~0u, add, 0);
            const uint32_t diff = ldg_rlx1(&g_tick[2]);
            const bool most = lo32(tk2) >> 24 == 60 && diff < 4;
            const int nh = most ? 2 : NH, sh = most ? 56 : 0, w = most ? 4 : 8, mk = (1 << w) - 1;
            const int n0 = (tk2 >> sh) & mk, n1 = (tk2 >> (sh + w)) & mk, tk = (add >> (sh + w * par)) & mk;
            hA = min(n0 >> 1, nh);
            const int q0 = 2 * hA, q1 = 2 * nh - q0;
            const int over = tk - (par ? q1 : q0), lack = max(par ? q0 - n0 : q1 - n1, 0);
            if (over < 0) pr = par ? q0 + tk : tk;
            else if (over < lack) pr = (par ? n0 : q0 + n1) + over;
            else pr = -1 - (over - lack + (par ? max(n0 - q0, 0) : 0));
            if (most && (reg || (!diff && (hi32(tk2) & 0xe0) == 0x80))) { pr = guess; hA = par ? 0 : NH; }
#pragma unroll
            for (int i = 0; i < 3; i++) hA |= ((hi32(tk2) >> (8 * i)) & 31) > 10 ? 256 << i : 0;
        }
    }
    asm volatile("barrier.cluster.wait.aligned;" ::: "memory");
    if (wid == 9 && rank == 0) {
        asm volatile("{.reg .pred p; .reg .b32 a; setp.lt.u32 p, %3, 2; @p mapa.shared::cluster.u32 a, %0, %3;\n"
                     " @p st.async.shared::cluster.mbarrier::complete_tx::bytes.v2.u32 [a + 192], {%1, %2}, [a + %4];}"
                     ::"r"(bars), "r"(pr), "r"(hA), "r"(lane), "n"(8 * B_ROLE) : "memory");
        if (b >= 128) atomicOr(&g_tick[4], (pr < 0 ? 4u : 1u) << ((b - 128) >> 1));
    }
    if (wid == 8) {
        int pu = guess;
        bool fast = false, known = false;
        wait_clk(clk32() + W_T0 + (lane & p.zero));
#pragma unroll 1
        for (int n = 0; n < 12; n++) {
            if (!known && (n == W_SPEC || pu < 0)) {
                mbar_wait_w(bars + 8 * B_ROLE, 0);
                known = true;
                const int r = __reduce_max_sync(~0u, sinfo[0]);
                if (r != pu) {
#pragma unroll 1
                    for (; n > 0; n--) {
                        mbar_wait_w(bars + 8 * (B_W + n - 1), 0);
                        asm volatile("{.reg .pred p; elect.sync _|p, 0xffffffff; @p mbarrier.arrive.shared.b64 _, [%0];}" ::"r"(bars + 8 * (B_W + n - 1)) : "memory");
                    }
                    pu = r;
                    fast = r < 4;
                }
                bar_arrive(NB_A, 384);
                if (b >= 128 && pu < 0) bar_sync(NB_B, 64);
                if (pu < 0) break;
            }
            const int rot = b >= 128 ? 8 : 0, i = (n + rot) % 12;
            if (rot && n == 4) bar_sync(NB_B, 64);
            if (n >= W_INFL && !fast) {
                const uint32_t v = ldg_rlx1(&g_tick[32 + (lane & 3) * 8]);
                mbar_wait_w(bars + 8 * (B_W + (n - W_INFL + rot) % 12), 0);
                fast = __all_sync(~0u, v != 0);
            }
            const int m = i < 8 ? i & 1 : 2, k = i < 8 ? i >> 1 : i - 8, c0 = (pu >> 1) * 128 + rank * 64, r0 = (pu & 1) * 512;
            const uint32_t dst = sb + m * 65536 + k * 16384, br = bars + 8 * (B_W + i);
            e_expect(br, 16384);
            e_tma2d_ef(dst, &mp.wq + m, c0, r0 + k * 128, br);
            e_tma2d_ef(dst + 8192, &mp.wq + m, c0, r0 + k * 128 + 64, br);
        }
    } else {
        bar_sync(NB_A, 384);
    }
    const int prr = __reduce_max_sync(~0u, sinfo[0]);
    hA = __reduce_max_sync(~0u, sinfo[1]);
    if (prr < 0) {
        int j = (b - 128) >> 1;
        if (b < 128) {
            uint32_t v;
            int it = 0;
#pragma unroll 1
            do { v = __reduce_max_sync(~0u, ldg_rlx1(&g_tick[4])); spin_guard(++it); } while (__popc(v) < 2);
            j = v == 3 ? -1 - prr : (v & 1) ^ 1;
        }
        rec_side((float*)smraw, p, j * 2 + rank);
        return;
    }
    const int role = (prr >> 1) * 4 + rank * 2 + (prr & 1);
    rec_main(sb, &mp.wo, arena, role, hA, wid >> 2, p.zero, p.tm);
}

__device__ __forceinline__ void wgmma_ss192(float* d, uint64_t a, uint64_t b, int sc) {
    asm volatile("{.reg .pred p; setp.ne.b32 p, %98, 0;\n wgmma.mma_async.sync.aligned.m64n192k16.f32.bf16.bf16 "
                 "{%0,%1,%2,%3,%4,%5,%6,%7,%8,%9,%10,%11,%12,%13,%14,%15,%16,%17,%18,%19,%20,%21,%22,%23,%24,%25,%26,%27,%28,%29,%30,%31,%32,%33,%34,%35,%36,%37,%38,%39,%40,%41,%42,%43,%44,%45,%46,%47,%48,%49,%50,%51,%52,%53,%54,%55,%56,%57,%58,%59,%60,%61,%62,%63,%64,%65,%66,%67,%68,%69,%70,%71,%72,%73,%74,%75,%76,%77,%78,%79,%80,%81,%82,%83,%84,%85,%86,%87,%88,%89,%90,%91,%92,%93,%94,%95}, %96, %97, p, 1, 1, 0, 1;}"
                 : F16(d, 0), F16(d, 16), F16(d, 32), F16(d, 48), F16(d, 64), F16(d, 80) : "l"(a), "l"(b), "r"(sc));
}

constexpr uint32_t P_B = 81920, P_PLANE = 40960, P_VEC = 212992, P_ROW = P_VEC + 6144, P_BAR = P_ROW + 4096, P_SMEM = P_BAR + 256;
constexpr uint32_t P_OUT = 180224, P_OUT3 = P_B + 2 * P_PLANE;
constexpr int E0 = 2;
constexpr int SL_B0 = 0x2222;
constexpr int SL_B1 = 0x8888;
constexpr int SL_C = 0x11110;
constexpr int SL_A0 = 0x5494;
constexpr int SL_A1 = 0x2929;
constexpr int X_DLY = 4000;
constexpr int P_ST = 5, P_ST0 = 4;
constexpr int PB_F = 0, PB_E = 5, PB_X = 10, PB_P = 12, PB_OUT = 14;
enum { C_Y = 0, C_G = 1, C_X1 = 2, C_U = 3, C_S1 = 8, C_S3 = 9 };
enum { V_GA = 0, V_A = 1, V_B = 2, V_GB = 3, V_VA = 4, V_VB = 5, V_VC = 6, V_C3 = 7 };
struct PostMaps { CUtensorMap o, wo, y, w1, g, w2, x1, w3, u, w4, out, x; };

struct GeluK { float k0, k1, kh; };
__device__ __forceinline__ GeluK gelu_k(float c) { return {0.7978845608028654f * c, 0.7978845608028654f * 0.044715f * c * c * c, 0.5f * c}; }
__device__ __forceinline__ float gelu_s(float t, const GeluK& k) {
    const float u = t * fmaf(t * t, k.k1, k.k0);
    float th; asm("tanh.approx.f32 %0, %1;" : "=f"(th) : "f"(u));
    const float hx = k.kh * t;
    return fmaf(hx, th, hx);
}
__device__ __forceinline__ float2 ldsv(uint32_t a) {
    float2 v; asm("ld.shared.v2.f32 {%0,%1}, [%2];" : "=f"(v.x), "=f"(v.y) : "r"(a)); return v;
}
__device__ __forceinline__ void wait_smem(uint32_t a, int target) {
    int it = 0;
#pragma unroll 1
    while (true) {
        int v;
        asm volatile("ld.acquire.cta.shared.u32 %0, [%1];" : "=r"(v) : "r"(a) : "memory");
        if (__all_sync(~0u, v >= target)) break;
        spin_guard(++it);
    }
}

struct Pipe { int st, ph; };
__device__ __forceinline__ void adv(Pipe& p) { if (++p.st == P_ST) { p.st = 0; p.ph ^= 1; } }
__device__ __forceinline__ int u_col(int r, int nb) { return r ? 512 + r * 1024 + nb * 128 : nb * 192; }

template <bool A>
__device__ __forceinline__ void post_produce(uint32_t sb, const PostMaps& mp, int mb, int nb, int rank) {
    const int rh = 2 * mb + rank, lane = threadIdx.x & 31;
    const uint32_t full = sb + P_BAR + 8 * PB_F, empty = sb + P_BAR + 8 * PB_E;
    Pipe p = {(P_ST0 + E0) % P_ST, !E0};
#pragma unroll 1
    for (int ph = 0; ph < 9; ph++) {
        const int GS = ph == 0 ? 8 : ph == 6 ? 3 : 2, kb0 = ph < 7 ? 0 : ph * 16 - 88;
        const CUtensorMap* tm = &mp.o + 2 * (ph < 3 ? ph : ph < 6 ? 3 : 4) + !A;
        const bool own = ph == 1 || ph == 3;
        const int n0 = ph >= 3 && ph < 6 ? u_col(ph - 3, nb) : nb * 128;
        const int amul = ph == 0 ? 256 : 64, arow = ph == 0 ? rh * 8 : rh * 64;
        const int wr = ph == 2 ? min(max(rh + min(lane >> 3, 2) - 1, 0), 31) : rh;
        const uint32_t* fl = &g_pflag[(ph < 3 ? ph - 1 : ph < 6 ? C_X1 : ph - 3) * 256 + wr * 8 + (lane & 7)];
        uint32_t have = ph == 0 || ph == 5 ? ~0u : 0u;
#pragma unroll 1
        for (int q = 0; q < 8; q++) {
            const int src = own && q < 2 ? nb ^ q : (q + (ph >= 1 && ph <= 3 ? nb & 6 : 0)) & 7;
            const bool skip = own && q == 0, both = own && q == 1;
            const uint32_t need = q < 2 && own ? 0 : (ph == 2 ? 0x10101 : 1) << src;
            if (A && both) {
                int it = 0;
                uint32_t ok;
#pragma unroll 1
                do {
                    asm volatile("{.reg .pred p; mbarrier.try_wait.parity.acquire.cluster.shared::cta.b64 p, [%1], %2; selp.u32 %0, 1, 0, p;}" : "=r"(ok) : "r"(sb + P_BAR + 8 * PB_P), "r"(ph >> 1) : "memory");
                    spin_guard(++it);
                } while (!__all_sync(~0u, ok));
                asm volatile("fence.proxy.async.global;" ::: "memory");
            }
            if (A && (have & need) != need) {
                int it = 0;
#pragma unroll 1
                do {
                    uint32_t v;
                    asm volatile("ld.acquire.gpu.global.u32 %0, [%1];" : "=r"(v) : "l"(fl) : "memory");
                    have = __ballot_sync(~0u, v != 0);
                    spin_guard(++it);
                } while ((have & need) != need);
                asm volatile("fence.proxy.async.global;" ::: "memory");
            }
            if (!A && q == 1 && (ph == 1 || ph == 2)) {
#pragma unroll 1
                for (int i = 0; i <= ph; i++)
                    asm volatile("{.reg .pred p; elect.sync _|p, 0xffffffff; @p cp.async.bulk.prefetch.tensor.2d.L2.global [%0, {%1, %2}];}"
                                 ::"l"(tm + 2), "r"((nb * (ph + 1) + i) * 64), "r"(mb * 64) : "memory");
            }
            if (!A && ph == 3 && q == 1) wait_smem(sb + P_BAR + 8 * (PB_OUT + (lane & 1)), 3);
            const int row = arow + (ph == 2 ? (int)((0x04000301u >> ((src & 6) * 4)) & 7) - 2 : 0);
            const uint32_t bytes = (skip ? 16384 : 32768) + (ph == 3 ? 8192 : 0);
            if ((ph | q) == 0) asm volatile("barrier.cluster.wait.aligned;" ::: "memory");
            if (A && (ph | q) == 0) asm volatile("griddepcontrol.wait;" ::: "memory");
#pragma unroll 1
            for (int e = kb0 + (src + 1) * GS, kb = e - GS + (ph | q ? 0 : E0); kb < e; kb++) {
                const uint32_t f = full + 8 * p.st;
                if (!(A && skip)) mbar_wait_w(empty + 8 * p.st, p.ph ^ 1);
                if (A) {
                    const uint32_t a = sb + p.st * 16384 + rank * 8192;
                    if (both) { e_tma2d_ef(a, tm, kb * 64, row, f); e_tma2d_ef(a + 8192 - rank * 16384, tm, kb * 64, row ^ 64, f); }
                    else if (!skip) e_tma2d_mc_ef(a, tm, kb * amul, row, f);
                } else {
                    const uint32_t b = sb + P_B + p.st * 8192;
                    e_expect(f, bytes);
                    e_tma2d_ef(b, tm, n0, kb * 64, f);
                    e_tma2d_ef(b + P_PLANE, tm, n0 + 64, kb * 64, f);
                    if (ph == 3 && both) mbar_wait_w(empty + 8 * p.st - 16, p.ph);
                    if (ph == 3) e_tma2d_ef(b + 2 * P_PLANE, tm, n0 + 128, kb * 64, f);
                }
                adv(p);
            }
        }
    }
    if (A) {
#pragma unroll 1
        for (int i = 0; i < P_ST; i++) mbar_wait_w(empty + 8 * i, p.ph ^ (i >= p.st));
    }
}

#define I4(d, i) "f"(d[i]), "f"(d[i + 1]), "f"(d[i + 2]), "f"(d[i + 3])
#define I16(d, i) I4(d, i), I4(d, i + 4), I4(d, i + 8), I4(d, i + 12)
#define O4(d, i) "=f"(d[i]), "=f"(d[i + 1]), "=f"(d[i + 2]), "=f"(d[i + 3])
__device__ __forceinline__ void pick32(float* v, int n, const float* c1, const float* vc, const float* old) {
    asm volatile("{PKT: .branchtargets PK0, PK1, PK2, PK3, PK4, PK5; brx.idx.uni %16, PKT;\n"
                 "PK0: fma.rn.f32 %0, %17, %19, %27; fma.rn.f32 %1, %17, %20, %28; fma.rn.f32 %2, %18, %19, %29; fma.rn.f32 %3, %18, %20, %30; fma.rn.f32 %4, %17, %21, %31; fma.rn.f32 %5, %17, %22, %32; fma.rn.f32 %6, %18, %21, %33; fma.rn.f32 %7, %18, %22, %34; fma.rn.f32 %8, %17, %23, %35; fma.rn.f32 %9, %17, %24, %36; fma.rn.f32 %10, %18, %23, %37; fma.rn.f32 %11, %18, %24, %38; fma.rn.f32 %12, %17, %25, %39; fma.rn.f32 %13, %17, %26, %40; fma.rn.f32 %14, %18, %25, %41; fma.rn.f32 %15, %18, %26, %42; bra.uni PKE;\n"
                 "PK1: fma.rn.f32 %0, %17, %19, %43; fma.rn.f32 %1, %17, %20, %44; fma.rn.f32 %2, %18, %19, %45; fma.rn.f32 %3, %18, %20, %46; fma.rn.f32 %4, %17, %21, %47; fma.rn.f32 %5, %17, %22, %48; fma.rn.f32 %6, %18, %21, %49; fma.rn.f32 %7, %18, %22, %50; fma.rn.f32 %8, %17, %23, %51; fma.rn.f32 %9, %17, %24, %52; fma.rn.f32 %10, %18, %23, %53; fma.rn.f32 %11, %18, %24, %54; fma.rn.f32 %12, %17, %25, %55; fma.rn.f32 %13, %17, %26, %56; fma.rn.f32 %14, %18, %25, %57; fma.rn.f32 %15, %18, %26, %58; bra.uni PKE;\n"
                 "PK2: fma.rn.f32 %0, %17, %19, %59; fma.rn.f32 %1, %17, %20, %60; fma.rn.f32 %2, %18, %19, %61; fma.rn.f32 %3, %18, %20, %62; fma.rn.f32 %4, %17, %21, %63; fma.rn.f32 %5, %17, %22, %64; fma.rn.f32 %6, %18, %21, %65; fma.rn.f32 %7, %18, %22, %66; fma.rn.f32 %8, %17, %23, %67; fma.rn.f32 %9, %17, %24, %68; fma.rn.f32 %10, %18, %23, %69; fma.rn.f32 %11, %18, %24, %70; fma.rn.f32 %12, %17, %25, %71; fma.rn.f32 %13, %17, %26, %72; fma.rn.f32 %14, %18, %25, %73; fma.rn.f32 %15, %18, %26, %74; bra.uni PKE;\n"
                 "PK3: fma.rn.f32 %0, %17, %19, %75; fma.rn.f32 %1, %17, %20, %76; fma.rn.f32 %2, %18, %19, %77; fma.rn.f32 %3, %18, %20, %78; fma.rn.f32 %4, %17, %21, %79; fma.rn.f32 %5, %17, %22, %80; fma.rn.f32 %6, %18, %21, %81; fma.rn.f32 %7, %18, %22, %82; fma.rn.f32 %8, %17, %23, %83; fma.rn.f32 %9, %17, %24, %84; fma.rn.f32 %10, %18, %23, %85; fma.rn.f32 %11, %18, %24, %86; fma.rn.f32 %12, %17, %25, %87; fma.rn.f32 %13, %17, %26, %88; fma.rn.f32 %14, %18, %25, %89; fma.rn.f32 %15, %18, %26, %90; bra.uni PKE;\n"
                 "PK4: fma.rn.f32 %0, %17, %19, %91; fma.rn.f32 %1, %17, %20, %92; fma.rn.f32 %2, %18, %19, %93; fma.rn.f32 %3, %18, %20, %94; fma.rn.f32 %4, %17, %21, %95; fma.rn.f32 %5, %17, %22, %96; fma.rn.f32 %6, %18, %21, %97; fma.rn.f32 %7, %18, %22, %98; fma.rn.f32 %8, %17, %23, %99; fma.rn.f32 %9, %17, %24, %100; fma.rn.f32 %10, %18, %23, %101; fma.rn.f32 %11, %18, %24, %102; fma.rn.f32 %12, %17, %25, %103; fma.rn.f32 %13, %17, %26, %104; fma.rn.f32 %14, %18, %25, %105; fma.rn.f32 %15, %18, %26, %106; bra.uni PKE;\n"
                 "PK5: fma.rn.f32 %0, %17, %19, %107; fma.rn.f32 %1, %17, %20, %108; fma.rn.f32 %2, %18, %19, %109; fma.rn.f32 %3, %18, %20, %110; fma.rn.f32 %4, %17, %21, %111; fma.rn.f32 %5, %17, %22, %112; fma.rn.f32 %6, %18, %21, %113; fma.rn.f32 %7, %18, %22, %114; fma.rn.f32 %8, %17, %23, %115; fma.rn.f32 %9, %17, %24, %116; fma.rn.f32 %10, %18, %23, %117; fma.rn.f32 %11, %18, %24, %118; fma.rn.f32 %12, %17, %25, %119; fma.rn.f32 %13, %17, %26, %120; fma.rn.f32 %14, %18, %25, %121; fma.rn.f32 %15, %18, %26, %122;\n"
                 "PKE: }"
                 : O4(v, 0), O4(v, 4), O4(v, 8), O4(v, 12)
                 : "r"(n), "f"(c1[0]), "f"(c1[1]), I4(vc, 0), I4(vc, 4), I16(old, 0), I16(old, 16), I16(old, 32), I16(old, 48), I16(old, 64), I16(old, 80));
}
template <int PH, class F>
__device__ __forceinline__ void post_mma(uint32_t sb, float* acc, Pipe& p, int NK, int wg, uint32_t rel, bool lead, int pi, F hook) {
    const uint32_t full = sb + P_BAR + 8 * PB_F;
    constexpr uint64_t DA = PH == 0 ? mkdesc(SB0, 128, 1024, 0) : mkdesc(SB0, 16, 1024, 1);
    constexpr uint64_t DB = mkdesc(SB0 + P_B, P_PLANE, 1024, 1);
    auto release = [&](uint32_t a) { asm volatile("{.reg .pred p; setp.gt.u32 p, %0, 63; @p mbarrier.arrive.shared::cluster.b64 _, [%0];}" ::"r"(a) : "memory"); };
    uint32_t prev = 0;
    if (PH & 1) { fence_async_smem(); bar_sync(12 + wg, 128); }
    bool ok = false;
#pragma unroll 1
    for (int kb = 0; kb < NK; kb++) {
        if (!ok) mbar_wait_w(full + 8 * p.st, p.ph);
        const uint32_t a = (uint32_t)DA + ((PH & 1) && kb < 2 ? P_OUT / 16 + wg * 1024 + kb * 512 : p.st * 1024 + wg * 512), b = (uint32_t)DB + p.st * 512;
        wg_fence();
#pragma unroll
        for (int k = 0; k < 4; k++) {
            const uint64_t da = (DA & 0xffffffff00000000ull) | (a + k * (PH == 0 ? 16 : 2)), db = (DB & 0xffffffff00000000ull) | (b + k * 128);
            if (PH == 3) wgmma_ss192(acc, da, db, (kb | k) != 0);
            else wgmma_ss128<PH == 0>(acc, da, db, (kb | k) != 0);
        }
        wg_commit();
        const uint32_t cur = rel + 8 * p.st;
        adv(p);
        uint32_t t;
        asm volatile("{.reg .pred p; mbarrier.test_wait.parity.shared.b64 p, [%1], %2; selp.u32 %0, 1, 0, p;}" : "=r"(t) : "r"(full + 8 * p.st), "r"(p.ph) : "memory");
        wg_wait<1>();
        release(prev);
        ok = __all_sync(~0u, t);
        prev = cur;
        hook(kb);
    }
    wg_wait<0>();
    release(prev);
}

__global__ void __cluster_dims__(2, 1, 1) __launch_bounds__(384, 1)
k_post(const __grid_constant__ PostMaps mp) {
    extern __shared__ uint8_t smraw[];
    const uint32_t sb = smem_u32(smraw);
    if ((sb & 0x3FFFF) != SB0) __trap();
    const int tid = threadIdx.x, lane = tid & 31;
    int d, pi;
    pair_place(blockIdx.x >> 1, d, pi);
    const int rank = blockIdx.x & 1, mb = (d >> 2) * 8 + pi, nb = (d & 3) * 2 + rank;
    const uint32_t bars = sb + P_BAR;
    const int w = __reduce_max_sync(~0u, (tid >> 5) - 8);
    if (w == 1) {
        if (lane == 0) {
#pragma unroll
            for (int i = 0; i <= PB_P; i++) mbar_init(bars + 8 * i, i >= PB_E && i < PB_X ? 4 : i == PB_P ? 2 : 1);
            mbar_arrive(bars + 8 * (PB_F + P_ST0));
            asm volatile("mbarrier.arrive.shared.b64 _, [%0], 4;" ::"r"(bars + 8 * (PB_E + P_ST0)) : "memory");
            sts4(bars + 8 * PB_OUT, 0, 0, 0, 0);
            asm volatile("fence.mbarrier_init.release.cluster; fence.proxy.async.shared::cta;" ::: "memory");
        }
        __syncwarp();
    }
    asm volatile("barrier.cluster.arrive.relaxed.aligned;" ::: "memory");
    if (w == 1 || w == 2) asm volatile("griddepcontrol.wait;" ::: "memory");
    if (w == 1) {
#pragma unroll
        for (int i = 0; i < E0; i++) {
            const int st = (P_ST0 + i) % P_ST;
            const uint32_t f = bars + 8 * (PB_F + st);
            e_expect(f, 32768);
#pragma unroll
            for (int h = 0; h < 2; h++) {
                e_tma2d_ef(sb + st * 16384 + h * 8192, &mp.o, i * 256, mb * 16 + h * 8, f);
                e_tma2d_ef(sb + P_B + st * 8192 + h * P_PLANE, &mp.wo, nb * 128 + h * 64, i * 64, f);
            }
        }
    }
    if (w != 0 && w != 3) asm volatile("barrier.cluster.wait.aligned;" ::: "memory");
    if (w >= 0) {
        asm volatile("setmaxnreg.dec.sync.aligned.u32 40;");
        if (w == 0) {
            post_produce<false>(sb, mp, mb, nb, rank);
        } else if (w < 3) {
            const int wg = w - 1, rh = 2 * mb + wg;
            float* rowc = (float*)(smraw + P_ROW) + (wg * 64 + lane * 2) * 8;
            int nout = 0, sig = 0;
            __nanosleep(X_DLY);
            if (wg && lane < 9) asm volatile("prefetch.tensormap [%0];" ::"l"(&mp.y + lane) : "memory");
            e_expect(bars + 8 * (PB_X + wg), 16384);
            e_tma2d_ef(sb + P_OUT + wg * 16384, &mp.x, nb * 128, rh * 64, bars + 8 * (PB_X + wg));
            e_tma2d_ef(sb + P_OUT + wg * 16384 + 8192, &mp.x, nb * 128 + 64, rh * 64, bars + 8 * (PB_X + wg));
            if (wg == 0) {
#pragma unroll 1
                for (int i = 0; i < 11; i++) {
                    const float* src = i < 4 ? g_mod + ((0x5342 >> (4 * i)) & 15) * DM + nb * 128 : g_vec + (i < 7 ? (i - 4) * DM + nb * 128 : 3 * DM + u_col(max(i - 8, 0), nb) + (i == 8) * 128);
                    if (i != 8 || lane < 16) cp_async16(sb + P_VEC + i * 512 - (i > 8) * 256 + lane * 16, src + lane * 4);
                }
                *(uint4*)&g_modp[blockIdx.x * 128 + lane * 4] = make_uint4(0, 0, 0, 0);
                if (blockIdx.x == 64) *(uint2*)&g_tick[lane * 2] = make_uint2(0, 0);
                asm volatile("cp.async.wait_all;" ::: "memory");
                const float4 a = lds4f(sb + P_VEC + V_A * 512 + lane * 16);
                sts4f(sb + P_VEC + V_A * 512 + lane * 16, 1.0f + a.x, 1.0f + a.y, 1.0f + a.z, 1.0f + a.w);
                bar_arrive(3, 288);
            }
#pragma unroll 1
            for (int i = 0; i < 9; i++) {
                const int cnt = i == 8 ? 6 : (0x54392180u >> (4 * i)) & 15;
                if (cnt < C_S1) {
                    const bool isu = cnt >= C_U && cnt < 6;
                    const int ng = cnt == C_U ? 3 : 2, c0 = isu ? u_col(cnt - C_U, nb) : nb * 128;
                    const uint32_t src = sb + (cnt == C_U ? P_OUT3 : P_OUT) + wg * ng * 8192;
#pragma unroll 1
                    for (int j = 0; j < ng; j++) {
                        bar_sync(4 + 4 * wg + (sig++ & 3), 160);
                        if (lane == 0) {
                            fence_async_smem();
                            asm volatile("cp.async.bulk.tensor.2d.global.shared::cta.bulk_group [%0, {%2, %3}], [%1]; cp.async.bulk.commit_group;"
                                         ::"l"(&mp.y + 2 * (isu ? 3 : min(cnt, 4))), "r"(src + j * 8192), "r"(c0 + j * 64), "r"(rh * 64) : "memory");
                        }
                        __syncwarp();
                    }
                    if (lane == 0) {
                        asm volatile("cp.async.bulk.wait_group 0; fence.proxy.async.global;" ::: "memory");
                        asm volatile("st.release.cta.shared.u32 [%0], %1;" ::"r"(bars + 8 * (PB_OUT + wg)), "r"(nout + 1) : "memory");
                        if (cnt < 6) asm volatile("fence.acq_rel.gpu; st.relaxed.gpu.global.u32 [%0], %1;" ::"l"(&g_pflag[cnt * 256 + rh * 8 + nb]), "r"(1) : "memory");
                        if (cnt == C_Y || cnt == C_X1)
                            asm volatile("{.reg .b32 r; mapa.shared::cluster.u32 r, %0, %1; mbarrier.arrive.relaxed.cluster.shared::cluster.b64 _, [r];}" ::"r"(bars + 8 * PB_P), "r"(rank ^ 1) : "memory");
                    }
                    nout++;
                    __syncwarp();
                    continue;
                }
                bar_sync(4 + 4 * wg + (sig++ & 3), 160);
#pragma unroll 1
                for (int q = 0; q < (cnt == C_S1 ? 3 : 1); q++) {
                    const float4 v = lds4f(sb + P_ROW + wg * 2048 + q * 512 + lane * 16);
                    asm volatile("red.relaxed.gpu.global.add.v4.f32 [%0], {%1, %2, %3, %4};"
                                 ::"l"((float4*)g_st + (cnt == C_S1 ? q : 3) * (S_ / 2) + rh * 32 + lane), "f"(v.x), "f"(v.y), "f"(v.z), "f"(v.w) : "memory");
                }
                __syncwarp();
                uint32_t* c = &g_pcnt[(cnt - C_S1) * 256 + rh * 8];
                if (lane == 0) { signal_count(c); wait_count1(c, 8); }
                __syncwarp();
                const float4* sp = (const float4*)g_st + rh * 32 + lane;
                float4 u[3] = {__ldcg(sp + (cnt == C_S1 ? 0 : 3) * (S_ / 2)), __ldcg(sp + S_ / 2), __ldcg(sp + S_)};
#pragma unroll 1
                for (int h = 0; h < 2; h++) {
                    const float id = 1.0f / DM;
                    const float m = u[0].x * id, var = fmaxf(u[0].y * id - m * m, 0.f) + 1e-5f, r = rsqrtf(var);
                    float sc = r, m2 = 0.f;
                    if (cnt == C_S1) {
                        m2 = r * (u[1].x * id - m * g_cst[0]) + g_cst[3];
                        const float e2 = r * r * (u[2].x * id - 2.0f * m * u[1].y * id + m * m * g_cst[1]) + 2.0f * r * (u[2].y * id - m * g_cst[2]) + g_cst[4];
                        sc = r * rsqrtf(fmaxf(e2 - m2 * m2, 0.f) + 1e-5f);
                    }
                    const GeluK k = gelu_k(sc);
                    *(float4*)(rowc + h * 8) = make_float4(k.k0, k.k1, k.kh, -m);
                    *(float4*)(rowc + h * 8 + 4) = make_float4(var * r, -m2 * var * r, r, -m * r);
#pragma unroll
                    for (int q = 0; q < 3; q++) { u[q].x = u[q].z; u[q].y = u[q].w; }
                }
                bar_arrive(1 + wg, 160);
            }
        } else {
            post_produce<true>(sb, mp, mb, nb, rank);
        }
    } else {
        asm volatile("setmaxnreg.inc.sync.aligned.u32 232;");
        const int wg = __reduce_max_sync(~0u, tid >> 7), wi = (tid >> 5) & 3, g = lane >> 2, tq = lane & 3;
        const bool lead = (tid & 127) == 0;
        uint32_t rel = 0;
        if ((tid & 127) < 2) asm("mapa.shared::cluster.u32 %0, %1, %2;" : "=r"(rel) : "r"(bars + 8 * PB_E), "r"(tid & 1));
        uint32_t vec = sb + P_VEC + tq * 8;
        const uint32_t stw = sb + (wi * 16 + ((lane >> 3) & 1) * 8 + (lane & 7)) * 128 + (((lane >> 4) ^ (lane & 7)) << 4);
        int sig = 0;
        auto signal = [&]() { bar_arrive(4 + 4 * wg + (sig++ & 3), 160); };
        auto put64 = [&](uint32_t o, const float* v) {
#pragma unroll
            for (int jj = 0; jj < 4; jj++, v += 8) stsm4((stw + o) ^ (jj << 5), pack2(v[0], v[1]), pack2(v[2], v[3]), pack2(v[4], v[5]), pack2(v[6], v[7]));
            signal();
        };
        auto out_free = [&](int n) { wait_smem(bars + 8 * (PB_OUT + (lane & 1)), n); };
        const uint32_t rowc = sb + P_ROW + (wg * 64 + wi * 16 + g) * 32, o128 = P_OUT + wg * 16384;
        const uint32_t rsum = sb + P_ROW + wg * 2048 + (wi * 16 + g) * 8;
        Pipe pa = {P_ST0, 1};
        auto none = [](int) {};
        uint32_t keep[32];
#define KEEP(jn, e) (((e) & 1) ? bfhi(keep[2 * (jn) + ((e) >> 1)]) : bflo(keep[2 * (jn) + ((e) >> 1)]))
        float mu1[2], r1[2];
        {
            float acc[64];
            post_mma<0>(sb, acc, pa, 64, wg, rel, lead, 1, [&](int kb) {
                if (kb != 40) return;
                bar_sync(3, 288);
                mbar_wait_w(bars + 8 * (PB_X + wg), 0);
#pragma unroll
                for (int jj = 0; jj < 8; jj++) ldsm4(keep + jj * 4, (stw + o128 + (jj >> 2) * 8192) ^ ((jj & 3) << 5));
            });
            asm volatile("" : "+r"(vec) :: "memory");
            float st[2][6];
#pragma unroll
            for (int q = 0; q < 6; q++) st[0][q] = st[1][q] = 0.f;
#pragma unroll
            for (int jn = 0; jn < 16; jn++) {
                const float2 ga = ldsv(vec + V_GA * 512 + jn * 32), a = ldsv(vec + V_A * 512 + jn * 32);
                float xa[4];
#pragma unroll
                for (int e = 0; e < 4; e++) {
                    xa[e] = fmaf((e & 1) ? ga.y : ga.x, acc[4 * jn + e], KEEP(jn, e));
                    st[e >> 1][0] += xa[e]; st[e >> 1][1] = fmaf(xa[e], xa[e], st[e >> 1][1]);
                    acc[4 * jn + e] = ((e & 1) ? a.y : a.x) * xa[e];
                }
                keep[2 * jn] = pack2(xa[0], xa[1]); keep[2 * jn + 1] = pack2(xa[2], xa[3]);
                if ((jn & 7) == 7) put64(o128 + (jn >> 3) * 8192, acc + 4 * jn - 28);
            }
#pragma unroll
            for (int jn = 0; jn < 16; jn++) {
                const float2 a = ldsv(vec + V_A * 512 + jn * 32), b = ldsv(vec + V_B * 512 + jn * 32);
#pragma unroll
                for (int e = 0; e < 4; e++) {
                    const float y = acc[4 * jn + e], aa = (e & 1) ? a.y : a.x, bb = (e & 1) ? b.y : b.x;
                    float* s = st[e >> 1];
                    s[2] += y; s[3] = fmaf(aa, y, s[3]); s[4] = fmaf(y, y, s[4]); s[5] = fmaf(bb, y, s[5]);
                }
            }
#pragma unroll
            for (int h = 0; h < 2; h++)
#pragma unroll
                for (int q = 0; q < 6; q++) { st[h][q] += __shfl_xor_sync(~0u, st[h][q], 1); st[h][q] += __shfl_xor_sync(~0u, st[h][q], 2); }
            if (tq < 3) {
#pragma unroll
                for (int h = 0; h < 2; h++)
                    sts2(rsum + tq * 512 + h * 64, tq == 0 ? st[h][0] : tq == 1 ? st[h][2] : st[h][4], tq == 0 ? st[h][1] : tq == 1 ? st[h][3] : st[h][5]);
            }
            signal();
        }
        {
            float acc[64];
            post_mma<1>(sb, acc, pa, 16, wg, rel, lead, 4, none);
            float c1[2], c2[2], c3[2];
            GeluK gk[2];
            bar_sync(1 + wg, 160);
#pragma unroll
            for (int h = 0; h < 2; h++) {
                const float4 a = lds4f(rowc + h * 256), b = lds4f(rowc + h * 256 + 16);
                gk[h] = {a.x, a.y, a.z}; c1[h] = a.w; c2[h] = b.x; c3[h] = b.y; mu1[h] = b.w; r1[h] = b.z;
            }
#pragma unroll
            for (int jn = 0; jn < 16; jn++) {
                const float2 va = ldsv(vec + V_VA * 512 + jn * 32), vb = ldsv(vec + V_VB * 512 + jn * 32), vc = ldsv(vec + V_VC * 512 + jn * 32);
#pragma unroll
                for (int e = 0; e < 4; e++) {
                    const int h = e >> 1;
                    const float t = fmaf(c1[h], (e & 1) ? va.y : va.x, fmaf(c2[h], (e & 1) ? vb.y : vb.x, fmaf(c3[h], (e & 1) ? vc.y : vc.x, acc[4 * jn + e])));
                    acc[4 * jn + e] = gelu_s(t, gk[h]);
                }
                if ((jn & 7) == 7) put64(o128 + (jn >> 3) * 8192, acc + 4 * jn - 28);
            }
        }
        {
            float acc[64];
            post_mma<2>(sb, acc, pa, 16, wg, rel, lead, 7, none);
#pragma unroll
            for (int jn = 0; jn < 16; jn++) {
                const float2 a = ldsv(vec + V_A * 512 + jn * 32), b = ldsv(vec + V_B * 512 + jn * 32);
#pragma unroll
                for (int e = 0; e < 4; e++) {
                    const int h = e >> 1;
                    acc[4 * jn + e] += fmaf(fmaf(KEEP(jn, e), r1[h], mu1[h]), (e & 1) ? a.y : a.x, (e & 1) ? b.y : b.x);
                }
                if ((jn & 7) == 7) put64(o128 + (jn >> 3) * 8192, acc + 4 * jn - 28);
            }
            float st[2][2] = {{0.f, 0.f}, {0.f, 0.f}};
#pragma unroll
            for (int jn = 0; jn < 16; jn++) {
                const float2 gb = ldsv(vec + V_GB * 512 + jn * 32);
                float z[4];
#pragma unroll
                for (int e = 0; e < 4; e++) {
                    const float x1 = acc[4 * jn + e];
                    st[e >> 1][0] += x1; st[e >> 1][1] = fmaf(x1, x1, st[e >> 1][1]);
                    z[e] = fmaf((e & 1) ? gb.y : gb.x, x1, KEEP(jn, e));
                }
                keep[2 * jn] = pack2(z[0], z[1]); keep[2 * jn + 1] = pack2(z[2], z[3]);
            }
#pragma unroll
            for (int h = 0; h < 2; h++)
#pragma unroll
                for (int q = 0; q < 2; q++) { st[h][q] += __shfl_xor_sync(~0u, st[h][q], 1); st[h][q] += __shfl_xor_sync(~0u, st[h][q], 2); }
            if (tq < 2) sts2(rsum + tq * 64, tq ? st[1][0] : st[0][0], tq ? st[1][1] : st[0][1]);
            signal();
        }
        {
            float old[96], acc[64];
            post_mma<3>(sb, old, pa, 16, wg, rel, lead, 10, none);
            uint32_t v3 = vec + V_C3 * 512;
            float c1[2], vc[8];
            auto next_vc = [&]() {
#pragma unroll
                for (int i = 0; i < 4; i++) { const float2 u = lds2f(v3 + i * 32); vc[2 * i] = u.x; vc[2 * i + 1] = u.y; }
                v3 += 128;
            };
            next_vc();
            GeluK gk[2];
            bar_sync(1 + wg, 160);
#pragma unroll
            for (int h = 0; h < 2; h++) { const float4 a = lds4f(rowc + h * 256); gk[h] = {a.x, a.y, a.z}; c1[h] = a.w; }
            bar_arrive(14 + wg, 256);
#pragma unroll 1
            for (int r = 0; r < 3; r++) {
                const uint32_t o = stw + (r ? o128 : P_OUT3 + wg * 24576);
                uint32_t when = r == 0 ? (wg ? SL_A1 : SL_A0) : r == 1 ? (wg ? SL_B1 : SL_B0) : SL_C << (2 * wg), n = 0;
                post_mma<2>(sb, acc, pa, r < 2 ? 16 : 56, wg, rel, lead, 12 + 2 * r, [&](int kb) {
                    const bool now = when & 1;
                    when >>= 1;
                    if (!now) return;
                    if (n == 0) { if (r == 0) bar_sync(15 - wg, 256); out_free(3 + r); }
                    float v[16];
                    pick32(v, n, c1, vc, old);
                    next_vc();
#pragma unroll
                    for (int e = 0; e < 16; e++) v[e] = gelu_s(v[e], gk[(e >> 1) & 1]);
                    const uint32_t a = (o + (n >> 1) * 8192) ^ ((n & 1) << 6);
                    stsm4(a, pack2(v[0], v[1]), pack2(v[2], v[3]), pack2(v[4], v[5]), pack2(v[6], v[7]));
                    stsm4(a ^ 32, pack2(v[8], v[9]), pack2(v[10], v[11]), pack2(v[12], v[13]), pack2(v[14], v[15]));
                    if ((++n & 1) == 0) signal();
                });
                if (r == 2) break;
#pragma unroll
                for (int i = 0; i < 64; i++) old[i] = acc[i];
            }
#pragma unroll
            for (int jn = 0; jn < 16; jn++) {
                const float2 gb = ldsv(vec + V_GB * 512 + jn * 32);
#pragma unroll
                for (int e = 0; e < 4; e++) acc[4 * jn + e] = fmaf((e & 1) ? gb.y : gb.x, acc[4 * jn + e], KEEP(jn, e));
                if ((jn & 7) == 7) put64(o128 + (jn >> 3) * 8192, acc + 4 * jn - 28);
            }
        }
    }
}

typedef CUresult (*EncFn)(CUtensorMap*, CUtensorMapDataType, cuuint32_t, void*, const cuuint64_t*, const cuuint64_t*, const cuuint32_t*,
                          const cuuint32_t*, CUtensorMapInterleave, CUtensorMapSwizzle, CUtensorMapL2promotion, CUtensorMapFloatOOBfill);

static CUtensorMap make_map(EncFn enc, const void* p, uint64_t inner, uint64_t outer) {
    CUtensorMap m;
    cuuint64_t dims[2] = {inner, outer};
    cuuint64_t str[1] = {inner * 2};
    cuuint32_t box[2] = {64, 64};
    cuuint32_t es[2] = {1, 1};
    enc(&m, CU_TENSOR_MAP_DATA_TYPE_BFLOAT16, 2, (void*)p, dims, str, box, es, CU_TENSOR_MAP_INTERLEAVE_NONE,
        CU_TENSOR_MAP_SWIZZLE_128B, CU_TENSOR_MAP_L2_PROMOTION_L2_256B, CU_TENSOR_MAP_FLOAT_OOB_FILL_NONE);
    return m;
}
static CUtensorMap make_map_o(EncFn enc, const void* p) {
    CUtensorMap m;
    cuuint64_t dims[2] = {16384, 256};
    cuuint64_t str[1] = {65536};
    cuuint32_t box[2] = {256, 8};
    cuuint32_t es[2] = {1, 1};
    enc(&m, CU_TENSOR_MAP_DATA_TYPE_UINT32, 2, (void*)p, dims, str, box, es, CU_TENSOR_MAP_INTERLEAVE_NONE, CU_TENSOR_MAP_SWIZZLE_NONE,
        CU_TENSOR_MAP_L2_PROMOTION_L2_256B, CU_TENSOR_MAP_FLOAT_OOB_FILL_NONE);
    return m;
}
template <class T> static T* sym(T& s) { void* p = nullptr; cudaGetSymbolAddress(&p, s); return (T*)p; }

constexpr RecTime g_time = {T_GO, T_X2, T_V, D_X2, H_D};
extern "C" void kernel_launch(void* const* d_in, const int* in_sizes, int n_in, void* d_out, int out_size) {
    const bf16* x = (const bf16*)d_in[0];
    const bf16* mem0 = (const bf16*)d_in[1];
    const bf16 *Wq = (const bf16*)d_in[2], *Wk = (const bf16*)d_in[3], *Wv = (const bf16*)d_in[4], *Wo = (const bf16*)d_in[5];
    const bf16 *w1 = (const bf16*)d_in[8], *w2 = (const bf16*)d_in[9], *w3 = (const bf16*)d_in[10], *w4 = (const bf16*)d_in[11];
    const bf16 *c = (const bf16*)d_in[12], *wmod = (const bf16*)d_in[13];
    bf16* out = (bf16*)d_out;

    EncFn enc = nullptr;
    cudaDriverEntryPointQueryResult qr;
    cudaGetDriverEntryPoint("cuTensorMapEncodeTiled", (void**)&enc, cudaEnableDefault, &qr);
    CUtensorMap tWq = make_map(enc, Wq, NH * DH, DM), tWk = make_map(enc, Wk, NH * DH, DM), tWv = make_map(enc, Wv, NH * DH, DM);
    PostMaps mp;
    mp.o = make_map_o(enc, sym(g_O)); mp.wo = make_map(enc, Wo, DM, NH * DH);
    mp.y = make_map(enc, sym(g_y), DM, S_); mp.w1 = make_map(enc, w1, DM, DM);
    mp.g = make_map(enc, sym(g_g), DM, S_); mp.w2 = make_map(enc, w2, DM, DM);
    mp.x1 = make_map(enc, sym(g_x1), DM, S_); mp.w3 = make_map(enc, w3, FF, DM);
    mp.u = make_map(enc, sym(g_u), FF, S_); mp.w4 = make_map(enc, w4, DM, FF);
    mp.out = make_map(enc, out, DM, S_); mp.x = make_map(enc, x, DM, S_);
    cudaFuncSetAttribute(k_rec, cudaFuncAttributeMaxDynamicSharedMemorySize, SM_REC_TOTAL);
    cudaFuncSetAttribute(k_post, cudaFuncAttributeMaxDynamicSharedMemorySize, P_SMEM);

    uint8_t* arena = (uint8_t*)(((uintptr_t)sym(g_arena) + (2u << 20) - 1) & ~(uintptr_t)((2u << 20) - 1));
    const RecPtrs rp = {x, mem0, c, wmod, w1, w3, arena, 0u, g_time};
    const RecMaps rm = {tWq, tWk, tWv, mp.wo};
    k_rec<<<132, 384, SM_REC_TOTAL, cudaStreamPerThread>>>(rm, rp);
    cudaLaunchConfig_t cfg = {};
    cfg.gridDim = dim3(128); cfg.blockDim = dim3(384); cfg.dynamicSmemBytes = P_SMEM; cfg.stream = cudaStreamPerThread;
    cudaLaunchAttribute at[1];
    at[0].id = cudaLaunchAttributeProgrammaticStreamSerialization;
    at[0].val.programmaticStreamSerializationAllowed = 1;
    cfg.attrs = at; cfg.numAttrs = 1;
    cudaLaunchKernelEx(&cfg, k_post, mp);
}
```

```cpp
#include <cuda_runtime.h>
#include <cuda.h>
#include <cuda_bf16.h>
#include <stdint.h>
#include <limits.h>

typedef __nv_bfloat16 bf16;

constexpr int S_ = 2048, DM = 1024, NH = 32, DH = 128, NSEG = 64, FF = 3584;
constexpr int SPIN_LIMIT = 1 << 22;
constexpr int W_INFL = 2;
constexpr int NPROBE = 4;

__device__ uint8_t g_arena[10 << 20];
__device__ __align__(16) uint32_t g_tick[64];
__device__ __align__(16) uint32_t g_modp[8 * 2 * DM];
__host__ __device__ constexpr uint32_t blk(uint32_t lb, uint32_t par) {
    return (lb << 13) | ((((lb) ^ (lb >> 3) ^ (lb >> 4) ^ (lb >> 6) ^ par) & 1) << 12);
}
__host__ __device__ constexpr uint32_t lb_x2(uint32_t h) { return (h & 1) | ((h >> 1) << 3); }
__host__ __device__ constexpr uint32_t acc_slot(uint32_t s) { return (1u << 20) + (s & 1) * 32768 + (s & 2) * 131072; }
__host__ __device__ constexpr uint32_t acc_piece(uint32_t half, uint32_t qd, uint32_t mt) { return mt * 1024 + (qd & 1) * 4096 + half * 8192 + (qd >> 1) * 16384; }
constexpr uint32_t LB_STAMP = 6;
__host__ __device__ constexpr uint32_t stamp_line(uint32_t w, uint32_t q) { return ((w & 1) * 2 + (q >> 1)) * 1024 + (q & 1) * 256; }
constexpr uint32_t ACC_ONE = 0x3c000000u, ACC_ALL = 0x50000000u;
constexpr uint32_t LB_PROBE = 6 | 64;
__host__ __device__ constexpr uint32_t lb_tok(uint32_t h) { return (h & 1) | ((h >> 1) << 3); }
__device__ __align__(16) float g_mod[6 * DM];
__device__ __align__(1024) bf16 g_himg[(S_ + 32) * DM];
__device__ __align__(1024) bf16 g_O[S_ * NH * DH];
__device__ __align__(1024) bf16 g_y[S_ * DM];
__device__ __align__(1024) bf16 g_g[S_ * DM];
__device__ __align__(1024) bf16 g_x1[S_ * DM];
__device__ __align__(16) float g_st[4 * S_ * 2];
__device__ __align__(16) float g_vec[3 * DM + FF];
__device__ float g_cst[8];
__device__ uint32_t g_pcnt[2 * 32 * 8], g_pflag[6 * 32 * 8];
__device__ __align__(1024) bf16 g_u[S_ * FF];

__device__ __forceinline__ uint32_t smem_u32(const void* p) { return (uint32_t)__cvta_generic_to_shared(p); }
__device__ __forceinline__ void spin_guard(int it) {
    asm volatile("{.reg .pred p; setp.gt.s32 p, %0, %1; @p st.global.u32 [%2], %0;}" ::"r"(it), "n"(SPIN_LIMIT), "l"(1ull));
}
__device__ __forceinline__ void wg_fence() { asm volatile("wgmma.fence.sync.aligned;" ::: "memory"); }
__device__ __forceinline__ void wg_commit() { asm volatile("wgmma.commit_group.sync.aligned;" ::: "memory"); }
template <int N> __device__ __forceinline__ void wg_wait() { asm volatile("wgmma.wait_group.sync.aligned %0;" ::"n"(N) : "memory"); }
__host__ __device__ constexpr uint64_t mkdesc(uint32_t addr, uint32_t lbo, uint32_t sbo, uint32_t swz) {
    return (uint64_t)((addr & 0x3FFFF) >> 4) | ((uint64_t)(lbo >> 4) << 16) | ((uint64_t)(sbo >> 4) << 32) | ((uint64_t)swz << 62);
}
__device__ __forceinline__ uint64_t dadd(uint64_t d, uint32_t o) { return (d & 0xffffffff00000000ull) | (uint32_t)((uint32_t)d + o); }
__device__ __forceinline__ void mbar_init(uint32_t b, uint32_t c) { asm volatile("mbarrier.init.shared.b64 [%0], %1;" ::"r"(b), "r"(c) : "memory"); }
__device__ __forceinline__ void mbar_expect(uint32_t b, uint32_t tx) { asm volatile("mbarrier.arrive.expect_tx.shared.b64 _, [%0], %1;" ::"r"(b), "r"(tx) : "memory"); }
__device__ __forceinline__ void mbar_arrive(uint32_t b) { asm volatile("mbarrier.arrive.shared.b64 _, [%0];" ::"r"(b) : "memory"); }
__device__ __forceinline__ void mbar_arrive_cluster_if(bool c, uint32_t b, uint32_t cta) {
    asm volatile("{.reg .pred p; .reg .b32 r; setp.ne.u32 p, %2, 0; mapa.shared::cluster.u32 r, %0, %1; @p mbarrier.arrive.shared::cluster.b64 _, [r];}" ::"r"(b), "r"(cta), "r"((uint32_t)c) : "memory");
}
__device__ __forceinline__ bool mbar_try(uint32_t b, uint32_t par) {
    uint32_t ok;
    asm volatile("{.reg .pred p; mbarrier.try_wait.parity.shared.b64 p, [%1], %2; selp.u32 %0, 1, 0, p;}" : "=r"(ok) : "r"(b), "r"(par) : "memory");
    return ok;
}
__device__ __forceinline__ void mbar_wait_w(uint32_t b, uint32_t par) {
    int it = 0;
    bool ok;
#pragma unroll 1
    do { ok = __all_sync(~0u, mbar_try(b, par)); spin_guard(++it); } while (!ok);
}
__device__ __forceinline__ void bar_sync(int id, int n) { asm volatile("bar.sync %0, %1;" ::"r"(id), "r"(n) : "memory"); }
__device__ __forceinline__ void bar_arrive(int id, int n) { asm volatile("bar.arrive %0, %1;" ::"r"(id), "r"(n) : "memory"); }
__device__ __forceinline__ void fence_async_smem() { asm volatile("fence.proxy.async.shared::cta;" ::: "memory"); }
__device__ __forceinline__ void ldsm4t(uint32_t* r, uint32_t a) {
    asm volatile("ldmatrix.sync.aligned.m8n8.x4.trans.shared.b16 {%0,%1,%2,%3}, [%4];" : "=r"(r[0]), "=r"(r[1]), "=r"(r[2]), "=r"(r[3]) : "r"(a) : "memory");
}
__device__ __forceinline__ void ldsm4(uint32_t* r, uint32_t a) {
    asm volatile("ldmatrix.sync.aligned.m8n8.x4.shared.b16 {%0,%1,%2,%3}, [%4];" : "=r"(r[0]), "=r"(r[1]), "=r"(r[2]), "=r"(r[3]) : "r"(a) : "memory");
}
__device__ __forceinline__ uint32_t movm(uint32_t a) {
    uint32_t d; asm volatile("movmatrix.sync.aligned.m8n8.trans.b16 %0, %1;" : "=r"(d) : "r"(a)); return d;
}
__device__ __forceinline__ void mma16816(float* d, uint32_t a0, uint32_t a1, uint32_t a2, uint32_t a3, uint32_t b0, uint32_t b1) {
    asm volatile("mma.sync.aligned.m16n8k16.row.col.f32.bf16.bf16.f32 {%0,%1,%2,%3},{%4,%5,%6,%7},{%8,%9},{%0,%1,%2,%3};"
                 : "+f"(d[0]), "+f"(d[1]), "+f"(d[2]), "+f"(d[3]) : "r"(a0), "r"(a1), "r"(a2), "r"(a3), "r"(b0), "r"(b1));
}
__device__ __forceinline__ void mma16816z(float* d, const uint32_t* a, uint32_t b0, uint32_t b1) {
    asm volatile("mma.sync.aligned.m16n8k16.row.col.f32.bf16.bf16.f32 {%0,%1,%2,%3},{%4,%5,%6,%7},{%8,%9},{%10,%10,%10,%10};"
                 : "=f"(d[0]), "=f"(d[1]), "=f"(d[2]), "=f"(d[3]) : "r"(a[0]), "r"(a[1]), "r"(a[2]), "r"(a[3]), "r"(b0), "r"(b1), "f"(0.f));
}
__device__ __forceinline__ void mma1688(float* d, uint32_t a0, uint32_t a1, uint32_t b0) {
    asm volatile("mma.sync.aligned.m16n8k8.row.col.f32.bf16.bf16.f32 {%0,%1,%2,%3},{%4,%5},{%6},{%0,%1,%2,%3};"
                 : "+f"(d[0]), "+f"(d[1]), "+f"(d[2]), "+f"(d[3]) : "r"(a0), "r"(a1), "r"(b0));
}
__device__ __forceinline__ uint32_t pack2(float lo, float hi) {
    uint32_t r; asm("cvt.rn.bf16x2.f32 %0, %1, %2;" : "=r"(r) : "f"(hi), "f"(lo)); return r;
}
__device__ __forceinline__ uint32_t hadd2v(uint32_t a, uint32_t b) {
    uint32_t r; asm volatile("add.rn.bf16x2 %0, %1, %2;" : "=r"(r) : "r"(a), "r"(b)); return r;
}
__device__ __forceinline__ uint32_t hmul2b(uint32_t a, uint32_t b) {
    uint32_t r; asm("mul.rn.bf16x2 %0, %1, %2;" : "=r"(r) : "r"(a), "r"(b)); return r;
}
__device__ __forceinline__ float bflo(uint32_t u) { return __uint_as_float(u << 16); }
__device__ __forceinline__ float bfhi(uint32_t u) { return __uint_as_float(u & 0xffff0000u); }
__device__ __forceinline__ float ex2(float x) { float r; asm("ex2.approx.ftz.f32 %0, %1;" : "=f"(r) : "f"(x)); return r; }
__device__ __forceinline__ uint4 ldg_rlx4(const void* p) {
    uint4 v; asm volatile("ld.relaxed.gpu.global.v4.u32 {%0,%1,%2,%3}, [%4];" : "=r"(v.x), "=r"(v.y), "=r"(v.z), "=r"(v.w) : "l"(p) : "memory"); return v;
}
__device__ __forceinline__ uint32_t ldg_rlx1(const void* p) {
    uint32_t v; asm volatile("ld.relaxed.gpu.global.u32 %0, [%1];" : "=r"(v) : "l"(p) : "memory"); return v;
}
__device__ __forceinline__ void stg_rlx1(void* p, uint32_t v) { asm volatile("st.relaxed.gpu.global.u32 [%0], %1;" ::"l"(p), "r"(v) : "memory"); }
__device__ __forceinline__ void stg_rlx2(void* p, uint32_t x, uint32_t y) {
    unsigned long long v = (unsigned long long)x | ((unsigned long long)y << 32);
    asm volatile("st.relaxed.gpu.global.b64 [%0], %1;" ::"l"(p), "l"(v) : "memory");
}
__device__ __forceinline__ void stg_rlx4(void* p, uint32_t x, uint32_t y, uint32_t z, uint32_t w) {
    asm volatile("st.relaxed.gpu.global.v4.u32 [%0], {%1,%2,%3,%4};" ::"l"(p), "r"(x), "r"(y), "r"(z), "r"(w) : "memory");
}
__device__ __forceinline__ void sts4(uint32_t a, uint32_t x, uint32_t y, uint32_t z, uint32_t w) {
    asm volatile("st.shared.v4.u32 [%0], {%1,%2,%3,%4};" ::"r"(a), "r"(x), "r"(y), "r"(z), "r"(w) : "memory");
}
__device__ __forceinline__ uint4 lds4(uint32_t a) {
    uint4 v; asm volatile("ld.shared.v4.u32 {%0,%1,%2,%3}, [%4];" : "=r"(v.x), "=r"(v.y), "=r"(v.z), "=r"(v.w) : "r"(a) : "memory"); return v;
}
#define F4(d, i) "+f"(d[i]), "+f"(d[i + 1]), "+f"(d[i + 2]), "+f"(d[i + 3])
template <bool V> __device__ __forceinline__ void wgmma_tok_rs(float* d, const uint32_t* a, uint64_t b, int sc) {
    if (V) asm volatile("{.reg .pred p; setp.ne.b32 p, %25, 0;\n wgmma.mma_async.sync.aligned.m64n40k16.f32.bf16.bf16 {%0,%1,%2,%3,%4,%5,%6,%7,%8,%9,%10,%11,%12,%13,%14,%15,%16,%17,%18,%19}, {%20,%21,%22,%23}, %24, p, 1, 1, 0;}"
                        : F4(d, 0), F4(d, 4), F4(d, 8), F4(d, 12), F4(d, 16) : "r"(a[0]), "r"(a[1]), "r"(a[2]), "r"(a[3]), "l"(b), "r"(sc));
    else asm volatile("{.reg .pred p; setp.ne.b32 p, %21, 0;\n wgmma.mma_async.sync.aligned.m64n32k16.f32.bf16.bf16 {%0,%1,%2,%3,%4,%5,%6,%7,%8,%9,%10,%11,%12,%13,%14,%15}, {%16,%17,%18,%19}, %20, p, 1, 1, 0;}"
                      : F4(d, 0), F4(d, 4), F4(d, 8), F4(d, 12) : "r"(a[0]), "r"(a[1]), "r"(a[2]), "r"(a[3]), "l"(b), "r"(sc));
}
template <bool V> __device__ __forceinline__ void wgmma_tok_ss(float* d, uint64_t a, uint64_t b) {
    if (V) asm volatile("wgmma.mma_async.sync.aligned.m64n40k16.f32.bf16.bf16 {%0,%1,%2,%3,%4,%5,%6,%7,%8,%9,%10,%11,%12,%13,%14,%15,%16,%17,%18,%19}, %20, %21, 1, 1, 1, 1, 0;"
                        : F4(d, 0), F4(d, 4), F4(d, 8), F4(d, 12), F4(d, 16) : "l"(a), "l"(b));
    else asm volatile("wgmma.mma_async.sync.aligned.m64n32k16.f32.bf16.bf16 {%0,%1,%2,%3,%4,%5,%6,%7,%8,%9,%10,%11,%12,%13,%14,%15}, %16, %17, 1, 1, 1, 1, 0;"
                      : F4(d, 0), F4(d, 4), F4(d, 8), F4(d, 12) : "l"(a), "l"(b));
}
#define F16(d, i) F4(d, i), F4(d, i + 4), F4(d, i + 8), F4(d, i + 12)
template <int TA>
__device__ __forceinline__ void wgmma_ss128(float* d, uint64_t a, uint64_t b, int sc) {
    asm volatile("{.reg .pred p; setp.ne.b32 p, %66, 0;\n wgmma.mma_async.sync.aligned.m64n128k16.f32.bf16.bf16 "
                 "{%0,%1,%2,%3,%4,%5,%6,%7,%8,%9,%10,%11,%12,%13,%14,%15,%16,%17,%18,%19,%20,%21,%22,%23,%24,%25,%26,%27,%28,%29,%30,%31,"
                 "%32,%33,%34,%35,%36,%37,%38,%39,%40,%41,%42,%43,%44,%45,%46,%47,%48,%49,%50,%51,%52,%53,%54,%55,%56,%57,%58,%59,%60,%61,%62,%63}, %64, %65, p, 1, 1, %67, 1;}"
                 : F16(d, 0), F16(d, 16), F16(d, 32), F16(d, 48) : "l"(a), "l"(b), "r"(sc), "n"(TA));
}

__device__ __forceinline__ float warp_sum(float v) {
#pragma unroll
    for (int o = 16; o; o >>= 1) v += __shfl_xor_sync(~0u, v, o);
    return v;
}
__device__ __forceinline__ float bfround(float x) { return __bfloat162float(__float2bfloat16(x)); }

__device__ __forceinline__ void wait_count1(const uint32_t* p, uint32_t target) {
    int it = 0;
#pragma unroll 1
    while (true) {
        uint32_t v;
        asm volatile("ld.acquire.gpu.global.u32 %0, [%1];" : "=r"(v) : "l"(p) : "memory");
        if (v >= target) break;
        spin_guard(++it);
    }
}
__device__ __forceinline__ void signal_count(uint32_t* p) { asm volatile("red.release.gpu.global.add.u32 [%0], 1;" ::"l"(p) : "memory"); }
__device__ __forceinline__ void e_expect(uint32_t b, uint32_t tx) {
    asm volatile("{.reg .pred p; elect.sync _|p, 0xffffffff; @p mbarrier.arrive.expect_tx.shared.b64 _, [%0], %1;}" ::"r"(b), "r"(tx) : "memory");
}
__device__ __forceinline__ uint64_t evict_first() { uint64_t p; asm("createpolicy.fractional.L2::evict_first.b64 %0, 1.0;" : "=l"(p)); return p; }
__device__ __forceinline__ void e_tma2d_ef(uint32_t dst, const CUtensorMap* m, int c0, int c1, uint32_t bar) {
    asm volatile("{.reg .pred p; elect.sync _|p, 0xffffffff;\n @p cp.async.bulk.tensor.2d.shared::cluster.global.mbarrier::complete_tx::bytes.L2::cache_hint [%0], [%1, {%3, %4}], [%2], %5;}"
                 ::"r"(dst), "l"(m), "r"(bar), "r"(c0), "r"(c1), "l"(evict_first()) : "memory");
}
__device__ __forceinline__ void e_tma2d(uint32_t dst, const CUtensorMap* m, int c0, int c1, uint32_t bar) {
    asm volatile("{.reg .pred p; elect.sync _|p, 0xffffffff;\n @p cp.async.bulk.tensor.2d.shared::cluster.global.mbarrier::complete_tx::bytes [%0], [%1, {%3, %4}], [%2];}"
                 ::"r"(dst), "l"(m), "r"(bar), "r"(c0), "r"(c1) : "memory");
}
__device__ __forceinline__ void e_tma2d_mc_ef(uint32_t dst, const CUtensorMap* m, int c0, int c1, uint32_t bar) {
    asm volatile("{.reg .pred p; elect.sync _|p, 0xffffffff;\n @p cp.async.bulk.tensor.2d.shared::cluster.global.mbarrier::complete_tx::bytes.multicast::cluster.L2::cache_hint [%0], [%1, {%3, %4}], [%2], %5, %6;}"
                 ::"r"(dst), "l"(m), "r"(bar), "r"(c0), "r"(c1), "h"((uint16_t)3), "l"(evict_first()) : "memory");
}
__device__ __forceinline__ uint32_t wait_count_w(const uint32_t* p, uint32_t target) {
    int it = 0;
#pragma unroll 1
    while (true) {
        uint32_t v;
        asm volatile("ld.acquire.gpu.global.u32 %0, [%1];" : "=r"(v) : "l"(p) : "memory");
        if (__all_sync(~0u, v >= target)) return v;
        spin_guard(++it);
    }
}

constexpr int NL = 6;
constexpr uint32_t HCH = 5120, HBUF = 8 * HCH;
constexpr uint32_t SM_SX = 0, SM_ST = 2560, SM_OX = 8192, SM_LX = 10240, SM_PX = 11392, SM_PA = 12288, SM_VF = 18432, SM_TAB = 26624, SM_WL2 = 41984, SM_HB = 49152, SM_WO = 131072,
                   SM_WL = 196608, SM_PRE = SM_WL, SM_BAR = 227328, SM_TRC = SM_BAR + 256, SM_REC_TOTAL = SM_TRC + 2688;
__host__ __device__ constexpr uint32_t sm_wl(int i) { return i < 5 ? SM_WL + i * 6144 : SM_WL2; }
constexpr uint32_t SB0 = 1024;
constexpr int B_WO = 0, B_HE = 1, B_ROLE = 2, B_HB = 3, B_W = 5;
constexpr int NB_MEM = 1, NB_QK = 2, NB_X1 = 3, NB_X2 = 4, NB_WIN = 5, NB_WG = 6, NB_KDONE = 7, NB_FIN0 = 8, NB_LN = 9, NB_MEM2 = 10, NB_H = 11, NB_A = 12, NB_B = 13, NB_C = 14, NB_F = 15;
constexpr int TPV_DLY = 6;
constexpr int L_AT = 3;
constexpr int D_X2 = 250;
constexpr int NPF1 = 6;
constexpr int NPF = 11;
constexpr int T_GO = 28;
constexpr int GATE_AT = 25;
constexpr int T_X2 = 1890;
constexpr int T_V = 400;
constexpr int VP_AT = 1;
constexpr int PD = 3;
constexpr int PV_FENCE = 0;
constexpr int SSG = 5;
constexpr int SSG_V = 4;
constexpr int SS0_K = 2;
constexpr int SS0_V = 6;
constexpr int NPF0 = 3;
constexpr int STG_FENCE = 9;
constexpr int WO_AT = 0x1100;
constexpr int W_SPEC = 7;
constexpr int NO_GUESS = 0;
constexpr int W_T0 = 2800;
constexpr int NPF2 = 7;
constexpr int PF_DLY = 6;
constexpr int H_D = 160;
constexpr int PIN_EPI = 0;

__device__ __forceinline__ uint32_t clk32() { uint32_t t; asm volatile("mov.u32 %0, %%clock;" : "=r"(t) :: "memory"); return t; }
__device__ __forceinline__ uint32_t gtime32() { uint32_t t; asm volatile("mov.u32 %0, %%globaltimer_lo;" : "=r"(t) :: "memory"); return t; }
template <int N> __device__ __forceinline__ uint32_t delay(uint32_t zero) {
    float x = __uint_as_float(clk32());
#pragma unroll
    for (int i = 0; i < N; i++) asm volatile("ex2.approx.ftz.f32 %0, %0;" : "+f"(x));
    return __float_as_uint(x) & zero;
}
__device__ __forceinline__ uint32_t clk_after(uint32_t x, uint32_t zero) {
    unsigned long long c = 0;
    asm volatile("{.reg .pred p; setp.eq.u32 p, %1, 0; @p mov.u64 %0, %%clock64;}" : "+l"(c) : "r"(x & zero) : "memory");
    return (uint32_t)c;
}
__device__ __forceinline__ uint32_t later(uint32_t a, uint32_t b) { return a + max((int)(b - a), 0); }
__device__ __forceinline__ void wait_clk(uint32_t t) {
#pragma unroll 1
    while (true) {
        unsigned long long c;
        asm volatile("mov.u64 %0, %%clock64;" : "=l"(c) :: "memory");
        if ((int)((uint32_t)c - t) >= 0) break;
    }
}
__device__ __forceinline__ uint32_t opaque(uint32_t v) { return __shfl_sync(~0u, v, threadIdx.x & 31); }
__device__ __forceinline__ uint32_t xor_or(uint32_t a, uint32_t b, uint32_t t) {
    uint32_t r; asm volatile("lop3.b32 %0, %1, %2, %3, 0x7E;" : "=r"(r) : "r"(a), "r"(b), "r"(t)); return r;
}
__device__ __forceinline__ uint32_t or3(uint32_t a, uint32_t b, uint32_t c) {
    uint32_t r; asm volatile("lop3.b32 %0, %1, %2, %3, 0xFE;" : "=r"(r) : "r"(a), "r"(b), "r"(c)); return r;
}
__device__ __forceinline__ uint32_t settag(uint32_t v, uint32_t tag) {
    uint32_t r; asm("lop3.b32 %0, %1, 1, %2, 0xB8;" : "=r"(r) : "r"(v), "r"(tag)); return r;
}
__device__ __forceinline__ void ldg1_if(uint32_t& v, const void* p, bool c) {
    asm volatile("{.reg .pred p; setp.ne.u32 p, %2, 0; @p ld.relaxed.gpu.global.u32 %0, [%1];}" : "+r"(v) : "l"(p), "r"((uint32_t)c) : "memory");
}
__device__ __forceinline__ void sts2(uint32_t a, float x, float y) { asm volatile("st.shared.v2.f32 [%0], {%1,%2};" ::"r"(a), "f"(x), "f"(y) : "memory"); }
__device__ __forceinline__ void sts4f(uint32_t a, float x, float y, float z, float w) {
    asm volatile("st.shared.v4.f32 [%0], {%1,%2,%3,%4};" ::"r"(a), "f"(x), "f"(y), "f"(z), "f"(w) : "memory");
}
__device__ __forceinline__ void sts1(uint32_t a, uint32_t x) { asm volatile("st.shared.u32 [%0], %1;" ::"r"(a), "r"(x) : "memory"); }
__device__ __forceinline__ uint32_t lds1(uint32_t a) { uint32_t v; asm volatile("ld.shared.u32 %0, [%1];" : "=r"(v) : "r"(a) : "memory"); return v; }
__device__ __forceinline__ float4 lds4f(uint32_t a) {
    float4 v; asm volatile("ld.shared.v4.f32 {%0,%1,%2,%3}, [%4];" : "=f"(v.x), "=f"(v.y), "=f"(v.z), "=f"(v.w) : "r"(a) : "memory"); return v;
}
__device__ __forceinline__ float2 lds2f(uint32_t a) {
    float2 v; asm volatile("ld.shared.v2.f32 {%0,%1}, [%2];" : "=f"(v.x), "=f"(v.y) : "r"(a) : "memory"); return v;
}
__device__ __forceinline__ bool any_bit0(uint32_t x) {
    uint32_t r;
    asm volatile("{.reg .pred p, q; .reg .b32 t; and.b32 t, %1, 1; setp.ne.u32 p, t, 0; vote.sync.any.pred q, p, 0xffffffff; selp.u32 %0, 1, 0, q;}" : "=r"(r) : "r"(x));
    return r;
}
__device__ __forceinline__ float rcp_fast(float x) { float r; asm("rcp.approx.ftz.f32 %0, %1;" : "=f"(r) : "f"(x)); return r; }
__device__ __forceinline__ void stsm4(uint32_t a, uint32_t r0, uint32_t r1, uint32_t r2, uint32_t r3) {
    asm volatile("stmatrix.sync.aligned.m8n8.x4.shared.b16 [%0], {%1,%2,%3,%4};" ::"r"(a), "r"(r0), "r"(r1), "r"(r2), "r"(r3) : "memory");
}
__device__ __forceinline__ void stsm4t(uint32_t a, uint32_t r0, uint32_t r1, uint32_t r2, uint32_t r3) {
    asm volatile("stmatrix.sync.aligned.m8n8.x4.trans.shared.b16 [%0], {%1,%2,%3,%4};" ::"r"(a), "r"(r0), "r"(r1), "r"(r2), "r"(r3) : "memory");
}
__device__ __forceinline__ void cp_async16(uint32_t dst, const void* src) { asm volatile("cp.async.cg.shared.global [%0], [%1], 16;" ::"r"(dst), "l"(src) : "memory"); }
__device__ __forceinline__ void cp_async16_ef(uint32_t dst, const void* src) {
    asm volatile("cp.async.cg.shared.global.L2::cache_hint [%0], [%1], 16, %2;" ::"r"(dst), "l"(src), "l"(evict_first()) : "memory");
}
__device__ __forceinline__ uint32_t prmt(uint32_t a, uint32_t b, uint32_t c) { uint32_t r; asm("prmt.b32 %0, %1, %2, %3;" : "=r"(r) : "r"(a), "r"(b), "r"(c)); return r; }
__device__ __forceinline__ uint32_t hadd2h(uint32_t a, uint32_t b) { uint32_t r; asm("add.rn.f16x2 %0, %1, %2;" : "=r"(r) : "r"(a), "r"(b)); return r; }
__device__ __forceinline__ uint32_t hmax2h(uint32_t a, uint32_t b) { uint32_t r; asm("max.f16x2 %0, %1, %2;" : "=r"(r) : "r"(a), "r"(b)); return r; }
__device__ __forceinline__ uint32_t max3u(uint32_t a, uint32_t b, uint32_t c) { return __vimax3_u32(a, b, c); }

__device__ __forceinline__ void h_load(uint32_t sb, const uint8_t* hsrc, int pass, uint32_t rank, uint32_t rot, uint32_t wq, bool arm = true, uint32_t skip = 0) {
    const uint32_t bar = sb + SM_BAR + 8 * (B_HB + (pass & 1)), c = (wq + rot) & 3, dst = sb + SM_HB + (pass & 1) * HBUF + (rank * 4 + c) * HCH + skip;
    const uint8_t* src = hsrc + ((size_t)pass * 65536 + c * 4096 + skip);
    if (arm && wq == 0) e_expect(bar, 32768 - 8 * skip);
    asm volatile("{.reg .pred p; elect.sync _|p, 0xffffffff;\n"
                 " @p cp.async.bulk.shared::cluster.global.mbarrier::complete_tx::bytes.multicast::cluster.L2::cache_hint [%0], [%1], %4, [%2], %3, %5;}"
                 ::"r"(dst), "l"(src), "r"(bar), "h"((uint16_t)3), "r"(4096 - skip), "l"(evict_first()) : "memory");
}
__device__ __forceinline__ uint4 ldg_b128(const void* p) {
    uint4 v;
    asm volatile("{.reg .b128 t; .reg .b64 a, b; ld.relaxed.gpu.global.b128 t, [%4]; mov.b128 {a, b}, t; mov.b64 {%0,%1}, a; mov.b64 {%2,%3}, b;}"
                 : "=r"(v.x), "=r"(v.y), "=r"(v.z), "=r"(v.w) : "l"(p) : "memory");
    return v;
}
__device__ __forceinline__ void stg_b128_if(bool c, void* p, uint32_t x, uint32_t y, uint32_t z, uint32_t w) {
    asm volatile("{.reg .pred p; .reg .b128 t; .reg .b64 a, b; setp.ne.u32 p, %5, 0; mov.b64 a, {%1,%2}; mov.b64 b, {%3,%4}; mov.b128 t, {a, b}; @p st.relaxed.gpu.global.b128 [%0], t;}"
                 ::"l"(p), "r"(x), "r"(y), "r"(z), "r"(w), "r"((uint32_t)c) : "memory");
}
__device__ __forceinline__ float pretag(float x, uint32_t add, uint32_t keep) { return __uint_as_float((__float_as_uint(x) + add) & keep); }

template <bool MASK, class F>
__device__ __forceinline__ void softmax_rows(uint32_t src, uint32_t dst, uint32_t g16, int row0, F mid) {
    const uint32_t u = (g16 >> 7) & 3, e = ((g16 >> 9) << 3) | ((g16 >> 4) & 7);
    const uint32_t se = src + e * 8, su = se + u * 1088;
    const float2 p0 = lds2f(su), p1 = lds2f(su + 256), p2 = lds2f(su + 512), p3 = lds2f(su + 768);
    const float2 m0 = lds2f(se + 4352), m1 = lds2f(se + 4352 + 256), m2 = lds2f(se + 4352 + 512), m3 = lds2f(se + 4352 + 768);
    float a0 = (p0.x + p1.x) + (p2.x + p3.x), a1 = (p0.y + p1.y) + (p2.y + p3.y);
    const float a2 = (m0.x + m1.x) + (m2.x + m3.x), a3 = (m0.y + m1.y) + (m2.y + m3.y);
    mid(__float_as_uint(a3));
    if (MASK) {
        const int vis = row0 + (e >> 2) - 2 * (e & 3) - 8 * u;
        if (vis < 0) a0 = -1e9f / 0.08838834764831845f;
        if (vis < 1) a1 = -1e9f / 0.08838834764831845f;
    }
    int k = __float_as_int(fmaxf(fmaxf(a0, a1), fmaxf(a2, a3)));
    k ^= (k >> 31) & 0x7fffffff;
    const bool hi = g16 & 64;
    const int k0 = __reduce_max_sync(~0u, hi ? INT_MIN : k), k1 = __reduce_max_sync(~0u, hi ? k : INT_MIN);
    k = hi ? k1 : k0;
    const float m = __int_as_float(k ^ ((k >> 31) & 0x7fffffff));
    const float sl2 = 0.08838834764831845f * 1.4426950408889634f, mb = -m * sl2;
    sts1(dst + e * 16 + u * 4, pack2(ex2(fmaf(a0, sl2, mb)), ex2(fmaf(a1, sl2, mb))));
    sts1(dst + 512 + e * 4, pack2(ex2(fmaf(a2, sl2, mb)), ex2(fmaf(a3, sl2, mb))));
}

__device__ __forceinline__ uint32_t pack_h2(float lo, float hi) {
    uint32_t r; asm("cvt.rn.satfinite.f16x2.f32 %0, %1, %2;" : "=r"(r) : "f"(hi), "f"(lo)); return r;
}
__device__ __forceinline__ float2 unpack_h2(uint32_t u) {
    float2 r; asm("{.reg .b16 l, h; mov.b32 {l, h}, %2; cvt.f32.f16 %0, l; cvt.f32.f16 %1, h;}" : "=f"(r.x), "=f"(r.y) : "r"(u)); return r;
}
__device__ __forceinline__ uint32_t h2bf(uint32_t u) {
    uint32_t r;
    asm volatile("{.reg .b16 l, h; .reg .f32 a, b; mov.b32 {l, h}, %1; cvt.f32.f16 a, l; cvt.f32.f16 b, h; cvt.rn.bf16x2.f32 %0, b, a;}" : "=r"(r) : "r"(u));
    return r;
}
__device__ __forceinline__ void red_h10(bool c, void* p, void* q, uint32_t x, uint32_t y, uint32_t z, uint32_t w, uint32_t e) {
    asm volatile("{.reg .pred p; setp.ne.u32 p, %7, 0; red.relaxed.gpu.global.add.noftz.v4.f16x2 [%0], {%2,%3,%4,%5};\n"
                 " @p red.relaxed.gpu.global.add.noftz.f16x2 [%1], %6;}" ::"l"(p), "l"(q), "r"(x), "r"(y), "r"(z), "r"(w), "r"(e), "r"((uint32_t)c) : "memory");
}
constexpr float Q_SCALE = 1024.0f;
constexpr float SM_L2E = 0.08838834764831845f * 1.4426950408889634f * Q_SCALE;
template <int V> struct IC { static constexpr int value = V; };
typedef unsigned long long u64;
__device__ __forceinline__ uint32_t lo32(u64 v) { return (uint32_t)v; }
__device__ __forceinline__ uint32_t hi32(u64 v) { return (uint32_t)(v >> 32); }
__device__ __forceinline__ u64 ldg_u64(const void* p) { u64 v; asm volatile("ld.relaxed.gpu.global.b64 %0, [%1];" : "=l"(v) : "l"(p) : "memory"); return v; }
struct RecTime { uint32_t go, x2, v, dx2, h; };
__device__ __forceinline__ void rec_main(uint32_t sb, const CUtensorMap* tWo, uint8_t* arena, int role, int hinfo, int wg, uint32_t zero, const RecTime& tm) {
    const int hA = hinfo & 255;
    const int tid = threadIdx.x, t = tid & 127, lane = tid & 31, wi = t >> 5;
    const uint32_t bars = sb + SM_BAR;
    const int head = role >> 2, qd = role & 3, j = blockIdx.x & 1, kh = role & 1;
    const uint32_t mypar = head >= hA;
    const uint32_t wiu = __reduce_max_sync(~0u, wi);
    const bool warp0 = wiu == 0;
    const uint8_t* hsrc = (const uint8_t*)g_himg + kh * 32768 + j * 16384;
    auto tokbase = [&](int ty) { return ((ty + 1) << 21) + blk(lb_tok(head), mypar ^ ((hinfo >> (8 + ty)) & 1)); };
    const uint32_t tbw = tokbase(wg), tbq = tokbase(0) + (qd >> 1) * 2048 + (qd & 1) * 8;
#define KS(p) (4 * (((p) >> 1) & 7) + ((p) >> 4) + 2 * ((p) & 1))
    uint32_t w[32 - NL][4];
    uint4 wl5;
    if (wg == 2) bar_arrive(NB_WIN, 384);
    const uint32_t po = (1 << 20) + j * 16384 + kh * 2048;
    const uint32_t c16 = kh * 2048 + ((2 * j + (wi >> 1)) * 32 + lane) * 16, xso = blk(lb_x2(head), mypar);
    const uint32_t x2o = xso + wg * 16384 + (wi & 1) * 2048 + (c16 >> 1), tko = tbw + (wi & 1) * 16384 + c16;
    {
        stg_rlx2(arena + x2o, 0, 0);
#pragma unroll
        for (int i = 0; i < 4; i++) stg_rlx4(arena + ((i & 1 ? tko : tbw + (po ^ 2048) + t * 16) + (i >> 1) * 32768), 0, 0, 0, 0);
    }
    const uint32_t frow = ((lane >> 4) * 8 + (lane & 7)) * 128, fx = ((lane >> 3) & 1) ^ (lane & 7);
    {
#pragma unroll 1
        for (int i = 0; i < 4; i++) mbar_wait_w(bars + 8 * (B_W + (wg == 2 ? 8 + i : 2 * i + wg)), 0);
        const uint32_t stg = sb + wg * 65536;
#pragma unroll
        for (int p = NL; p < 32; p++) ldsm4t(w[p - NL], stg + KS(p) * 2048 + frow + ((fx ^ (2 * wi)) << 4));
#pragma unroll
        for (int i = 0; i < NL; i++) {
            wl5 = lds4(stg + KS(i) * 2048 + t * 16);
            if (i < 5) sts4(sb + sm_wl(i) + tid * 16, wl5.x, wl5.y, wl5.z, wl5.w);
        }
        fence_async_smem();
        if (wg < 2) bar_sync(NB_WG, 256);
        if (wg > 0) wait_count_w(&g_tick[32 + (lane & 3) * 8], wg);
        if (wg == 1) {
            mbar_arrive_cluster_if(t == 0, bars + 8 * B_HE, j ^ 1);
            asm volatile("fence.proxy.async.global;" ::: "memory");
            mbar_wait_w(bars + 8 * B_HE, 0);
#pragma unroll 1
            for (int i = 0; i < 2; i++) h_load(sb, hsrc, i, j, head, wiu, true, i ? 0 : 2048);
        }
    }
    uint32_t g16 = opaque(t * 16);
    {
        const uint32_t wr = ((wg * 4 + wi) ^ head) & 7;
        const uint32_t pc = wg < 2 ? acc_piece(wr >> 2, qd, wr & 3) : acc_piece(kh, wi, 0);
        const uint32_t lm = sb + SM_HB + 4096 + (lane & 7) * 128;
        const uint32_t a0 = wg < 2 ? sb + SM_WL + wg * 2048 + frow + ((fx ^ (2 * wi)) << 4) : blk(LB_STAMP + (wi >> 1), mypar) + stamp_line(wi, lane >> 3) + (lane & 7) * 16;
        const uint32_t a1 = pc + lane * 16;
        const uint32_t a2 = wg < 2 ? pc + 512 + (lane >> 3) * 4 : (role >> 2) * 1024 + (lane < 8 ? (role & 3) * 128 : 384) + lane * 16;
        const uint32_t a3 = wg < 2 ? sb + SM_WO + (wr >> 2) * 32768 + frow + ((fx ^ (2 * (wr & 3))) << 4) : qd * 65536 + head * 2048 + wi * 512 + lane * 4;
        const uint32_t a4 = wg < 2 ? lm + ((fx ^ ((lane >> 4) * 4)) << 4) : lm + (fx << 4) + ((lane >> 4) + 2 * wi) * HCH;
        if (wg < 2) bar_arrive(NB_X2, 384);
        else bar_sync(NB_X2, 384);
        if (NL > 5) {
            sts4(sb + SM_WL2 + tid * 16, wl5.x, wl5.y, wl5.z, wl5.w);
            fence_async_smem();
            bar_sync(NB_WG + 1 + wg, 128);
        }
        sts4(sb + SM_TAB + wg * 5120 + g16, a0, x2o,
             wg ? xso + (wg == 2 ? 32768 : 0) + t * 8 : blk(LB_STAMP + ((lane >> 1) & 1), (lane >> 2) & 1) + stamp_line(lane, qd) + head * 4, tko);
        sts4(sb + SM_TAB + wg * 5120 + 2048 + g16, a1, a2, a3, a4);
        sts2(sb + SM_TAB + wg * 5120 + 4096 + t * 8, __uint_as_float(tbw + t * 16), __uint_as_float((wg ? tbq : tokbase(1)) + t * 16));
    }
    const uint32_t ONES = 0x3f803f80u, tabw = sb + SM_TAB + wg * 5120;
#define LAST ((g16 & 0x70) == 0x70)

    auto pa_ptr = [&](int p) { return arena + (((p & 1) ^ 1) * 32768 + po + lds1(tabw + 4096 + (g16 >> 1))); };
    auto pa_request = [&](int p) { cp_async16(sb + SM_PA + wg * 2048 + g16, pa_ptr(p)); };
    auto pa_get = [&](int p) {
        asm volatile("cp.async.wait_all;" ::: "memory");
        uint4 pa = lds4(sb + SM_PA + wg * 2048 + g16);
        int it = 0;
#pragma unroll 1
        while (any_bit0(pa.x ^ ((p - 1) >> 1) ^ 1) && p > 0 && p <= NSEG) { pa = ldg_b128(pa_ptr(p)); spin_guard(++it); }
        return pa;
    };
    auto pass_init = [&](float* acc, int n, uint4 pa) {
#pragma unroll
        for (int i = 0; i < 4; i++) { acc[2 * i] = bflo((&pa.x)[i]); acc[2 * i + 1] = bfhi((&pa.x)[i]); }
#pragma unroll
        for (int i = 8; i < n; i++) acc[i] = 0.f;
    };
    auto pass_run = [&](auto vc, int p, float* acc, auto mid) {
        constexpr bool V = decltype(vc)::value;
#define HB(ks) dadd(mkdesc(SB0 + SM_HB + ((ks) >> 2) * HCH + ((ks) & 3) * 32, 16, 1024, 1), (p & 1) * (HBUF / 16))
        wg_fence();
#pragma unroll
        for (int i = 0; i < 32; i++) {
            constexpr int GAP = V ? SSG_V : SSG, SS0 = V ? SS0_V : SS0_K;
            const int u = i < SS0 ? 0 : (i - SS0 + GAP - 1) / GAP, q = i - (u < NL ? u : NL);
            if (i >= SS0 && (i - SS0) % GAP == 0 && u < NL) wgmma_tok_ss<V>(acc, dadd(mkdesc(SB0 + sm_wl(u), 8192, 1024, 1), (V ? 2 : wg) * 128), HB(KS(u)));
            else wgmma_tok_rs<V>(acc, w[q], HB(KS(NL + q)), 1);
            mid(i);
        }
        wg_commit();
    };
    auto pass_out = [&](auto tc, int p, float* acc, auto mid) {
        constexpr int TY = decltype(tc)::value;
        const bool V = TY == 2 || (TY == 4 && wg == 2), Q = TY >= 3 && wg == 0;
        const int b = p & 1, s = p - 2;
        (void)s;
        const uint32_t ftag = (((p - 1) >> 1) & 1) ^ 1, ptag = ((p >> 1) & 1) ^ 1;
        const bool tg = V || !(g16 & 64);
        const uint32_t add = tg ? (ftag ^ 1) << 16 : 0u, keep = tg ? 0xfffe0000u : ~0u;
        const uint32_t add1 = V ? 0u : add, keep1 = V ? ~0u : keep;
        const uint32_t add2 = Q ? add : 0u, keep2 = Q ? keep : ~0u;
        uint8_t* pdst = arena + (b * 32768 + (po ^ 2048) + lds1(tabw + 4096 + (g16 >> 1)));
        uint8_t* fdst = arena + ((b ^ 1) * 32768 + lds1(tabw + 12 + g16));
        if (PIN_EPI) asm volatile("" : "+l"(pdst), "+l"(fdst));
        mid(0);
        uint32_t r0 = pack2(pretag(acc[0], add, keep), pretag(acc[1], add1, keep1));
        uint32_t r1 = pack2(acc[2], acc[3]), r3 = pack2(acc[6], acc[7]);
        uint32_t r2 = pack2(pretag(acc[4], add2, keep2), pretag(acc[5], add2, keep2));
        if (!V) { r0 = movm(r0); r1 = movm(r1); r2 = movm(r2); r3 = movm(r3); }
        mid(1);
        stg_b128_if(p < NSEG, pdst, settag(pack2(pretag(acc[8], (ptag ^ 1) << 16, 0xfffe0000u), acc[9]), ptag), pack2(acc[10], acc[11]), pack2(acc[12], acc[13]), pack2(acc[14], acc[15]));
        stg_b128_if(p > 0 && p <= NSEG, fdst, settag(r0, ftag), r1, Q ? settag(r2, ftag) : r2, r3);
    };
    auto nop = [](int) {};
    auto wait0 = [](int i) { if (i == 0) wg_wait<0>(); };
    uint4 tf[2][2];
    auto load_tok = [&](int s, uint32_t o) {
        const uint8_t* ts = arena + ((s & 1) * 32768 + o);
#pragma unroll
        for (int a = 0; a < 2; a++)
#pragma unroll
            for (int b = 0; b < 2; b++) tf[a][b] = ldg_b128(ts + a * 16384 + b * 2048);
    };

    auto wo_load = [&](int stage) {
        if (wg == 2 && ((WO_AT >> (4 * wiu)) & 15) == stage) {
            const int c0 = (wiu >> 1) * 512 + qd * 128 + (wiu & 1) * 64;
            e_expect(bars + 8 * B_WO, 16384);
            e_tma2d(sb + SM_WO + wiu * 16384, tWo, c0, head * DH, bars + 8 * B_WO);
            e_tma2d(sb + SM_WO + wiu * 16384 + 8192, tWo, c0, head * DH + 64, bars + 8 * B_WO);
        }
    };
#pragma unroll 1
    for (int p = 0; p <= (wg >> 1); p++) {
        mbar_wait_w(bars + 8 * (B_HB + p), 0);
        float acc[16];
        pass_init(acc, 16, pa_get(p));
        wo_load(p);
        pass_run(IC<0>(), p, acc, nop);
        if (p) {
            mbar_wait_w(bars + 8 * B_HE, 1);
            asm volatile("fence.proxy.async.global;" ::: "memory");
            h_load(sb, hsrc, 2, j, head, wiu);
        }
        pass_out(IC<4>(), p, acc, wait0);
        if (wg < 2) {
            bar_arrive(NB_C, 384);
            if (wg == 0) bar_arrive(NB_WIN, 384);
        } else if (p == 0) {
            bar_sync(NB_C, 384);
            mbar_arrive_cluster_if(g16 == 0, bars + 8 * B_HE, j ^ 1);
        }
        pa_request(p + 1);
    }
    if (wg < 2) {
        mbar_wait_w(bars + 8 * (B_HB + 1), 0);
        uint4 pa = pa_get(1);
        uint32_t wl = lds1(tabw + g16);
#pragma unroll 1
        for (int s = 0; s < NSEG; s++) {
            uint32_t w0[NL][4], xo, lm, fz = 0;
            float acc[16];
#pragma unroll
            for (int i = 0; i < 4; i++)
                asm volatile("shl.b32 %0, %4, 16; and.b32 %1, %4, 0xffff0000; mov.b32 %2, %5; mov.b32 %3, %5;"
                             : "=&f"(acc[2 * i]), "=f"(acc[2 * i + 1]), "=f"(acc[8 + 2 * i]), "=f"(acc[9 + 2 * i]) : "r"((&pa.x)[i]), "r"(zero));
#pragma unroll
            for (int i = 0; i < NL; i++) ldsm4t(w0[i], wl + (sm_wl(i) - SM_WL));
            if (wg == 0) bar_sync(NB_B, 256);
            else bar_sync(NB_WIN, 384);
            pass_run(IC<0>(), s + 1, acc, [&](int i) { if (i == GATE_AT && wg) bar_arrive(NB_B, 256); });
            xo = lds1(tabw + 4 + g16);
            lm = lds1(tabw + 2060 + g16) + (s & 1) * HBUF;
            pass_out(IC<3>(), s + 1, acc, [&](int i) {
                if (i == 0) {
                    wg_wait<0>();
                    if (wg == 0) bar_arrive(NB_MEM, 384);
                    fz |= clk32();
                }
                if (i == 1 && wg) bar_sync(NB_F, 256);
            });
            asm volatile("" : "+r"(lm));
            if (wg == 0) bar_sync(NB_MEM2, 256);
            else bar_sync(NB_MEM, 384);
            float c[4][4];
            uint32_t bq[PD][4];
#define MEMF(it) ((lm ^ (((it) >> 3) * 32)) + ((it) & 7) * HCH)
#pragma unroll
            for (int it = 0; it < PD; it++) ldsm4(bq[it], MEMF(it));
#pragma unroll
            for (int it = 0; it < 16; it++) {
                uint32_t* bfr = bq[it % PD];
                const uint32_t* wa = 2 * it < NL ? w0[2 * it < NL ? 2 * it : 0] : w[2 * it < NL ? 0 : 2 * it - NL];
                const uint32_t* wb = 2 * it + 1 < NL ? w0[2 * it + 1 < NL ? 2 * it + 1 : 0] : w[2 * it + 1 < NL ? 0 : 2 * it + 1 - NL];
                float *ca = c[(2 * it) & 3], *cb = c[(2 * it + 1) & 3];
                if (it < 2) { mma16816z(ca, wa, bfr[0], bfr[1]); mma16816z(cb, wb, bfr[2], bfr[3]); }
                else { mma16816(ca, wa[0], wa[1], wa[2], wa[3], bfr[0], bfr[1]); mma16816(cb, wb[0], wb[1], wb[2], wb[3], bfr[2], bfr[3]); }
                if (it + PD < 16) ldsm4(bfr, MEMF(it + PD));
            }
            const float qs = wg ? 1.0f : 1.0f / Q_SCALE;
#define CSUM(e) fmaf(c[2][e] + c[3][e], qs, (c[0][e] + c[1][e]) * qs)
            const uint32_t r0 = pack2(CSUM(0), CSUM(1)), r1 = pack2(CSUM(2), CSUM(3));
            bar_arrive(NB_QK + (r0 & zero), 384);
            stg_rlx2(arena + xo, settag(movm(r0), (s & 1) ^ 1), movm(r1));
            const uint32_t tx = later(lds1(sb + SM_LX + 1040) + tm.x2, clk_after(r0, zero) + tm.dx2);
            g16 |= (fz | tx) & zero;
            {
                const uint32_t l16 = sb + (g16 & 0x1f0), g8 = g16 >> 1;
                const uint32_t tag = (s & 1) ^ 1, ttag = ((s >> 1) & 1) ^ 1;
                uint32_t wf[NPF][4], a3;
#define WF(f) (a3 + ((f) & 1) * 16384 + ((f) >> 1) * 2048)
                if (wg == 1) {
                    float sc[5][4];
                    uint4 (&kf)[2][2] = tf;
                    uint32_t qa[2][4], km[4], fz;
                    const uint32_t sd = lds1(sb + SM_TAB + 8 + g16);
                    int it = 0;
                    bool bad;
#pragma unroll 1
                    do {
                        u64 qf[2], x[8];
                        const float2 u = lds2f(tabw + 4096 + g8);
                        load_tok(s, __float_as_uint(u.x));
                        const uint8_t *xp = arena + lds1(tabw + 8 + g16), *tq = arena + ((s & 1) * 32768 + __float_as_uint(u.y));
                        asm volatile("" : "+l"(xp));
                        asm volatile("" : "+l"(tq));
#pragma unroll
                        for (int a = 0; a < 2; a++) qf[a] = ldg_u64(tq + a * 16384);
                        spin_guard(++it);
                        wait_clk(tx);
#pragma unroll
                        for (int i = 0; i < 8; i++) x[i] = ldg_u64(xp + (i >> 2) * 16384 + (i & 3) * 1024);
                        fz = clk32();
                        const uint32_t bt = or3(xor_or(lo32(qf[0]), lo32(qf[1]), ttag), xor_or(kf[0][0].x, kf[0][1].x, ttag), xor_or(kf[1][0].x, kf[1][1].x, ttag));
#pragma unroll
                        for (int a = 0; a < 2; a++) { qa[a][1] = or3(lo32(qf[a]), zero, 0); qa[a][3] = or3(hi32(qf[a]), zero, 0); }
                        fz |= clk32();
#pragma unroll
                        for (int a = 0; a < 2; a++) { qa[a][0] = hadd2v(lo32(x[2 * a]), lo32(x[2 * a + 1])); qa[a][2] = hadd2v(hi32(x[2 * a]), hi32(x[2 * a + 1])); }
#pragma unroll
                        for (int a = 0; a < 2; a++) { km[2 * a] = hadd2v(lo32(x[4 + 2 * a]), lo32(x[5 + 2 * a])); km[2 * a + 1] = hadd2v(hi32(x[4 + 2 * a]), hi32(x[5 + 2 * a])); }
                        bad = any_bit0(or3(or3(bt, xor_or(lo32(x[0]), lo32(x[1]), tag), xor_or(lo32(x[2]), lo32(x[3]), tag)), xor_or(lo32(x[4]), lo32(x[5]), tag), xor_or(lo32(x[6]), lo32(x[7]), tag)));
                    } while (bad);
                    mma16816z(sc[0], qa[0], kf[0][0].x, kf[0][0].y);
                    mma16816z(sc[1], qa[0], kf[0][0].z, kf[0][0].w);
                    mma16816z(sc[2], qa[0], kf[0][1].x, kf[0][1].y);
                    mma16816z(sc[3], qa[0], kf[0][1].z, kf[0][1].w);
                    mma16816z(sc[4], qa[0], km[0], km[1]);
                    mma16816(sc[0], qa[1][0], qa[1][1], qa[1][2], qa[1][3], kf[1][0].x, kf[1][0].y);
                    mma16816(sc[1], qa[1][0], qa[1][1], qa[1][2], qa[1][3], kf[1][0].z, kf[1][0].w);
                    mma16816(sc[2], qa[1][0], qa[1][1], qa[1][2], qa[1][3], kf[1][1].x, kf[1][1].y);
                    mma16816(sc[3], qa[1][0], qa[1][1], qa[1][2], qa[1][3], kf[1][1].z, kf[1][1].w);
                    mma16816(sc[4], qa[1][0], qa[1][1], qa[1][2], qa[1][3], km[2], km[3]);
                    const uint32_t sx = sb + SM_SX + (g16 & 0x1f0) * 5;
                    sts4(sx + (g16 >> 5 & 0x30), pack_h2(sc[0][0], sc[0][1]), pack_h2(sc[1][0], sc[1][1]),
                         pack_h2(sc[2][0], sc[2][1]), pack_h2(sc[3][0], sc[3][1]));
                    sts1(sx + 64 + (g16 >> 7 & 0xc), pack_h2(sc[4][0], sc[4][1]));
                    bar_arrive(NB_X1, 256);
                    const uint32_t now = gtime32();
#pragma unroll
                    for (int n = 0; n < 5; n++) sts2(sb + SM_ST + g8 + n * 1088, sc[n][2], sc[n][3]);
                    bar_arrive(NB_H, 256);
                    a3 = lds1(tabw + 2056 + g16) | (fz & zero);
                    asm volatile("{.reg .pred p; setp.lt.u32 p, %2, 128; @p red.relaxed.gpu.global.max.u32 [%0], %1;}"
                                 ::"l"(arena + sd), "r"(__funnelshift_r(now * 8, s + 1, 8)), "r"(g16) : "memory");
                    if (s == 0) mbar_wait_w(bars + 8 * B_WO, 0);
                    a3 += delay<PF_DLY>(zero);
#pragma unroll
                    for (int f = 0; f < NPF; f++) ldsm4t(wf[f], WF(f));
                } else {
                    if (s == 0) { mbar_wait_w(bars + 8 * B_WO, 0); }
                    const uint32_t need = warp0 ? min(s / 2 + 3, 32) : 0;
                    uint32_t seen = s ? lds1(sb + SM_LX + 1024 + ((g16 >> 2) & 12)) : 0;
                    const bool look = __any_sync(~0u, seen < need);
                    ldg1_if(seen, &g_tick[32 + ((g16 >> 4) & 3) * 8], look);
                    a3 = lds1(tabw + 2056 + g16);
#pragma unroll
                    for (int f = 0; f < NPF0; f++) ldsm4t(wf[f], WF(f));
                    const float2 u = lds2f(tabw + 4096 + g8);
                    const uint8_t *q0 = arena + (tag * 32768 + po + __float_as_uint(u.x)), *q1 = arena + (tag * 32768 + po + __float_as_uint(u.y));
                    wait_clk(tx + tm.h);
                    int it = 0;
                    bool bad;
#pragma unroll 1
                    do {
                        const uint4 p0 = ldg_b128(q0), p1 = ldg_b128(q1);
                        spin_guard(++it);
                        wait_clk(tx + tm.v);
#pragma unroll
                        for (int f = NPF0; f < NPF1; f++) ldsm4t(wf[f], WF(f));
                        sts4(sb + SM_PA + g16, p0.x, p0.y, p0.z, p0.w);
                        sts4(sb + SM_PA + 2048 + g16, p1.x, p1.y, p1.z, p1.w);
                        bad = any_bit0(xor_or(p0.x, p1.x, ((s + 1) >> 1) ^ 1)) && s + 2 <= NSEG;
                    } while (bad);
                    if (look) {
                        if (__any_sync(~0u, seen < need)) seen = wait_count_w(&g_tick[32 + ((g16 >> 4) & 3) * 8], need);
                        asm volatile("fence.acquire.gpu;" ::: "memory");
                        sts1(sb + SM_LX + 1024 + ((g16 >> 2) & 12), seen);
                    }
                    bar_sync(NB_H, 256);
                    softmax_rows<true>(sb + SM_ST, sb + SM_PX, g16, qd * 8, [&](uint32_t v) {
                        a3 += v & zero;
#pragma unroll
                        for (int f = NPF1; f < NPF2; f++) ldsm4t(wf[f], WF(f));
                    });
#pragma unroll
                    for (int f = NPF2; f < NPF; f++) ldsm4t(wf[f], WF(f));
                }
                float2 ls, a12;
                uint8_t *d0, *d1;
                bar_sync(NB_X2, 384);
                float c[4][4];
#pragma unroll
                for (int q = 0; q < 4; q++) {
                    uint32_t ob[4];
                    ldsm4t(ob, l16 + SM_OX + q * 512);
                    if (q == L_AT) ls = lds2f(sb + SM_LX + g8);
                    if (q == 2) { pa = lds4(sb + SM_PA + wg * 2048 + g16); wl = lds1(tabw + g16); }
                    if (q == 2) { a12 = lds2f(tabw + 2048 + g16); d0 = arena + (acc_slot(s + 1) + __float_as_uint(a12.x)); d1 = arena + (acc_slot(s + 1) + __float_as_uint(a12.y)); }
#pragma unroll
                    for (int f = 4 * q; f < 4 * q + 4; f++) {
                        const uint32_t* a = wf[f % NPF];
                        if (f < 4) mma16816z(c[f], a, ob[f & 2], ob[(f & 2) + 1]);
                        else mma16816(c[f & 3], a[0], a[1], a[2], a[3], ob[f & 2], ob[(f & 2) + 1]);
                        if (f + NPF < 16) ldsm4t(wf[f % NPF], WF(f + NPF));
                    }
                }
                if (wg == 0) bar_arrive(NB_WIN, 384);
                const float i0 = rcp_fast(ls.x), i1 = rcp_fast(ls.y);
                uint32_t v[4];
#pragma unroll
                for (int m = 0; m < 4; m++) v[m] = pack_h2((c[m >> 1][(m & 1) * 2] + c[(m >> 1) + 2][(m & 1) * 2]) * i0, (c[m >> 1][(m & 1) * 2 + 1] + c[(m >> 1) + 2][(m & 1) * 2 + 1]) * i1);
                red_h10(LAST, d0, d1, v[0], v[1], v[2], prmt(v[3], ACC_ONE, LAST ? 0x7610 : 0x3210), prmt(v[3], ACC_ONE, 0x7632));
                g16 |= v[0] & zero;
            }
        }
        if (wg) bar_sync(NB_WIN, 384);
    } else {
        auto request = [&](int s, uint32_t o) {
            cp_async16(sb + SM_PA + 4096 + g16, arena + (((s & 1) ^ 1) * 32768 + po + o));
            const uint8_t* ts = arena + ((s & 1) * 32768 + o);
#pragma unroll
            for (int i = 0; i < 4; i++) cp_async16(sb + SM_VF + i * 2048 + g16, ts + (i >> 1) * 16384 + (i & 1) * 2048);
        };
        auto fetch = [&](int s, uint4 t1, auto wait, auto after) {
            const uint32_t mo = acc_slot(s) + t1.x, eo = mo - (g16 & 0x1f0) + 512 + ((g16 >> 5) & 12);
            const uint8_t *ms = arena + mo, *es = arena + eo;
            uint32_t e[4] = {0, 0, 0, 0}, sel = LAST ? 0x5410 : 0x3210, dst[4];
#pragma unroll
            for (int i = 0; i < 4; i++) dst[i] = (t1.w + (s & 1) * HBUF) ^ (i * 32);
            asm volatile("" : "+l"(ms), "+l"(es), "+r"(e[0]), "+r"(e[1]), "+r"(e[2]), "+r"(e[3]), "+r"(sel), "+r"(dst[0]), "+r"(dst[1]), "+r"(dst[2]), "+r"(dst[3]));
            uint32_t late = wait(), fz;
            int it = 0;
            bool bad;
#pragma unroll 1
            do {
                uint4 m[4];
                uint32_t b = 0;
#pragma unroll
                for (int i = 0; i < 4; i++) {
                    m[i] = ldg_rlx4(ms + i * 1024);
                    ldg1_if(e[i], es + i * 1024, LAST);
                }
                if (it == 0) bar_arrive(NB_F, 256);
                const uint32_t now = clk32();
                fz = now;
                after(now & zero);
                sts1(sb + SM_LX + 1040, now - min(late >> 8, 8u) * 57);
                late = 0;
                spin_guard(++it);
#pragma unroll
                for (int i = 0; i < 4; i++) {
                    if (STG_FENCE >> i & 1) fz |= clk32();
                    b |= xor_or(m[i].w, e[i], ACC_ALL);
                    stsm4t(dst[i], h2bf(m[i].x), h2bf(m[i].y), h2bf(m[i].z), h2bf(prmt(m[i].w, e[i], sel)));
                }
                bad = __any_sync(~0u, LAST && b > 0xffffu);
            } while (bad);
            bar_arrive(NB_MEM, 384);
            bar_arrive(NB_MEM2, 256);
            g16 |= fz & zero;
        };
        fetch(0, lds4(tabw + 2048 + g16), []() { return 0u; }, [&](uint32_t z) { request(0, lds1(tabw + 4096 + (g16 >> 1)) + z); });
        wo_load(2);
#pragma unroll 1
        for (int s = 0;; s++) {
            const uint32_t tag = (s & 1) ^ 1, ttag = ((s >> 1) & 1) ^ 1, l16 = sb + (g16 & 0x1f0), g8 = g16 >> 1;
            const int p = s + 2;
            fence_async_smem();
            stg_b128_if(g16 < ((role & 3) ? 128 : 160), arena + (acc_slot(s + 3) + lds1(tabw + 2052 + g16)), 0, 0, 0, 0);
            const uint4 pa = pa_get(p);
            if (p <= NSEG) mbar_wait_w(bars + 8 * (B_HB + (p & 1)), (p >> 1) & 1);
            asm volatile("fence.proxy.async.global;" ::: "memory");
            if (warp0 && s + 3 <= NSEG) e_expect(bars + 8 * (B_HB + ((s + 3) & 1)), 32768);
            uint8_t* xd = arena + lds1(tabw + 4 + g16);
            uint32_t tx;
            float acc[20];
            pass_init(acc, 20, pa);
            bar_sync(NB_QK, 384);
            pass_run(IC<1>(), p, acc, nop);
            pass_out(IC<2>(), p, acc, [&](int i) {
                if (i) return;
                wg_wait<0>();
                const uint32_t r0 = pack2(acc[16], acc[17]);
                stg_rlx2(xd, settag(r0, tag), pack2(acc[18], acc[19]));
                tx = clk_after(r0, zero) + 100;
            });
            uint4 (&vf)[2][2] = tf;
#pragma unroll
            for (int i = 0; i < 4; i++) vf[i >> 1][i & 1] = lds4(sb + SM_VF + i * 2048 + g16);
            uint32_t xv[4] = {0, 0, 0, 0};
            float oc[2][4], lc[4];
            auto pv = [&](uint32_t p0, uint32_t p1, uint32_t p2, uint32_t p3, uint32_t p4, auto mid) {
                lc[0] = lc[1] = lc[2] = lc[3] = 0.f;
                mma16816z(oc[0], &vf[0][0].x, p0, p1);
                mma16816z(oc[1], &vf[1][0].x, p0, p1);
                mma16816(lc, ONES, ONES, ONES, ONES, p0, p1);
                mma16816(oc[0], vf[0][1].x, vf[0][1].y, vf[0][1].z, vf[0][1].w, p2, p3);
                mma16816(oc[1], vf[1][1].x, vf[1][1].y, vf[1][1].z, vf[1][1].w, p2, p3);
                mma16816(lc, ONES, ONES, ONES, ONES, p2, p3);
                mid();
                mma1688(oc[0], xv[0], xv[1], p4);
                mma1688(oc[1], xv[2], xv[3], p4);
                mma1688(lc, ONES, ONES, p4);
            };
            uint32_t so, to, fz = 0;
            uint4 t1;
            int it = 0;
            bool bad;
#pragma unroll 1
            do {
#pragma unroll 1
                for (int i = it; i > 0; i &= zero) load_tok(s, lds1(tabw + 4096 + g8));
                u64 xr[4];
                const uint8_t* xp = arena + lds1(tabw + 8 + g16);
                asm volatile("" : "+l"(xp));
                const uint32_t bt = or3(xor_or(vf[0][0].x, vf[0][1].x, ttag), xor_or(vf[1][0].x, vf[1][1].x, ttag), 0);
                uint32_t sa = sb + SM_SX + (g16 & 0x1f0) * 5;
                asm volatile("" : "+r"(sa));
                spin_guard(it);
                wait_clk(tx);
                if (it++ == 0) bar_sync(NB_X1, 256);
                uint4 sx[5];
#pragma unroll
                for (int i = 0; i < 5; i++) sx[i] = lds4(sa + i * 16);
                __syncwarp();
#pragma unroll
                for (int i = 0; i < 4; i++) xr[i] = ldg_u64(xp + (VP_AT == 2 ? sx[0].x & zero : 0) + i * 1024);
                uint32_t a[5], pm[5];
#pragma unroll
                for (int n = 0; n < 5; n++) {
                    uint32_t u[4];
#pragma unroll
                    for (int w = 0; w < 4; w++) u[w] = n < 4 ? (&sx[w].x)[n] : (&sx[4].x)[w];
                    a[n] = hadd2h(hadd2h(u[0], u[1]), hadd2h(u[2], u[3]));
                }
                uint32_t m = hmax2h(hmax2h(hmax2h(a[0], a[1]), hmax2h(a[2], a[3])), a[4]);
                const uint32_t m1 = __shfl_xor_sync(~0u, m, 1), m2 = __shfl_xor_sync(~0u, m, 2), m3 = __shfl_xor_sync(~0u, m, 3);
                m = hmax2h(hmax2h(m, m1), hmax2h(m2, m3));
                so = lds1(tabw + g16); t1 = lds4(tabw + 2048 + g16); to = lds1(tabw + 4096 + g8);
                const float2 mm = unpack_h2(m);
                const float mf = -SM_L2E * fmaxf(mm.x, mm.y);
#pragma unroll
                for (int n = 0; n < 5; n++) { const float2 u = unpack_h2(a[n]); pm[n] = pack2(ex2(fmaf(u.x, SM_L2E, mf)), ex2(fmaf(u.y, SM_L2E, mf))); }
                pv(pm[0], pm[1], pm[2], pm[3], pm[4], [&]() {
                    if (PV_FENCE & 1) fz = clk32();
#pragma unroll
                    for (int i = 0; i < 2; i++) { xv[2 * i] = hadd2v(lo32(xr[2 * i]), lo32(xr[2 * i + 1])); xv[2 * i + 1] = hadd2v(hi32(xr[2 * i]), hi32(xr[2 * i + 1])); }
                });
                bad = any_bit0(or3(bt, xor_or(lo32(xr[0]), lo32(xr[1]), tag), xor_or(lo32(xr[2]), lo32(xr[3]), tag)));
                if (PV_FENCE & 2) fz |= clk32();
                stsm4(sb + SM_OX + g16, pack2(oc[0][0], oc[0][1]), pack2(oc[0][2], oc[0][3]), pack2(oc[1][0], oc[1][1]), pack2(oc[1][2], oc[1][3]));
                sts2(sb + SM_LX + g8, lc[0], lc[1]);
            } while (bad);
            bar_sync(NB_X2, 384);
            const uint8_t* sp = arena + so;
            uint4 sv = ldg_rlx4(sp);
            if (s + 3 <= NSEG) h_load(sb, hsrc, s + 3, j, head, wiu, false);
            const uint4 pp = lds4(l16 + SM_PX + delay<TPV_DLY>(zero));
            pv(pp.x, pp.y, pp.z, pp.w, lds1(sb + SM_PX + 512 + ((g16 >> 2) & 0x7c)), []() {});
            const float i0 = rcp_fast(lc[0]), i1 = rcp_fast(lc[1]);
            bar_arrive(NB_WIN + ((__float_as_uint(i0) | fz) & zero), 384);
            uint8_t* od = (uint8_t*)g_O + ((size_t)s * (32 * NH * DH * 2) + t1.z);
            const uint32_t ov[4] = {pack2(oc[0][0] * i0, oc[0][1] * i1), pack2(oc[0][2] * i0, oc[0][3] * i1), pack2(oc[1][0] * i0, oc[1][1] * i1), pack2(oc[1][2] * i0, oc[1][3] * i1)};
#pragma unroll
            for (int a = 0; a < 4; a++) if (s + 1 == NSEG) stg_rlx1(od + a * 128, ov[a]);
            if (s + 1 == NSEG) break;
            fetch(s + 1, t1, [&]() {
                int it = 0;
#pragma unroll 1
                while (__any_sync(~0u, (int)(min(__vimin3_u32(sv.x, sv.y, sv.z), sv.w) >> 24) <= s)) {
                    sv = ldg_rlx4(sp);
                    spin_guard(++it);
                }
                const uint32_t tgo = (__reduce_max_sync(~0u, max(max3u(sv.x, sv.y, sv.z), sv.w)) + tm.go + (sv.x & zero)) << 8;
                int late;
#pragma unroll 1
                do { late = gtime32() * 8 - tgo; } while (late < 0);
                __syncwarp();
                return (uint32_t)late;
            }, [&](uint32_t z) {
#pragma unroll
                for (int a = 0; a < 4; a++) stg_rlx1(od + a * 128, ov[a]);
                request(s + 1, to + z);
            });
        }
    }
    asm volatile("cp.async.wait_all;" ::: "memory");
}

struct RecMaps { CUtensorMap wq, wk, wv, wo; };
struct RecPtrs { const bf16 *x, *mem0, *c, *wmod, *w1, *w3; uint8_t* arena; uint32_t zero; RecTime tm; };

__device__ __forceinline__ float silu_bf(const bf16* c, int i) {
    const float v = __bfloat162float(c[i]);
    return bfround(__fdividef(v, 1.0f + __expf(-v)));
}
__device__ __noinline__ void rec_ln(float* coef, const RecPtrs& p, int id, int r0) {
    int r1 = 32;
    const int tid = threadIdx.x;
    const int lane = tid & 31, wid = tid >> 5;
    const uint32_t ring = smem_u32(coef) - SM_PRE + wid * 8192 + lane * 16;
    auto fetch = [&](int r) {
        if (r < r1) {
            const bf16* src = p.x + (size_t)(r * 64 + (id * 8 + wid) * 2) * DM + lane * 8;
#pragma unroll
            for (int i = 0; i < 8; i++) cp_async16(ring + (r & 1) * 4096 + i * 512, src + i * 256);
        }
        asm volatile("cp.async.commit_group;" ::: "memory");
    };
    auto row8 = [&](uint32_t a, float* f) {
        const uint4 v = lds4(a);
        f[0] = bflo(v.x); f[1] = bfhi(v.x); f[2] = bflo(v.y); f[3] = bfhi(v.y); f[4] = bflo(v.z); f[5] = bfhi(v.z); f[6] = bflo(v.w); f[7] = bfhi(v.w);
    };
#pragma unroll 1
    for (int r = r0 - 2; r < r1; r++) {
        if (r >= r0) {
            asm volatile("cp.async.wait_group 1;" ::: "memory");
            const uint32_t a = ring + (r & 1) * 4096;
            float m[2] = {0.f, 0.f}, t[2];
#pragma unroll 1
            for (int ps = 0; ps < 2; ps++) {
                t[0] = t[1] = 0.f;
#pragma unroll 1
                for (int i = 0; i < 4; i++)
#pragma unroll
                    for (int h = 0; h < 2; h++) {
                        float f[8];
                        row8(a + h * 2048 + i * 512, f);
#pragma unroll
                        for (int e = 0; e < 8; e++) { const float d = f[e] - m[h]; t[h] = fmaf(d, ps ? d : 1.0f, t[h]); }
                    }
#pragma unroll
                for (int o = 16; o; o >>= 1) { t[0] += __shfl_xor_sync(~0u, t[0], o); t[1] += __shfl_xor_sync(~0u, t[1], o); }
                if (ps == 0) { m[0] = t[0] * (1.0f / DM); m[1] = t[1] * (1.0f / DM); }
            }
            uint32_t nm[2];
#pragma unroll
            for (int h = 0; h < 2; h++) { nm[h] = pack2(-m[h], -m[h]); t[h] = rcp_fast(bfround(sqrtf(bfround(bfround(t[h] * (1.0f / DM)) + 1e-5f)))); }
            if (r == r0) {
#pragma unroll 1
                for (int i = tid; i < 2 * DM / 4; i += 256) {
                    float4 u;
                    int it = 0;
                    uint32_t ok;
#pragma unroll 1
                    do {
                        uint4 v[8];
#pragma unroll
                        for (int k = 0; k < 8; k++) v[k] = ldg_rlx4(g_modp + k * 2 * DM + i * 4);
                        ok = 1;
                        u = make_float4(0.f, 0.f, 0.f, 0.f);
#pragma unroll
                        for (int k = 0; k < 8; k++) {
                            ok &= v[k].x & v[k].y & v[k].z & v[k].w;
                            u.x += __uint_as_float(v[k].x); u.y += __uint_as_float(v[k].y); u.z += __uint_as_float(v[k].z); u.w += __uint_as_float(v[k].w);
                        }
                        spin_guard(++it);
                    } while (!ok);
                    const uint32_t one = i >= DM / 4 ? 0x3f803f80u : 0u;
                    ((uint2*)coef)[i] = make_uint2(hadd2v(pack2(u.x, u.y), one), hadd2v(pack2(u.z, u.w), one));
                }
                bar_sync(NB_FIN0, 256);
            }
            const int row = r * 64 + (id * 8 + wid) * 2;
#pragma unroll 1
            for (int i = 0; i < 4; i++) {
                const uint4 sh = ((const uint4*)coef)[i * 32 + lane], sc = ((const uint4*)coef)[128 + i * 32 + lane];
                const int own = ((row >> 4) & 1) == (i >> 1), rr = row & 15;
                const uint32_t off = ((row >> 5) + own) * 65536 + (i * 4 + (lane >> 3)) * 4096 + (rr + (own ? 0 : 16)) * 128 + (((lane & 7) ^ (rr & 7)) << 4);
#pragma unroll
                for (int h = 0; h < 2; h++) {
                    uint4 y = lds4(a + h * 2048 + i * 512);
#pragma unroll
                    for (int e = 0; e < 4; e++) {
                        const uint32_t d = hadd2v((&y.x)[e], nm[h]);
                        (&y.x)[e] = hadd2v(hmul2b(pack2(bflo(d) * t[h], bfhi(d) * t[h]), (&sc.x)[e]), (&sh.x)[e]);
                    }
                    *(uint4*)((uint8_t*)g_himg + (off ^ (h * 144))) = y;
                }
            }
            if (r == 0) {
                int v, it = 0;
#pragma unroll 1
                do { v = *(volatile int*)((uint8_t*)coef - SM_PRE + SM_BAR + 192); spin_guard(++it); } while (v == INT_MIN);
                if (v >= 0) r1 = 2;
            }
        }
        fetch(r + 2);
        if (r < r0) continue;
        bar_sync(r == 0 ? NB_C : r == 1 ? NB_FIN0 : NB_LN, r == 0 ? 320 : r == 1 ? 256 : 288);
        if (r < 2 && wid == r) {
            if (r == 1) bar_arrive(NB_B, 64);
            if (lane == 0) { signal_count(&g_tick[32 + id * 8]); }
            __syncwarp();
        }
    }
}
template <int NQ, int CG>
__device__ __forceinline__ void side_gemv(const bf16* w, int ld, int ncol, const float* coef, float* red, float* out, int ostride, bool round) {
    constexpr int KG = 384 / CG, W = CG * 8;
    const int tid = threadIdx.x, cg = tid % CG, kg = tid / CG;
    float acc[NQ][8];
#pragma unroll
    for (int q = 0; q < NQ; q++)
#pragma unroll
        for (int j = 0; j < 8; j++) acc[q][j] = 0.f;
    if (cg * 8 < ncol) {
        const bf16* src = w + cg * 8;
        const uint32_t ring = smem_u32(red) + 36864 + tid * 16;
        auto fetch = [&](int k0, int slot) {
#pragma unroll
            for (int i = 0; i < 4; i++)
                if (k0 + i * KG < DM) cp_async16_ef(ring + (slot * 4 + i) * 6144, src + (size_t)(k0 + i * KG) * ld);
            asm volatile("cp.async.commit_group;" ::: "memory");
        };
#pragma unroll 1
        for (int g = 0; g < 5; g++) fetch(kg + g * 4 * KG, g);
#pragma unroll 1
        for (int k0 = kg, slot = 0; k0 < DM; k0 += 4 * KG) {
            fetch(k0 + 20 * KG, slot ? slot - 1 : 5);
            asm volatile("cp.async.wait_group 5;" ::: "memory");
#pragma unroll
            for (int i = 0; i < 4; i++) {
                const int k = k0 + i * KG;
                if (k < DM) {
                    const uint4 v = lds4(ring + (slot * 4 + i) * 6144);
                    const float f[8] = {bflo(v.x), bfhi(v.x), bflo(v.y), bfhi(v.y), bflo(v.z), bfhi(v.z), bflo(v.w), bfhi(v.w)};
#pragma unroll
                    for (int q = 0; q < NQ; q++) {
                        const float cf = coef[q * DM + k];
#pragma unroll
                        for (int j = 0; j < 8; j++) acc[q][j] = fmaf(cf, f[j], acc[q][j]);
                    }
                }
            }
            slot = slot == 5 ? 0 : slot + 1;
        }
    }
    __syncthreads();
#pragma unroll
    for (int q = 0; q < NQ; q++)
#pragma unroll
        for (int j = 0; j < 8; j++) red[(kg * NQ + q) * W + cg * 8 + j] = acc[q][j];
    __syncthreads();
#pragma unroll 1
    for (int i = tid; i < NQ * W; i += 384) {
        const int q = i / W, cidx = i % W;
        float t = 0.f;
#pragma unroll
        for (int k = 0; k < KG; k++) t += red[k * NQ * W + i];
        if (cidx < ncol) out[q * ostride + cidx] = round ? bfround(t) : t;
    }
}
__device__ __noinline__ void rec_side(float* sm, const RecPtrs& p, int id) {
    const int tid = threadIdx.x;
    float *coef = sm, *red = sm + 3 * DM;
    if (tid < 256 && blockIdx.x < 128) rec_ln(sm + SM_PRE / 4, p, id, 2);
    if (tid >> 5 == 8) {
#pragma unroll 1
        for (int n = 1; n < 31; n++) {
            bar_sync(NB_LN, 288);
            if (tid == 256) { if (n == 1) wait_count1(&g_tick[32 + id * 8], 2); signal_count(&g_tick[32 + id * 8]); }
            __syncwarp();
        }
    }
    __syncthreads();
    for (int i = tid; i < 2 * S_; i += 384) g_st[id * 2 * S_ + i] = 0.f;
    if (id == 0) for (int i = tid; i < 2 * 32; i += 384) g_pcnt[i * 8] = 0;
    if (id == 1) for (int i = tid; i < 6 * 256; i += 384) g_pflag[i] = 0;
    for (int i = tid; i < DM; i += 384) { coef[i] = silu_bf(p.c, i); coef[2 * DM + i] = 1.0f; }
    __syncthreads();
    side_gemv<1, 128>(p.wmod + (2 + id) * DM, 6 * DM, DM, coef, red, g_mod + (2 + id) * DM, 0, true);
    __syncthreads();
    if (tid == 0) signal_count(&g_tick[8]);
    side_gemv<1, 128>(p.w3 + id * (FF / 4), FF, FF / 4, coef + 2 * DM, red, g_vec + 3 * DM + id * (FF / 4), 0, false);
    if (tid == 0) wait_count1(&g_tick[8], 4);
    __syncthreads();
    for (int i = tid; i < DM; i += 384) { coef[i] = 1.0f + __ldcg(g_mod + 4 * DM + i); coef[DM + i] = __ldcg(g_mod + 3 * DM + i); }
    __syncthreads();
    if (id == 1 && tid < 32) {
        float t[5] = {0, 0, 0, 0, 0};
        for (int i = tid; i < DM; i += 32) {
            const float a = coef[i], b = coef[DM + i];
            t[0] += a; t[1] += a * a; t[2] += a * b; t[3] += b; t[4] += b * b;
        }
#pragma unroll
        for (int q = 0; q < 5; q++) { const float r = warp_sum(t[q]); if (tid == 0) g_cst[q] = r * (1.0f / DM); }
    }
    side_gemv<3, 32>(p.w1 + id * 256, DM, 256, coef, red, g_vec + id * 256, DM, false);
}

__device__ __forceinline__ void pair_place(int c, int& d, int& pi) {
    const int c7 = ((c - 36) * 37) >> 8;
    d = c < 4 ? 0 : c < 36 ? (c - 4) & 7 : c - 35 - 7 * c7;
    pi = c < 4 ? c : c < 36 ? ((c - 4) >> 3) + (d ? 0 : 4) : 4 + c7;
}
__global__ void __cluster_dims__(2, 1, 1) __launch_bounds__(384, 1)
k_rec(const __grid_constant__ RecMaps mp, const __grid_constant__ RecPtrs p) {
    extern __shared__ uint8_t smraw[];
    const uint32_t sb = smem_u32(smraw);
    if ((sb & 0x3FFFF) != SB0) __trap();
    const uint32_t bars = sb + SM_BAR;
    const int tid = threadIdx.x, lane = tid & 31, b = blockIdx.x;
    const int wid = __reduce_max_sync(~0u, tid >> 5);
    const uint32_t rank = b & 1;
    uint8_t* arena = p.arena;
    volatile int* sinfo = (volatile int*)(smraw + SM_BAR + 192);
    if (tid == 0) sinfo[0] = INT_MIN;
    uint32_t smid;
    asm("mov.u32 %0, %%smid;" : "=r"(smid));
    smid = __reduce_max_sync(~0u, smid);
    int d, pi;
    pair_place(smid >= 124 ? (smid >> 1) - 62 : (smid >> 1) + 4, d, pi);
    const int guess = b < 128 && smid < 132 && (smid & ~3u) != 120 && (NO_GUESS % 5 == 0 || (NO_GUESS == 2 && b != 20)) ? d * 8 + pi : -9;
    if (wid == 8) {
        if (lane == 0) {
#pragma unroll
            for (int i = 0; i < 17; i++) mbar_init(bars + 8 * i, i == B_WO ? 4 : 1);
            asm volatile("fence.mbarrier_init.release.cluster; fence.proxy.async.shared::cta;" ::: "memory");
            mbar_expect(bars + 8 * B_ROLE, 8);
        }
        __syncwarp();
    }
    asm volatile("barrier.cluster.arrive.relaxed.aligned;" ::: "memory");
    int pr = 0, hA = 0;
    if (wid < 8) {
        if (b < 128) {
            const int cb = (b & 15) * 128, k0 = (b >> 4) * 128 + (tid >> 4);
            uint4 v[8];
#pragma unroll
            for (int i = 0; i < 8; i++) v[i] = __ldg((const uint4*)(p.wmod + (size_t)(k0 + 16 * i) * (6 * DM) + cb + (tid & 15) * 8));
            float acc[8] = {0, 0, 0, 0, 0, 0, 0, 0};
            const float sl = silu_bf(p.c, k0 + 16 * (lane & 7));
#pragma unroll
            for (int i = 0; i < 8; i++) {
                const float sv = __shfl_sync(~0u, sl, i, 16);
                acc[0] += sv * bflo(v[i].x); acc[1] += sv * bfhi(v[i].x); acc[2] += sv * bflo(v[i].y); acc[3] += sv * bfhi(v[i].y);
                acc[4] += sv * bflo(v[i].z); acc[5] += sv * bfhi(v[i].z); acc[6] += sv * bflo(v[i].w); acc[7] += sv * bfhi(v[i].w);
            }
            float* red = (float*)(smraw + SM_PRE);
            *(float4*)(red + (tid >> 4) * 128 + (tid & 15) * 8) = make_float4(acc[0], acc[1], acc[2], acc[3]);
            *(float4*)(red + (tid >> 4) * 128 + (tid & 15) * 8 + 4) = make_float4(acc[4], acc[5], acc[6], acc[7]);
            bar_sync(NB_FIN0, 256);
            if (wid < 4) {
                float t = 0;
#pragma unroll
                for (int i = 0; i < 16; i++) t += red[i * 128 + tid];
                stg_rlx1(&g_modp[(b >> 4) * 2 * DM + cb + tid], __float_as_uint(t) | 1u);
            }
        } else {
            rec_ln((float*)(smraw + SM_PRE), p, b - 128, 0);
        }
    } else if (wid >= 10 && b >= 128) {
        {
            const int u = (b - 128) * 2 + wid - 10;
            const uint16_t* src = (const uint16_t*)p.mem0 + (lane & 3) * 2 * DM + (u >> 1) * 128 + (u & 1) * 32 + (lane >> 2);
            stg_rlx4(arena + (LB_STAMP << 13) + u * 2048 + (lane >> 4) * 1024 + ((lane >> 3) & 1) * 256 + (lane & 7) * 16, 0, 0, 0, 0);
#pragma unroll 1
            for (int r = 0; r < 4; r++) {
                uint32_t w[5];
#pragma unroll
                for (int e = 0; e < 4; e++) {
                    const uint16_t* q = src + (r >> 1) * 512 + (r & 1) * 16 + (e & 2) * 32 + (e & 1) * 8;
                    w[e] = pack_h2(bflo(q[0]), bflo(q[DM]));
                }
                w[4] = __shfl_sync(~0u, __byte_perm(w[3], ACC_ALL, 0x7632), lane * 8 + 7);
                w[3] = __byte_perm(w[3], ACC_ALL, (lane & 7) == 7 ? 0x7610 : 0x3210);
#pragma unroll 1
                for (int i = 0; i < 3; i++) {
                    uint8_t* d = arena + acc_slot(i) + acc_piece(r >> 1, u >> 1, (u & 1) * 2 + (r & 1));
                    stg_rlx4(d + lane * 16, w[0], w[1], w[2], w[3]);
                    if (lane < 8) stg_rlx1(d + 512 + lane * 4, w[4]);
                    w[0] = w[1] = w[2] = w[3] = w[4] = 0;
                }
            }
            bar_arrive(NB_C, 320);
        }
    } else if (rank == 0 && (wid > 8 || b >= 128)) {
        uint32_t best = ~0u;
        const int pg = wid < 11 ? 0 : 1 + (b >> 1) % 3;
        uint32_t* q = (uint32_t*)(arena + (pg << 21) + (pg ? blk(b >> 1, 1) : blk(LB_PROBE, wid & 1) + b * 16));
        if (lane < 8) stg_rlx1(q + lane, 0);
        u64 tk2 = ldg_u64(&g_tick[0]);
        __syncwarp();
        if (lane == 0) {
            q += 3;
            uint32_t v = atomicAdd(q, 1u);
#pragma unroll 1
            for (int r = 0; r < NPROBE; r++) {
                const uint32_t t0 = clk32() + (v >> 8);
                v = atomicAdd(q + (v >> 8), 1u);
                uint32_t t1;
                asm volatile("{.reg .pred p; setp.eq.u32 p, %1, 0xffffffff; @p exit; mov.u32 %0, %%clock;}" : "=r"(t1) : "r"(v) : "memory");
                best = min(best, t1 - t0);
            }
            sinfo[pg ? 4 : 2 + (wid & 1)] = best;
        }
        bar_sync(NB_KDONE, b < 128 ? 96 : 64);
        if (wid == 9) {
            const int par = (sinfo[2] > sinfo[3]) ^ (NO_GUESS == 5 && smid == 126), ncl = gridDim.x >> 1;
            const bool ok = guess >= 0 && !(smid & 1), reg = ok && guess >= 4;
            u64 add = (1u << (8 * par)) + 65536 + (reg ? 1ull << 24 : (1ull << (56 + 4 * par)) + ((u64)ok << 37));
            if (b < 128) add += (u64)((2 * sinfo[4] < sinfo[2] + sinfo[3]) != par) << (32 + 8 * ((b >> 1) % 3));
            int it = 0;
            if (NO_GUESS % 5 >= 3 ? b < 2 * (NO_GUESS - 2) || (NO_GUESS == 3 && b == 130) : b >= 128) {
#pragma unroll 1
                while (!__all_sync(~0u, (int)((lo32(tk2) >> 16) & 255) >= ncl - 2)) { tk2 = ldg_u64(&g_tick[0]); spin_guard(++it); }
            }
            if (lane == 0) {
                if (guess >= 0) add += atomicXor(&g_tick[2], par << (guess >> 1)) & p.zero;
                add = atomicAdd((u64*)&g_tick[0], add);
            }
#pragma unroll 1
            while (!__all_sync(~0u, (int)((lo32(tk2) >> 16) & 255) >= ncl)) { tk2 = ldg_u64(&g_tick[0]); spin_guard(++it); }
            add = __shfl_sync(~0u, add, 0);
            const uint32_t diff = ldg_rlx1(&g_tick[2]);
            const bool most = lo32(tk2) >> 24 == 60 && diff < 4;
            const int nh = most ? 2 : NH, sh = most ? 56 : 0, w = most ? 4 : 8, mk = (1 << w) - 1;
            const int n0 = (tk2 >> sh) & mk, n1 = (tk2 >> (sh + w)) & mk, tk = (add >> (sh + w * par)) & mk;
            hA = min(n0 >> 1, nh);
            const int q0 = 2 * hA, q1 = 2 * nh - q0;
            const int over = tk - (par ? q1 : q0), lack = max(par ? q0 - n0 : q1 - n1, 0);
            if (over < 0) pr = par ? q0 + tk : tk;
            else if (over < lack) pr = (par ? n0 : q0 + n1) + over;
            else pr = -1 - (over - lack + (par ? max(n0 - q0, 0) : 0));
            if (most && (reg || (!diff && (hi32(tk2) & 0xe0) == 0x80))) { pr = guess; hA = par ? 0 : NH; }
#pragma unroll
            for (int i = 0; i < 3; i++) hA |= ((hi32(tk2) >> (8 * i)) & 31) > 10 ? 256 << i : 0;
        }
    }
    asm volatile("barrier.cluster.wait.aligned;" ::: "memory");
    if (wid == 9 && rank == 0) {
        asm volatile("{.reg .pred p; .reg .b32 a; setp.lt.u32 p, %3, 2; @p mapa.shared::cluster.u32 a, %0, %3;\n"
                     " @p st.async.shared::cluster.mbarrier::complete_tx::bytes.v2.u32 [a + 192], {%1, %2}, [a + %4];}"
                     ::"r"(bars), "r"(pr), "r"(hA), "r"(lane), "n"(8 * B_ROLE) : "memory");
        if (b >= 128) atomicOr(&g_tick[4], (pr < 0 ? 4u : 1u) << ((b - 128) >> 1));
    }
    if (wid == 8) {
        int pu = guess;
        bool fast = false, known = false;
        wait_clk(clk32() + W_T0 + (lane & p.zero));
#pragma unroll 1
        for (int n = 0; n < 12; n++) {
            if (!known && (n == W_SPEC || pu < 0)) {
                mbar_wait_w(bars + 8 * B_ROLE, 0);
                known = true;
                const int r = __reduce_max_sync(~0u, sinfo[0]);
                if (r != pu) {
#pragma unroll 1
                    for (; n > 0; n--) {
                        mbar_wait_w(bars + 8 * (B_W + n - 1), 0);
                        asm volatile("{.reg .pred p; elect.sync _|p, 0xffffffff; @p mbarrier.arrive.shared.b64 _, [%0];}" ::"r"(bars + 8 * (B_W + n - 1)) : "memory");
                    }
                    pu = r;
                    fast = r < 4;
                }
                bar_arrive(NB_A, 384);
                if (b >= 128 && pu < 0) bar_sync(NB_B, 64);
                if (pu < 0) break;
            }
            const int rot = b >= 128 ? 8 : 0, i = (n + rot) % 12;
            if (rot && n == 4) bar_sync(NB_B, 64);
            if (n >= W_INFL && !fast) {
                const uint32_t v = ldg_rlx1(&g_tick[32 + (lane & 3) * 8]);
                mbar_wait_w(bars + 8 * (B_W + (n - W_INFL + rot) % 12), 0);
                fast = __all_sync(~0u, v != 0);
            }
            const int m = i < 8 ? i & 1 : 2, k = i < 8 ? i >> 1 : i - 8, c0 = (pu >> 1) * 128 + rank * 64, r0 = (pu & 1) * 512;
            const uint32_t dst = sb + m * 65536 + k * 16384, br = bars + 8 * (B_W + i);
            e_expect(br, 16384);
            e_tma2d_ef(dst, &mp.wq + m, c0, r0 + k * 128, br);
            e_tma2d_ef(dst + 8192, &mp.wq + m, c0, r0 + k * 128 + 64, br);
        }
    } else {
        bar_sync(NB_A, 384);
    }
    const int prr = __reduce_max_sync(~0u, sinfo[0]);
    hA = __reduce_max_sync(~0u, sinfo[1]);
    if (prr < 0) {
        int j = (b - 128) >> 1;
        if (b < 128) {
            uint32_t v;
            int it = 0;
#pragma unroll 1
            do { v = __reduce_max_sync(~0u, ldg_rlx1(&g_tick[4])); spin_guard(++it); } while (__popc(v) < 2);
            j = v == 3 ? -1 - prr : (v & 1) ^ 1;
        }
        rec_side((float*)smraw, p, j * 2 + rank);
        return;
    }
    const int role = (prr >> 1) * 4 + rank * 2 + (prr & 1);
    rec_main(sb, &mp.wo, arena, role, hA, wid >> 2, p.zero, p.tm);
}

__device__ __forceinline__ void wgmma_ss192(float* d, uint64_t a, uint64_t b, int sc) {
    asm volatile("{.reg .pred p; setp.ne.b32 p, %98, 0;\n wgmma.mma_async.sync.aligned.m64n192k16.f32.bf16.bf16 "
                 "{%0,%1,%2,%3,%4,%5,%6,%7,%8,%9,%10,%11,%12,%13,%14,%15,%16,%17,%18,%19,%20,%21,%22,%23,%24,%25,%26,%27,%28,%29,%30,%31,%32,%33,%34,%35,%36,%37,%38,%39,%40,%41,%42,%43,%44,%45,%46,%47,%48,%49,%50,%51,%52,%53,%54,%55,%56,%57,%58,%59,%60,%61,%62,%63,%64,%65,%66,%67,%68,%69,%70,%71,%72,%73,%74,%75,%76,%77,%78,%79,%80,%81,%82,%83,%84,%85,%86,%87,%88,%89,%90,%91,%92,%93,%94,%95}, %96, %97, p, 1, 1, 0, 1;}"
                 : F16(d, 0), F16(d, 16), F16(d, 32), F16(d, 48), F16(d, 64), F16(d, 80) : "l"(a), "l"(b), "r"(sc));
}

constexpr uint32_t P_B = 81920, P_PLANE = 40960, P_VEC = 212992, P_ROW = P_VEC + 6144, P_BAR = P_ROW + 4096, P_SMEM = P_BAR + 256;
constexpr uint32_t P_OUT = 180224, P_OUT3 = P_B + 2 * P_PLANE;
constexpr int E0 = 2;
constexpr int SL_B0 = 0x2222;
constexpr int SL_B1 = 0x8888;
constexpr int SL_C = 0x11110;
constexpr int SL_A0 = 0x5494;
constexpr int SL_A1 = 0x2929;
constexpr int X_DLY = 4000;
constexpr int P_ST = 5, P_ST0 = 4;
constexpr int PB_F = 0, PB_E = 5, PB_X = 10, PB_P = 12, PB_OUT = 14;
enum { C_Y = 0, C_G = 1, C_X1 = 2, C_U = 3, C_S1 = 8, C_S3 = 9 };
enum { V_GA = 0, V_A = 1, V_B = 2, V_GB = 3, V_VA = 4, V_VB = 5, V_VC = 6, V_C3 = 7 };
struct PostMaps { CUtensorMap o, wo, y, w1, g, w2, x1, w3, u, w4, out, x; };

struct GeluK { float k0, k1, kh; };
__device__ __forceinline__ GeluK gelu_k(float c) { return {0.7978845608028654f * c, 0.7978845608028654f * 0.044715f * c * c * c, 0.5f * c}; }
__device__ __forceinline__ float gelu_s(float t, const GeluK& k) {
    const float u = t * fmaf(t * t, k.k1, k.k0);
    float th; asm("tanh.approx.f32 %0, %1;" : "=f"(th) : "f"(u));
    const float hx = k.kh * t;
    return fmaf(hx, th, hx);
}
__device__ __forceinline__ float2 ldsv(uint32_t a) {
    float2 v; asm("ld.shared.v2.f32 {%0,%1}, [%2];" : "=f"(v.x), "=f"(v.y) : "r"(a)); return v;
}
__device__ __forceinline__ void wait_smem(uint32_t a, int target) {
    int it = 0;
#pragma unroll 1
    while (true) {
        int v;
        asm volatile("ld.acquire.cta.shared.u32 %0, [%1];" : "=r"(v) : "r"(a) : "memory");
        if (__all_sync(~0u, v >= target)) break;
        spin_guard(++it);
    }
}

struct Pipe { int st, ph; };
__device__ __forceinline__ void adv(Pipe& p) { if (++p.st == P_ST) { p.st = 0; p.ph ^= 1; } }
__device__ __forceinline__ int u_col(int r, int nb) { return r ? 512 + r * 1024 + nb * 128 : nb * 192; }

template <bool A>
__device__ __forceinline__ void post_produce(uint32_t sb, const PostMaps& mp, int mb, int nb, int rank) {
    const int rh = 2 * mb + rank, lane = threadIdx.x & 31;
    const uint32_t full = sb + P_BAR + 8 * PB_F, empty = sb + P_BAR + 8 * PB_E;
    Pipe p = {(P_ST0 + E0) % P_ST, !E0};
#pragma unroll 1
    for (int ph = 0; ph < 9; ph++) {
        const int GS = ph == 0 ? 8 : ph == 6 ? 3 : 2, kb0 = ph < 7 ? 0 : ph * 16 - 88;
        const CUtensorMap* tm = &mp.o + 2 * (ph < 3 ? ph : ph < 6 ? 3 : 4) + !A;
        const bool own = ph == 1 || ph == 3;
        const int n0 = ph >= 3 && ph < 6 ? u_col(ph - 3, nb) : nb * 128;
        const int amul = ph == 0 ? 256 : 64, arow = ph == 0 ? rh * 8 : rh * 64;
        const int wr = ph == 2 ? min(max(rh + min(lane >> 3, 2) - 1, 0), 31) : rh;
        const uint32_t* fl = &g_pflag[(ph < 3 ? ph - 1 : ph < 6 ? C_X1 : ph - 3) * 256 + wr * 8 + (lane & 7)];
        uint32_t have = ph == 0 || ph == 5 ? ~0u : 0u;
#pragma unroll 1
        for (int q = 0; q < 8; q++) {
            const int src = own && q < 2 ? nb ^ q : (q + (ph >= 1 && ph <= 3 ? nb & 6 : 0)) & 7;
            const bool skip = own && q == 0, both = own && q == 1;
            const uint32_t need = q < 2 && own ? 0 : (ph == 2 ? 0x10101 : 1) << src;
            if (A && both) {
                int it = 0;
                uint32_t ok;
#pragma unroll 1
                do {
                    asm volatile("{.reg .pred p; mbarrier.try_wait.parity.acquire.cluster.shared::cta.b64 p, [%1], %2; selp.u32 %0, 1, 0, p;}" : "=r"(ok) : "r"(sb + P_BAR + 8 * PB_P), "r"(ph >> 1) : "memory");
                    spin_guard(++it);
                } while (!__all_sync(~0u, ok));
                asm volatile("fence.proxy.async.global;" ::: "memory");
            }
            if (A && (have & need) != need) {
                int it = 0;
#pragma unroll 1
                do {
                    uint32_t v;
                    asm volatile("ld.acquire.gpu.global.u32 %0, [%1];" : "=r"(v) : "l"(fl) : "memory");
                    have = __ballot_sync(~0u, v != 0);
                    spin_guard(++it);
                } while ((have & need) != need);
                asm volatile("fence.proxy.async.global;" ::: "memory");
            }
            if (!A && q == 1 && (ph == 1 || ph == 2)) {
#pragma unroll 1
                for (int i = 0; i <= ph; i++)
                    asm volatile("{.reg .pred p; elect.sync _|p, 0xffffffff; @p cp.async.bulk.prefetch.tensor.2d.L2.global [%0, {%1, %2}];}"
                                 ::"l"(tm + 2), "r"((nb * (ph + 1) + i) * 64), "r"(mb * 64) : "memory");
            }
            if (!A && ph == 3 && q == 1) wait_smem(sb + P_BAR + 8 * (PB_OUT + (lane & 1)), 3);
            const int row = arow + (ph == 2 ? (int)((0x04000301u >> ((src & 6) * 4)) & 7) - 2 : 0);
            const uint32_t bytes = (skip ? 16384 : 32768) + (ph == 3 ? 8192 : 0);
            if ((ph | q) == 0) asm volatile("barrier.cluster.wait.aligned;" ::: "memory");
            if (A && (ph | q) == 0) asm volatile("griddepcontrol.wait;" ::: "memory");
#pragma unroll 1
            for (int e = kb0 + (src + 1) * GS, kb = e - GS + (ph | q ? 0 : E0); kb < e; kb++) {
                const uint32_t f = full + 8 * p.st;
                if (!(A && skip)) mbar_wait_w(empty + 8 * p.st, p.ph ^ 1);
                if (A) {
                    const uint32_t a = sb + p.st * 16384 + rank * 8192;
                    if (both) { e_tma2d_ef(a, tm, kb * 64, row, f); e_tma2d_ef(a + 8192 - rank * 16384, tm, kb * 64, row ^ 64, f); }
                    else if (!skip) e_tma2d_mc_ef(a, tm, kb * amul, row, f);
                } else {
                    const uint32_t b = sb + P_B + p.st * 8192;
                    e_expect(f, bytes);
                    e_tma2d_ef(b, tm, n0, kb * 64, f);
                    e_tma2d_ef(b + P_PLANE, tm, n0 + 64, kb * 64, f);
                    if (ph == 3 && both) mbar_wait_w(empty + 8 * p.st - 16, p.ph);
                    if (ph == 3) e_tma2d_ef(b + 2 * P_PLANE, tm, n0 + 128, kb * 64, f);
                }
                adv(p);
            }
        }
    }
    if (A) {
#pragma unroll 1
        for (int i = 0; i < P_ST; i++) mbar_wait_w(empty + 8 * i, p.ph ^ (i >= p.st));
    }
}

#define I4(d, i) "f"(d[i]), "f"(d[i + 1]), "f"(d[i + 2]), "f"(d[i + 3])
#define I16(d, i) I4(d, i), I4(d, i + 4), I4(d, i + 8), I4(d, i + 12)
#define O4(d, i) "=f"(d[i]), "=f"(d[i + 1]), "=f"(d[i + 2]), "=f"(d[i + 3])
__device__ __forceinline__ void pick32(float* v, int n, const float* c1, const float* vc, const float* old) {
    asm volatile("{PKT: .branchtargets PK0, PK1, PK2, PK3, PK4, PK5; brx.idx.uni %16, PKT;\n"
                 "PK0: fma.rn.f32 %0, %17, %19, %27; fma.rn.f32 %1, %17, %20, %28; fma.rn.f32 %2, %18, %19, %29; fma.rn.f32 %3, %18, %20, %30; fma.rn.f32 %4, %17, %21, %31; fma.rn.f32 %5, %17, %22, %32; fma.rn.f32 %6, %18, %21, %33; fma.rn.f32 %7, %18, %22, %34; fma.rn.f32 %8, %17, %23, %35; fma.rn.f32 %9, %17, %24, %36; fma.rn.f32 %10, %18, %23, %37; fma.rn.f32 %11, %18, %24, %38; fma.rn.f32 %12, %17, %25, %39; fma.rn.f32 %13, %17, %26, %40; fma.rn.f32 %14, %18, %25, %41; fma.rn.f32 %15, %18, %26, %42; bra.uni PKE;\n"
                 "PK1: fma.rn.f32 %0, %17, %19, %43; fma.rn.f32 %1, %17, %20, %44; fma.rn.f32 %2, %18, %19, %45; fma.rn.f32 %3, %18, %20, %46; fma.rn.f32 %4, %17, %21, %47; fma.rn.f32 %5, %17, %22, %48; fma.rn.f32 %6, %18, %21, %49; fma.rn.f32 %7, %18, %22, %50; fma.rn.f32 %8, %17, %23, %51; fma.rn.f32 %9, %17, %24, %52; fma.rn.f32 %10, %18, %23, %53; fma.rn.f32 %11, %18, %24, %54; fma.rn.f32 %12, %17, %25, %55; fma.rn.f32 %13, %17, %26, %56; fma.rn.f32 %14, %18, %25, %57; fma.rn.f32 %15, %18, %26, %58; bra.uni PKE;\n"
                 "PK2: fma.rn.f32 %0, %17, %19, %59; fma.rn.f32 %1, %17, %20, %60; fma.rn.f32 %2, %18, %19, %61; fma.rn.f32 %3, %18, %20, %62; fma.rn.f32 %4, %17, %21, %63; fma.rn.f32 %5, %17, %22, %64; fma.rn.f32 %6, %18, %21, %65; fma.rn.f32 %7, %18, %22, %66; fma.rn.f32 %8, %17, %23, %67; fma.rn.f32 %9, %17, %24, %68; fma.rn.f32 %10, %18, %23, %69; fma.rn.f32 %11, %18, %24, %70; fma.rn.f32 %12, %17, %25, %71; fma.rn.f32 %13, %17, %26, %72; fma.rn.f32 %14, %18, %25, %73; fma.rn.f32 %15, %18, %26, %74; bra.uni PKE;\n"
                 "PK3: fma.rn.f32 %0, %17, %19, %75; fma.rn.f32 %1, %17, %20, %76; fma.rn.f32 %2, %18, %19, %77; fma.rn.f32 %3, %18, %20, %78; fma.rn.f32 %4, %17, %21, %79; fma.rn.f32 %5, %17, %22, %80; fma.rn.f32 %6, %18, %21, %81; fma.rn.f32 %7, %18, %22, %82; fma.rn.f32 %8, %17, %23, %83; fma.rn.f32 %9, %17, %24, %84; fma.rn.f32 %10, %18, %23, %85; fma.rn.f32 %11, %18, %24, %86; fma.rn.f32 %12, %17, %25, %87; fma.rn.f32 %13, %17, %26, %88; fma.rn.f32 %14, %18, %25, %89; fma.rn.f32 %15, %18, %26, %90; bra.uni PKE;\n"
                 "PK4: fma.rn.f32 %0, %17, %19, %91; fma.rn.f32 %1, %17, %20, %92; fma.rn.f32 %2, %18, %19, %93; fma.rn.f32 %3, %18, %20, %94; fma.rn.f32 %4, %17, %21, %95; fma.rn.f32 %5, %17, %22, %96; fma.rn.f32 %6, %18, %21, %97; fma.rn.f32 %7, %18, %22, %98; fma.rn.f32 %8, %17, %23, %99; fma.rn.f32 %9, %17, %24, %100; fma.rn.f32 %10, %18, %23, %101; fma.rn.f32 %11, %18, %24, %102; fma.rn.f32 %12, %17, %25, %103; fma.rn.f32 %13, %17, %26, %104; fma.rn.f32 %14, %18, %25, %105; fma.rn.f32 %15, %18, %26, %106; bra.uni PKE;\n"
                 "PK5: fma.rn.f32 %0, %17, %19, %107; fma.rn.f32 %1, %17, %20, %108; fma.rn.f32 %2, %18, %19, %109; fma.rn.f32 %3, %18, %20, %110; fma.rn.f32 %4, %17, %21, %111; fma.rn.f32 %5, %17, %22, %112; fma.rn.f32 %6, %18, %21, %113; fma.rn.f32 %7, %18, %22, %114; fma.rn.f32 %8, %17, %23, %115; fma.rn.f32 %9, %17, %24, %116; fma.rn.f32 %10, %18, %23, %117; fma.rn.f32 %11, %18, %24, %118; fma.rn.f32 %12, %17, %25, %119; fma.rn.f32 %13, %17, %26, %120; fma.rn.f32 %14, %18, %25, %121; fma.rn.f32 %15, %18, %26, %122;\n"
                 "PKE: }"
                 : O4(v, 0), O4(v, 4), O4(v, 8), O4(v, 12)
                 : "r"(n), "f"(c1[0]), "f"(c1[1]), I4(vc, 0), I4(vc, 4), I16(old, 0), I16(old, 16), I16(old, 32), I16(old, 48), I16(old, 64), I16(old, 80));
}
template <int PH, class F>
__device__ __forceinline__ void post_mma(uint32_t sb, float* acc, Pipe& p, int NK, int wg, uint32_t rel, bool lead, int pi, F hook) {
    const uint32_t full = sb + P_BAR + 8 * PB_F;
    constexpr uint64_t DA = PH == 0 ? mkdesc(SB0, 128, 1024, 0) : mkdesc(SB0, 16, 1024, 1);
    constexpr uint64_t DB = mkdesc(SB0 + P_B, P_PLANE, 1024, 1);
    auto release = [&](uint32_t a) { asm volatile("{.reg .pred p; setp.gt.u32 p, %0, 63; @p mbarrier.arrive.shared::cluster.b64 _, [%0];}" ::"r"(a) : "memory"); };
    uint32_t prev = 0;
    if (PH & 1) { fence_async_smem(); bar_sync(12 + wg, 128); }
    bool ok = false;
#pragma unroll 1
    for (int kb = 0; kb < NK; kb++) {
        if (!ok) mbar_wait_w(full + 8 * p.st, p.ph);
        const uint32_t a = (uint32_t)DA + ((PH & 1) && kb < 2 ? P_OUT / 16 + wg * 1024 + kb * 512 : p.st * 1024 + wg * 512), b = (uint32_t)DB + p.st * 512;
        wg_fence();
#pragma unroll
        for (int k = 0; k < 4; k++) {
            const uint64_t da = (DA & 0xffffffff00000000ull) | (a + k * (PH == 0 ? 16 : 2)), db = (DB & 0xffffffff00000000ull) | (b + k * 128);
            if (PH == 3) wgmma_ss192(acc, da, db, (kb | k) != 0);
            else wgmma_ss128<PH == 0>(acc, da, db, (kb | k) != 0);
        }
        wg_commit();
        const uint32_t cur = rel + 8 * p.st;
        adv(p);
        uint32_t t;
        asm volatile("{.reg .pred p; mbarrier.test_wait.parity.shared.b64 p, [%1], %2; selp.u32 %0, 1, 0, p;}" : "=r"(t) : "r"(full + 8 * p.st), "r"(p.ph) : "memory");
        wg_wait<1>();
        release(prev);
        ok = __all_sync(~0u, t);
        prev = cur;
        hook(kb);
    }
    wg_wait<0>();
    release(prev);
}

__global__ void __cluster_dims__(2, 1, 1) __launch_bounds__(384, 1)
k_post(const __grid_constant__ PostMaps mp) {
    extern __shared__ uint8_t smraw[];
    const uint32_t sb = smem_u32(smraw);
    if ((sb & 0x3FFFF) != SB0) __trap();
    const int tid = threadIdx.x, lane = tid & 31;
    int d, pi;
    pair_place(blockIdx.x >> 1, d, pi);
    const int rank = blockIdx.x & 1, mb = (d >> 2) * 8 + pi, nb = (d & 3) * 2 + rank;
    const uint32_t bars = sb + P_BAR;
    const int w = __reduce_max_sync(~0u, (tid >> 5) - 8);
    if (w == 1) {
        if (lane == 0) {
#pragma unroll
            for (int i = 0; i <= PB_P; i++) mbar_init(bars + 8 * i, i >= PB_E && i < PB_X ? 4 : i == PB_P ? 2 : 1);
            mbar_arrive(bars + 8 * (PB_F + P_ST0));
            asm volatile("mbarrier.arrive.shared.b64 _, [%0], 4;" ::"r"(bars + 8 * (PB_E + P_ST0)) : "memory");
            sts4(bars + 8 * PB_OUT, 0, 0, 0, 0);
            asm volatile("fence.mbarrier_init.release.cluster; fence.proxy.async.shared::cta;" ::: "memory");
        }
        __syncwarp();
    }
    asm volatile("barrier.cluster.arrive.relaxed.aligned;" ::: "memory");
    if (w == 1 || w == 2) asm volatile("griddepcontrol.wait;" ::: "memory");
    if (w == 1) {
#pragma unroll
        for (int i = 0; i < E0; i++) {
            const int st = (P_ST0 + i) % P_ST;
            const uint32_t f = bars + 8 * (PB_F + st);
            e_expect(f, 32768);
#pragma unroll
            for (int h = 0; h < 2; h++) {
                e_tma2d_ef(sb + st * 16384 + h * 8192, &mp.o, i * 256, mb * 16 + h * 8, f);
                e_tma2d_ef(sb + P_B + st * 8192 + h * P_PLANE, &mp.wo, nb * 128 + h * 64, i * 64, f);
            }
        }
    }
    if (w != 0 && w != 3) asm volatile("barrier.cluster.wait.aligned;" ::: "memory");
    if (w >= 0) {
        asm volatile("setmaxnreg.dec.sync.aligned.u32 40;");
        if (w == 0) {
            post_produce<false>(sb, mp, mb, nb, rank);
        } else if (w < 3) {
            const int wg = w - 1, rh = 2 * mb + wg;
            float* rowc = (float*)(smraw + P_ROW) + (wg * 64 + lane * 2) * 8;
            int nout = 0, sig = 0;
            __nanosleep(X_DLY);
            if (wg && lane < 9) asm volatile("prefetch.tensormap [%0];" ::"l"(&mp.y + lane) : "memory");
            e_expect(bars + 8 * (PB_X + wg), 16384);
            e_tma2d_ef(sb + P_OUT + wg * 16384, &mp.x, nb * 128, rh * 64, bars + 8 * (PB_X + wg));
            e_tma2d_ef(sb + P_OUT + wg * 16384 + 8192, &mp.x, nb * 128 + 64, rh * 64, bars + 8 * (PB_X + wg));
            if (wg == 0) {
#pragma unroll 1
                for (int i = 0; i < 11; i++) {
                    const float* src = i < 4 ? g_mod + ((0x5342 >> (4 * i)) & 15) * DM + nb * 128 : g_vec + (i < 7 ? (i - 4) * DM + nb * 128 : 3 * DM + u_col(max(i - 8, 0), nb) + (i == 8) * 128);
                    if (i != 8 || lane < 16) cp_async16(sb + P_VEC + i * 512 - (i > 8) * 256 + lane * 16, src + lane * 4);
                }
                *(uint4*)&g_modp[blockIdx.x * 128 + lane * 4] = make_uint4(0, 0, 0, 0);
                if (blockIdx.x == 64) *(uint2*)&g_tick[lane * 2] = make_uint2(0, 0);
                asm volatile("cp.async.wait_all;" ::: "memory");
                const float4 a = lds4f(sb + P_VEC + V_A * 512 + lane * 16);
                sts4f(sb + P_VEC + V_A * 512 + lane * 16, 1.0f + a.x, 1.0f + a.y, 1.0f + a.z, 1.0f + a.w);
                bar_arrive(3, 288);
            }
#pragma unroll 1
            for (int i = 0; i < 9; i++) {
                const int cnt = i == 8 ? 6 : (0x54392180u >> (4 * i)) & 15;
                if (cnt < C_S1) {
                    const bool isu = cnt >= C_U && cnt < 6;
                    const int ng = cnt == C_U ? 3 : 2, c0 = isu ? u_col(cnt - C_U, nb) : nb * 128;
                    const uint32_t src = sb + (cnt == C_U ? P_OUT3 : P_OUT) + wg * ng * 8192;
#pragma unroll 1
                    for (int j = 0; j < ng; j++) {
                        bar_sync(4 + 4 * wg + (sig++ & 3), 160);
                        if (lane == 0) {
                            fence_async_smem();
                            asm volatile("cp.async.bulk.tensor.2d.global.shared::cta.bulk_group [%0, {%2, %3}], [%1]; cp.async.bulk.commit_group;"
                                         ::"l"(&mp.y + 2 * (isu ? 3 : min(cnt, 4))), "r"(src + j * 8192), "r"(c0 + j * 64), "r"(rh * 64) : "memory");
                        }
                        __syncwarp();
                    }
                    if (lane == 0) {
                        asm volatile("cp.async.bulk.wait_group 0; fence.proxy.async.global;" ::: "memory");
                        asm volatile("st.release.cta.shared.u32 [%0], %1;" ::"r"(bars + 8 * (PB_OUT + wg)), "r"(nout + 1) : "memory");
                        if (cnt < 6) asm volatile("fence.acq_rel.gpu; st.relaxed.gpu.global.u32 [%0], %1;" ::"l"(&g_pflag[cnt * 256 + rh * 8 + nb]), "r"(1) : "memory");
                        if (cnt == C_Y || cnt == C_X1)
                            asm volatile("{.reg .b32 r; mapa.shared::cluster.u32 r, %0, %1; mbarrier.arrive.relaxed.cluster.shared::cluster.b64 _, [r];}" ::"r"(bars + 8 * PB_P), "r"(rank ^ 1) : "memory");
                    }
                    nout++;
                    __syncwarp();
                    continue;
                }
                bar_sync(4 + 4 * wg + (sig++ & 3), 160);
#pragma unroll 1
                for (int q = 0; q < (cnt == C_S1 ? 3 : 1); q++) {
                    const float4 v = lds4f(sb + P_ROW + wg * 2048 + q * 512 + lane * 16);
                    asm volatile("red.relaxed.gpu.global.add.v4.f32 [%0], {%1, %2, %3, %4};"
                                 ::"l"((float4*)g_st + (cnt == C_S1 ? q : 3) * (S_ / 2) + rh * 32 + lane), "f"(v.x), "f"(v.y), "f"(v.z), "f"(v.w) : "memory");
                }
                __syncwarp();
                uint32_t* c = &g_pcnt[(cnt - C_S1) * 256 + rh * 8];
                if (lane == 0) { signal_count(c); wait_count1(c, 8); }
                __syncwarp();
                const float4* sp = (const float4*)g_st + rh * 32 + lane;
                float4 u[3] = {__ldcg(sp + (cnt == C_S1 ? 0 : 3) * (S_ / 2)), __ldcg(sp + S_ / 2), __ldcg(sp + S_)};
#pragma unroll 1
                for (int h = 0; h < 2; h++) {
                    const float id = 1.0f / DM;
                    const float m = u[0].x * id, var = fmaxf(u[0].y * id - m * m, 0.f) + 1e-5f, r = rsqrtf(var);
                    float sc = r, m2 = 0.f;
                    if (cnt == C_S1) {
                        m2 = r * (u[1].x * id - m * g_cst[0]) + g_cst[3];
                        const float e2 = r * r * (u[2].x * id - 2.0f * m * u[1].y * id + m * m * g_cst[1]) + 2.0f * r * (u[2].y * id - m * g_cst[2]) + g_cst[4];
                        sc = r * rsqrtf(fmaxf(e2 - m2 * m2, 0.f) + 1e-5f);
                    }
                    const GeluK k = gelu_k(sc);
                    *(float4*)(rowc + h * 8) = make_float4(k.k0, k.k1, k.kh, -m);
                    *(float4*)(rowc + h * 8 + 4) = make_float4(var * r, -m2 * var * r, r, -m * r);
#pragma unroll
                    for (int q = 0; q < 3; q++) { u[q].x = u[q].z; u[q].y = u[q].w; }
                }
                bar_arrive(1 + wg, 160);
            }
        } else {
            post_produce<true>(sb, mp, mb, nb, rank);
        }
    } else {
        asm volatile("setmaxnreg.inc.sync.aligned.u32 232;");
        const int wg = __reduce_max_sync(~0u, tid >> 7), wi = (tid >> 5) & 3, g = lane >> 2, tq = lane & 3;
        const bool lead = (tid & 127) == 0;
        uint32_t rel = 0;
        if ((tid & 127) < 2) asm("mapa.shared::cluster.u32 %0, %1, %2;" : "=r"(rel) : "r"(bars + 8 * PB_E), "r"(tid & 1));
        uint32_t vec = sb + P_VEC + tq * 8;
        const uint32_t stw = sb + (wi * 16 + ((lane >> 3) & 1) * 8 + (lane & 7)) * 128 + (((lane >> 4) ^ (lane & 7)) << 4);
        int sig = 0;
        auto signal = [&]() { bar_arrive(4 + 4 * wg + (sig++ & 3), 160); };
        auto put64 = [&](uint32_t o, const float* v) {
#pragma unroll
            for (int jj = 0; jj < 4; jj++, v += 8) stsm4((stw + o) ^ (jj << 5), pack2(v[0], v[1]), pack2(v[2], v[3]), pack2(v[4], v[5]), pack2(v[6], v[7]));
            signal();
        };
        auto out_free = [&](int n) { wait_smem(bars + 8 * (PB_OUT + (lane & 1)), n); };
        const uint32_t rowc = sb + P_ROW + (wg * 64 + wi * 16 + g) * 32, o128 = P_OUT + wg * 16384;
        const uint32_t rsum = sb + P_ROW + wg * 2048 + (wi * 16 + g) * 8;
        Pipe pa = {P_ST0, 1};
        auto none = [](int) {};
        uint32_t keep[32];
#define KEEP(jn, e) (((e) & 1) ? bfhi(keep[2 * (jn) + ((e) >> 1)]) : bflo(keep[2 * (jn) + ((e) >> 1)]))
        float mu1[2], r1[2];
        {
            float acc[64];
            post_mma<0>(sb, acc, pa, 64, wg, rel, lead, 1, [&](int kb) {
                if (kb != 40) return;
                bar_sync(3, 288);
                mbar_wait_w(bars + 8 * (PB_X + wg), 0);
#pragma unroll
                for (int jj = 0; jj < 8; jj++) ldsm4(keep + jj * 4, (stw + o128 + (jj >> 2) * 8192) ^ ((jj & 3) << 5));
            });
            asm volatile("" : "+r"(vec) :: "memory");
            float st[2][6];
#pragma unroll
            for (int q = 0; q < 6; q++) st[0][q] = st[1][q] = 0.f;
#pragma unroll
            for (int jn = 0; jn < 16; jn++) {
                const float2 ga = ldsv(vec + V_GA * 512 + jn * 32), a = ldsv(vec + V_A * 512 + jn * 32);
                float xa[4];
#pragma unroll
                for (int e = 0; e < 4; e++) {
                    xa[e] = fmaf((e & 1) ? ga.y : ga.x, acc[4 * jn + e], KEEP(jn, e));
                    st[e >> 1][0] += xa[e]; st[e >> 1][1] = fmaf(xa[e], xa[e], st[e >> 1][1]);
                    acc[4 * jn + e] = ((e & 1) ? a.y : a.x) * xa[e];
                }
                keep[2 * jn] = pack2(xa[0], xa[1]); keep[2 * jn + 1] = pack2(xa[2], xa[3]);
                if ((jn & 7) == 7) put64(o128 + (jn >> 3) * 8192, acc + 4 * jn - 28);
            }
#pragma unroll
            for (int jn = 0; jn < 16; jn++) {
                const float2 a = ldsv(vec + V_A * 512 + jn * 32), b = ldsv(vec + V_B * 512 + jn * 32);
#pragma unroll
                for (int e = 0; e < 4; e++) {
                    const float y = acc[4 * jn + e], aa = (e & 1) ? a.y : a.x, bb = (e & 1) ? b.y : b.x;
                    float* s = st[e >> 1];
                    s[2] += y; s[3] = fmaf(aa, y, s[3]); s[4] = fmaf(y, y, s[4]); s[5] = fmaf(bb, y, s[5]);
                }
            }
#pragma unroll
            for (int h = 0; h < 2; h++)
#pragma unroll
                for (int q = 0; q < 6; q++) { st[h][q] += __shfl_xor_sync(~0u, st[h][q], 1); st[h][q] += __shfl_xor_sync(~0u, st[h][q], 2); }
            if (tq < 3) {
#pragma unroll
                for (int h = 0; h < 2; h++)
                    sts2(rsum + tq * 512 + h * 64, tq == 0 ? st[h][0] : tq == 1 ? st[h][2] : st[h][4], tq == 0 ? st[h][1] : tq == 1 ? st[h][3] : st[h][5]);
            }
            signal();
        }
        {
            float acc[64];
            post_mma<1>(sb, acc, pa, 16, wg, rel, lead, 4, none);
            float c1[2], c2[2], c3[2];
            GeluK gk[2];
            bar_sync(1 + wg, 160);
#pragma unroll
            for (int h = 0; h < 2; h++) {
                const float4 a = lds4f(rowc + h * 256), b = lds4f(rowc + h * 256 + 16);
                gk[h] = {a.x, a.y, a.z}; c1[h] = a.w; c2[h] = b.x; c3[h] = b.y; mu1[h] = b.w; r1[h] = b.z;
            }
#pragma unroll
            for (int jn = 0; jn < 16; jn++) {
                const float2 va = ldsv(vec + V_VA * 512 + jn * 32), vb = ldsv(vec + V_VB * 512 + jn * 32), vc = ldsv(vec + V_VC * 512 + jn * 32);
#pragma unroll
                for (int e = 0; e < 4; e++) {
                    const int h = e >> 1;
                    const float t = fmaf(c1[h], (e & 1) ? va.y : va.x, fmaf(c2[h], (e & 1) ? vb.y : vb.x, fmaf(c3[h], (e & 1) ? vc.y : vc.x, acc[4 * jn + e])));
                    acc[4 * jn + e] = gelu_s(t, gk[h]);
                }
                if ((jn & 7) == 7) put64(o128 + (jn >> 3) * 8192, acc + 4 * jn - 28);
            }
        }
        {
            float acc[64];
            post_mma<2>(sb, acc, pa, 16, wg, rel, lead, 7, none);
#pragma unroll
            for (int jn = 0; jn < 16; jn++) {
                const float2 a = ldsv(vec + V_A * 512 + jn * 32), b = ldsv(vec + V_B * 512 + jn * 32);
#pragma unroll
                for (int e = 0; e < 4; e++) {
                    const int h = e >> 1;
                    acc[4 * jn + e] += fmaf(fmaf(KEEP(jn, e), r1[h], mu1[h]), (e & 1) ? a.y : a.x, (e & 1) ? b.y : b.x);
                }
                if ((jn & 7) == 7) put64(o128 + (jn >> 3) * 8192, acc + 4 * jn - 28);
            }
            float st[2][2] = {{0.f, 0.f}, {0.f, 0.f}};
#pragma unroll
            for (int jn = 0; jn < 16; jn++) {
                const float2 gb = ldsv(vec + V_GB * 512 + jn * 32);
                float z[4];
#pragma unroll
                for (int e = 0; e < 4; e++) {
                    const float x1 = acc[4 * jn + e];
                    st[e >> 1][0] += x1; st[e >> 1][1] = fmaf(x1, x1, st[e >> 1][1]);
                    z[e] = fmaf((e & 1) ? gb.y : gb.x, x1, KEEP(jn, e));
                }
                keep[2 * jn] = pack2(z[0], z[1]); keep[2 * jn + 1] = pack2(z[2], z[3]);
            }
#pragma unroll
            for (int h = 0; h < 2; h++)
#pragma unroll
                for (int q = 0; q < 2; q++) { st[h][q] += __shfl_xor_sync(~0u, st[h][q], 1); st[h][q] += __shfl_xor_sync(~0u, st[h][q], 2); }
            if (tq < 2) sts2(rsum + tq * 64, tq ? st[1][0] : st[0][0], tq ? st[1][1] : st[0][1]);
            signal();
        }
        {
            float old[96], acc[64];
            post_mma<3>(sb, old, pa, 16, wg, rel, lead, 10, none);
            uint32_t v3 = vec + V_C3 * 512;
            float c1[2], vc[8];
            auto next_vc = [&]() {
#pragma unroll
                for (int i = 0; i < 4; i++) { const float2 u = lds2f(v3 + i * 32); vc[2 * i] = u.x; vc[2 * i + 1] = u.y; }
                v3 += 128;
            };
            next_vc();
            GeluK gk[2];
            bar_sync(1 + wg, 160);
#pragma unroll
            for (int h = 0; h < 2; h++) { const float4 a = lds4f(rowc + h * 256); gk[h] = {a.x, a.y, a.z}; c1[h] = a.w; }
            bar_arrive(14 + wg, 256);
#pragma unroll 1
            for (int r = 0; r < 3; r++) {
                const uint32_t o = stw + (r ? o128 : P_OUT3 + wg * 24576);
                uint32_t when = r == 0 ? (wg ? SL_A1 : SL_A0) : r == 1 ? (wg ? SL_B1 : SL_B0) : SL_C << (2 * wg), n = 0;
                post_mma<2>(sb, acc, pa, r < 2 ? 16 : 56, wg, rel, lead, 12 + 2 * r, [&](int kb) {
                    const bool now = when & 1;
                    when >>= 1;
                    if (!now) return;
                    if (n == 0) { if (r == 0) bar_sync(15 - wg, 256); out_free(3 + r); }
                    float v[16];
                    pick32(v, n, c1, vc, old);
                    next_vc();
#pragma unroll
                    for (int e = 0; e < 16; e++) v[e] = gelu_s(v[e], gk[(e >> 1) & 1]);
                    const uint32_t a = (o + (n >> 1) * 8192) ^ ((n & 1) << 6);
                    stsm4(a, pack2(v[0], v[1]), pack2(v[2], v[3]), pack2(v[4], v[5]), pack2(v[6], v[7]));
                    stsm4(a ^ 32, pack2(v[8], v[9]), pack2(v[10], v[11]), pack2(v[12], v[13]), pack2(v[14], v[15]));
                    if ((++n & 1) == 0) signal();
                });
                if (r == 2) break;
#pragma unroll
                for (int i = 0; i < 64; i++) old[i] = acc[i];
            }
#pragma unroll
            for (int jn = 0; jn < 16; jn++) {
                const float2 gb = ldsv(vec + V_GB * 512 + jn * 32);
#pragma unroll
                for (int e = 0; e < 4; e++) acc[4 * jn + e] = fmaf((e & 1) ? gb.y : gb.x, acc[4 * jn + e], KEEP(jn, e));
                if ((jn & 7) == 7) put64(o128 + (jn >> 3) * 8192, acc + 4 * jn - 28);
            }
        }
    }
}

typedef CUresult (*EncFn)(CUtensorMap*, CUtensorMapDataType, cuuint32_t, void*, const cuuint64_t*, const cuuint64_t*, const cuuint32_t*,
                          const cuuint32_t*, CUtensorMapInterleave, CUtensorMapSwizzle, CUtensorMapL2promotion, CUtensorMapFloatOOBfill);

static CUtensorMap make_map(EncFn enc, const void* p, uint64_t inner, uint64_t outer) {
    CUtensorMap m;
    cuuint64_t dims[2] = {inner, outer};
    cuuint64_t str[1] = {inner * 2};
    cuuint32_t box[2] = {64, 64};
    cuuint32_t es[2] = {1, 1};
    enc(&m, CU_TENSOR_MAP_DATA_TYPE_BFLOAT16, 2, (void*)p, dims, str, box, es, CU_TENSOR_MAP_INTERLEAVE_NONE,
        CU_TENSOR_MAP_SWIZZLE_128B, CU_TENSOR_MAP_L2_PROMOTION_L2_256B, CU_TENSOR_MAP_FLOAT_OOB_FILL_NONE);
    return m;
}
static CUtensorMap make_map_o(EncFn enc, const void* p) {
    CUtensorMap m;
    cuuint64_t dims[2] = {16384, 256};
    cuuint64_t str[1] = {65536};
    cuuint32_t box[2] = {256, 8};
    cuuint32_t es[2] = {1, 1};
    enc(&m, CU_TENSOR_MAP_DATA_TYPE_UINT32, 2, (void*)p, dims, str, box, es, CU_TENSOR_MAP_INTERLEAVE_NONE, CU_TENSOR_MAP_SWIZZLE_NONE,
        CU_TENSOR_MAP_L2_PROMOTION_L2_256B, CU_TENSOR_MAP_FLOAT_OOB_FILL_NONE);
    return m;
}
template <class T> static T* sym(T& s) { void* p = nullptr; cudaGetSymbolAddress(&p, s); return (T*)p; }

constexpr RecTime g_time = {T_GO, T_X2, T_V, D_X2, H_D};
extern "C" void kernel_launch(void* const* d_in, const int* in_sizes, int n_in, void* d_out, int out_size) {
    const bf16* x = (const bf16*)d_in[0];
    const bf16* mem0 = (const bf16*)d_in[1];
    const bf16 *Wq = (const bf16*)d_in[2], *Wk = (const bf16*)d_in[3], *Wv = (const bf16*)d_in[4], *Wo = (const bf16*)d_in[5];
    const bf16 *w1 = (const bf16*)d_in[8], *w2 = (const bf16*)d_in[9], *w3 = (const bf16*)d_in[10], *w4 = (const bf16*)d_in[11];
    const bf16 *c = (const bf16*)d_in[12], *wmod = (const bf16*)d_in[13];
    bf16* out = (bf16*)d_out;

    EncFn enc = nullptr;
    cudaDriverEntryPointQueryResult qr;
    cudaGetDriverEntryPoint("cuTensorMapEncodeTiled", (void**)&enc, cudaEnableDefault, &qr);
    CUtensorMap tWq = make_map(enc, Wq, NH * DH, DM), tWk = make_map(enc, Wk, NH * DH, DM), tWv = make_map(enc, Wv, NH * DH, DM);
    PostMaps mp;
    mp.o = make_map_o(enc, sym(g_O)); mp.wo = make_map(enc, Wo, DM, NH * DH);
    mp.y = make_map(enc, sym(g_y), DM, S_); mp.w1 = make_map(enc, w1, DM, DM);
    mp.g = make_map(enc, sym(g_g), DM, S_); mp.w2 = make_map(enc, w2, DM, DM);
    mp.x1 = make_map(enc, sym(g_x1), DM, S_); mp.w3 = make_map(enc, w3, FF, DM);
    mp.u = make_map(enc, sym(g_u), FF, S_); mp.w4 = make_map(enc, w4, DM, FF);
    mp.out = make_map(enc, out, DM, S_); mp.x = make_map(enc, x, DM, S_);
    cudaFuncSetAttribute(k_rec, cudaFuncAttributeMaxDynamicSharedMemorySize, SM_REC_TOTAL);
    cudaFuncSetAttribute(k_post, cudaFuncAttributeMaxDynamicSharedMemorySize, P_SMEM);

    uint8_t* arena = (uint8_t*)(((uintptr_t)sym(g_arena) + (2u << 20) - 1) & ~(uintptr_t)((2u << 20) - 1));
    const RecPtrs rp = {x, mem0, c, wmod, w1, w3, arena, 0u, g_time};
    const RecMaps rm = {tWq, tWk, tWv, mp.wo};
    k_rec<<<132, 384, SM_REC_TOTAL, cudaStreamPerThread>>>(rm, rp);
    cudaLaunchConfig_t cfg = {};
    cfg.gridDim = dim3(128); cfg.blockDim = dim3(384); cfg.dynamicSmemBytes = P_SMEM; cfg.stream = cudaStreamPerThread;
    cudaLaunchAttribute at[1];
    at[0].id = cudaLaunchAttributeProgrammaticStreamSerialization;
    at[0].val.programmaticStreamSerializationAllowed = 1;
    cfg.attrs = at; cfg.numAttrs = 1;
    cudaLaunchKernelEx(&cfg, k_post, mp);
}
```
